```python
import torch

def _softmax(x, axis=-1):
    return torch.softmax(x, dim=axis)
def _gelu(x):
    return torch.nn.functional.gelu(x, approximate="tanh")
def _silu(x):
    return torch.nn.functional.silu(x)
def _sigmoid(x):
    return torch.sigmoid(x)
def _layernorm(x, axis=-1, eps=1e-5):
    m = x.mean(dim=axis, keepdim=True)
    v = x.var(dim=axis, keepdim=True, unbiased=False)
    return (x - m) / torch.sqrt(v + eps)
def _scatter_add(tgt, idx, src, axis=0):
    return tgt.clone().index_add_(axis, idx, src)
def _segment_sum(src, seg, n):
    out = torch.zeros((n,) + src.shape[1:], dtype=src.dtype)
    return out.index_add_(0, seg, src)
def _pad(x, pw):
    flat = tuple(v for pair in reversed(pw) for v in pair)
    return torch.nn.functional.pad(x, flat)

kernel_name = 'parallel_sum__sliding_local_dilated__mixer_token_mlp__prompt'

def setup_inputs():

    _w = (lambda a: (lambda t: t.to(torch.bfloat16) if t.is_floating_point() else t)(torch.as_tensor(a)))
    def _A_setup():
        B, S, D = 1, 2048, 448
        return {
            "x": _w((lambda *s: torch.randn(*s, dtype=torch.bfloat16) * 0.05)(B, S, D)),
            "wqkv": _w((lambda *s: torch.randn(*s, dtype=torch.bfloat16) * 0.05)(D, 3 * D)),
            "wo": _w((lambda *s: torch.randn(*s, dtype=torch.bfloat16) * 0.05)(D, D)),
        }
    _A_in = _A_setup()

    def _B_setup():
        B, S, D, F = 1, 2048, 448, 1792
        return {
            "x": _w((lambda *s: torch.randn(*s, dtype=torch.bfloat16) * 0.05)(B, S, D)),
            "w1": _w((lambda *s: torch.randn(*s, dtype=torch.bfloat16) * 1.6)(S, F) * (S ** -0.5)),
            "b1": _w((lambda *s: torch.randn(*s, dtype=torch.bfloat16) * 12.8)(F) * 0.02),
            "w2": _w((lambda *s: torch.randn(*s, dtype=torch.bfloat16) * 0.4)(F, S) * (F ** -0.5)),
            "b2": _w((lambda *s: torch.randn(*s, dtype=torch.bfloat16) * 6.4)(S) * 0.02),
        }
    _B_in = _B_setup()

    return {
        "A_x": _A_in["x"],
        "A_wqkv": _A_in["wqkv"],
        "A_wo": _A_in["wo"],
        "B_x": _B_in["x"],
        "B_w1": _B_in["w1"],
        "B_b1": _B_in["b1"],
        "B_w2": _B_in["w2"],
        "B_b2": _B_in["b2"],
    }

def reference(A_x, A_wqkv, A_wo, B_x, B_w1, B_b1, B_w2, B_b2):
    def _A_ref(x, wqkv, wo):
        B, S, D = x.shape
        H = 16; Dh = D // H
        W, dil = 8, 2
        qkv = (lambda x, *d: x.permute(*d))((x @ wqkv).reshape(B, S, 3, H, Dh), 2, 0, 3, 1, 4)
        q, k, v = qkv[0], qkv[1], qkv[2]
        scale = Dh ** -0.5
        pos = torch.arange(S)
        off = torch.arange(W) * dil
        idx = pos[:, None] - off[None, :]
        mask = idx >= 0
        idx_c = torch.where(mask, idx, 0).reshape(-1)
        kg = k[:, :, idx_c, :].reshape(B, H, S, W, Dh)
        vg = v[:, :, idx_c, :].reshape(B, H, S, W, Dh)
        logits = torch.einsum("bhsd,bhswd->bhsw", q, kg) * scale
        logits = torch.where(mask[None, None, :, :], logits, -1e9)
        attn = _softmax(logits, axis=-1)
        o = torch.einsum("bhsw,bhswd->bhsd", attn, vg)
        return (lambda x, *d: x.permute(*d))(o, 0, 2, 1, 3).reshape(B, S, D) @ wo

    def _B_ref(x, w1, b1, w2, b2):
        B, S, D = x.shape
        h = _layernorm(x, axis=-1)
        u = torch.einsum("bsd,sf->bdf", h, w1) + b1
        u = _gelu(u)
        y = torch.einsum("bdf,fs->bds", u, w2) + b2
        return (lambda x, *d: x.permute(*d))(y, 0, 2, 1)

    x = A_x
    xn = _layernorm(x, axis=-1)
    return x + _A_ref(xn, A_wqkv, A_wo) + _B_ref(xn, B_w1, B_b1, B_w2, B_b2)
```

```cpp
#include <cuda_runtime.h>
#include <cuda_bf16.h>
#include <cuda.h>
#include <stdint.h>

#define QE 3
#define PF1 1
#define PF2 1
#define POLL_NS 40
#define INFL 1
#define CLUSTER 2

namespace {

constexpr int S_ = 2048, D_ = 448, F_ = 1792;
constexpr int NCTA = 128, NG1 = 112, NTHREADS = 384;
constexpr int NSLOT = 7, SLOT = 24576, TILEB = 14336, SLAB = 3584;
constexpr int ATT_TILE = 11 * 512;
constexpr int OFF_ATT = NSLOT * SLOT;
constexpr int OFF_CS = OFF_ATT + 8 * ATT_TILE;
constexpr int OFF_ST = OFF_CS + 768;
constexpr int OFF_BAR = OFF_ST + 1024;
constexpr int SMEM_BYTES = OFF_BAR + 256;
constexpr float LN_EPS = 1e-5f;
constexpr int SPIN_LIMIT = 1 << 22;

__device__ __align__(1024) uint8_t g_H[32 * 4 * TILEB];
__device__ __align__(1024) uint8_t g_U[28 * 4 * TILEB];
__device__ __align__(1024) __nv_bfloat16 g_O[S_ * D_];
__device__ __align__(128) float2 g_stats[S_];
__device__ __align__(128) float g_colsum[3 * D_];
__device__ __align__(128) uint4 g_halo[NCTA][7 * 32];
__device__ __align__(128) uint32_t g_flagH[32];
__device__ __align__(128) uint32_t g_flagU[4][32];
__device__ __align__(128) uint32_t g_flagO[32];
__device__ __align__(128) uint32_t g_flagHalo[NCTA];
__device__ __align__(128) uint32_t g_flagCS[32];
__device__ __align__(128) uint32_t g_epoch[NCTA];

#define TS(i)
#define TS0(i)

struct Params {
    CUtensorMap tmX, tmWqkv, tmW1, tmW2, tmO, tmWo;
    const __nv_bfloat16 *x, *wqkv, *wo, *w1, *b1, *w2, *b2;
    __nv_bfloat16* out;
};

__device__ __forceinline__ void spin_guard(uint32_t it) {
    asm volatile("{\n.reg .pred p;\nsetp.gt.u32 p, %0, %1;\n@p st.global.u32 [%2], %0;\n}" ::"r"(it), "n"(SPIN_LIMIT), "l"(0ull) : "memory");
}
__device__ __forceinline__ void mbar_init(uint32_t b, uint32_t c) { asm volatile("mbarrier.init.shared::cta.b64 [%0], %1;" ::"r"(b), "r"(c) : "memory"); }
__device__ __forceinline__ void mbar_expect(uint32_t b, uint32_t tx) { asm volatile("mbarrier.arrive.expect_tx.shared::cta.b64 _, [%0], %1;" ::"r"(b), "r"(tx) : "memory"); }
__device__ __forceinline__ void mbar_arrive(uint32_t b, uint32_t n) { asm volatile("mbarrier.arrive.shared::cta.b64 _, [%0], %1;" ::"r"(b), "r"(n) : "memory"); }
__device__ __forceinline__ void mbar_wait(uint32_t b, uint32_t parity) {
    uint32_t ok, it = 0;
    do {
        asm volatile("{\n.reg .pred p;\nmbarrier.try_wait.parity.shared::cta.b64 p, [%1], %2;\nselp.u32 %0, 1, 0, p;\n}" : "=r"(ok) : "r"(b), "r"(parity) : "memory");
        spin_guard(++it);
    } while (!ok);
}
__device__ __forceinline__ void tma2d(uint32_t dst, const CUtensorMap* tm, uint32_t bar, int c0, int c1) {
    asm volatile("cp.async.bulk.tensor.2d.shared::cluster.global.mbarrier::complete_tx::bytes [%0], [%1, {%3, %4}], [%2];" ::"r"(dst), "l"(tm), "r"(bar), "r"(c0), "r"(c1) : "memory");
}
__device__ __forceinline__ void tma3d(uint32_t dst, const CUtensorMap* tm, uint32_t bar, int c0, int c1, int c2) {
    asm volatile("cp.async.bulk.tensor.3d.shared::cluster.global.mbarrier::complete_tx::bytes [%0], [%1, {%3, %4, %5}], [%2];" ::"r"(dst), "l"(tm), "r"(bar), "r"(c0), "r"(c1), "r"(c2) : "memory");
}
__device__ __forceinline__ void bulk_load(uint32_t dst, const void* src, uint32_t bytes, uint32_t bar) {
    asm volatile("cp.async.bulk.shared::cluster.global.mbarrier::complete_tx::bytes [%0], [%1], %2, [%3];" ::"r"(dst), "l"(src), "r"(bytes), "r"(bar) : "memory");
}
__device__ __forceinline__ void l2_prefetch(const void* p, uint32_t bytes) { asm volatile("cp.async.bulk.prefetch.L2.global [%0], %1;" ::"l"(p), "r"(bytes) : "memory"); }
__device__ __forceinline__ uint32_t ld_acquire(const uint32_t* p) { uint32_t v; asm volatile("ld.acquire.gpu.global.u32 %0, [%1];" : "=r"(v) : "l"(p) : "memory"); return v; }
__device__ __forceinline__ uint32_t ld_relaxed(const uint32_t* p) { uint32_t v; asm volatile("ld.relaxed.gpu.global.u32 %0, [%1];" : "=r"(v) : "l"(p) : "memory"); return v; }
__device__ __forceinline__ void red_release(uint32_t* p) { asm volatile("red.release.gpu.global.add.u32 [%0], 1;" ::"l"(p) : "memory"); }
__device__ __forceinline__ void fence_async_global() { asm volatile("fence.proxy.async.global;" ::: "memory"); }
__device__ __forceinline__ void wait_flag(const uint32_t* p, uint32_t target) {
    uint32_t it = 0;
    while (ld_acquire(p) != target) { __nanosleep(POLL_NS); spin_guard(++it); }
}
__device__ __forceinline__ void bar_sync(int id, int n) { asm volatile("bar.sync %0, %1;" ::"r"(id), "r"(n) : "memory"); }
__device__ __forceinline__ void bar_arrive(int id, int n) { asm volatile("bar.arrive %0, %1;" ::"r"(id), "r"(n) : "memory"); }
__device__ __forceinline__ void wg_fence() { asm volatile("wgmma.fence.sync.aligned;" ::: "memory"); }
__device__ __forceinline__ void wg_commit() { asm volatile("wgmma.commit_group.sync.aligned;" ::: "memory"); }
template <int N> __device__ __forceinline__ void wg_wait() { asm volatile("wgmma.wait_group.sync.aligned %0;" ::"n"(N) : "memory"); }
template <int N> __device__ __forceinline__ void pin(float (&d)[N]) {
#pragma unroll
    for (int i = 0; i < N; i++) asm volatile("" : "+f"(d[i])::"memory");
}
__device__ __forceinline__ constexpr uint64_t desc_hi(uint32_t lbo, uint32_t sbo, uint32_t swz) {
    return ((uint64_t)(lbo >> 4) << 16) | ((uint64_t)(sbo >> 4) << 32) | ((uint64_t)swz << 62);
}
__device__ __forceinline__ uint32_t desc_lo(uint32_t addr) { return (addr & 0x3FFFFu) >> 4; }
__device__ __forceinline__ uint32_t pack2(float lo, float hi) { uint32_t r; asm("cvt.rn.bf16x2.f32 %0, %1, %2;" : "=r"(r) : "f"(hi), "f"(lo)); return r; }
__device__ __forceinline__ float bf_lo(uint32_t v) { return __uint_as_float(v << 16); }
__device__ __forceinline__ float bf_lo_late(uint32_t v) { float f; asm volatile("shl.b32 %0, %1, 16;" : "=f"(f) : "r"(v)); return f; }
__device__ __forceinline__ float bf_hi(uint32_t v) { return __uint_as_float(v & 0xffff0000u); }
__device__ __forceinline__ uint32_t movm(uint32_t a) { uint32_t d; asm volatile("movmatrix.sync.aligned.m8n8.trans.b16 %0, %1;" : "=r"(d) : "r"(a)); return d; }
__device__ __forceinline__ void stsm4(uint32_t a, uint32_t r0, uint32_t r1, uint32_t r2, uint32_t r3) {
    asm volatile("stmatrix.sync.aligned.m8n8.x4.shared.b16 [%0], {%1, %2, %3, %4};" ::"r"(a), "r"(r0), "r"(r1), "r"(r2), "r"(r3) : "memory");
}
__device__ __forceinline__ void sts4(uint32_t a, uint32_t r0, uint32_t r1, uint32_t r2, uint32_t r3) {
    asm volatile("st.shared.v4.b32 [%0], {%1, %2, %3, %4};" ::"r"(a), "r"(r0), "r"(r1), "r"(r2), "r"(r3) : "memory");
}
__device__ __forceinline__ uint4 lds4(uint32_t a) { uint4 v; asm volatile("ld.shared.v4.b32 {%0, %1, %2, %3}, [%4];" : "=r"(v.x), "=r"(v.y), "=r"(v.z), "=r"(v.w) : "r"(a) : "memory"); return v; }
__device__ __forceinline__ float2 lds2f(uint32_t a) { float2 v; asm volatile("ld.shared.v2.f32 {%0, %1}, [%2];" : "=f"(v.x), "=f"(v.y) : "r"(a) : "memory"); return v; }
__device__ __forceinline__ void mma16816(float (&c)[4], uint32_t a0, uint32_t a1, uint32_t a2, uint32_t a3, uint32_t b0, uint32_t b1) {
    asm volatile("mma.sync.aligned.m16n8k16.row.col.f32.bf16.bf16.f32 {%0, %1, %2, %3}, {%4, %5, %6, %7}, {%8, %9}, {%0, %1, %2, %3};"
                 : "+f"(c[0]), "+f"(c[1]), "+f"(c[2]), "+f"(c[3]) : "r"(a0), "r"(a1), "r"(a2), "r"(a3), "r"(b0), "r"(b1));
}
__device__ __forceinline__ float gelu_tanh(float u) {
    float z = u * fmaf(u * u, 0.044715f * 0.7978845608028654f, 0.7978845608028654f), t;
    asm("tanh.approx.f32 %0, %1;" : "=f"(t) : "f"(z));
    float hu = 0.5f * u;
    return fmaf(hu, t, hu);
}

template <int TA, int TB>
__device__ __forceinline__ void wgmma_n112(float (&d)[56], uint64_t da, uint64_t db, int accumulate) {
    asm volatile("{\n.reg .pred p;\nsetp.ne.b32 p, %58, 0;\n"
        "wgmma.mma_async.sync.aligned.m64n112k16.f32.bf16.bf16 {"
        "%0, %1, %2, %3, %4, %5, %6, %7, %8, %9, %10, %11, %12, %13, %14, %15, "
        "%16, %17, %18, %19, %20, %21, %22, %23, %24, %25, %26, %27, %28, %29, %30, %31, "
        "%32, %33, %34, %35, %36, %37, %38, %39, %40, %41, %42, %43, %44, %45, %46, %47, "
        "%48, %49, %50, %51, %52, %53, %54, %55"
        "}, %56, %57, p, 1, 1, %59, %60;\n}\n"
        : "+f"(d[0]), "+f"(d[1]), "+f"(d[2]), "+f"(d[3]), "+f"(d[4]), "+f"(d[5]), "+f"(d[6]), "+f"(d[7]),
          "+f"(d[8]), "+f"(d[9]), "+f"(d[10]), "+f"(d[11]), "+f"(d[12]), "+f"(d[13]), "+f"(d[14]), "+f"(d[15]),
          "+f"(d[16]), "+f"(d[17]), "+f"(d[18]), "+f"(d[19]), "+f"(d[20]), "+f"(d[21]), "+f"(d[22]), "+f"(d[23]),
          "+f"(d[24]), "+f"(d[25]), "+f"(d[26]), "+f"(d[27]), "+f"(d[28]), "+f"(d[29]), "+f"(d[30]), "+f"(d[31]),
          "+f"(d[32]), "+f"(d[33]), "+f"(d[34]), "+f"(d[35]), "+f"(d[36]), "+f"(d[37]), "+f"(d[38]), "+f"(d[39]),
          "+f"(d[40]), "+f"(d[41]), "+f"(d[42]), "+f"(d[43]), "+f"(d[44]), "+f"(d[45]), "+f"(d[46]), "+f"(d[47]),
          "+f"(d[48]), "+f"(d[49]), "+f"(d[50]), "+f"(d[51]), "+f"(d[52]), "+f"(d[53]), "+f"(d[54]), "+f"(d[55])
        : "l"(da), "l"(db), "r"(accumulate), "n"(TA), "n"(TB));
}

template <int TA, int TB>
__device__ __forceinline__ void wgmma_n184(float (&d)[92], uint64_t da, uint64_t db, int accumulate) {
    asm volatile("{\n.reg .pred p;\nsetp.ne.b32 p, %94, 0;\n"
        "wgmma.mma_async.sync.aligned.m64n184k16.f32.bf16.bf16 {"
        "%0, %1, %2, %3, %4, %5, %6, %7, %8, %9, %10, %11, %12, %13, %14, %15, "
        "%16, %17, %18, %19, %20, %21, %22, %23, %24, %25, %26, %27, %28, %29, %30, %31, "
        "%32, %33, %34, %35, %36, %37, %38, %39, %40, %41, %42, %43, %44, %45, %46, %47, "
        "%48, %49, %50, %51, %52, %53, %54, %55, %56, %57, %58, %59, %60, %61, %62, %63, "
        "%64, %65, %66, %67, %68, %69, %70, %71, %72, %73, %74, %75, %76, %77, %78, %79, "
        "%80, %81, %82, %83, %84, %85, %86, %87, %88, %89, %90, %91"
        "}, %92, %93, p, 1, 1, %95, %96;\n}\n"
        : "+f"(d[0]), "+f"(d[1]), "+f"(d[2]), "+f"(d[3]), "+f"(d[4]), "+f"(d[5]), "+f"(d[6]), "+f"(d[7]),
          "+f"(d[8]), "+f"(d[9]), "+f"(d[10]), "+f"(d[11]), "+f"(d[12]), "+f"(d[13]), "+f"(d[14]), "+f"(d[15]),
          "+f"(d[16]), "+f"(d[17]), "+f"(d[18]), "+f"(d[19]), "+f"(d[20]), "+f"(d[21]), "+f"(d[22]), "+f"(d[23]),
          "+f"(d[24]), "+f"(d[25]), "+f"(d[26]), "+f"(d[27]), "+f"(d[28]), "+f"(d[29]), "+f"(d[30]), "+f"(d[31]),
          "+f"(d[32]), "+f"(d[33]), "+f"(d[34]), "+f"(d[35]), "+f"(d[36]), "+f"(d[37]), "+f"(d[38]), "+f"(d[39]),
          "+f"(d[40]), "+f"(d[41]), "+f"(d[42]), "+f"(d[43]), "+f"(d[44]), "+f"(d[45]), "+f"(d[46]), "+f"(d[47]),
          "+f"(d[48]), "+f"(d[49]), "+f"(d[50]), "+f"(d[51]), "+f"(d[52]), "+f"(d[53]), "+f"(d[54]), "+f"(d[55]),
          "+f"(d[56]), "+f"(d[57]), "+f"(d[58]), "+f"(d[59]), "+f"(d[60]), "+f"(d[61]), "+f"(d[62]), "+f"(d[63]),
          "+f"(d[64]), "+f"(d[65]), "+f"(d[66]), "+f"(d[67]), "+f"(d[68]), "+f"(d[69]), "+f"(d[70]), "+f"(d[71]),
          "+f"(d[72]), "+f"(d[73]), "+f"(d[74]), "+f"(d[75]), "+f"(d[76]), "+f"(d[77]), "+f"(d[78]), "+f"(d[79]),
          "+f"(d[80]), "+f"(d[81]), "+f"(d[82]), "+f"(d[83]), "+f"(d[84]), "+f"(d[85]), "+f"(d[86]), "+f"(d[87]),
          "+f"(d[88]), "+f"(d[89]), "+f"(d[90]), "+f"(d[91])
        : "l"(da), "l"(db), "r"(accumulate), "n"(TA), "n"(TB));
}

struct Ring {
    int slot; uint32_t ph;
    __device__ __forceinline__ void set(int job, uint32_t flip) { slot = job % NSLOT; ph = ((job / NSLOT) & 1) ^ flip; }
    __device__ __forceinline__ void next() { if (++slot == NSLOT) { slot = 0; ph ^= 1; } }
};

__device__ __forceinline__ void qkv_blocks(float (&acc)[92], Ring& r, int n, int first, uint32_t sbase, int wg, bool lead) {
    const uint32_t full = sbase + OFF_BAR, empty = full + 64;
    const uint64_t dA0 = desc_hi(16, 1024, 1) | desc_lo(sbase + wg * 8192), dB0 = desc_hi(8192, 1024, 1) | desc_lo(sbase);
    int p0 = 0, p1 = 0;
#pragma unroll 1
    for (int i = 0; i < n; i++) {
        const int s0 = r.slot; mbar_wait(full + 8 * s0, r.ph); r.next();
        const int s1 = r.slot; mbar_wait(full + 8 * s1, r.ph); r.next();
        const uint64_t dA = dA0 + s0 * (SLOT >> 4), dB = dB0 + s1 * (SLOT >> 4);
        wg_fence();
        wgmma_n184<0, 1>(acc, dA, dB, !(first && i == 0));
#pragma unroll
        for (int k = 1; k < 4; k++) wgmma_n184<0, 1>(acc, dA + k * 2, dB + k * 128, 1);
        wg_commit();
        wg_wait<1>();
        if (i > 0 && lead) { mbar_arrive(empty + 8 * p0, 1); mbar_arrive(empty + 8 * p1, 1); }
        p0 = s0; p1 = s1;
    }
    wg_wait<0>();
    if (lead) { mbar_arrive(empty + 8 * p0, 1); mbar_arrive(empty + 8 * p1, 1); }
}

template <int TA, int ASTEP, int BSTEP, bool SIGNAL_LAST>
__device__ __forceinline__ void tile_blocks(float (&acc)[56], Ring& r, int n, uint32_t sbase, uint64_t hiA, uint64_t hiB, bool lead) {
    const uint32_t full = sbase + OFF_BAR, empty = full + 64;
    const uint64_t dA0 = hiA | desc_lo(sbase), dB0 = hiB | desc_lo(sbase + 8192);
    int rel = r.slot;
#pragma unroll 1
    for (int i = 0; i < n; i++) {
        const int s = r.slot; mbar_wait(full + 8 * s, r.ph); r.next();
        const uint64_t dA = dA0 + s * (SLOT >> 4), dB = dB0 + s * (SLOT >> 4);
        wg_fence();
#pragma unroll
        for (int k = 0; k < 4; k++) wgmma_n112<TA, 1>(acc, dA + k * ASTEP, dB + k * BSTEP, 1);
        wg_commit();
        if (SIGNAL_LAST && i == n - 1) bar_arrive(1, 256);
        wg_wait<INFL>();
        if (i >= INFL) { if (lead) mbar_arrive(empty + 8 * rel, 2); if (++rel == NSLOT) rel = 0; }
    }
    wg_wait<0>();
#pragma unroll
    for (int i = 0; i < INFL; i++) { if (lead) mbar_arrive(empty + 8 * rel, 2); if (++rel == NSLOT) rel = 0; }
}

__device__ __forceinline__ void qkv_dump(float (&acc)[92], uint32_t sbase, int tile, int lane, uint4* halo) {
    const float2 st0 = lds2f(sbase + OFF_ST + (tile * 16 + (lane >> 2)) * 8), st1 = lds2f(sbase + OFF_ST + (tile * 16 + 8 + (lane >> 2)) * 8);
    const uint32_t dst = sbase + OFF_ATT + tile * ATT_TILE + lane * 16;
    const uint32_t csa = sbase + OFF_CS + (lane & 3) * 8;
#pragma unroll
    for (int v = 0; v < 11; v++) {
        uint32_t fr[4] = {0u, 0u, 0u, 0u};
#pragma unroll
        for (int e = 0; e < 2; e++) {
            const int i = 2 * v + e;
            if (i < 21) {
                const int p = i < 7 ? 1 : i < 14 ? 2 : 0, ga = p * 8 + i % 7, a = ga * 4;
                const float2 cs = lds2f(csa + ga * 32);
                uint32_t lo = pack2(st0.y * fmaf(-st0.x, cs.x, acc[a]), st0.y * fmaf(-st0.x, cs.y, acc[a + 1]));
                uint32_t hi = pack2(st1.y * fmaf(-st1.x, cs.x, acc[a + 2]), st1.y * fmaf(-st1.x, cs.y, acc[a + 3]));
                if (p == 2) { lo = movm(lo); hi = movm(hi); }
                fr[2 * e] = lo; fr[2 * e + 1] = hi;
            }
        }
        sts4(dst + v * 512, fr[0], fr[1], fr[2], fr[3]);
        if (v < 7 && halo) __stcg(halo + v * 32 + lane, make_uint4(fr[0], fr[1], fr[2], fr[3]));
    }
}

__device__ __forceinline__ void attend(const uint32_t (&cur)[44], const uint32_t (&prv)[28], bool no_prev, int lane, __nv_bfloat16* orow) {
    const int c = lane & 3, r = lane >> 2;
    const bool odd = r & 1, near = 2 * c <= (r & 6);
    const float sc = 0.1889822365046136f * 1.4426950408889634f;
    float o3[2][4];
#pragma unroll
    for (int h = 0; h < 2; h++) {
        const int g0 = h * 3;
        uint32_t q[8];
#pragma unroll
        for (int i = 0; i < 8; i++) q[i] = cur[28 + g0 * 2 + i];
        const bool mine = h == 0 ? c < 2 : c >= 2;
        const int m = h == 0 ? 6 : 0;
        q[m] = mine ? q[m] : 0u; q[m + 1] = mine ? q[m + 1] : 0u;
        float s[4][4];
#pragma unroll
        for (int j = 0; j < 4; j++) {
            s[j][0] = s[j][1] = s[j][2] = s[j][3] = 0.f;
#pragma unroll
            for (int k = 0; k < 2; k++) {
                const int g = g0 + 2 * k, b = g * 2 + (j & 1);
                mma16816(s[j], q[4 * k], q[4 * k + 1], q[4 * k + 2], q[4 * k + 3], j < 2 ? prv[b] : cur[b], j < 2 ? prv[b + 2] : cur[b + 2]);
            }
        }
        float e[4][2];
#pragma unroll
        for (int j = 0; j < 4; j++) { e[j][0] = odd ? s[j][1] : s[j][0]; e[j][1] = odd ? s[j][3] : s[j][2]; }
        const float NEG = -1e30f;
        float a0 = no_prev ? NEG : e[1][0], b0 = near ? e[2][0] : (no_prev ? NEG : e[0][0]);
        float a1 = e[2][1], b1 = near ? e[3][1] : (no_prev ? NEG : e[1][1]);
        float m0 = fmaxf(a0, b0), m1 = fmaxf(a1, b1);
        m0 = fmaxf(m0, __shfl_xor_sync(~0u, m0, 1)); m1 = fmaxf(m1, __shfl_xor_sync(~0u, m1, 1));
        m0 = fmaxf(m0, __shfl_xor_sync(~0u, m0, 2)); m1 = fmaxf(m1, __shfl_xor_sync(~0u, m1, 2));
        a0 = exp2f((a0 - m0) * sc); b0 = exp2f((b0 - m0) * sc); a1 = exp2f((a1 - m1) * sc); b1 = exp2f((b1 - m1) * sc);
        float t0 = a0 + b0, t1 = a1 + b1;
        t0 += __shfl_xor_sync(~0u, t0, 1); t1 += __shfl_xor_sync(~0u, t1, 1);
        t0 += __shfl_xor_sync(~0u, t0, 2); t1 += __shfl_xor_sync(~0u, t1, 2);
        t0 = __frcp_rn(t0); t1 = __frcp_rn(t1);
        const int sh = odd ? 16 : 0;
        const uint32_t pa0 = (pack2(a0 * t0, 0.f) & 0xffffu) << sh, pb0 = (pack2(b0 * t0, 0.f) & 0xffffu) << sh;
        const uint32_t pa1 = (pack2(a1 * t1, 0.f) & 0xffffu) << sh, pb1 = (pack2(b1 * t1, 0.f) & 0xffffu) << sh;
        const uint32_t A0 = near ? 0u : pb0, A2 = pa0, A3 = near ? 0u : pb1;
        const uint32_t B0 = near ? pb0 : 0u, B1 = pa1, B3 = near ? pb1 : 0u;
#pragma unroll
        for (int gg = 0; gg < 4; gg++) {
            const int g = g0 + gg;
            float o[4] = {0.f, 0.f, 0.f, 0.f};
            mma16816(o, A0, 0u, A2, A3, prv[14 + 2 * g], prv[15 + 2 * g]);
            mma16816(o, B0, B1, 0u, B3, cur[14 + 2 * g], cur[15 + 2 * g]);
            if (g == 3) {
#pragma unroll
                for (int i = 0; i < 4; i++) o3[h][i] = o[i];
            } else {
                *(uint32_t*)(orow + g * 8) = pack2(o[0], o[1]);
                *(uint32_t*)(orow + 8 * D_ + g * 8) = pack2(o[2], o[3]);
            }
        }
    }
    const bool lo = c < 2;
    *(uint32_t*)(orow + 24) = pack2(lo ? o3[0][0] : o3[1][0], lo ? o3[0][1] : o3[1][1]);
    *(uint32_t*)(orow + 8 * D_ + 24) = pack2(lo ? o3[0][2] : o3[1][2], lo ? o3[0][3] : o3[1][3]);
}

__device__ __forceinline__ float oct_sum(float v) {
    v += __shfl_xor_sync(~0u, v, 1); v += __shfl_xor_sync(~0u, v, 2); v += __shfl_xor_sync(~0u, v, 4);
    return v;
}
__device__ __forceinline__ void row_stats(const float (&f)[56], float& mean, float& rstd) {
    float s0 = 0.f, s1 = 0.f, s2 = 0.f, s3 = 0.f;
#pragma unroll
    for (int i = 0; i < 56; i += 4) { s0 += f[i]; s1 += f[i + 1]; s2 += f[i + 2]; s3 += f[i + 3]; }
    mean = oct_sum((s0 + s1) + (s2 + s3)) * (1.f / D_);
    s0 = s1 = s2 = s3 = 0.f;
#pragma unroll
    for (int i = 0; i < 56; i += 4) {
        float d0 = f[i] - mean, d1 = f[i + 1] - mean, d2 = f[i + 2] - mean, d3 = f[i + 3] - mean;
        s0 = fmaf(d0, d0, s0); s1 = fmaf(d1, d1, s1); s2 = fmaf(d2, d2, s2); s3 = fmaf(d3, d3, s3);
    }
    rstd = rsqrtf(oct_sum((s0 + s1) + (s2 + s3)) * (1.f / D_) + LN_EPS);
}

__global__ void __launch_bounds__(NTHREADS, 1) fused_kernel(const __grid_constant__ Params P) {
    extern __shared__ __align__(1024) uint8_t smem[];
    const uint32_t sbase = (uint32_t)__cvta_generic_to_shared(smem);
    const uint32_t full = sbase + OFF_BAR, empty = full + 64;
    const int c = blockIdx.x, lane = threadIdx.x & 31;
    const int warp = __shfl_sync(~0u, threadIdx.x >> 5, 0);
    const int tb = c >> 3, hp = c & 7, mt = c >> 2, nt = c & 3;
    const bool has_g1 = c < NG1;
    const int job_late = 2 * QE + (has_g1 ? 32 : 0);

    if (threadIdx.x == 256) {
        TS(0);
        for (int i = 0; i < NSLOT; i++) { mbar_init(full + 8 * i, 1); mbar_init(empty + 8 * i, 2); }
        asm volatile("fence.mbarrier_init.release.cluster;" ::: "memory");
        asm volatile("fence.proxy.async.shared::cta;" ::: "memory");
#pragma unroll
        for (int kb = 0; kb < 3; kb++) {
            mbar_expect(full + 16 * kb, 16384);
            tma2d(sbase + 2 * kb * SLOT, &P.tmX, full + 16 * kb, kb * 64, tb * 128);
            mbar_expect(full + 16 * kb + 8, 24576);
            tma3d(sbase + (2 * kb + 1) * SLOT, &P.tmWqkv, full + 16 * kb + 8, hp * 56, kb * 64, 0);
        }
    }
    uint4 xv[7];
    if (warp < 4) {
        const uint4* xr = (const uint4*)(P.x + (c * 16 + warp * 4 + (lane >> 3)) * D_) + (lane & 7);
#pragma unroll
        for (int i = 0; i < 7; i++) xv[i] = __ldg(xr + 8 * i);
    }
    uint32_t braw0 = 0, braw1 = 0;
    if (warp < 8 && (warp >= 4 || has_g1)) {
        const uint16_t* bp = (const uint16_t*)(warp < 4 ? P.b1 : P.b2) + mt * 64 + (warp & 3) * 16 + (lane >> 2);
        braw0 = __ldg(bp); braw1 = __ldg(bp + 8);
    }
    const uint32_t ep = ld_relaxed(&g_epoch[c]) + 1;
    __syncthreads();

    if (warp >= 8) {
        asm volatile("setmaxnreg.dec.sync.aligned.u32 72;");
        if (warp == 8) {
            if (lane == 0) {
                Ring r; r.set(6, 1);
                auto qkv_jobs = [&](int k0, int k1) {
#pragma unroll 1
                    for (int kb = k0; kb < k1; kb++) {
                        mbar_wait(empty + 8 * r.slot, r.ph); mbar_expect(full + 8 * r.slot, 16384);
                        tma2d(sbase + r.slot * SLOT, &P.tmX, full + 8 * r.slot, kb * 64, tb * 128); r.next();
                        mbar_wait(empty + 8 * r.slot, r.ph); mbar_expect(full + 8 * r.slot, 24576);
                        tma3d(sbase + r.slot * SLOT, &P.tmWqkv, full + 8 * r.slot, hp * 56, kb * 64, 0); r.next();
                    }
                };
                qkv_jobs(3, QE);
                if (has_g1) {
#pragma unroll 1
                    for (int kb = 0; kb < 32; kb++) {
                        mbar_wait(empty + 8 * r.slot, r.ph); mbar_expect(full + 8 * r.slot, 8192 + TILEB);
                        tma2d(sbase + r.slot * SLOT, &P.tmW1, full + 8 * r.slot, mt * 64, kb * 64); r.next();
                    }
                }
                qkv_jobs(QE, 7);
#pragma unroll 1
                for (int kb = 0; kb < 28; kb++) {
                    mbar_wait(empty + 8 * r.slot, r.ph); mbar_expect(full + 8 * r.slot, 8192 + TILEB);
                    tma2d(sbase + r.slot * SLOT, &P.tmW2, full + 8 * r.slot, mt * 64, kb * 64); r.next();
                }
#pragma unroll 1
                for (int kb = 0; kb < 7; kb++) {
                    mbar_wait(empty + 8 * r.slot, r.ph); mbar_expect(full + 8 * r.slot, 24576);
                    tma2d(sbase + r.slot * SLOT + 8192, &P.tmWo, full + 8 * r.slot, nt * 112, kb * 64);
                    tma2d(sbase + r.slot * SLOT + 16384, &P.tmWo, full + 8 * r.slot, nt * 112 + 64, kb * 64); r.next();
                }
            }
        } else if (warp == 9) {
            Ring r; r.set(6, 1);
            auto skip = [&](int n) {
#pragma unroll 1
                for (int i = 0; i < n; i++) { mbar_wait(empty + 8 * r.slot, r.ph); r.next(); }
            };
            auto dep_tiles = [&](const uint8_t* src, const uint32_t* flags, uint32_t target, int n, int tsi) {
                uint32_t ready = 0;
#pragma unroll 1
                for (int kb = 0; kb < n; kb++) {
                    if (!((ready >> kb) & 1)) {
                        uint32_t it = 0;
                        while (ready = __ballot_sync(~0u, ld_acquire(flags + lane) == target), !((ready >> kb) & 1)) { __nanosleep(POLL_NS); spin_guard(++it); }
                        __syncwarp();
                        fence_async_global();
                        if (lane == 0 && kb == 0) TS(tsi);
                    }
                    mbar_wait(empty + 8 * r.slot, r.ph);
                    if (lane == 0) bulk_load(sbase + r.slot * SLOT + 8192, src + (size_t)kb * 4 * TILEB, TILEB, full + 8 * r.slot);
                    r.next();
                }
            };
            skip(2 * QE - 6);
            if (has_g1) dep_tiles(g_H + nt * TILEB, g_flagH, 16 * ep, 32, 16);
            skip(2 * (7 - QE));
            dep_tiles(g_U + nt * TILEB, g_flagU[nt], 4 * ep, 28, 17);
            if (lane == 0) {
                wait_flag(&g_flagO[mt], 32 * ep);
                fence_async_global();
                TS(18);
#pragma unroll 1
                for (int kb = 0; kb < 7; kb++) {
                    mbar_wait(empty + 8 * r.slot, r.ph);
                    tma2d(sbase + r.slot * SLOT, &P.tmO, full + 8 * r.slot, kb * 64, mt * 64); r.next();
                }
            }
        } else if (warp == 10) {
            if (c < 84) {
                const uint4* wp = (const uint4*)(P.wqkv + (lane >> 1) * (3 * D_) + c * 16) + (lane & 1);
                float s[8];
#pragma unroll
                for (int i = 0; i < 8; i++) s[i] = 0.f;
#pragma unroll 1
                for (int i0 = 0; i0 < 28; i0 += 7) {
                    uint4 v[7];
#pragma unroll
                    for (int i = 0; i < 7; i++) v[i] = __ldg(wp + (size_t)(i0 + i) * 16 * (3 * D_ / 8));
#pragma unroll
                    for (int i = 0; i < 7; i++) {
                        s[0] += bf_lo(v[i].x); s[1] += bf_hi(v[i].x); s[2] += bf_lo(v[i].y); s[3] += bf_hi(v[i].y);
                        s[4] += bf_lo(v[i].z); s[5] += bf_hi(v[i].z); s[6] += bf_lo(v[i].w); s[7] += bf_hi(v[i].w);
                    }
                }
#pragma unroll
                for (int i = 0; i < 8; i++) {
#pragma unroll
                    for (int o = 2; o < 32; o <<= 1) s[i] += __shfl_xor_sync(~0u, s[i], o);
                }
                if (lane < 2) {
                    float4* dst = (float4*)(g_colsum + c * 16 + lane * 8);
                    __stcg(dst, make_float4(s[0], s[1], s[2], s[3])); __stcg(dst + 1, make_float4(s[4], s[5], s[6], s[7]));
                }
                __syncwarp();
                if (lane == 0) red_release(&g_flagCS[0]);
            }
            mbar_wait(full + 8 * ((2 * QE) % NSLOT), ((2 * QE) / NSLOT) & 1);
            if (lane < 3) wait_flag(lane == 2 ? &g_flagCS[0] : &g_flagH[tb * 2 + lane], lane == 2 ? 84 * ep : 16 * ep);
            __syncwarp();
            const uint4 s0 = __ldcg((const uint4*)(g_stats + tb * 128) + lane), s1 = __ldcg((const uint4*)(g_stats + tb * 128) + 32 + lane);
            float2 cs[3];
#pragma unroll
            for (int p = 0; p < 3; p++) cs[p] = __ldcg((const float2*)(g_colsum + p * D_ + hp * 56) + min(lane, 27));
            sts4(sbase + OFF_ST + lane * 16, s0.x, s0.y, s0.z, s0.w); sts4(sbase + OFF_ST + 512 + lane * 16, s1.x, s1.y, s1.z, s1.w);
#pragma unroll
            for (int p = 0; p < 3; p++) asm volatile("st.shared.v2.f32 [%0], {%1, %2};" ::"r"(sbase + OFF_CS + p * 256 + lane * 8), "f"(cs[p].x), "f"(cs[p].y) : "memory");
            bar_arrive(2, 160); bar_arrive(4, 160);
            if (lane == 0) TS(20);
        } else {
            if (lane < 16) l2_prefetch(P.w1 + (size_t)(lane * 128 + c) * F_, F_ * 2);
            mbar_wait(full + 8 * 5, 0);
            if (PF2 && lane < 14) l2_prefetch(P.w2 + (size_t)(lane * 128 + c) * S_, S_ * 2);
            if (lane == 14 && c < 98) l2_prefetch(P.wo + (size_t)c * 2048, 4096);
        }
    } else {
        asm volatile("setmaxnreg.inc.sync.aligned.u32 216;");
        const bool lead = (threadIdx.x & 127) == 0;
        const int w = warp & 3;
        float accq[92];
        float acc[56];
        Ring r; r.set(0, 0);
        if (warp < 4) {
            {
                float f[56];
#pragma unroll
                for (int i = 0; i < 7; i++) {
                    f[8 * i] = bf_lo(xv[i].x); f[8 * i + 1] = bf_hi(xv[i].x); f[8 * i + 2] = bf_lo(xv[i].y); f[8 * i + 3] = bf_hi(xv[i].y);
                    f[8 * i + 4] = bf_lo(xv[i].z); f[8 * i + 5] = bf_hi(xv[i].z); f[8 * i + 6] = bf_lo(xv[i].w); f[8 * i + 7] = bf_hi(xv[i].w);
                }
                TS0(1);
                float mean, rstd;
                row_stats(f, mean, rstd);
                const int r16 = w * 4 + (lane >> 3);
                if ((lane & 7) == 0) __stcg(&g_stats[c * 16 + r16], make_float2(mean, rstd));
#pragma unroll
                for (int i = 0; i < 56; i += 2) {
                    const uint32_t p = pack2((f[i] - mean) * rstd, (f[i + 1] - mean) * rstd);
                    f[i] = bf_lo(p); f[i + 1] = bf_hi(p);
                }
                row_stats(f, mean, rstd);
                uint8_t* hb = g_H + (size_t)(c >> 2) * 4 * TILEB + (c & 3) * SLAB + r16 * 32 + (((lane ^ (r16 >> 2)) & 1) << 4);
#pragma unroll
                for (int i = 0; i < 7; i++) {
                    const int atom = ((lane & 7) + 8 * i) >> 1;
                    const int t = atom / 7;
                    uint4 o;
                    o.x = pack2((f[8 * i] - mean) * rstd, (f[8 * i + 1] - mean) * rstd); o.y = pack2((f[8 * i + 2] - mean) * rstd, (f[8 * i + 3] - mean) * rstd);
                    o.z = pack2((f[8 * i + 4] - mean) * rstd, (f[8 * i + 5] - mean) * rstd); o.w = pack2((f[8 * i + 6] - mean) * rstd, (f[8 * i + 7] - mean) * rstd);
                    __stcg((uint4*)(hb + t * TILEB + (atom - 7 * t) * 512), o);
                }
                __syncwarp();
                TS0(2);
                if (lane == 0) red_release(&g_flagH[c >> 2]);
                TS0(3);
            }
            qkv_blocks(accq, r, QE, 1, sbase, 0, lead);
            TS0(4);
            if (has_g1) {
                const float b0 = bf_lo_late(braw0), b1 = bf_lo_late(braw1);
#pragma unroll
                for (int i = 0; i < 56; i += 4) { acc[i] = acc[i + 1] = b0; acc[i + 2] = acc[i + 3] = b1; }
                tile_blocks<1, 128, SLAB / 16, true>(acc, r, 32, sbase, desc_hi(8192, 1024, 1), desc_hi(512, 256, 3), lead);
                pin(acc);
                TS0(5);
                const uint32_t stg = sbase + OFF_ATT + w * ATT_TILE;
                const int r16 = (lane & 7) + (lane & 8);
                const uint32_t sa = stg + r16 * 32 + ((((lane >> 4) ^ (r16 >> 2)) & 1) << 4);
#pragma unroll
                for (int a = 0; a < 7; a++) {
                    uint32_t p[4];
#pragma unroll
                    for (int i = 0; i < 4; i++) p[i] = pack2(gelu_tanh(acc[8 * a + 2 * i]), gelu_tanh(acc[8 * a + 2 * i + 1]));
                    stsm4(sa + a * 512, p[0], p[1], p[2], p[3]);
                }
                __syncwarp();
                uint4* ub = (uint4*)(g_U + (size_t)c * TILEB + w * SLAB) + lane;
#pragma unroll
                for (int a = 0; a < 7; a++) __stcg(ub + a * 32, lds4(stg + a * 512 + lane * 16));
                __syncwarp();
                TS0(6);
                if (lane == 0) red_release(&g_flagU[nt][mt]);
                TS0(7);
            } else {
                bar_arrive(1, 256);
            }
            qkv_blocks(accq, r, 7 - QE, 0, sbase, 0, lead);
            pin(accq);
            TS0(8);
            bar_sync(2, 160);
            qkv_dump(accq, sbase, w, lane, nullptr);
            bar_sync(3, 256);
            TS0(9);
#pragma unroll 1
            for (int it = 0; it < 2; it++) {
                const int tile = it == 0 ? 4 + w : w;
                uint32_t cur[44], prv[28];
                const uint32_t src = sbase + OFF_ATT + tile * ATT_TILE + lane * 16;
#pragma unroll
                for (int v = 0; v < 11; v++) { const uint4 t = lds4(src + v * 512); cur[4 * v] = t.x; cur[4 * v + 1] = t.y; cur[4 * v + 2] = t.z; cur[4 * v + 3] = t.w; }
                const bool no_prev = tile == 0 && tb == 0;
                if (tile > 0) {
#pragma unroll
                    for (int v = 0; v < 7; v++) { const uint4 t = lds4(src - ATT_TILE + v * 512); prv[4 * v] = t.x; prv[4 * v + 1] = t.y; prv[4 * v + 2] = t.z; prv[4 * v + 3] = t.w; }
                } else if (!no_prev) {
                    if (lane == 0) wait_flag(&g_flagHalo[c - 8], ep);
                    __syncwarp();
#pragma unroll
                    for (int v = 0; v < 7; v++) { const uint4 t = __ldcg(&g_halo[c - 8][v * 32 + lane]); prv[4 * v] = t.x; prv[4 * v + 1] = t.y; prv[4 * v + 2] = t.z; prv[4 * v + 3] = t.w; }
                } else {
#pragma unroll
                    for (int v = 0; v < 28; v++) prv[v] = 0u;
                }
                __syncwarp();
                attend(cur, prv, no_prev, lane, g_O + (size_t)(tb * 128 + tile * 16 + (lane >> 2)) * D_ + hp * 56 + (lane & 3) * 2);
                __syncwarp();
                TS0(21 + 2 * it);
                if (lane == 0) red_release(&g_flagO[tb * 2 + (tile >> 2)]);
                TS0(22 + 2 * it);
            }
            TS0(10);
        } else {
            qkv_blocks(accq, r, QE, 1, sbase, 1, lead);
            TS0(11);
            {
                const int row = mt * 64 + w * 16 + (lane >> 2);
                const float b0 = bf_lo_late(braw0), b1 = bf_lo_late(braw1);
                const uint32_t* xp = (const uint32_t*)(P.x + row * D_ + nt * 112) + (lane & 3);
#pragma unroll
                for (int g = 0; g < 14; g++) {
                    const uint32_t u0 = __ldg(xp + g * 4), u1 = __ldg(xp + 4 * D_ + g * 4);
                    acc[4 * g] = bf_lo(u0) + b0; acc[4 * g + 1] = bf_hi(u0) + b0; acc[4 * g + 2] = bf_lo(u1) + b1; acc[4 * g + 3] = bf_hi(u1) + b1;
                }
            }
            bar_sync(1, 256);
            r.set(job_late, 0);
            TS0(12);
            qkv_blocks(accq, r, 7 - QE, 0, sbase, 1, lead);
            pin(accq);
            bar_sync(4, 160);
            const bool pub = w == 3 && tb < 15;
            qkv_dump(accq, sbase, 4 + w, lane, pub ? g_halo[c] : nullptr);
            bar_arrive(3, 256);
            if (pub) { __syncwarp(); if (lane == 0) red_release(&g_flagHalo[c]); }
            TS0(13);
            pin(acc);
            tile_blocks<1, 128, SLAB / 16, false>(acc, r, 28, sbase, desc_hi(8192, 1024, 1), desc_hi(512, 256, 3), lead);
            TS0(14);
            tile_blocks<0, 2, 128, false>(acc, r, 7, sbase, desc_hi(16, 1024, 1), desc_hi(8192, 1024, 1), lead);
            pin(acc);
            TS0(15);
            const uint32_t stg = sbase + OFF_ATT + (4 + w) * ATT_TILE;
            const uint32_t sa = stg + ((lane & 7) + (lane & 8)) * 240 + (lane >> 4) * 16;
#pragma unroll
            for (int a = 0; a < 7; a++)
                stsm4(sa + a * 32, pack2(acc[8 * a], acc[8 * a + 1]), pack2(acc[8 * a + 2], acc[8 * a + 3]), pack2(acc[8 * a + 4], acc[8 * a + 5]), pack2(acc[8 * a + 6], acc[8 * a + 7]));
            __syncwarp();
            __nv_bfloat16* ob = P.out + (size_t)(mt * 64 + w * 16) * D_ + nt * 112;
#pragma unroll
            for (int i = 0; i < 7; i++) {
                const int idx = lane + 32 * i, row = idx / 14, ch = idx - row * 14;
                *(uint4*)(ob + row * D_ + ch * 8) = lds4(stg + row * 240 + ch * 16);
            }
            if (lead) g_epoch[c] = ep;
            TS0(19);
        }
    }
}

typedef CUresult (*EncodeFn)(CUtensorMap*, CUtensorMapDataType, cuuint32_t, void*, const cuuint64_t*, const cuuint64_t*, const cuuint32_t*, const cuuint32_t*,
                             CUtensorMapInterleave, CUtensorMapSwizzle, CUtensorMapL2promotion, CUtensorMapFloatOOBfill);

void make_map(EncodeFn enc, CUtensorMap* tm, const void* base, int rank, const cuuint64_t* dims, const cuuint64_t* strides, const cuuint32_t* box) {
    const cuuint32_t es[3] = {1, 1, 1};
    enc(tm, CU_TENSOR_MAP_DATA_TYPE_BFLOAT16, rank, (void*)base, dims, strides, box, es, CU_TENSOR_MAP_INTERLEAVE_NONE, CU_TENSOR_MAP_SWIZZLE_128B,
        CU_TENSOR_MAP_L2_PROMOTION_L2_128B, CU_TENSOR_MAP_FLOAT_OOB_FILL_NONE);
}
void make_map2(EncodeFn enc, CUtensorMap* tm, const void* base, int cols, int rows, int box_rows) {
    const cuuint64_t dims[2] = {(cuuint64_t)cols, (cuuint64_t)rows}, strides[1] = {(cuuint64_t)cols * 2};
    const cuuint32_t box[2] = {64, (cuuint32_t)box_rows};
    make_map(enc, tm, base, 2, dims, strides, box);
}

}

extern "C" void kernel_launch(void* const* d_in, const int* in_sizes, int n_in, void* d_out, int out_size) {
    static EncodeFn enc = nullptr;
    static void* o_ptr = nullptr;
    if (!enc) {
        void* fn = nullptr;
        cudaDriverEntryPointQueryResult qr;
        cudaGetDriverEntryPoint("cuTensorMapEncodeTiled", &fn, cudaEnableDefault, &qr);
        enc = (EncodeFn)fn;
        cudaGetSymbolAddress(&o_ptr, g_O);
        cudaFuncSetAttribute(fused_kernel, cudaFuncAttributeMaxDynamicSharedMemorySize, SMEM_BYTES);
    }
    Params P;
    P.x = (const __nv_bfloat16*)d_in[0]; P.wqkv = (const __nv_bfloat16*)d_in[1]; P.wo = (const __nv_bfloat16*)d_in[2];
    P.w1 = (const __nv_bfloat16*)d_in[4]; P.b1 = (const __nv_bfloat16*)d_in[5]; P.w2 = (const __nv_bfloat16*)d_in[6]; P.b2 = (const __nv_bfloat16*)d_in[7];
    P.out = (__nv_bfloat16*)d_out;
    make_map2(enc, &P.tmX, P.x, D_, S_, 128);
    make_map2(enc, &P.tmW1, P.w1, F_, S_, 64);
    make_map2(enc, &P.tmW2, P.w2, S_, F_, 64);
    make_map2(enc, &P.tmO, o_ptr, D_, S_, 64);
    make_map2(enc, &P.tmWo, P.wo, D_, D_, 64);
    {
        const cuuint64_t dims[3] = {D_, D_, 3}, strides[2] = {3 * D_ * 2, D_ * 2};
        const cuuint32_t box[3] = {64, 64, 3};
        make_map(enc, &P.tmWqkv, P.wqkv, 3, dims, strides, box);
    }
    cudaLaunchConfig_t cfg = {};
    cfg.gridDim = NCTA; cfg.blockDim = NTHREADS; cfg.dynamicSmemBytes = SMEM_BYTES; cfg.stream = cudaStreamPerThread;
    cudaLaunchAttribute at[1];
    at[0].id = cudaLaunchAttributeClusterDimension; at[0].val.clusterDim.x = CLUSTER; at[0].val.clusterDim.y = 1; at[0].val.clusterDim.z = 1;
    cfg.attrs = at; cfg.numAttrs = CLUSTER > 1 ? 1 : 0;
    cudaLaunchKernelEx(&cfg, fused_kernel, P);
}
```

```cpp
#include <cuda_runtime.h>
#include <cuda_bf16.h>
#include <cuda.h>
#include <stdint.h>

#define LAG 4
#define POLL_NS 20
#define PF1 0
#define PF2 0
#define QPRE 2
#define G1MAP 3

namespace {

constexpr int S_ = 2048, D_ = 448, F_ = 1792;
constexpr int NCTA = 128, NG1 = 112, NTHREADS = 384;
constexpr int NSLOT = 5, SLOT = 32768, QSLOT = 40960, TILEB = 14336, SLAB = 3584;
constexpr int OFF_STG = NSLOT * SLOT;
constexpr int KVROW = 456, QROW = 232, HALO = 4 * KVROW, QOFF = 36 * KVROW, PAR = QOFF + 32 * QROW;
constexpr int OFF_OST = OFF_STG + 47744;
constexpr int OFF_CS = OFF_OST + TILEB;
constexpr int OFF_ST = OFF_CS + 768;
constexpr int OFF_REC = OFF_ST + 1024;
constexpr int OFF_BAR = OFF_REC + 384;
constexpr int SMEM_BYTES = OFF_BAR + 512;
constexpr int B_QFULL = 0, B_QEMPTY = 56, B_FULL = 112, B_EMPTY = 152, B_HRDY = 192, B_XFREE = 200, B_X = 208, B_HALO = 224, NBAR = 29;
static_assert(2 * PAR <= 47744 && PAR % 16 == 0 && HALO % 16 == 0, "staging layout");
constexpr float LN_EPS = 1e-5f;
constexpr int SPIN_LIMIT = 1 << 22;

struct Scratch {
    uint8_t H[32 * 4 * TILEB];
    uint8_t U[28 * 4 * TILEB];
    __nv_bfloat16 O[S_ * D_];
    uint8_t halo[NCTA][2 * HALO];
    float rec[NCTA][96];
    uint32_t flagH[32];
    uint32_t flagU[4][32];
    uint32_t flagO[32];
    uint32_t flagHalo[NCTA];
    uint32_t epoch[NCTA];
};
__device__ __align__(1024) Scratch g_s;

#define TS(i)
#define TS0(i)
#define TSL(i)
#define TSDEP(i, v)
#define TSDUMP()

struct Params {
    CUtensorMap tmX, tmWqkv, tmW1, tmW2, tmO, tmOst, tmWo, tmOut;
    const __nv_bfloat16 *x, *wqkv, *wo, *w1, *b1, *w2, *b2;
    __nv_bfloat16* out;
};

__device__ __forceinline__ void spin_guard(uint32_t it) {
    asm volatile("{\n.reg .pred p;\nsetp.gt.u32 p, %0, %1;\n@p st.global.u32 [%2], %0;\n}" ::"r"(it), "n"(SPIN_LIMIT), "l"(0ull) : "memory");
}
__device__ __forceinline__ bool elect() {
    uint32_t p;
    asm volatile("{\n.reg .pred p;\nelect.sync _|p, 0xffffffff;\nselp.u32 %0, 1, 0, p;\n}" : "=r"(p));
    return p;
}
__device__ __forceinline__ uint32_t inc_late(uint32_t v) { asm volatile("add.u32 %0, %0, 1;" : "+r"(v)); return v; }
__device__ __forceinline__ void mbar_init(uint32_t b, uint32_t c) { asm volatile("mbarrier.init.shared::cta.b64 [%0], %1;" ::"r"(b), "r"(c) : "memory"); }
__device__ __forceinline__ void mbar_expect(uint32_t b, uint32_t tx) { asm volatile("mbarrier.arrive.expect_tx.shared::cta.b64 _, [%0], %1;" ::"r"(b), "r"(tx) : "memory"); }
__device__ __forceinline__ void mbar_arrive(uint32_t b) { asm volatile("mbarrier.arrive.shared::cta.b64 _, [%0];" ::"r"(b) : "memory"); }
__device__ __forceinline__ void mbar_arrive_remote(uint32_t b) { asm volatile("mbarrier.arrive.shared::cluster.b64 _, [%0];" ::"r"(b) : "memory"); }
#define MBAR_WAIT_ASM(SEM)                                                                                   \
    asm volatile("{\n.reg .pred p;\n.reg .u32 n;\nmov.u32 n, 0;\nWAIT:\nadd.u32 n, n, 1;\nsetp.gt.u32 p, n, %2;\n"       \
                 "@p st.global.u32 [%3], n;\nmbarrier.try_wait.parity" SEM ".shared::cta.b64 p, [%0], %1;\n@!p bra WAIT;\n}" \
                 ::"r"(b), "r"(parity), "n"(SPIN_LIMIT), "l"(0ull) : "memory")
__device__ __forceinline__ void mbar_wait(uint32_t b, uint32_t parity) { MBAR_WAIT_ASM(""); }
__device__ __forceinline__ void mbar_wait_cluster(uint32_t b) { const uint32_t parity = 0; MBAR_WAIT_ASM(".acquire.cluster"); }
__device__ __forceinline__ uint32_t mapa(uint32_t a, uint32_t rank) { uint32_t r; asm("mapa.shared::cluster.u32 %0, %1, %2;" : "=r"(r) : "r"(a), "r"(rank)); return r; }
__device__ __forceinline__ void tma2d(uint32_t dst, const CUtensorMap* tm, uint32_t bar, int c0, int c1) {
    asm volatile("cp.async.bulk.tensor.2d.shared::cluster.global.mbarrier::complete_tx::bytes [%0], [%1, {%3, %4}], [%2];" ::"r"(dst), "l"(tm), "r"(bar), "r"(c0), "r"(c1) : "memory");
}
__device__ __forceinline__ void tma3d(uint32_t dst, const CUtensorMap* tm, uint32_t bar, int c0, int c1, int c2) {
    asm volatile("cp.async.bulk.tensor.3d.shared::cluster.global.mbarrier::complete_tx::bytes [%0], [%1, {%3, %4, %5}], [%2];" ::"r"(dst), "l"(tm), "r"(bar), "r"(c0), "r"(c1), "r"(c2) : "memory");
}
__device__ __forceinline__ void bulk_load(uint32_t dst, const void* src, uint32_t bytes, uint32_t bar) {
    asm volatile("cp.async.bulk.shared::cluster.global.mbarrier::complete_tx::bytes [%0], [%1], %2, [%3];" ::"r"(dst), "l"(src), "r"(bytes), "r"(bar) : "memory");
}
__device__ __forceinline__ void bulk_store(void* dst, uint32_t src, uint32_t bytes) {
    asm volatile("cp.async.bulk.global.shared::cta.bulk_group [%0], [%1], %2;" ::"l"(dst), "r"(src), "r"(bytes) : "memory");
}
__device__ __forceinline__ void bulk_commit() { asm volatile("cp.async.bulk.commit_group;" ::: "memory"); }
__device__ __forceinline__ void bulk_wait_all() { asm volatile("cp.async.bulk.wait_group 0;" ::: "memory"); }
__device__ __forceinline__ void l2_prefetch(const void* p, uint32_t bytes) { asm volatile("cp.async.bulk.prefetch.L2.global [%0], %1;" ::"l"(p), "r"(bytes) : "memory"); }
__device__ __forceinline__ uint32_t ld_acquire(const uint32_t* p) { uint32_t v; asm volatile("ld.acquire.gpu.global.u32 %0, [%1];" : "=r"(v) : "l"(p) : "memory"); return v; }
__device__ __forceinline__ uint32_t ld_relaxed(const uint32_t* p) { uint32_t v; asm volatile("ld.relaxed.gpu.global.u32 %0, [%1];" : "=r"(v) : "l"(p) : "memory"); return v; }
__device__ __forceinline__ void red_release(uint32_t* p) { asm volatile("red.release.gpu.global.add.u32 [%0], 1;" ::"l"(p) : "memory"); }
__device__ __forceinline__ void red_after_bulk(uint32_t* p) {
    asm volatile("red.relaxed.gpu.global.add.u32 [%0], 1;" ::"l"(p) : "memory");
}
__device__ __forceinline__ void fence_async_global() { asm volatile("fence.proxy.async.global;" ::: "memory"); }
__device__ __forceinline__ void fence_async_shared() { asm volatile("fence.proxy.async.shared::cta;" ::: "memory"); }
__device__ __forceinline__ void wait_flag(const uint32_t* p, uint32_t target) {
    uint32_t it = 0;
    while (ld_acquire(p) != target) { __nanosleep(POLL_NS); spin_guard(++it); }
}
__device__ __forceinline__ void bar_sync(int id, int n) { asm volatile("bar.sync %0, %1;" ::"r"(id), "r"(n) : "memory"); }
__device__ __forceinline__ void bar_arrive(int id, int n) { asm volatile("bar.arrive %0, %1;" ::"r"(id), "r"(n) : "memory"); }
__device__ __forceinline__ void wg_fence() { asm volatile("wgmma.fence.sync.aligned;" ::: "memory"); }
__device__ __forceinline__ void wg_commit() { asm volatile("wgmma.commit_group.sync.aligned;" ::: "memory"); }
template <int N> __device__ __forceinline__ void wg_wait() { asm volatile("wgmma.wait_group.sync.aligned %0;" ::"n"(N) : "memory"); }
template <int N> __device__ __forceinline__ void pin(float (&d)[N]) {
#pragma unroll
    for (int i = 0; i < N; i++) asm volatile("" : "+f"(d[i])::"memory");
}
__device__ __forceinline__ constexpr uint64_t desc_hi(uint32_t lbo, uint32_t sbo, uint32_t swz) {
    return ((uint64_t)(lbo >> 4) << 16) | ((uint64_t)(sbo >> 4) << 32) | ((uint64_t)swz << 62);
}
__device__ __forceinline__ uint32_t desc_lo(uint32_t addr) { return (addr & 0x3FFFFu) >> 4; }
__device__ __forceinline__ uint32_t pack2(float lo, float hi) { uint32_t r; asm("cvt.rn.bf16x2.f32 %0, %1, %2;" : "=r"(r) : "f"(hi), "f"(lo)); return r; }
__device__ __forceinline__ float bf_lo(uint32_t v) { return __uint_as_float(v << 16); }
__device__ __forceinline__ float bf_hi(uint32_t v) { return __uint_as_float(v & 0xffff0000u); }
__device__ __forceinline__ uint32_t add_bf2(uint32_t a, uint32_t b) { uint32_t r; asm("add.rn.bf16x2 %0, %1, %2;" : "=r"(r) : "r"(a), "r"(b)); return r; }
__device__ __forceinline__ void stsm4(uint32_t a, uint32_t r0, uint32_t r1, uint32_t r2, uint32_t r3) {
    asm volatile("stmatrix.sync.aligned.m8n8.x4.shared.b16 [%0], {%1, %2, %3, %4};" ::"r"(a), "r"(r0), "r"(r1), "r"(r2), "r"(r3) : "memory");
}
__device__ __forceinline__ void stsm2(uint32_t a, uint32_t r0, uint32_t r1) {
    asm volatile("stmatrix.sync.aligned.m8n8.x2.shared.b16 [%0], {%1, %2};" ::"r"(a), "r"(r0), "r"(r1) : "memory");
}
__device__ __forceinline__ void sts1(uint32_t a, uint32_t r0) { asm volatile("st.shared.b32 [%0], %1;" ::"r"(a), "r"(r0) : "memory"); }
__device__ __forceinline__ void sts2(uint32_t a, uint32_t r0, uint32_t r1) { asm volatile("st.shared.v2.b32 [%0], {%1, %2};" ::"r"(a), "r"(r0), "r"(r1) : "memory"); }
__device__ __forceinline__ void sts4(uint32_t a, uint4 v) { asm volatile("st.shared.v4.b32 [%0], {%1, %2, %3, %4};" ::"r"(a), "r"(v.x), "r"(v.y), "r"(v.z), "r"(v.w) : "memory"); }
__device__ __forceinline__ uint4 lds4(uint32_t a) { uint4 v; asm volatile("ld.shared.v4.b32 {%0, %1, %2, %3}, [%4];" : "=r"(v.x), "=r"(v.y), "=r"(v.z), "=r"(v.w) : "r"(a) : "memory"); return v; }
__device__ __forceinline__ uint2 lds2(uint32_t a) { uint2 v; asm volatile("ld.shared.v2.b32 {%0, %1}, [%2];" : "=r"(v.x), "=r"(v.y) : "r"(a) : "memory"); return v; }
__device__ __forceinline__ void st_async4(uint32_t a, uint32_t bar, float v0, float v1, float v2, float v3) {
    asm volatile("st.async.weak.shared::cluster.mbarrier::complete_tx::bytes.v4.f32 [%0], {%2, %3, %4, %5}, [%1];" ::"r"(a), "r"(bar), "f"(v0), "f"(v1), "f"(v2), "f"(v3) : "memory");
}
__device__ __forceinline__ float gelu_tanh(float u) {
    float z = u * fmaf(u * u, 0.044715f * 0.7978845608028654f, 0.7978845608028654f), t;
    asm("tanh.approx.f32 %0, %1;" : "=f"(t) : "f"(z));
    const float hu = 0.5f * u;
    return fmaf(hu, t, hu);
}
__device__ __forceinline__ float oct_sum(float v) {
    v += __shfl_xor_sync(~0u, v, 1); v += __shfl_xor_sync(~0u, v, 2); v += __shfl_xor_sync(~0u, v, 4);
    return v;
}

template <int TA, int TB>
__device__ __forceinline__ void wgmma_n112(float (&d)[56], uint64_t da, uint64_t db, int accumulate) {
    asm volatile("{\n.reg .pred p;\nsetp.ne.b32 p, %58, 0;\n"
        "wgmma.mma_async.sync.aligned.m64n112k16.f32.bf16.bf16 {"
        "%0, %1, %2, %3, %4, %5, %6, %7, %8, %9, %10, %11, %12, %13, %14, %15, "
        "%16, %17, %18, %19, %20, %21, %22, %23, %24, %25, %26, %27, %28, %29, %30, %31, "
        "%32, %33, %34, %35, %36, %37, %38, %39, %40, %41, %42, %43, %44, %45, %46, %47, "
        "%48, %49, %50, %51, %52, %53, %54, %55"
        "}, %56, %57, p, 1, 1, %59, %60;\n}\n"
        : "+f"(d[0]), "+f"(d[1]), "+f"(d[2]), "+f"(d[3]), "+f"(d[4]), "+f"(d[5]), "+f"(d[6]), "+f"(d[7]),
          "+f"(d[8]), "+f"(d[9]), "+f"(d[10]), "+f"(d[11]), "+f"(d[12]), "+f"(d[13]), "+f"(d[14]), "+f"(d[15]),
          "+f"(d[16]), "+f"(d[17]), "+f"(d[18]), "+f"(d[19]), "+f"(d[20]), "+f"(d[21]), "+f"(d[22]), "+f"(d[23]),
          "+f"(d[24]), "+f"(d[25]), "+f"(d[26]), "+f"(d[27]), "+f"(d[28]), "+f"(d[29]), "+f"(d[30]), "+f"(d[31]),
          "+f"(d[32]), "+f"(d[33]), "+f"(d[34]), "+f"(d[35]), "+f"(d[36]), "+f"(d[37]), "+f"(d[38]), "+f"(d[39]),
          "+f"(d[40]), "+f"(d[41]), "+f"(d[42]), "+f"(d[43]), "+f"(d[44]), "+f"(d[45]), "+f"(d[46]), "+f"(d[47]),
          "+f"(d[48]), "+f"(d[49]), "+f"(d[50]), "+f"(d[51]), "+f"(d[52]), "+f"(d[53]), "+f"(d[54]), "+f"(d[55])
        : "l"(da), "l"(db), "r"(accumulate), "n"(TA), "n"(TB));
}

template <int TA, int TB>
__device__ __forceinline__ void wgmma_n184(float (&d)[92], uint64_t da, uint64_t db, int accumulate) {
    asm volatile("{\n.reg .pred p;\nsetp.ne.b32 p, %94, 0;\n"
        "wgmma.mma_async.sync.aligned.m64n184k16.f32.bf16.bf16 {"
        "%0, %1, %2, %3, %4, %5, %6, %7, %8, %9, %10, %11, %12, %13, %14, %15, "
        "%16, %17, %18, %19, %20, %21, %22, %23, %24, %25, %26, %27, %28, %29, %30, %31, "
        "%32, %33, %34, %35, %36, %37, %38, %39, %40, %41, %42, %43, %44, %45, %46, %47, "
        "%48, %49, %50, %51, %52, %53, %54, %55, %56, %57, %58, %59, %60, %61, %62, %63, "
        "%64, %65, %66, %67, %68, %69, %70, %71, %72, %73, %74, %75, %76, %77, %78, %79, "
        "%80, %81, %82, %83, %84, %85, %86, %87, %88, %89, %90, %91"
        "}, %92, %93, p, 1, 1, %95, %96;\n}\n"
        : "+f"(d[0]), "+f"(d[1]), "+f"(d[2]), "+f"(d[3]), "+f"(d[4]), "+f"(d[5]), "+f"(d[6]), "+f"(d[7]),
          "+f"(d[8]), "+f"(d[9]), "+f"(d[10]), "+f"(d[11]), "+f"(d[12]), "+f"(d[13]), "+f"(d[14]), "+f"(d[15]),
          "+f"(d[16]), "+f"(d[17]), "+f"(d[18]), "+f"(d[19]), "+f"(d[20]), "+f"(d[21]), "+f"(d[22]), "+f"(d[23]),
          "+f"(d[24]), "+f"(d[25]), "+f"(d[26]), "+f"(d[27]), "+f"(d[28]), "+f"(d[29]), "+f"(d[30]), "+f"(d[31]),
          "+f"(d[32]), "+f"(d[33]), "+f"(d[34]), "+f"(d[35]), "+f"(d[36]), "+f"(d[37]), "+f"(d[38]), "+f"(d[39]),
          "+f"(d[40]), "+f"(d[41]), "+f"(d[42]), "+f"(d[43]), "+f"(d[44]), "+f"(d[45]), "+f"(d[46]), "+f"(d[47]),
          "+f"(d[48]), "+f"(d[49]), "+f"(d[50]), "+f"(d[51]), "+f"(d[52]), "+f"(d[53]), "+f"(d[54]), "+f"(d[55]),
          "+f"(d[56]), "+f"(d[57]), "+f"(d[58]), "+f"(d[59]), "+f"(d[60]), "+f"(d[61]), "+f"(d[62]), "+f"(d[63]),
          "+f"(d[64]), "+f"(d[65]), "+f"(d[66]), "+f"(d[67]), "+f"(d[68]), "+f"(d[69]), "+f"(d[70]), "+f"(d[71]),
          "+f"(d[72]), "+f"(d[73]), "+f"(d[74]), "+f"(d[75]), "+f"(d[76]), "+f"(d[77]), "+f"(d[78]), "+f"(d[79]),
          "+f"(d[80]), "+f"(d[81]), "+f"(d[82]), "+f"(d[83]), "+f"(d[84]), "+f"(d[85]), "+f"(d[86]), "+f"(d[87]),
          "+f"(d[88]), "+f"(d[89]), "+f"(d[90]), "+f"(d[91])
        : "l"(da), "l"(db), "r"(accumulate), "n"(TA), "n"(TB));
}

struct Ring {
    int slot; uint32_t ph;
    __device__ __forceinline__ void next() { if (++slot == NSLOT) { slot = 0; ph ^= 1; } }
};
__device__ __forceinline__ uint32_t qslot(int kb) { return (uint32_t)((kb + 2) % 5) * QSLOT; }

constexpr uint64_t HI_WT = desc_hi(8192, 1024, 1);
constexpr uint64_t HI_KM = desc_hi(16, 1024, 1);
constexpr uint64_t HI_TILE = desc_hi(128, 256, 0);

template <int TA, int ASTEP, int BSTEP>
__device__ __forceinline__ void tile_blocks(float (&a0)[56], float (&a1)[56], Ring& r, int& pend, int n, int accumulate, uint32_t bars, uint64_t dA0, uint64_t dB0, bool lead) {
#pragma unroll 1
    for (int i = 0; i < n; i++) {
        const int s = r.slot;
        mbar_wait(bars + B_FULL + 8 * s, r.ph); r.next();
        const uint64_t dA = dA0 + s * (SLOT >> 4), dB = dB0 + s * (SLOT >> 4);
        wg_fence();
#pragma unroll
        for (int k = 0; k < 4; k++) {
            wgmma_n112<TA, 1>(a0, dA + k * ASTEP, dB + k * BSTEP, k > 0 || accumulate);
            wgmma_n112<TA, 1>(a1, dA + 512 + k * ASTEP, dB + k * BSTEP, k > 0 || accumulate);
        }
        wg_commit();
        accumulate = 1;
        wg_wait<1>();
        if (lead && pend >= 0) mbar_arrive(bars + B_EMPTY + 8 * pend);
        pend = s;
    }
}
__device__ __forceinline__ void tile_tail(float (&a0)[56], float (&a1)[56], Ring r, int pend, uint32_t bars, uint64_t dA0, uint64_t dB0, bool lead, int sig) {
    int s = r.slot;
#pragma unroll
    for (int i = 0; i < LAG; i++) {
        mbar_wait(bars + B_FULL + 8 * r.slot, r.ph);
        const uint64_t dA = dA0 + r.slot * (SLOT >> 4), dB = dB0 + r.slot * (SLOT >> 4);
        r.next();
        wg_fence();
#pragma unroll
        for (int k = 0; k < 4; k++) wgmma_n112<1, 1>(a0, dA + k * 128, dB + k * (SLAB >> 4), 1);
        if (i == 0) { wg_commit(); wg_wait<1>(); if (lead) mbar_arrive(bars + B_EMPTY + 8 * pend); }
    }
    wg_commit();
#pragma unroll
    for (int i = 0; i < LAG; i++) {
        const uint64_t dA = dA0 + s * (SLOT >> 4), dB = dB0 + s * (SLOT >> 4);
        if (++s == NSLOT) s = 0;
#pragma unroll
        for (int k = 0; k < 4; k++) wgmma_n112<1, 1>(a1, dA + 512 + k * 128, dB + k * (SLAB >> 4), 1);
        wg_commit();
    }
    if (sig) bar_arrive(sig, 256);
    wg_wait<LAG>();
    pin(a0);
}

__device__ __forceinline__ void out_tile(float (&a)[56], uint32_t stg, const CUtensorMap* tm, int col, int row, int lane) {
    const uint32_t sa = stg + (lane & 15) * 224 + (lane >> 4) * 16;
#pragma unroll
    for (int g = 0; g < 7; g++)
        stsm4(sa + g * 32, pack2(a[8 * g], a[8 * g + 1]), pack2(a[8 * g + 2], a[8 * g + 3]), pack2(a[8 * g + 4], a[8 * g + 5]), pack2(a[8 * g + 6], a[8 * g + 7]));
    fence_async_shared();
    __syncwarp();
    if (elect()) {
        asm volatile("cp.reduce.async.bulk.tensor.2d.global.shared::cta.add.tile.bulk_group [%0, {%2, %3}], [%1];" ::"l"(tm), "r"(stg), "r"(col), "r"(row) : "memory");
        bulk_commit();
    }
}

__global__ void __launch_bounds__(NTHREADS, 1) fused_kernel(const __grid_constant__ Params P) {
    extern __shared__ __align__(1024) uint8_t smem[];
    const uint32_t sbase = (uint32_t)__cvta_generic_to_shared(smem);
    const uint32_t bars = sbase + OFF_BAR;
    const int c = blockIdx.x, lane = threadIdx.x & 31;
    const int warp = __shfl_sync(~0u, threadIdx.x >> 5, 0), w = warp & 3;
    const int tb = c >> 3, hp = c & 7;
    const bool has_g1 = c < NG1;
    const int rank = c & 1;
    const int q1 = ((c >> 1) & 7) * 7 + (c >> 4), nt1 = q1 & 3, ft = q1 >> 2;
    const int nt2 = c & 3, mt = (c >> 2) & 15, ks = c >> 6;
    const int nwo = 4 - ks;

    auto qkv_load = [&](int kb) {
        mbar_expect(bars + B_QFULL + 8 * kb, QSLOT);
        tma3d(sbase + qslot(kb), &P.tmX, bars + B_QFULL + 8 * kb, kb * 64, tb * 64, 0);
        tma3d(sbase + qslot(kb) + 16384, &P.tmWqkv, bars + B_QFULL + 8 * kb, hp * 56, kb * 64, 0);
    };
    uint4 xv[7];
    uint32_t braw[4], ep;
    if (warp >= 4) {
        const int tok = c * 16 + w * 4 + (lane >> 3);
        const uint4* src = warp >= 8 ? (const uint4*)(P.wqkv + (w * 112 + (lane >> 1)) * (3 * D_) + min(c, 83) * 16) + (lane & 1) : (const uint4*)(P.x + tok * D_) + (lane & 7);
        const int step = warp >= 8 ? 16 * (3 * D_ / 8) : 8;
#pragma unroll
        for (int i = 0; i < 7; i++) xv[i] = __ldg(src + i * step);
        braw[0] = __ldg((const uint16_t*)P.b2 + tok);
        ep = ld_relaxed(&g_s.epoch[c]);
    } else if (warp == 0) {
        if (elect()) {
            TS(0);
#pragma unroll
            for (int i = 0; i < NBAR; i++) mbar_init(bars + 8 * i, ((i >= B_QEMPTY / 8 && i < B_FULL / 8) || i == B_XFREE / 8) ? 2 : 1);
            asm volatile("fence.mbarrier_init.release.cluster;" ::: "memory");
        }
        __syncwarp();
    }
    asm volatile("barrier.cluster.arrive.relaxed.aligned;" ::: "memory");
    if (warp == 0) {
        if (elect()) {
#pragma unroll 1
            for (int kb = 0; kb < QPRE; kb++) qkv_load(kb);
            mbar_expect(bars + B_X, TILEB); mbar_expect(bars + B_X + 8, TILEB);
            TS(23);
        }
        __syncwarp();
    }

    if (warp >= 8) {
        {
            float s[8];
#pragma unroll
            for (int i = 0; i < 8; i++) s[i] = 0.f;
#pragma unroll
            for (int i = 0; i < 7; i++) {
                s[0] += bf_lo(xv[i].x); s[1] += bf_hi(xv[i].x); s[2] += bf_lo(xv[i].y); s[3] += bf_hi(xv[i].y);
                s[4] += bf_lo(xv[i].z); s[5] += bf_hi(xv[i].z); s[6] += bf_lo(xv[i].w); s[7] += bf_hi(xv[i].w);
            }
#pragma unroll 1
            for (int o = 2; o < 32; o <<= 1) {
#pragma unroll
                for (int i = 0; i < 8; i++) s[i] += __shfl_xor_sync(~0u, s[i], o);
            }
            if (lane < 2) {
                const uint32_t dst = sbase + OFF_REC + 128 + w * 64 + lane * 32;
                sts4(dst, make_uint4(__float_as_uint(s[0]), __float_as_uint(s[1]), __float_as_uint(s[2]), __float_as_uint(s[3])));
                sts4(dst + 16, make_uint4(__float_as_uint(s[4]), __float_as_uint(s[5]), __float_as_uint(s[6]), __float_as_uint(s[7])));
            }
            fence_async_shared();
        }
        ep = inc_late(ep);
        if (w == 0) TSL(24);
        if (w != 2) bar_arrive(6, 256);
        asm volatile("barrier.cluster.wait.aligned;" ::: "memory");
        if (w < 2) {
            Ring r{0, 1};
            int job = 0;
            auto acquire = [&]() {
                if (job < NSLOT) mbar_wait(bars + B_QEMPTY + 8 * min(job + 3, 6), 0); else mbar_wait(bars + B_EMPTY + 8 * r.slot, r.ph);
                job++;
            };
            if (w == 0) {
                if (elect()) {
#pragma unroll 1
                    for (int kb = QPRE; kb < 7; kb++) {
                        if (kb >= 5) mbar_wait(bars + B_QEMPTY + 8 * (kb - 5), 0);
                        qkv_load(kb);
                    }
                    if (has_g1) {
#pragma unroll 1
                        for (int kb = 0; kb < 16; kb++) {
                            acquire(); mbar_expect(bars + B_FULL + 8 * r.slot, 16384 + TILEB);
                            tma3d(sbase + r.slot * SLOT, &P.tmW1, bars + B_FULL + 8 * r.slot, 0, (rank * 16 + kb) * 64, ft * 2); r.next();
                        }
                    }
#pragma unroll 1
                    for (int kb = 0; kb < nwo; kb++) {
                        acquire(); mbar_expect(bars + B_FULL + 8 * r.slot, SLOT);
                        tma2d(sbase + r.slot * SLOT + 16384, &P.tmWo, bars + B_FULL + 8 * r.slot, nt2 * 112, (ks * 4 + kb) * 64);
                        tma2d(sbase + r.slot * SLOT + 24576, &P.tmWo, bars + B_FULL + 8 * r.slot, nt2 * 112 + 64, (ks * 4 + kb) * 64); r.next();
                    }
#pragma unroll 1
                    for (int i = 0; i < 14; i++) {
                        const int kb = ks * 14 + (i < 7 ? 2 * i : 2 * i - 13);
                        acquire(); mbar_expect(bars + B_FULL + 8 * r.slot, 16384 + TILEB);
                        tma3d(sbase + r.slot * SLOT, &P.tmW2, bars + B_FULL + 8 * r.slot, 0, kb * 64, mt * 2); r.next();
                    }
                }
            } else {
                {
                    uint32_t it = 0;
                    while (!__all_sync(~0u, ld_acquire(&g_s.flagH[lane]) == 4 * ep)) { __nanosleep(POLL_NS); spin_guard(++it); }
                    __syncwarp();
                }
                if (elect()) {
                    mbar_arrive(bars + B_HRDY);
                    fence_async_global();
                    TS(16);
                    if (has_g1) {
                        const uint8_t* src = g_s.H + (size_t)(rank * 64 + nt1) * TILEB;
#pragma unroll 1
                        for (int kb = 0; kb < 16; kb++) {
                            acquire();
                            bulk_load(sbase + r.slot * SLOT + 16384, src, TILEB, bars + B_FULL + 8 * r.slot); r.next();
                            src += 4 * TILEB;
                        }
                    }
                    wait_flag(&g_s.flagO[mt], 16 * ep);
                    fence_async_global();
                    TS(18);
#pragma unroll 1
                    for (int kb = 0; kb < nwo; kb++) {
                        acquire();
                        tma2d(sbase + r.slot * SLOT, &P.tmO, bars + B_FULL + 8 * r.slot, (ks * 4 + kb) * 64, mt * 128); r.next();
                    }
                }
                __syncwarp();
                job = (has_g1 ? 16 : 0) + nwo; r.slot = job % NSLOT; r.ph = ((job / NSLOT) & 1) ^ 1;
                uint32_t ready = 0;
#pragma unroll 1
                for (int i = 0; i < 14; i++) {
                    const int kb = ks * 14 + (i < 7 ? 2 * i : 2 * i - 13);
                    if (!((ready >> kb) & 1)) {
                        uint32_t it = 0;
                        while (ready = __ballot_sync(~0u, ld_acquire(&g_s.flagU[nt2][lane]) == 8 * ep), !((ready >> kb) & 1)) { __nanosleep(POLL_NS); spin_guard(++it); }
                        __syncwarp();
                        fence_async_global();
                    }
                    if (i == 0) TSL(17);
                    acquire();
                    if (elect()) bulk_load(sbase + r.slot * SLOT + 16384, g_s.U + (size_t)(kb * 4 + nt2) * TILEB, TILEB, bars + B_FULL + 8 * r.slot);
                    r.next();
                }
            }
        } else {
            if (w == 2) {
                bar_sync(6, 256);
                TSL(2);
                if (elect()) {
#pragma unroll
                    for (int i = 0; i < 4; i++) bulk_store(g_s.H + (size_t)((c >> 2) * 4 + i) * TILEB + (c & 3) * SLAB, sbase + OFF_OST + i * SLAB, SLAB);
                    bulk_store(g_s.rec[c], sbase + OFF_REC, 384);
                    bulk_commit();
                    bulk_wait_all();
                    red_after_bulk(&g_s.flagH[c >> 2]);
                }
                __syncwarp();
                TSL(3);
                mbar_wait(bars + B_HRDY, 0);
                const uint4* sp = (const uint4*)g_s.rec[tb * 8 + (lane >> 3)] + (lane & 7);
                const uint4 s0 = __ldcg(sp), s1 = __ldcg(sp + 4 * 24);
                float2 cs[3][4];
#pragma unroll
                for (int p = 0; p < 3; p++) {
                    const int col = p * D_ + hp * 56 + min(lane, 27) * 2;
#pragma unroll
                    for (int q = 0; q < 4; q++) cs[p][q] = __ldcg((const float2*)(g_s.rec[col >> 4] + 32 + q * 16 + (col & 15)));
                }
                sts4(sbase + OFF_ST + lane * 16, s0); sts4(sbase + OFF_ST + 512 + lane * 16, s1);
#pragma unroll
                for (int p = 0; p < 3; p++)
                    sts2(sbase + OFF_CS + p * 256 + lane * 8, __float_as_uint((cs[p][0].x + cs[p][1].x) + (cs[p][2].x + cs[p][3].x)), __float_as_uint((cs[p][0].y + cs[p][1].y) + (cs[p][2].y + cs[p][3].y)));
                bar_arrive(2, 160); bar_arrive(4, 160);
                TSL(20);
                mbar_wait(bars + B_QEMPTY + 8 * 6, 0);
                if (tb > 0) {
                    if (elect()) {
                        mbar_expect(bars + B_HALO, 2 * HALO);
                        wait_flag(&g_s.flagHalo[c - 8], ep);
                        fence_async_global();
                        bulk_load(sbase + OFF_STG, g_s.halo[c - 8], HALO, bars + B_HALO);
                        bulk_load(sbase + OFF_STG + PAR, g_s.halo[c - 8] + HALO, HALO, bars + B_HALO);
                    }
                } else {
#pragma unroll 1
                    for (int i = lane; i < HALO / 16; i += 32) { sts4(sbase + OFF_STG + i * 16, make_uint4(0u, 0u, 0u, 0u)); sts4(sbase + OFF_STG + PAR + i * 16, make_uint4(0u, 0u, 0u, 0u)); }
                    __syncwarp();
                    if (lane == 0) mbar_arrive(bars + B_HALO);
                }
                TSL(21);
            } else {
                bar_sync(3, 288);
                if (elect()) {
                    if (tb < 15) {
                        bulk_store(g_s.halo[c], sbase + OFF_STG + 32 * KVROW, HALO);
                        bulk_store(g_s.halo[c] + HALO, sbase + OFF_STG + PAR + 32 * KVROW, HALO);
                        bulk_commit();
                        bulk_wait_all();
                        red_after_bulk(&g_s.flagHalo[c]);
                    }
                    mbar_arrive_remote(mapa(bars + B_XFREE, rank ^ 1));
                    red_release(&g_s.flagO[tb]);
                }
                __syncwarp();
            }
        }
    } else {
        const bool lead = (threadIdx.x & 127) == 0;
        const int wg = warp >> 2;
        if (wg == 1) {
            const int r16 = w * 4 + (lane >> 3), tok = c * 16 + r16;
            const uint32_t b2 = braw[0] * 0x10001u;
            uint4* op = (uint4*)(P.out + tok * D_) + (lane & 7);
            float f[56];
#pragma unroll
            for (int i = 0; i < 7; i++) {
                f[8 * i] = bf_lo(xv[i].x); f[8 * i + 1] = bf_hi(xv[i].x); f[8 * i + 2] = bf_lo(xv[i].y); f[8 * i + 3] = bf_hi(xv[i].y);
                f[8 * i + 4] = bf_lo(xv[i].z); f[8 * i + 5] = bf_hi(xv[i].z); f[8 * i + 6] = bf_lo(xv[i].w); f[8 * i + 7] = bf_hi(xv[i].w);
            }
            float s0 = 0.f, s1 = 0.f, s2 = 0.f, s3 = 0.f;
#pragma unroll
            for (int i = 0; i < 56; i += 4) { s0 += f[i]; s1 += f[i + 1]; s2 += f[i + 2]; s3 += f[i + 3]; }
            const float mean = oct_sum((s0 + s1) + (s2 + s3)) * (1.f / D_);
            TSDEP(1, mean);
            s0 = s1 = s2 = s3 = 0.f;
#pragma unroll
            for (int i = 0; i < 56; i += 4) {
                f[i] -= mean; f[i + 1] -= mean; f[i + 2] -= mean; f[i + 3] -= mean;
                s0 = fmaf(f[i], f[i], s0); s1 = fmaf(f[i + 1], f[i + 1], s1); s2 = fmaf(f[i + 2], f[i + 2], s2); s3 = fmaf(f[i + 3], f[i + 3], s3);
            }
            const float var = oct_sum((s0 + s1) + (s2 + s3)) * (1.f / D_);
            const float rstd = rsqrtf(var + LN_EPS);
            const float sc = rstd * rsqrtf(var * rstd * rstd + LN_EPS);
            if ((lane & 7) == 0) sts2(sbase + OFF_REC + r16 * 8, __float_as_uint(rstd), __float_as_uint(-mean * rstd));
            const uint32_t hb = sbase + OFF_OST + r16 * 16;
#pragma unroll
            for (int i = 0; i < 7; i++) {
                const int ch = (lane & 7) + 8 * i;
                const int pos = c < 64 ? ch : ch + ((ch % 14) < 7 ? 7 : -7);
                sts4(hb + pos * 256, make_uint4(pack2(f[8 * i] * sc, f[8 * i + 1] * sc), pack2(f[8 * i + 2] * sc, f[8 * i + 3] * sc),
                                                pack2(f[8 * i + 4] * sc, f[8 * i + 5] * sc), pack2(f[8 * i + 6] * sc, f[8 * i + 7] * sc)));
            }
            TS0(25);
            fence_async_shared();
            TS0(31);
            bar_arrive(6, 256);
#pragma unroll
            for (int i = 0; i < 7; i++) op[8 * i] = make_uint4(add_bf2(xv[i].x, b2), add_bf2(xv[i].y, b2), add_bf2(xv[i].z, b2), add_bf2(xv[i].w, b2));
        } else {
            const uint16_t* bp = (const uint16_t*)P.b1 + min(ft, 13) * 128 + w * 16 + (lane >> 2);
            braw[0] = __ldg(bp); braw[1] = __ldg(bp + 8); braw[2] = __ldg(bp + 64); braw[3] = __ldg(bp + 72);
        }
        asm volatile("barrier.cluster.wait.aligned;" ::: "memory");
        {
            float acc[92];
            const uint64_t dA0 = HI_KM | desc_lo(sbase + wg * 8192), dB0 = HI_WT | desc_lo(sbase + 16384);
#pragma unroll 1
            for (int kb = 0; kb < 7; kb++) {
                if (kb == 5 && wg == 1) bar_sync(7, 256);
                mbar_wait(bars + B_QFULL + 8 * kb, 0);
                const uint64_t dA = dA0 + (qslot(kb) >> 4), dB = dB0 + (qslot(kb) >> 4);
                wg_fence();
#pragma unroll
                for (int k = 0; k < 4; k++) wgmma_n184<0, 1>(acc, dA + k * 2, dB + k * 128, k > 0 || kb > 0);
                wg_commit();
                if (kb == 6 && wg == 0) bar_arrive(7, 256);
                if (kb == 4 && wg == 1) { wg_wait<0>(); if (lead) mbar_arrive(bars + B_QEMPTY + 8 * 4); } else wg_wait<1>();
                if (lead && kb > 0 && !(kb == 5 && wg == 1)) mbar_arrive(bars + B_QEMPTY + 8 * (kb - 1));
            }
            wg_wait<0>();
            pin(acc);
            if (lead) mbar_arrive(bars + B_QEMPTY + 8 * 6);
            TS0(4 + 7 * wg);
            bar_sync(2 + 2 * wg, 160);
            mbar_wait(bars + B_QEMPTY + 8 * 2, 0);
            const int r = lane >> 2;
            const uint2 st0 = lds2(sbase + OFF_ST + ((w * 16 + r) * 2 + wg) * 8), st1 = lds2(sbase + OFF_ST + ((w * 16 + 8 + r) * 2 + wg) * 8);
            const float r0 = __uint_as_float(st0.x), n0 = __uint_as_float(st0.y), r1 = __uint_as_float(st1.x), n1 = __uint_as_float(st1.y);
            const uint32_t csa = sbase + OFF_CS + (lane & 3) * 8;
            const uint32_t stg = sbase + OFF_STG + wg * PAR + (lane & 3) * 4;
            const uint32_t dkv = stg + (w * 8 + 4 + (r >> 1)) * KVROW + (r & 1) * 224, dq = stg + QOFF + (w * 8 + (r >> 1)) * QROW + (r & 1) * 112;
#pragma unroll
            for (int p = 2; p >= 0; p--) {
                uint2 cs[7];
#pragma unroll
                for (int g = 0; g < 7; g++) cs[g] = lds2(csa + (p * 8 + g) * 32);
#pragma unroll
                for (int g = 0; g < 7; g++) {
                    const int a = (p * 8 + g) * 4;
                    const float c0 = __uint_as_float(cs[g].x), c1 = __uint_as_float(cs[g].y);
                    const uint32_t dst = (p == 0 ? dq : dkv + (p - 1) * 112) + g * 16;
                    sts1(dst, pack2(fmaf(acc[a], r0, n0 * c0), fmaf(acc[a + 1], r0, n0 * c1)));
                    sts1(dst + 4 * (p == 0 ? QROW : KVROW), pack2(fmaf(acc[a + 2], r1, n1 * c0), fmaf(acc[a + 3], r1, n1 * c1)));
                }
            }
            fence_async_shared();
        }
        float a0[56], a1[56];
        const uint64_t dA0 = HI_WT | desc_lo(sbase), dB0 = HI_TILE | desc_lo(sbase + 16384);
        if (wg == 0) {
            bar_arrive(3, 288);
            TS0(9);
            if (has_g1) {
                Ring r{0, 0};
                int pend = -1;
                tile_blocks<1, 128, SLAB / 16>(a0, a1, r, pend, 16 - LAG, 0, bars, dA0, dB0, lead);
                tile_tail(a0, a1, r, pend, bars, dA0, dB0, lead, 1);
                TS0(5);
                mbar_wait_cluster(bars + B_XFREE);
                const uint32_t xb = sbase + OFF_STG + threadIdx.x * 16;
                const uint32_t rx = mapa(xb, rank ^ 1), rbar = mapa(bars + B_X, rank ^ 1);
#pragma unroll
                for (int i = 0; i < 7; i++) {
                    st_async4(rx + i * 2048, rbar, a0[28 + 4 * i], a0[29 + 4 * i], a0[30 + 4 * i], a0[31 + 4 * i]);
                    if (i >= 7 - LAG) {
                        if (i == 6) wg_wait<0>(); else if (i == 5) wg_wait<1>(); else if (i == 4) wg_wait<2>(); else if (i == 3) wg_wait<3>(); else wg_wait<4>();
                        if (lead) mbar_arrive(bars + B_EMPTY + 8 * r.slot);
                        r.next();
                    }
                }
                pin(a1);
                TS0(6);
#pragma unroll 1
                for (int m = 0; m < 2; m++) {
#pragma unroll
                    for (int i = 0; i < 28; i++) a0[i] += bf_lo(braw[(i >> 1) & 1]);
                    mbar_wait_cluster(bars + B_X + 8 * m);
                    const uint32_t stg = sbase + OFF_STG + 2 * TILEB + (m * 4 + w) * 1792;
                    uint32_t u[14];
#pragma unroll
                    for (int i = 0; i < 7; i++) {
                        const uint4 t = lds4(xb + m * TILEB + i * 2048);
                        u[2 * i] = pack2(gelu_tanh(a0[4 * i] + __uint_as_float(t.x)), gelu_tanh(a0[4 * i + 1] + __uint_as_float(t.y)));
                        u[2 * i + 1] = pack2(gelu_tanh(a0[4 * i + 2] + __uint_as_float(t.z)), gelu_tanh(a0[4 * i + 3] + __uint_as_float(t.w)));
                    }
#pragma unroll
                    for (int i = 0; i < 3; i++) stsm4(stg + lane * 16 + i * 512, u[4 * i], u[4 * i + 1], u[4 * i + 2], u[4 * i + 3]);
                    stsm2(stg + (lane & 15) * 16 + 1536, u[12], u[13]);
                    fence_async_shared();
                    __syncwarp();
                    if (elect()) {
                        bulk_store(g_s.U + (size_t)((ft * 2 + m) * 4 + nt1) * TILEB + w * SLAB + rank * 1792, stg, 1792);
                        bulk_commit();
                        bulk_wait_all();
                        red_after_bulk(&g_s.flagU[nt1][ft * 2 + m]);
                    }
                    __syncwarp();
                    TS0(7 + m);
                    if (m == 0) {
#pragma unroll
                        for (int i = 0; i < 7; i++) st_async4(rx + TILEB + i * 2048, rbar + 8, a1[28 + 4 * i], a1[29 + 4 * i], a1[30 + 4 * i], a1[31 + 4 * i]);
#pragma unroll
                        for (int i = 0; i < 28; i++) a0[i] = a1[i];
                        braw[0] = braw[2]; braw[1] = braw[3];
                    }
                }
            } else {
                bar_arrive(1, 256);
            }
            bar_arrive(8, 256);
        } else {
            bar_sync(3, 288);
            mbar_wait(bars + B_HALO, 0);
            TS0(12);
            {
                const uint32_t pb = sbase + OFF_STG + (w >> 1) * PAR + (w & 1) * 56;
                uint32_t pk = pb + (lane + 4) * KVROW, pq = pb + QOFF + lane * QROW;
                uint2 raw[11];
                auto load_kv = [&]() {
#pragma unroll
                    for (int j = 0; j < 9; j++) raw[j] = lds2(pk + ((j + 1) & 1) * 224 - (j >> 1) * KVROW);
                };
                float l0[8], l1[8];
#pragma unroll
                for (int j = 0; j < 8; j++) l0[j] = l1[j] = 0.f;
                load_kv(); raw[9] = lds2(pq); raw[10] = lds2(pq + 112);
#pragma unroll 1
                for (int ch = 0; ch < 7; ch++) {
                    float v[44];
#pragma unroll
                    for (int j = 0; j < 11; j++) { v[4 * j] = bf_lo(raw[j].x); v[4 * j + 1] = bf_hi(raw[j].x); v[4 * j + 2] = bf_lo(raw[j].y); v[4 * j + 3] = bf_hi(raw[j].y); }
                    pin(v);
                    pk += ch == 6 ? 112 - 48 : 8; pq += 8;
                    load_kv(); raw[9] = lds2(pq); raw[10] = lds2(pq + 112);
#pragma unroll
                    for (int e = 0; e < 4; e++)
#pragma unroll
                        for (int j = 0; j < 8; j++) { l0[j] = fmaf(v[36 + e], v[4 * j + 4 + e], l0[j]); l1[j] = fmaf(v[40 + e], v[4 * j + e], l1[j]); }
                }
                const int lim = tb == 0 ? 2 * lane : 64;
                const float sc = 0.1889822365046136f * 1.4426950408889634f;
                float m0 = l0[0], m1 = l1[0];
#pragma unroll
                for (int j = 1; j < 8; j++) {
                    l0[j] = j > lim ? -1e30f : l0[j]; l1[j] = j > lim + 1 ? -1e30f : l1[j];
                    m0 = fmaxf(m0, l0[j]); m1 = fmaxf(m1, l1[j]);
                }
                float t0 = 0.f, t1 = 0.f;
#pragma unroll
                for (int j = 0; j < 8; j++) {
                    asm("ex2.approx.ftz.f32 %0, %1;" : "=f"(l0[j]) : "f"((l0[j] - m0) * sc)); t0 += l0[j];
                    asm("ex2.approx.ftz.f32 %0, %1;" : "=f"(l1[j]) : "f"((l1[j] - m1) * sc)); t1 += l1[j];
                }
                t0 = __fdividef(1.f, t0); t1 = __fdividef(1.f, t1);
#pragma unroll
                for (int j = 0; j < 8; j++) { l0[j] *= t0; l1[j] *= t1; }
                uint32_t oa = sbase + OFF_OST + (w >> 1) * 3584 + lane * 112 + (w & 1) * 56;
#pragma unroll 1
                for (int ch = 0; ch < 7; ch++) {
                    float v[36];
#pragma unroll
                    for (int j = 0; j < 9; j++) { v[4 * j] = bf_lo(raw[j].x); v[4 * j + 1] = bf_hi(raw[j].x); v[4 * j + 2] = bf_lo(raw[j].y); v[4 * j + 3] = bf_hi(raw[j].y); }
                    pin(v);
                    pk += 8;
                    load_kv();
                    float o0[4], o1[4];
#pragma unroll
                    for (int e = 0; e < 4; e++) { o0[e] = l0[0] * v[4 + e]; o1[e] = l1[0] * v[e]; }
#pragma unroll
                    for (int j = 1; j < 8; j++)
#pragma unroll
                        for (int e = 0; e < 4; e++) { o0[e] = fmaf(l0[j], v[4 * j + 4 + e], o0[e]); o1[e] = fmaf(l1[j], v[4 * j + e], o1[e]); }
                    sts2(oa, pack2(o0[0], o0[1]), pack2(o0[2], o0[3]));
                    sts2(oa + 2 * 3584, pack2(o1[0], o1[1]), pack2(o1[2], o1[3]));
                    oa += 8;
                }
                fence_async_shared();
                bar_sync(9, 128);
                TS0(10);
                if (w == 0 && elect()) {
                    mbar_arrive_remote(mapa(bars + B_XFREE, rank ^ 1));
                    asm volatile("cp.async.bulk.tensor.3d.global.shared::cta.tile.bulk_group [%0, {%2, %3, %4}], [%1];" ::"l"(&P.tmOst), "r"(sbase + OFF_OST), "r"(hp * 56), "r"(tb * 32), "r"(0) : "memory");
                    bulk_commit();
                    bulk_wait_all();
                    red_after_bulk(&g_s.flagO[tb]);
                    TS(22);
                }
                __syncwarp();
            }
            bar_sync(1, 256);
            Ring r{has_g1 ? 16 % NSLOT : 0, has_g1 ? (16u / NSLOT) & 1u : 0u};
            int pend = -1;
            tile_blocks<0, 2, 128>(a0, a1, r, pend, nwo, 0, bars, HI_KM | desc_lo(sbase), HI_WT | desc_lo(sbase + 16384), lead);
            TS0(13);
            tile_blocks<1, 128, SLAB / 16>(a0, a1, r, pend, 14 - LAG, 1, bars, dA0, dB0, lead);
            bar_sync(8, 256);
            tile_tail(a0, a1, r, pend, bars, dA0, dB0, lead, 0);
            TS0(14);
            fence_async_global();
            out_tile(a0, sbase + OFF_STG + w * SLAB, &P.tmOut, nt2 * 112, mt * 128 + w * 16, lane);
            wg_wait<0>();
            pin(a1);
            TS0(15);
            out_tile(a1, sbase + OFF_STG + TILEB + w * SLAB, &P.tmOut, nt2 * 112, mt * 128 + 64 + w * 16, lane);
            if (lead) g_s.epoch[c] = inc_late(ep);
            if (elect()) asm volatile("cp.async.bulk.wait_group.read 0;" ::: "memory");
            TS0(19);
            TSDUMP();
        }
    }
}

typedef CUresult (*EncodeFn)(CUtensorMap*, CUtensorMapDataType, cuuint32_t, void*, const cuuint64_t*, const cuuint64_t*, const cuuint32_t*, const cuuint32_t*,
                             CUtensorMapInterleave, CUtensorMapSwizzle, CUtensorMapL2promotion, CUtensorMapFloatOOBfill);

void make_map(EncodeFn enc, CUtensorMap* tm, const void* base, bool swizzle, int d0, int d1, int d2, int s1, int s2, int b0, int b1, int b2) {
    const cuuint64_t dims[3] = {(cuuint64_t)d0, (cuuint64_t)d1, (cuuint64_t)d2}, strides[2] = {(cuuint64_t)s1 * 2, (cuuint64_t)s2 * 2};
    const cuuint32_t box[3] = {(cuuint32_t)b0, (cuuint32_t)b1, (cuuint32_t)b2}, es[3] = {1, 1, 1};
    enc(tm, CU_TENSOR_MAP_DATA_TYPE_BFLOAT16, d2 ? 3 : 2, (void*)base, dims, strides, box, es, CU_TENSOR_MAP_INTERLEAVE_NONE,
        swizzle ? CU_TENSOR_MAP_SWIZZLE_128B : CU_TENSOR_MAP_SWIZZLE_NONE, CU_TENSOR_MAP_L2_PROMOTION_L2_128B, CU_TENSOR_MAP_FLOAT_OOB_FILL_NONE);
}

}

extern "C" void kernel_launch(void* const* d_in, const int* in_sizes, int n_in, void* d_out, int out_size) {
    static EncodeFn enc = nullptr;
    static Scratch* scratch = nullptr;
    if (!enc) {
        void* fn = nullptr;
        cudaDriverEntryPointQueryResult qr;
        cudaGetDriverEntryPoint("cuTensorMapEncodeTiled", &fn, cudaEnableDefault, &qr);
        enc = (EncodeFn)fn;
        cudaGetSymbolAddress((void**)&scratch, g_s);
        cudaFuncSetAttribute(fused_kernel, cudaFuncAttributeMaxDynamicSharedMemorySize, SMEM_BYTES);
    }
    Params P;
    P.x = (const __nv_bfloat16*)d_in[0]; P.wqkv = (const __nv_bfloat16*)d_in[1]; P.wo = (const __nv_bfloat16*)d_in[2];
    P.w1 = (const __nv_bfloat16*)d_in[4]; P.b1 = (const __nv_bfloat16*)d_in[5]; P.w2 = (const __nv_bfloat16*)d_in[6]; P.b2 = (const __nv_bfloat16*)d_in[7];
    P.out = (__nv_bfloat16*)d_out;
    make_map(enc, &P.tmX, P.x, true, D_, S_ / 2, 2, 2 * D_, D_, 64, 64, 2);
    make_map(enc, &P.tmWqkv, P.wqkv, true, D_, D_, 3, 3 * D_, D_, 64, 64, 3);
    make_map(enc, &P.tmW1, P.w1, true, 64, S_, F_ / 64, F_, 64, 64, 64, 2);
    make_map(enc, &P.tmW2, P.w2, true, 64, F_, S_ / 64, S_, 64, 64, 64, 2);
    make_map(enc, &P.tmO, scratch->O, true, D_, S_, 0, D_, 0, 64, 128, 1);
    make_map(enc, &P.tmOst, scratch->O, false, D_, S_ / 4, 4, 4 * D_, D_, 56, 32, 4);
    make_map(enc, &P.tmWo, P.wo, true, D_, D_, 0, D_, 0, 64, 64, 1);
    make_map(enc, &P.tmOut, P.out, false, D_, S_, 0, D_, 0, 112, 16, 1);
    cudaLaunchConfig_t cfg = {};
    cfg.gridDim = NCTA; cfg.blockDim = NTHREADS; cfg.dynamicSmemBytes = SMEM_BYTES; cfg.stream = cudaStreamPerThread;
    cudaLaunchAttribute at[1];
    at[0].id = cudaLaunchAttributeClusterDimension; at[0].val.clusterDim.x = 2; at[0].val.clusterDim.y = 1; at[0].val.clusterDim.z = 1;
    cfg.attrs = at; cfg.numAttrs = 1;
    cudaLaunchKernelEx(&cfg, fused_kernel, P);
}
```

```cpp
#include <cuda_runtime.h>
#include <cuda_bf16.h>
#include <cuda.h>
#include <stdint.h>

#define POLL_NS 20
#define PACE 800
#define PAUSE 7
#define LEAD 2
#define LAG1 4
#define LAG2 3
#define G1MAP 3

namespace {

constexpr int S_ = 2048, D_ = 448, F_ = 1792;
constexpr int NCTA = 128, NG1 = 112, NTHREADS = 384;
constexpr int NSLOT = 6, SLOT = 32768, QSLOT = 40960, TILEB = 14336, SLAB = 3584, HALF = 7168;
constexpr int KV = 1792, XW = 5 * KV;
constexpr int OFF_X = NSLOT * SLOT;
constexpr int OFF_REC = OFF_X + 16384;
constexpr int OFF_Y = OFF_X + 2 * XW;
constexpr int OFF_CS = OFF_Y + TILEB;
constexpr int OFF_ST = OFF_CS + 768;
constexpr int OFF_BAR = OFF_ST + 1152;
constexpr int SMEM_BYTES = OFF_BAR + 1024;
constexpr int B_QFULL = 0, B_FULL = 56, B_REC = 104, B_ROW = 112, B_X = 120, B_HALO = 136, B_FREE = 144, B_QEMPTY = 152, B_EMPTY = 168, NBAR = 27;
constexpr float LN_EPS = 1e-5f;
constexpr int SPIN_LIMIT = 1 << 22;

struct Scratch {
    uint8_t H[32 * 4 * TILEB];
    uint8_t U[28 * 4 * TILEB];
    uint8_t O[NCTA * TILEB];
    uint8_t halo[NCTA][2 * KV];
    float2 stat[16 + S_];
    float colsum[2][8][192];
    uint32_t flagH[32];
    uint32_t flagU[16][32];
    uint32_t flagO[32][32];
    uint32_t flagInit[16][32];
    uint32_t flagHalo[NCTA];
    uint32_t epoch[NCTA];
};
__device__ __align__(1024) Scratch g_s;

#define TS(i)
#define TS0(i)
#define TSL(i)
#define TSDEP(i, v)
#define TSDUMP()
#define TSC(i)

struct Params {
    CUtensorMap tmX, tmWqkv, tmW1, tmW2, tmWo, tmOut;
};

__device__ __forceinline__ void spin_guard(uint32_t it) {
    asm volatile("{\n.reg .pred p;\nsetp.gt.u32 p, %0, %1;\n@p st.global.u32 [%2], %0;\n}" ::"r"(it), "n"(SPIN_LIMIT), "l"(0ull) : "memory");
}
__device__ __forceinline__ bool elect() {
    uint32_t p;
    asm volatile("{\n.reg .pred p;\nelect.sync _|p, 0xffffffff;\nselp.u32 %0, 1, 0, p;\n}" : "=r"(p));
    return p;
}
__device__ __forceinline__ uint32_t inc_late(uint32_t v) { asm volatile("add.u32 %0, %0, 1;" : "+r"(v)); return v; }
__device__ __forceinline__ void mbar_init(uint32_t b, uint32_t c) { asm volatile("mbarrier.init.shared::cta.b64 [%0], %1;" ::"r"(b), "r"(c) : "memory"); }
__device__ __forceinline__ void mbar_expect(uint32_t b, uint32_t tx) { asm volatile("mbarrier.arrive.expect_tx.shared::cta.b64 _, [%0], %1;" ::"r"(b), "r"(tx) : "memory"); }
__device__ __forceinline__ void mbar_arrive(uint32_t b) { asm volatile("mbarrier.arrive.shared::cta.b64 _, [%0];" ::"r"(b) : "memory"); }
__device__ __forceinline__ void mbar_arrive_remote(uint32_t b) { asm volatile("mbarrier.arrive.shared::cluster.b64 _, [%0];" ::"r"(b) : "memory"); }
#define MBAR_WAIT_ASM(SEM)                                                                                   \
    asm volatile("{\n.reg .pred p;\n.reg .u32 n;\nmov.u32 n, 0;\nWAIT:\nadd.u32 n, n, 1;\nsetp.gt.u32 p, n, %2;\n"       \
                 "@p st.global.u32 [%3], n;\nmbarrier.try_wait.parity" SEM ".shared::cta.b64 p, [%0], %1;\n@!p bra WAIT;\n}" \
                 ::"r"(b), "r"(parity), "n"(SPIN_LIMIT), "l"(0ull) : "memory")
__device__ __forceinline__ void mbar_wait(uint32_t b, uint32_t parity) { MBAR_WAIT_ASM(""); }
__device__ __forceinline__ void mbar_wait_cluster(uint32_t b, uint32_t parity) { MBAR_WAIT_ASM(".acquire.cluster"); }
__device__ __forceinline__ uint32_t mapa(uint32_t a, uint32_t rank) { uint32_t r; asm("mapa.shared::cluster.u32 %0, %1, %2;" : "=r"(r) : "r"(a), "r"(rank)); return r; }
__device__ __forceinline__ void tma3d(uint32_t dst, const CUtensorMap* tm, uint32_t bar, int c0, int c1, int c2) {
    asm volatile("cp.async.bulk.tensor.3d.shared::cluster.global.mbarrier::complete_tx::bytes [%0], [%1, {%3, %4, %5}], [%2];" ::"r"(dst), "l"(tm), "r"(bar), "r"(c0), "r"(c1), "r"(c2) : "memory");
}
__device__ __forceinline__ void tma2d_pair(uint32_t dst, const CUtensorMap* tm, uint32_t bar, int c0, int c1) {
    asm volatile("cp.async.bulk.tensor.2d.shared::cluster.global.mbarrier::complete_tx::bytes.multicast::cluster [%0], [%1, {%3, %4}], [%2], %5;" ::"r"(dst), "l"(tm), "r"(bar), "r"(c0), "r"(c1), "h"((uint16_t)3) : "memory");
}
__device__ __forceinline__ void tma3d_pair(uint32_t dst, const CUtensorMap* tm, uint32_t bar, int c0, int c1, int c2) {
    asm volatile("cp.async.bulk.tensor.3d.shared::cluster.global.mbarrier::complete_tx::bytes.multicast::cluster [%0], [%1, {%3, %4, %5}], [%2], %6;" ::"r"(dst), "l"(tm), "r"(bar), "r"(c0), "r"(c1), "r"(c2), "h"((uint16_t)3) : "memory");
}
__device__ __forceinline__ void bulk_load(uint32_t dst, const void* src, uint32_t bytes, uint32_t bar) {
    asm volatile("cp.async.bulk.shared::cluster.global.mbarrier::complete_tx::bytes [%0], [%1], %2, [%3];" ::"r"(dst), "l"(src), "r"(bytes), "r"(bar) : "memory");
}
__device__ __forceinline__ void bulk_load_pair(uint32_t dst, const void* src, uint32_t bytes, uint32_t bar) {
    asm volatile("cp.async.bulk.shared::cluster.global.mbarrier::complete_tx::bytes.multicast::cluster [%0], [%1], %2, [%3], %4;" ::"r"(dst), "l"(src), "r"(bytes), "r"(bar), "h"((uint16_t)3) : "memory");
}
__device__ __forceinline__ void bulk_store(void* dst, uint32_t src, uint32_t bytes) {
    asm volatile("cp.async.bulk.global.shared::cta.bulk_group [%0], [%1], %2;" ::"l"(dst), "r"(src), "r"(bytes) : "memory");
}
__device__ __forceinline__ void bulk_commit() { asm volatile("cp.async.bulk.commit_group;" ::: "memory"); }
__device__ __forceinline__ void bulk_wait_all() { asm volatile("cp.async.bulk.wait_group 0;" ::: "memory"); }
__device__ __forceinline__ uint32_t ld_acquire(const uint32_t* p) { uint32_t v; asm volatile("ld.acquire.gpu.global.u32 %0, [%1];" : "=r"(v) : "l"(p) : "memory"); return v; }
__device__ __forceinline__ uint32_t ld_u16(const void* p) { uint32_t v; asm volatile("ld.global.nc.u16 %0, [%1];" : "=r"(v) : "l"(p)); return v; }
__device__ __forceinline__ uint32_t ld_relaxed(const uint32_t* p) { uint32_t v; asm volatile("ld.relaxed.gpu.global.u32 %0, [%1];" : "=r"(v) : "l"(p) : "memory"); return v; }
__device__ __forceinline__ void red_release(uint32_t* p) { asm volatile("red.release.gpu.global.add.u32 [%0], 1;" ::"l"(p) : "memory"); }
__device__ __forceinline__ void red_after_bulk(uint32_t* p) {
    asm volatile("red.relaxed.gpu.global.add.u32 [%0], 1;" ::"l"(p) : "memory");
}
__device__ __forceinline__ void fence_async_global() { asm volatile("fence.proxy.async.global;" ::: "memory"); }
__device__ __forceinline__ void fence_async_shared() { asm volatile("fence.proxy.async.shared::cta;" ::: "memory"); }
__device__ __forceinline__ void wait_flag(const uint32_t* p, uint32_t target) {
    uint32_t it = 0;
    while (ld_acquire(p) != target) { __nanosleep(POLL_NS); spin_guard(++it); }
}
__device__ __forceinline__ void bar_sync(int id, int n) { asm volatile("bar.sync %0, %1;" ::"r"(id), "r"(n) : "memory"); }
__device__ __forceinline__ void bar_arrive(int id, int n) { asm volatile("bar.arrive %0, %1;" ::"r"(id), "r"(n) : "memory"); }
__device__ __forceinline__ void wg_fence() { asm volatile("wgmma.fence.sync.aligned;" ::: "memory"); }
__device__ __forceinline__ void wg_commit() { asm volatile("wgmma.commit_group.sync.aligned;" ::: "memory"); }
template <int N> __device__ __forceinline__ void wg_wait() { asm volatile("wgmma.wait_group.sync.aligned %0;" ::"n"(N) : "memory"); }
template <int N> __device__ __forceinline__ void pin(float (&d)[N]) {
#pragma unroll
    for (int i = 0; i < N; i++) asm volatile("" : "+f"(d[i])::"memory");
}
__device__ __forceinline__ constexpr uint64_t desc_hi(uint32_t lbo, uint32_t sbo, uint32_t swz) {
    return ((uint64_t)(lbo >> 4) << 16) | ((uint64_t)(sbo >> 4) << 32) | ((uint64_t)swz << 62);
}
__device__ __forceinline__ uint32_t desc_lo(uint32_t addr) { return (addr & 0x3FFFFu) >> 4; }
__device__ __forceinline__ uint32_t pack2(float lo, float hi) { uint32_t r; asm("cvt.rn.bf16x2.f32 %0, %1, %2;" : "=r"(r) : "f"(hi), "f"(lo)); return r; }
__device__ __forceinline__ float bf_lo(uint32_t v) { return __uint_as_float(v << 16); }
__device__ __forceinline__ float bf_hi(uint32_t v) { return __uint_as_float(v & 0xffff0000u); }
__device__ __forceinline__ uint32_t add_bf2(uint32_t a, uint32_t b) { uint32_t r; asm("add.rn.bf16x2 %0, %1, %2;" : "=r"(r) : "r"(a), "r"(b)); return r; }
__device__ __forceinline__ void stsm4(uint32_t a, uint32_t r0, uint32_t r1, uint32_t r2, uint32_t r3) {
    asm volatile("stmatrix.sync.aligned.m8n8.x4.shared.b16 [%0], {%1, %2, %3, %4};" ::"r"(a), "r"(r0), "r"(r1), "r"(r2), "r"(r3) : "memory");
}
__device__ __forceinline__ void stsm2(uint32_t a, uint32_t r0, uint32_t r1) {
    asm volatile("stmatrix.sync.aligned.m8n8.x2.shared.b16 [%0], {%1, %2};" ::"r"(a), "r"(r0), "r"(r1) : "memory");
}
__device__ __forceinline__ void sts2(uint32_t a, uint32_t r0, uint32_t r1) { asm volatile("st.shared.v2.b32 [%0], {%1, %2};" ::"r"(a), "r"(r0), "r"(r1) : "memory"); }
__device__ __forceinline__ void sts4(uint32_t a, uint4 v) { asm volatile("st.shared.v4.b32 [%0], {%1, %2, %3, %4};" ::"r"(a), "r"(v.x), "r"(v.y), "r"(v.z), "r"(v.w) : "memory"); }
__device__ __forceinline__ uint4 lds4(uint32_t a) { uint4 v; asm volatile("ld.shared.v4.b32 {%0, %1, %2, %3}, [%4];" : "=r"(v.x), "=r"(v.y), "=r"(v.z), "=r"(v.w) : "r"(a) : "memory"); return v; }
__device__ __forceinline__ uint2 lds2(uint32_t a) { uint2 v; asm volatile("ld.shared.v2.b32 {%0, %1}, [%2];" : "=r"(v.x), "=r"(v.y) : "r"(a) : "memory"); return v; }
__device__ __forceinline__ float lds1f(uint32_t a) { float v; asm volatile("ld.shared.f32 %0, [%1];" : "=f"(v) : "r"(a) : "memory"); return v; }
__device__ __forceinline__ void ldsm4(uint32_t* r, uint32_t a) {
    asm volatile("ldmatrix.sync.aligned.m8n8.x4.shared.b16 {%0, %1, %2, %3}, [%4];" : "=r"(r[0]), "=r"(r[1]), "=r"(r[2]), "=r"(r[3]) : "r"(a) : "memory");
}
__device__ __forceinline__ void ldsm4t(uint32_t* r, uint32_t a) {
    asm volatile("ldmatrix.sync.aligned.m8n8.x4.trans.shared.b16 {%0, %1, %2, %3}, [%4];" : "=r"(r[0]), "=r"(r[1]), "=r"(r[2]), "=r"(r[3]) : "r"(a) : "memory");
}
__device__ __forceinline__ uint32_t transpose8(uint32_t v) { uint32_t r; asm volatile("movmatrix.sync.aligned.m8n8.trans.b16 %0, %1;" : "=r"(r) : "r"(v)); return r; }
__device__ __forceinline__ void mma16(float (&c)[4], uint32_t a0, uint32_t a1, uint32_t a2, uint32_t a3, uint32_t b0, uint32_t b1) {
    asm volatile("mma.sync.aligned.m16n8k16.row.col.f32.bf16.bf16.f32 {%0, %1, %2, %3}, {%4, %5, %6, %7}, {%8, %9}, {%0, %1, %2, %3};"
                 : "+f"(c[0]), "+f"(c[1]), "+f"(c[2]), "+f"(c[3]) : "r"(a0), "r"(a1), "r"(a2), "r"(a3), "r"(b0), "r"(b1));
}
__device__ __forceinline__ void mma8(float (&c)[4], uint32_t a0, uint32_t a1, uint32_t b0) {
    asm volatile("mma.sync.aligned.m16n8k8.row.col.f32.bf16.bf16.f32 {%0, %1, %2, %3}, {%4, %5}, {%6}, {%0, %1, %2, %3};"
                 : "+f"(c[0]), "+f"(c[1]), "+f"(c[2]), "+f"(c[3]) : "r"(a0), "r"(a1), "r"(b0));
}
__device__ __forceinline__ void st_async4(uint32_t a, uint32_t bar, uint32_t v0, uint32_t v1, uint32_t v2, uint32_t v3) {
    asm volatile("st.async.weak.shared::cluster.mbarrier::complete_tx::bytes.v4.b32 [%0], {%2, %3, %4, %5}, [%1];" ::"r"(a), "r"(bar), "r"(v0), "r"(v1), "r"(v2), "r"(v3) : "memory");
}
__device__ __forceinline__ void st_async2(uint32_t a, uint32_t bar, uint32_t v0, uint32_t v1) {
    asm volatile("st.async.weak.shared::cluster.mbarrier::complete_tx::bytes.v2.b32 [%0], {%2, %3}, [%1];" ::"r"(a), "r"(bar), "r"(v0), "r"(v1) : "memory");
}
__device__ __forceinline__ float quad_max(float v) { v = fmaxf(v, __shfl_xor_sync(~0u, v, 1)); return fmaxf(v, __shfl_xor_sync(~0u, v, 2)); }
__device__ __forceinline__ float quad_sum(float v) { v += __shfl_xor_sync(~0u, v, 1); return v + __shfl_xor_sync(~0u, v, 2); }
__device__ __forceinline__ float ex2(float v) { float r; asm("ex2.approx.ftz.f32 %0, %1;" : "=f"(r) : "f"(v)); return r; }
__device__ __forceinline__ float gelu_tanh(float u) {
    float z = u * fmaf(u * u, 0.044715f * 0.7978845608028654f, 0.7978845608028654f), t;
    asm("tanh.approx.f32 %0, %1;" : "=f"(t) : "f"(z));
    const float hu = 0.5f * u;
    return fmaf(hu, t, hu);
}
__device__ __forceinline__ float oct_sum(float v) {
    v += __shfl_xor_sync(~0u, v, 4); v += __shfl_xor_sync(~0u, v, 8); v += __shfl_xor_sync(~0u, v, 16);
    return v;
}

template <int TA, int TB>
__device__ __forceinline__ void wgmma_n112(float (&d)[56], uint64_t da, uint64_t db, int accumulate) {
    asm volatile("{\n.reg .pred p;\nsetp.ne.b32 p, %58, 0;\n"
        "wgmma.mma_async.sync.aligned.m64n112k16.f32.bf16.bf16 {"
        "%0, %1, %2, %3, %4, %5, %6, %7, %8, %9, %10, %11, %12, %13, %14, %15, "
        "%16, %17, %18, %19, %20, %21, %22, %23, %24, %25, %26, %27, %28, %29, %30, %31, "
        "%32, %33, %34, %35, %36, %37, %38, %39, %40, %41, %42, %43, %44, %45, %46, %47, "
        "%48, %49, %50, %51, %52, %53, %54, %55"
        "}, %56, %57, p, 1, 1, %59, %60;\n}\n"
        : "+f"(d[0]), "+f"(d[1]), "+f"(d[2]), "+f"(d[3]), "+f"(d[4]), "+f"(d[5]), "+f"(d[6]), "+f"(d[7]),
          "+f"(d[8]), "+f"(d[9]), "+f"(d[10]), "+f"(d[11]), "+f"(d[12]), "+f"(d[13]), "+f"(d[14]), "+f"(d[15]),
          "+f"(d[16]), "+f"(d[17]), "+f"(d[18]), "+f"(d[19]), "+f"(d[20]), "+f"(d[21]), "+f"(d[22]), "+f"(d[23]),
          "+f"(d[24]), "+f"(d[25]), "+f"(d[26]), "+f"(d[27]), "+f"(d[28]), "+f"(d[29]), "+f"(d[30]), "+f"(d[31]),
          "+f"(d[32]), "+f"(d[33]), "+f"(d[34]), "+f"(d[35]), "+f"(d[36]), "+f"(d[37]), "+f"(d[38]), "+f"(d[39]),
          "+f"(d[40]), "+f"(d[41]), "+f"(d[42]), "+f"(d[43]), "+f"(d[44]), "+f"(d[45]), "+f"(d[46]), "+f"(d[47]),
          "+f"(d[48]), "+f"(d[49]), "+f"(d[50]), "+f"(d[51]), "+f"(d[52]), "+f"(d[53]), "+f"(d[54]), "+f"(d[55])
        : "l"(da), "l"(db), "r"(accumulate), "n"(TA), "n"(TB));
}

template <int TA, int TB>
__device__ __forceinline__ void wgmma_n184(float (&d)[92], uint64_t da, uint64_t db, int accumulate) {
    asm volatile("{\n.reg .pred p;\nsetp.ne.b32 p, %94, 0;\n"
        "wgmma.mma_async.sync.aligned.m64n184k16.f32.bf16.bf16 {"
        "%0, %1, %2, %3, %4, %5, %6, %7, %8, %9, %10, %11, %12, %13, %14, %15, "
        "%16, %17, %18, %19, %20, %21, %22, %23, %24, %25, %26, %27, %28, %29, %30, %31, "
        "%32, %33, %34, %35, %36, %37, %38, %39, %40, %41, %42, %43, %44, %45, %46, %47, "
        "%48, %49, %50, %51, %52, %53, %54, %55, %56, %57, %58, %59, %60, %61, %62, %63, "
        "%64, %65, %66, %67, %68, %69, %70, %71, %72, %73, %74, %75, %76, %77, %78, %79, "
        "%80, %81, %82, %83, %84, %85, %86, %87, %88, %89, %90, %91"
        "}, %92, %93, p, 1, 1, %95, %96;\n}\n"
        : "+f"(d[0]), "+f"(d[1]), "+f"(d[2]), "+f"(d[3]), "+f"(d[4]), "+f"(d[5]), "+f"(d[6]), "+f"(d[7]),
          "+f"(d[8]), "+f"(d[9]), "+f"(d[10]), "+f"(d[11]), "+f"(d[12]), "+f"(d[13]), "+f"(d[14]), "+f"(d[15]),
          "+f"(d[16]), "+f"(d[17]), "+f"(d[18]), "+f"(d[19]), "+f"(d[20]), "+f"(d[21]), "+f"(d[22]), "+f"(d[23]),
          "+f"(d[24]), "+f"(d[25]), "+f"(d[26]), "+f"(d[27]), "+f"(d[28]), "+f"(d[29]), "+f"(d[30]), "+f"(d[31]),
          "+f"(d[32]), "+f"(d[33]), "+f"(d[34]), "+f"(d[35]), "+f"(d[36]), "+f"(d[37]), "+f"(d[38]), "+f"(d[39]),
          "+f"(d[40]), "+f"(d[41]), "+f"(d[42]), "+f"(d[43]), "+f"(d[44]), "+f"(d[45]), "+f"(d[46]), "+f"(d[47]),
          "+f"(d[48]), "+f"(d[49]), "+f"(d[50]), "+f"(d[51]), "+f"(d[52]), "+f"(d[53]), "+f"(d[54]), "+f"(d[55]),
          "+f"(d[56]), "+f"(d[57]), "+f"(d[58]), "+f"(d[59]), "+f"(d[60]), "+f"(d[61]), "+f"(d[62]), "+f"(d[63]),
          "+f"(d[64]), "+f"(d[65]), "+f"(d[66]), "+f"(d[67]), "+f"(d[68]), "+f"(d[69]), "+f"(d[70]), "+f"(d[71]),
          "+f"(d[72]), "+f"(d[73]), "+f"(d[74]), "+f"(d[75]), "+f"(d[76]), "+f"(d[77]), "+f"(d[78]), "+f"(d[79]),
          "+f"(d[80]), "+f"(d[81]), "+f"(d[82]), "+f"(d[83]), "+f"(d[84]), "+f"(d[85]), "+f"(d[86]), "+f"(d[87]),
          "+f"(d[88]), "+f"(d[89]), "+f"(d[90]), "+f"(d[91])
        : "l"(da), "l"(db), "r"(accumulate), "n"(TA), "n"(TB));
}

struct Ring {
    int slot; uint32_t ph;
    __device__ __forceinline__ void next() { if (++slot == NSLOT) { slot = 0; ph ^= 1; } }
};
__device__ __forceinline__ uint32_t qslot(int i) { return (uint32_t)(i < 2 ? i + 3 : i - 2) * QSLOT; }

constexpr uint64_t HI_WT = desc_hi(8192, 1024, 1);
constexpr uint64_t HI_WQ = desc_hi(4096, 1024, 1);
constexpr uint64_t HI_KM = desc_hi(16, 1024, 1);
constexpr uint64_t HI_TILE = desc_hi(128, 256, 0);
constexpr uint64_t HI_O = desc_hi(1024, 128, 0);

struct Mma {
    uint32_t bars, rel;
    bool lead;
    int wg;
    Ring r;
    int pend;
    __device__ __forceinline__ void release() { if (lead && pend >= 0) mbar_arrive_remote(rel + B_EMPTY + 8 * pend); }
    template <bool WO>
    __device__ __forceinline__ void run(float (&a)[56], int n, int nrel, int lag, int accumulate, uint64_t dA0, uint64_t dB0, int ts) {
#pragma unroll 1
        for (int i = 0; i < n; i++) {
            if (lag && wg == 1 && i == n - lag) bar_sync(7, 256);
            const int s = r.slot;
            mbar_wait(bars + B_FULL + 8 * s, r.ph); r.next();
            const uint64_t dA = dA0 + s * (SLOT >> 4), dB = dB0 + s * (SLOT >> 4);
            wg_fence();
#pragma unroll
            for (int k = 0; k < 4; k++) {
                if (WO) wgmma_n112<0, 1>(a, dA + k * 128 - (k == 3 ? desc_hi(1024, 0, 0) : 0), dB + k * 128, k > 0 || accumulate);
                else wgmma_n112<1, 1>(a, dA + k * 128, dB + k * (SLAB >> 4), k > 0 || accumulate);
                if (k == 1) { wg_commit(); wg_wait<1>(); if (i < nrel) release(); }
            }
            wg_commit();
            accumulate = 1;
            pend = s;
        }
        if (lag && wg == 0) bar_arrive(7, 256);
    }
    __device__ __forceinline__ void drain(float (&a)[56]) { wg_wait<0>(); pin(a); release(); pend = -1; }
};

__global__ void __cluster_dims__(2, 1, 1) __launch_bounds__(NTHREADS, 1)
fused_kernel(const __nv_bfloat16* __restrict__ x, const __nv_bfloat16* __restrict__ b1, const __nv_bfloat16* __restrict__ b2, __nv_bfloat16* out, Scratch* G,
             const __grid_constant__ Params P) {
    extern __shared__ __align__(1024) uint8_t smem[];
    const uint32_t sbase = (uint32_t)__cvta_generic_to_shared(smem);
    const uint32_t bars = sbase + OFF_BAR;
    const int c = blockIdx.x, lane = threadIdx.x & 31;
    const int warp = __shfl_sync(~0u, threadIdx.x >> 5, 0), w = warp & 3;
    const int tb = c & 15, hp = c >> 4;
    const bool has_g1 = c < NG1;
    const int rank = c & 1;
    const int q1 = ((c >> 1) & 7) * 7 + (c >> 4), nt1 = q1 & 3, ft = q1 >> 2;
    const int nt2 = c & 3, mt = (c >> 2) & 15, ks = c >> 6;

    if (warp == 8) {
        if (elect()) {
            TS(0);
#pragma unroll
            for (int i = 0; i < NBAR; i++) mbar_init(bars + 8 * i, i < B_HALO / 8 ? 1 : i < B_QEMPTY / 8 ? 2 : i == B_QEMPTY / 8 ? 7 : 4);
            asm volatile("fence.mbarrier_init.release.cluster;" ::: "memory");
            mbar_expect(bars + B_ROW, TILEB);
            bulk_load(sbase + OFF_Y, x + (tb * 128 + hp * 16) * D_, TILEB, bars + B_ROW);
        }
        __syncwarp();
    }
    asm volatile("barrier.cluster.arrive.relaxed.aligned;\nbarrier.cluster.wait.aligned;" ::: "memory");

    if (warp == 8) {
        if (elect()) {
            int kq = (tb >> 1) == 7 ? 0 : tb >> 1;
            uint32_t due = (uint32_t)clock();
#pragma unroll 1
            for (int i = 0; i < 7; i++) {
                if (i >= 5) mbar_wait(bars + B_QEMPTY + 8 * (i - 5), 0);
                else { while ((int)((uint32_t)clock() - due) < 0) {} due += PACE; }
                mbar_expect(bars + B_QFULL + 8 * i, QSLOT);
                tma3d(sbase + qslot(i), &P.tmX, bars + B_QFULL + 8 * i, kq * 64, tb * 64, 0);
                tma3d_pair(sbase + qslot(i) + 16384 + rank * 12288, &P.tmWqkv, bars + B_QFULL + 8 * i, (hp * 56) & ~15, kq * 64 + rank * 32, 0);
                if (++kq == 7) kq = 0;
                if (i == 0) TS(23);
            }
            mbar_expect(bars + B_X, HALF); mbar_expect(bars + B_X + 8, HALF);
            Ring r{0, 0};
#pragma unroll 1
            for (int j = has_g1 ? 0 : 16; j < 34; j++) {
                const uint32_t dst = sbase + r.slot * SLOT, full = bars + B_FULL + 8 * r.slot;
                mbar_wait(bars + B_EMPTY + 8 * r.slot, r.ph);
                mbar_expect(full, 16384 + TILEB);
                if (j < 16) {
                    tma3d(dst, &P.tmW1, full, 0, (rank * 16 + j) * 64, ft * 2);
                } else if (j < 20) {
                    tma3d(dst + 16384, &P.tmWo, full, nt2 * 112, 0, ks * 4 + j - 16);
                    tma3d(dst + 24576, &P.tmWo, full, nt2 * 112 + 64, 0, ks * 4 + j - 16);
                } else {
                    tma2d_pair(dst + rank * 8192, &P.tmW2, full, mt * 128 + rank * 64, (ks * 14 + (j < 27 ? 2 * j - 40 : 2 * j - 53)) * 64);
                }
                r.next();
            }
        }
    } else if (warp > 8) {
        uint32_t ep = ld_relaxed(&G->epoch[c]);
        if (w == 2) {
            bar_sync(6, 160);
            if (elect()) {
#pragma unroll
                for (int i = 0; i < 4; i++) bulk_store(G->H + (size_t)((tb * 2 + (hp >> 2)) * 4 + i) * TILEB + (hp & 3) * SLAB, sbase + OFF_Y + i * SLAB, SLAB);
                bulk_store(G->stat + 16 + tb * 128 + hp * 16, sbase + OFF_REC, 128);
            }
            __syncwarp();
        }
        {
            mbar_wait(bars + B_QFULL, 0);
            const uint32_t src = sbase + qslot(0) + 16384 + rank * 12288 + (w - 1) * 4096 + lane * 4;
            float s0 = 0.f, s1 = 0.f;
#pragma unroll 1
            for (int i = 0; i < 2; i++) {
                uint32_t v[16];
#pragma unroll
                for (int k = 0; k < 16; k++) v[k] = __float_as_uint(lds1f((src ^ ((k & 7) * 144)) + (k >> 3) * 1024 + i * 2048));
#pragma unroll
                for (int k = 0; k < 16; k++) { s0 += bf_lo(v[k]); s1 += bf_hi(v[k]); }
            }
            sts2(sbase + OFF_REC + 128 + (w - 1) * 256 + lane * 8, __float_as_uint(s0), __float_as_uint(s1));
            fence_async_shared();
            __syncwarp();
            if (w == 1) TSL(24);
            if (tb == 15) *(float2*)(G->colsum[ep & 1][hp] + (w - 1) * 64 + lane * 2) = make_float2(0.f, 0.f);
            ep = inc_late(ep);
            if (elect()) {
                mbar_arrive(bars + B_QEMPTY);
                if (tb < 14)
                    asm volatile("cp.reduce.async.bulk.global.shared::cta.bulk_group.add.f32 [%0], [%1], 256;" ::"l"(G->colsum[ep & 1][hp] + (w - 1) * 64), "r"(sbase + OFF_REC + 128 + (w - 1) * 256) : "memory");
                bulk_commit();
                bulk_wait_all();
                red_after_bulk(&G->flagH[c >> 2]);
                if (w == 2) TS(3);
            }
            __syncwarp();
        }
        if (w == 1) {
            uint32_t it = 0;
            while (!__all_sync(~0u, ld_acquire(&G->flagH[lane]) == 12 * ep)) { __nanosleep(POLL_NS); spin_guard(++it); }
            if (elect()) {
                fence_async_global();
                TS(16);
                mbar_expect(bars + B_REC, 1152 + 768);
                bulk_load(sbase + OFF_CS, G->colsum[ep & 1][hp], 768, bars + B_REC);
                bulk_load(sbase + OFF_ST, G->stat + tb * 128, 1152, bars + B_REC);
                Ring r{0, 0};
#pragma unroll 1
                for (int j = has_g1 ? 0 : 16; j < 34; j++) {
                    if (j == 16 || j == 20 || j == 26 || j == 27) {
                        wait_flag(j == 16 ? G->flagO[mt * 2 + ks] : j == 27 ? G->flagInit[mt] : G->flagU[nt2 * 4 + ks * 2 + (j == 26)], (j == 16 ? 4 : j == 27 ? 1 : 14) * ep);
                        fence_async_global();
                        TS(j == 16 ? 18 : j == 20 ? 17 : j);
                    }
                    const uint32_t dst = sbase + r.slot * SLOT, full = bars + B_FULL + 8 * r.slot;
                    mbar_wait(bars + B_EMPTY + 8 * r.slot, r.ph);
                    if (j >= 16 && j < 20) bulk_load_pair(dst + rank * 8192, G->O + (size_t)((ks * 4 + j - 16) * 16 + mt) * TILEB + rank * HALF, HALF, full);
                    else bulk_load(dst + 16384, G->H + (size_t)(j < 16 ? (rank * 16 + j) * 4 + nt1 : (32 + ks * 14 + (j < 27 ? 2 * j - 40 : 2 * j - 53)) * 4 + nt2) * TILEB, TILEB, full);
                    r.next();
                }
                G->epoch[c] = ep;
            }
        } else {
            bar_sync(3, 320);
            if (w == 2) {
                if (tb > 0) {
                    if (elect()) {
                        mbar_expect(bars + B_HALO, 2 * KV);
                        wait_flag(&G->flagHalo[c - 1], ep);
                        fence_async_global();
                        bulk_load(sbase + OFF_X, G->halo[c - 1], KV, bars + B_HALO);
                        bulk_load(sbase + OFF_X + XW, G->halo[c - 1] + KV, KV, bars + B_HALO);
                        TS(21);
                    }
                } else {
#pragma unroll 1
                    for (int i = lane; i < KV / 16; i += 32) { sts4(sbase + OFF_X + i * 16, make_uint4(0u, 0u, 0u, 0u)); sts4(sbase + OFF_X + XW + i * 16, make_uint4(0u, 0u, 0u, 0u)); }
                    __syncwarp();
                    if (lane == 0) mbar_arrive(bars + B_HALO);
                }
                __syncwarp();
            } else {
                if (elect()) {
                    mbar_arrive(bars + B_HALO);
                    bulk_store(G->halo[c], sbase + OFF_X + 4 * KV, KV);
                    bulk_store(G->halo[c] + KV, sbase + OFF_X + XW + 4 * KV, KV);
                    bulk_commit();
                    bulk_wait_all();
                    red_after_bulk(&G->flagHalo[c]);
                }
                __syncwarp();
                bar_sync(4, 288);
                if (elect()) {
                    bulk_store(G->O + (size_t)c * TILEB, sbase + OFF_Y, TILEB);
                    bulk_commit();
                    mbar_arrive_remote(mapa(bars + B_FREE, rank ^ 1));
                    bulk_wait_all();
                    red_after_bulk(G->flagO[tb * 2 + (hp >> 2)]);
                    mbar_arrive(bars + B_FREE);
                    TS(22);
                    if (!has_g1) red_release(G->flagInit[tb]);
                }
                __syncwarp();
            }
            if (has_g1) {
                bar_sync(w + 6, 160);
                if (elect()) {
                    const int m = w - 2;
#pragma unroll
                    for (int i = 0; i < 4; i++) bulk_store(G->U + (size_t)((ft * 2 + m) * 4 + nt1) * TILEB + i * SLAB + rank * KV, sbase + OFF_Y + m * HALF + i * KV, KV);
                    bulk_commit();
                    bulk_wait_all();
                    red_after_bulk(G->flagU[nt1 * 4 + (ft >= 7) * 2 + m]);
                    mbar_arrive(bars + B_FREE);
                    TS(5 + w);
                }
            }
        }
    } else {
        const int wg = warp >> 2;
        Mma M{bars, mapa(bars, rank ^ (lane & 1)), (threadIdx.x & 127) < 2, wg, Ring{0, 0}, -1};
        if (wg == 1) {
            const int r16 = w * 4 + (lane & 3), c8 = ((lane >> 2) + 2 * lane) & 7;
            const uint32_t row = sbase + OFF_Y + r16 * (2 * D_) + c8 * 16;
            mbar_wait(bars + B_ROW, 0);
            TS0(67);
            float f[56];
#pragma unroll
            for (int i = 0; i < 7; i++) {
                const uint4 v = lds4(row + i * 128);
                f[8 * i] = bf_lo(v.x); f[8 * i + 1] = bf_hi(v.x); f[8 * i + 2] = bf_lo(v.y); f[8 * i + 3] = bf_hi(v.y);
                f[8 * i + 4] = bf_lo(v.z); f[8 * i + 5] = bf_hi(v.z); f[8 * i + 6] = bf_lo(v.w); f[8 * i + 7] = bf_hi(v.w);
            }
            float s0 = 0.f, s1 = 0.f, s2 = 0.f, s3 = 0.f;
#pragma unroll
            for (int i = 0; i < 56; i += 4) { s0 += f[i]; s1 += f[i + 1]; s2 += f[i + 2]; s3 += f[i + 3]; }
            const float mean = oct_sum((s0 + s1) + (s2 + s3)) * (1.f / D_);
            bar_sync(5, 128);
            s0 = s1 = s2 = s3 = 0.f;
#pragma unroll
            for (int i = 0; i < 56; i += 4) {
                f[i] -= mean; f[i + 1] -= mean; f[i + 2] -= mean; f[i + 3] -= mean;
                s0 = fmaf(f[i], f[i], s0); s1 = fmaf(f[i + 1], f[i + 1], s1); s2 = fmaf(f[i + 2], f[i + 2], s2); s3 = fmaf(f[i + 3], f[i + 3], s3);
            }
            const float var = oct_sum((s0 + s1) + (s2 + s3)) * (1.f / D_);
            const float rstd = rsqrtf(var + LN_EPS);
            const float sc = rstd * rsqrtf(var * rstd * rstd + LN_EPS);
            if (lane < 4) sts2(sbase + OFF_REC + r16 * 8, __float_as_uint(rstd), __float_as_uint(-mean));
            const int sw = tb < 8 ? 0 : 7 * 256;
            const uint32_t hb = sbase + OFF_Y + r16 * 16 + c8 * 256;
#pragma unroll
            for (int i = 0; i < 7; i++) {
                const int lo = (8 * i) % 14;
                const bool up = lo < 7 ? c8 < 7 - lo : c8 >= 14 - lo;
                sts4(hb + (up ? sw : -sw) + i * 2048, make_uint4(pack2(f[8 * i] * sc, f[8 * i + 1] * sc), pack2(f[8 * i + 2] * sc, f[8 * i + 3] * sc),
                                                                  pack2(f[8 * i + 4] * sc, f[8 * i + 5] * sc), pack2(f[8 * i + 6] * sc, f[8 * i + 7] * sc)));
            }
            fence_async_shared();
            TS0(25);
            bar_arrive(6, 160);
        }
        const int r = lane >> 2, t = lane & 3;
        const uint32_t bias0 = ld_u16(b1 + min(ft, 13) * 128 + warp * 16 + r), bias1 = ld_u16(b1 + min(ft, 13) * 128 + warp * 16 + r + 8);
        const uint32_t xw = sbase + OFF_X + (1 - wg) * XW;
        const uint32_t st = sbase + OFF_ST + (16 + w * 32 + wg) * 8;
        uint32_t q[7][2], k0[7], v0[7];
        {
            float acc[92];
            const uint64_t dA0 = HI_KM | desc_lo(sbase + wg * 8192), dB0 = HI_WQ | (desc_lo(sbase + 16384) + (hp & 1));
#pragma unroll 1
            for (int kb = 0; kb < 7; kb++) {
                if (kb == 5 && wg == 1) { wg_wait<0>(); if (M.lead) mbar_arrive_remote(M.rel + B_QEMPTY + 8 * 4); bar_sync(7, 256); }
                mbar_wait(bars + B_QFULL + 8 * kb, 0);
                TS0(68 + wg * 7 + kb);
                const uint64_t dA = dA0 + (qslot(kb) >> 4), dB = dB0 + (qslot(kb) >> 4);
                wg_fence();
#pragma unroll
                for (int k = 0; k < 4; k++) {
                    wgmma_n184<0, 1>(acc, dA + k * 2, dB + (k & 1) * 128 + (k >> 1) * 768, k > 0 || kb > 0);
                    if (k == 0) { wg_commit(); wg_wait<1>(); if (M.lead && kb > 0 && !(kb == 5 && wg == 1)) mbar_arrive_remote(M.rel + B_QEMPTY + 8 * (kb - 1)); }
                }
                wg_commit();
            }
            if (wg == 0) bar_arrive(7, 256);
            mbar_wait(bars + B_REC, 0);
            const float n0 = lds1f(st + r * 16 + 4), n1 = lds1f(st + r * 16 + 132);
            const uint32_t csa = sbase + OFF_CS + t * 8 + (hp & 1) * 32;
            wg_wait<0>();
            pin(acc);
            if (M.lead) { mbar_arrive_remote(M.rel + B_QEMPTY + 8 * 6); mbar_arrive_remote(M.rel + B_QEMPTY + 8 * 7); }
            TS0(4 + 7 * wg);
            uint32_t hi[14];
#pragma unroll
            for (int p = 2; p >= 0; p--) {
#pragma unroll
                for (int g = 0; g < 7; g++) {
                    const uint2 cs = lds2(csa + (p * 8 + g) * 32);
                    const int a = (p * 8 + g) * 4;
                    const float c0 = __uint_as_float(cs.x), c1 = __uint_as_float(cs.y);
                    const uint32_t lo2 = pack2(fmaf(n0, c0, acc[a]), fmaf(n0, c1, acc[a + 1])), hi2 = pack2(fmaf(n1, c0, acc[a + 2]), fmaf(n1, c1, acc[a + 3]));
                    if (p == 0) { q[g][0] = lo2; q[g][1] = hi2; } else { (p == 1 ? k0 : v0)[g] = lo2; hi[(p - 1) * 7 + g] = hi2; }
                }
                if (p == 1) {
                    const uint32_t dst = xw + (w + 1) * KV + lane * 16;
#pragma unroll
                    for (int i = 0; i < 3; i++) stsm4(dst + i * 512, hi[4 * i], hi[4 * i + 1], hi[4 * i + 2], hi[4 * i + 3]);
                    stsm2(dst + 1536, hi[12], hi[13]);
                    if (w == 3) fence_async_shared();
                    bar_arrive(3, 320);
                }
            }
        }
        TS0(9 + 11 * wg);
        float a[56];
        const uint64_t dA0 = HI_WT | desc_lo(sbase + wg * 8192), dB0 = HI_TILE | desc_lo(sbase + 16384);
        const int n1 = PAUSE + (wg == 0 ? LEAD : 0);
        if (has_g1) {
            M.run<false>(a, n1, 16, 0, 0, dA0, dB0, 32);
        } else {
#pragma unroll 1
            for (int i = 0; i < 2; i++) {
                const int tok = tb * 128 + warp * 16 + i * 8 + (lane >> 3);
                const uint4* src = (const uint4*)(x + tok * D_) + (lane & 7);
                uint4* dst = (uint4*)(out + tok * D_) + (lane & 7);
                const uint32_t b[2] = {ld_u16(b2 + tok) * 0x10001u, ld_u16(b2 + tok + 4) * 0x10001u};
                uint4 v[14];
#pragma unroll
                for (int k = 0; k < 14; k++) v[k] = __ldg(src + (k / 7) * 224 + (k % 7) * 8);
#pragma unroll
                for (int k = 0; k < 14; k++) dst[(k / 7) * 224 + (k % 7) * 8] = make_uint4(add_bf2(v[k].x, b[k / 7]), add_bf2(v[k].y, b[k / 7]), add_bf2(v[k].z, b[k / 7]), add_bf2(v[k].w, b[k / 7]));
            }
#pragma unroll
            for (int i = 0; i < 56; i++) asm volatile("" : "=f"(a[i]));
        }
        {
            uint32_t kp[8], k1[8], vp[8], v1[8];
            mbar_wait(bars + B_HALO, 0);
            const uint32_t src = xw + w * KV + lane * 16;
            ldsm4(kp, src); ldsm4(kp + 4, src + 512); ldsm4(k1, src + KV); ldsm4(k1 + 4, src + KV + 512);
            ldsm4t(vp, src + 896); ldsm4t(vp + 4, src + 1408); ldsm4t(v1, src + KV + 896); ldsm4t(v1 + 4, src + KV + 1408);
#pragma unroll
            for (int g = 0; g < 7; g++) v0[g] = transpose8(v0[g]);
            const bool e0 = 2 * t > r, e1 = 2 * t + 1 > r;
            const uint32_t ka = st + t * 32 - (e0 ? 128 : 0), kb = st + t * 32 + 16 - (e1 ? 128 : 0);
            const float rk[4] = {lds1f(ka), lds1f(kb), lds1f(ka + 128), lds1f(kb + 128)};
            const float sq0 = lds1f(st + r * 16) * (0.1889822365046136f * 1.4426950408889634f), sq1 = lds1f(st + r * 16 + 128) * (0.1889822365046136f * 1.4426950408889634f);
            const float sc[4] = {sq0 * rk[0], sq0 * rk[1], sq1 * rk[2], sq1 * rk[3]};
            const uint32_t mask = (e0 ? 0xffffu : 0u) | (e1 ? 0xffff0000u : 0u);
            const bool first = tb == 0 && w == 0;
            M.drain(a);
            bar_sync(2, 256);
            TS0(12 + 16 * wg);
            float sv[2][4];
#pragma unroll
            for (int h = 0; h < 2; h++) {
                const uint32_t m0 = (t < 2) == (h == 0) ? q[3][0] : 0u, m1 = (t < 2) == (h == 0) ? q[3][1] : 0u;
                const int ga = h * 4, gb = h * 4 + 1, gc = h * 4 + 2;
                float s[3][4] = {};
                mma16(s[0], q[ga][0], q[ga][1], q[gb][0], q[gb][1], kp[ga], kp[gb]);
                mma16(s[1], q[ga][0], q[ga][1], q[gb][0], q[gb][1], k0[ga], k0[gb]);
                mma16(s[2], q[ga][0], q[ga][1], q[gb][0], q[gb][1], k1[ga], k1[gb]);
                mma16(s[0], q[gc][0], q[gc][1], m0, m1, kp[gc], kp[3]);
                mma16(s[1], q[gc][0], q[gc][1], m0, m1, k0[gc], k0[3]);
                mma16(s[2], q[gc][0], q[gc][1], m0, m1, k1[gc], k1[3]);
                sv[h][0] = e0 ? (first ? -1e30f : s[0][0] * sc[0]) : s[1][0] * sc[0];
                sv[h][1] = e1 ? (first ? -1e30f : s[0][1] * sc[1]) : s[1][1] * sc[1];
                sv[h][2] = (e0 ? s[1][2] : s[2][2]) * sc[2];
                sv[h][3] = (e1 ? s[1][3] : s[2][3]) * sc[3];
            }
            uint32_t pp[2][2];
#pragma unroll
            for (int i = 0; i < 4; i++) {
                float* v = &sv[i >> 1][(i & 1) * 2];
                const float m = quad_max(fmaxf(v[0], v[1]));
                const float p0 = ex2(v[0] - m), p1 = ex2(v[1] - m);
                const float inv = __fdividef(1.f, quad_sum(p0 + p1));
                pp[i >> 1][i & 1] = pack2(p0 * inv * rk[(i & 1) * 2], p1 * inv * rk[(i & 1) * 2 + 1]);
            }
            uint32_t o[8][2];
#pragma unroll
            for (int i = 0; i < 8; i++) {
                const int h = i >> 2, g = i - h;
                float d[4] = {};
                mma16(d, pp[h][0] & mask, 0u, pp[h][0] & ~mask, pp[h][1] & mask, vp[g], v0[g]);
                mma8(d, 0u, pp[h][1] & ~mask, v1[g]);
                o[i][0] = pack2(d[0], d[1]); o[i][1] = pack2(d[2], d[3]);
            }
            if (t >= 2) { o[3][0] = o[4][0]; o[3][1] = o[4][1]; }
            const uint32_t dst = sbase + OFF_Y + (w >> 1) * HALF + ((w & 1) * 32 + (lane & 15) * 2 + wg) * 16 + (lane >> 4) * 1024;
            stsm4(dst, o[0][0], o[0][1], o[1][0], o[1][1]);
            stsm4(dst + 2048, o[2][0], o[2][1], o[3][0], o[3][1]);
            stsm4(dst + 4096, o[5][0], o[5][1], o[6][0], o[6][1]);
            stsm2(dst + 6144, o[7][0], o[7][1]);
            fence_async_shared();
            bar_sync(4, 288);
            TS0(10 + 19 * wg);
        }
        if (has_g1) {
            M.run<false>(a, 16 - n1, 16, LAG1, 1, dA0, dB0, 32 + PAUSE + LEAD);
            mbar_wait_cluster(bars + B_FREE, 0);
            const uint32_t xb = xw + (threadIdx.x & 127) * 16;
            const uint32_t rx = mapa(xb, rank ^ 1), rbar = mapa(bars + B_X + 8 * wg, rank ^ 1);
            M.drain(a);
            TS0(5 + wg);
#pragma unroll
            for (int i = 0; i < 3; i++)
                st_async4(rx + i * 2048, rbar, pack2(a[28 + 8 * i], a[29 + 8 * i]), pack2(a[30 + 8 * i], a[31 + 8 * i]), pack2(a[32 + 8 * i], a[33 + 8 * i]), pack2(a[34 + 8 * i], a[35 + 8 * i]));
            st_async2(rx + 6144, rbar, pack2(a[52], a[53]), pack2(a[54], a[55]));
#pragma unroll
            for (int i = 0; i < 28; i++) a[i] += bf_lo((i & 2) ? bias1 : bias0);
            mbar_wait_cluster(bars + B_X + 8 * wg, 0);
            TS0(1 + wg);
            uint32_t u[16];
#pragma unroll
            for (int i = 0; i < 4; i++) { const uint4 v = lds4(xb + i * 2048); u[4 * i] = v.x; u[4 * i + 1] = v.y; u[4 * i + 2] = v.z; u[4 * i + 3] = v.w; }
#pragma unroll
            for (int i = 0; i < 14; i++) u[i] = pack2(gelu_tanh(a[2 * i] + bf_lo(u[i])), gelu_tanh(a[2 * i + 1] + bf_hi(u[i])));
            const uint32_t stg = sbase + OFF_Y + warp * KV + lane * 16;
#pragma unroll
            for (int i = 0; i < 3; i++) stsm4(stg + i * 512, u[4 * i], u[4 * i + 1], u[4 * i + 2], u[4 * i + 3]);
            stsm2(stg + 1536, u[12], u[13]);
            fence_async_shared();
            bar_arrive(8 + wg, 160);
            TS0(30 + wg);
        }
        M.run<true>(a, 4, 4, 0, 0, HI_O | desc_lo(sbase + wg * 8192), HI_WT | desc_lo(sbase + 16384), 48);
        if (wg == 1) TS0(13);
        M.run<false>(a, 14, 15 - NSLOT, LAG2, 1, dA0, dB0, 52);
        mbar_wait(bars + B_FREE, has_g1);
        const uint32_t stg = sbase + (wg == 0 ? OFF_X : OFF_Y) + w * SLAB;
        const uint32_t sa = stg + (lane & 15) * 224 + (lane >> 4) * 16;
        wg_wait<0>();
        pin(a);
        TS0(14 + wg);
#pragma unroll
        for (int g = 0; g < 7; g++)
            stsm4(sa + g * 32, pack2(a[8 * g], a[8 * g + 1]), pack2(a[8 * g + 2], a[8 * g + 3]), pack2(a[8 * g + 4], a[8 * g + 5]), pack2(a[8 * g + 6], a[8 * g + 7]));
        fence_async_shared();
        __syncwarp();
        if (elect()) {
            asm volatile("cp.reduce.async.bulk.tensor.2d.global.shared::cta.add.tile.bulk_group [%0, {%2, %3}], [%1];" ::"l"(&P.tmOut), "r"(stg), "r"(nt2 * 112), "r"(mt * 128 + warp * 16) : "memory");
            bulk_commit();
            asm volatile("cp.async.bulk.wait_group.read 0;" ::: "memory");
        }
        if (wg == 1) TS0(19);
        TSDUMP();
    }
}

typedef CUresult (*EncodeFn)(CUtensorMap*, CUtensorMapDataType, cuuint32_t, void*, const cuuint64_t*, const cuuint64_t*, const cuuint32_t*, const cuuint32_t*,
                             CUtensorMapInterleave, CUtensorMapSwizzle, CUtensorMapL2promotion, CUtensorMapFloatOOBfill);

void make_map(EncodeFn enc, CUtensorMap* tm, const void* base, bool swizzle, int d0, int d1, int d2, int s1, int s2, int b0, int b1, int b2) {
    const cuuint64_t dims[3] = {(cuuint64_t)d0, (cuuint64_t)d1, (cuuint64_t)d2}, strides[2] = {(cuuint64_t)s1 * 2, (cuuint64_t)s2 * 2};
    const cuuint32_t box[3] = {(cuuint32_t)b0, (cuuint32_t)b1, (cuuint32_t)b2}, es[3] = {1, 1, 1};
    enc(tm, CU_TENSOR_MAP_DATA_TYPE_BFLOAT16, d2 ? 3 : 2, (void*)base, dims, strides, box, es, CU_TENSOR_MAP_INTERLEAVE_NONE,
        swizzle ? CU_TENSOR_MAP_SWIZZLE_128B : CU_TENSOR_MAP_SWIZZLE_NONE, CU_TENSOR_MAP_L2_PROMOTION_L2_128B, CU_TENSOR_MAP_FLOAT_OOB_FILL_NONE);
}

}

extern "C" void kernel_launch(void* const* d_in, const int* in_sizes, int n_in, void* d_out, int out_size) {
    static EncodeFn enc = nullptr;
    static Scratch* scratch = nullptr;
    if (!enc) {
        void* fn = nullptr;
        cudaDriverEntryPointQueryResult qr;
        cudaGetDriverEntryPoint("cuTensorMapEncodeTiled", &fn, cudaEnableDefault, &qr);
        enc = (EncodeFn)fn;
        cudaGetSymbolAddress((void**)&scratch, g_s);
        cudaFuncSetAttribute(fused_kernel, cudaFuncAttributeMaxDynamicSharedMemorySize, SMEM_BYTES);
    }
    Params P;
    const __nv_bfloat16* x = (const __nv_bfloat16*)d_in[0];
    make_map(enc, &P.tmX, x, true, D_, S_ / 2, 2, 2 * D_, D_, 64, 64, 2);
    make_map(enc, &P.tmWqkv, d_in[1], true, D_, D_, 3, 3 * D_, D_, 64, 32, 3);
    make_map(enc, &P.tmW1, d_in[4], true, 64, S_, F_ / 64, F_, 64, 64, 64, 2);
    make_map(enc, &P.tmW2, d_in[6], true, S_, F_, 0, S_, 0, 64, 64, 1);
    make_map(enc, &P.tmWo, d_in[2], true, D_, 56, 8, D_, 56 * D_, 64, 64, 1);
    make_map(enc, &P.tmOut, d_out, false, D_, S_, 0, D_, 0, 112, 16, 1);
    fused_kernel<<<NCTA, NTHREADS, SMEM_BYTES, cudaStreamPerThread>>>(x, (const __nv_bfloat16*)d_in[5], (const __nv_bfloat16*)d_in[7], (__nv_bfloat16*)d_out, scratch, P);
}
```

```cpp
#include <cuda_runtime.h>
#include <cuda_bf16.h>
#include <cuda.h>
#include <stdint.h>

#define POLL_NS 20
#define GATE0 0
#define GATE1 0
#define GATE2 0
#define PACE 800
#define PAUSE 9
#define LEAD 0
#define LAG1 4
#define LAG2 4
#define G1MAP 3

namespace {

constexpr int S_ = 2048, D_ = 448, F_ = 1792;
constexpr int NCTA = 128, NG1 = 112, NTHREADS = 384;
constexpr int NSLOT = 6, SLOT = 32768, QSLOT = 40960, TILEB = 14336, SLAB = 3584, HALF = 7168;
constexpr int KV = 1792, XW = 5 * KV;
constexpr int OFF_X = NSLOT * SLOT;
constexpr int OFF_REC = OFF_X + 16384;
constexpr int OFF_Y = OFF_X + 2 * XW;
constexpr int OFF_CS = OFF_Y + TILEB;
constexpr int OFF_ST = OFF_CS + 768;
constexpr int OFF_BAR = OFF_ST + 1152;
constexpr int SMEM_BYTES = OFF_BAR + 1024;
constexpr int B_QFULL = 0, B_FULL = 56, B_REC = 104, B_ROW = 112, B_X = 120, B_HALO = 136, B_FREE = 144, B_DONE = 152, B_QEMPTY = 160, B_EMPTY = 176, NBAR = 28;
constexpr float LN_EPS = 1e-5f;
constexpr int SPIN_LIMIT = 1 << 22;

struct Scratch {
    uint8_t H[32 * 4 * TILEB];
    uint8_t U[28 * 4 * TILEB];
    uint8_t O[NCTA * TILEB];
    uint8_t halo[NCTA][2 * KV];
    float2 stat[16 + S_];
    float colsum[2][8][192];
    uint32_t flagH[32];
    uint32_t flagU[16][32];
    uint32_t flagO[16][32];
    uint32_t flagHalo[NCTA];
    uint32_t epoch[NCTA];
};
__device__ __align__(1024) Scratch g_s;

#define TS(i)
#define TS0(i)
#define TSL(i)
#define TSDEP(i, v)
#define TSDUMP()
#define TSC(i)

struct Params {
    CUtensorMap tmX, tmWqkv, tmW1, tmW2, tmWo, tmOut;
};

__device__ __forceinline__ void spin_guard(uint32_t it) {
    asm volatile("{\n.reg .pred p;\nsetp.gt.u32 p, %0, %1;\n@p st.global.u32 [%2], %0;\n}" ::"r"(it), "n"(SPIN_LIMIT), "l"(0ull) : "memory");
}
__device__ __forceinline__ bool elect() {
    uint32_t p;
    asm volatile("{\n.reg .pred p;\nelect.sync _|p, 0xffffffff;\nselp.u32 %0, 1, 0, p;\n}" : "=r"(p));
    return p;
}
__device__ __forceinline__ uint32_t now_ns() { uint32_t t; asm volatile("mov.u32 %0, %%globaltimer_lo;" : "=r"(t)); return t; }
__device__ __forceinline__ void gate(uint32_t t) { while ((int)(now_ns() - t) < 0) {} }
__device__ __forceinline__ uint32_t inc_late(uint32_t v) { asm volatile("add.u32 %0, %0, 1;" : "+r"(v)); return v; }
__device__ __forceinline__ void mbar_init(uint32_t b, uint32_t c) { asm volatile("mbarrier.init.shared::cta.b64 [%0], %1;" ::"r"(b), "r"(c) : "memory"); }
__device__ __forceinline__ void mbar_expect(uint32_t b, uint32_t tx) { asm volatile("mbarrier.arrive.expect_tx.shared::cta.b64 _, [%0], %1;" ::"r"(b), "r"(tx) : "memory"); }
__device__ __forceinline__ void mbar_arrive(uint32_t b) { asm volatile("mbarrier.arrive.shared::cta.b64 _, [%0];" ::"r"(b) : "memory"); }
__device__ __forceinline__ void mbar_arrive_remote(uint32_t b) { asm volatile("mbarrier.arrive.shared::cluster.b64 _, [%0];" ::"r"(b) : "memory"); }
#define MBAR_WAIT_ASM(SEM)                                                                                   \
    asm volatile("{\n.reg .pred p;\n.reg .u32 n;\nmov.u32 n, 0;\nWAIT:\nadd.u32 n, n, 1;\nsetp.gt.u32 p, n, %2;\n"       \
                 "@p st.global.u32 [%3], n;\nmbarrier.try_wait.parity" SEM ".shared::cta.b64 p, [%0], %1;\n@!p bra WAIT;\n}" \
                 ::"r"(b), "r"(parity), "n"(SPIN_LIMIT), "l"(0ull) : "memory")
__device__ __forceinline__ void mbar_wait(uint32_t b, uint32_t parity) { MBAR_WAIT_ASM(""); }
__device__ __forceinline__ void mbar_wait_cluster(uint32_t b, uint32_t parity) { MBAR_WAIT_ASM(".acquire.cluster"); }
__device__ __forceinline__ uint32_t mapa(uint32_t a, uint32_t rank) { uint32_t r; asm("mapa.shared::cluster.u32 %0, %1, %2;" : "=r"(r) : "r"(a), "r"(rank)); return r; }
__device__ __forceinline__ void tma3d(uint32_t dst, const CUtensorMap* tm, uint32_t bar, int c0, int c1, int c2) {
    asm volatile("cp.async.bulk.tensor.3d.shared::cluster.global.mbarrier::complete_tx::bytes [%0], [%1, {%3, %4, %5}], [%2];" ::"r"(dst), "l"(tm), "r"(bar), "r"(c0), "r"(c1), "r"(c2) : "memory");
}
__device__ __forceinline__ void tma2d_pair(uint32_t dst, const CUtensorMap* tm, uint32_t bar, int c0, int c1) {
    asm volatile("cp.async.bulk.tensor.2d.shared::cluster.global.mbarrier::complete_tx::bytes.multicast::cluster [%0], [%1, {%3, %4}], [%2], %5;" ::"r"(dst), "l"(tm), "r"(bar), "r"(c0), "r"(c1), "h"((uint16_t)3) : "memory");
}
__device__ __forceinline__ void tma3d_pair(uint32_t dst, const CUtensorMap* tm, uint32_t bar, int c0, int c1, int c2) {
    asm volatile("cp.async.bulk.tensor.3d.shared::cluster.global.mbarrier::complete_tx::bytes.multicast::cluster [%0], [%1, {%3, %4, %5}], [%2], %6;" ::"r"(dst), "l"(tm), "r"(bar), "r"(c0), "r"(c1), "r"(c2), "h"((uint16_t)3) : "memory");
}
__device__ __forceinline__ void bulk_load(uint32_t dst, const void* src, uint32_t bytes, uint32_t bar) {
    asm volatile("cp.async.bulk.shared::cluster.global.mbarrier::complete_tx::bytes [%0], [%1], %2, [%3];" ::"r"(dst), "l"(src), "r"(bytes), "r"(bar) : "memory");
}
__device__ __forceinline__ void bulk_load_pair(uint32_t dst, const void* src, uint32_t bytes, uint32_t bar) {
    asm volatile("cp.async.bulk.shared::cluster.global.mbarrier::complete_tx::bytes.multicast::cluster [%0], [%1], %2, [%3], %4;" ::"r"(dst), "l"(src), "r"(bytes), "r"(bar), "h"((uint16_t)3) : "memory");
}
__device__ __forceinline__ void bulk_store(void* dst, uint32_t src, uint32_t bytes) {
    asm volatile("cp.async.bulk.global.shared::cta.bulk_group [%0], [%1], %2;" ::"l"(dst), "r"(src), "r"(bytes) : "memory");
}
__device__ __forceinline__ void bulk_commit() { asm volatile("cp.async.bulk.commit_group;" ::: "memory"); }
__device__ __forceinline__ void bulk_wait_all() { asm volatile("cp.async.bulk.wait_group 0;" ::: "memory"); }
__device__ __forceinline__ uint32_t ld_acquire(const uint32_t* p) { uint32_t v; asm volatile("ld.acquire.gpu.global.u32 %0, [%1];" : "=r"(v) : "l"(p) : "memory"); return v; }
__device__ __forceinline__ uint32_t ld_u16(const void* p) { uint32_t v; asm volatile("ld.global.nc.u16 %0, [%1];" : "=r"(v) : "l"(p)); return v; }
__device__ __forceinline__ uint32_t ld_relaxed(const uint32_t* p) { uint32_t v; asm volatile("ld.relaxed.gpu.global.u32 %0, [%1];" : "=r"(v) : "l"(p) : "memory"); return v; }
__device__ __forceinline__ void red_release(uint32_t* p) { asm volatile("red.release.gpu.global.add.u32 [%0], 1;" ::"l"(p) : "memory"); }
__device__ __forceinline__ void red_after_bulk(uint32_t* p) {
    asm volatile("red.relaxed.gpu.global.add.u32 [%0], 1;" ::"l"(p) : "memory");
}
__device__ __forceinline__ void fence_async_global() { asm volatile("fence.proxy.async.global;" ::: "memory"); }
__device__ __forceinline__ void fence_async_shared() { asm volatile("fence.proxy.async.shared::cta;" ::: "memory"); }
__device__ __forceinline__ void wait_flag(const uint32_t* p, uint32_t target) {
    uint32_t it = 0;
    while (ld_acquire(p) != target) { __nanosleep(POLL_NS); spin_guard(++it); }
}
__device__ __forceinline__ void bar_sync(int id, int n) { asm volatile("bar.sync %0, %1;" ::"r"(id), "r"(n) : "memory"); }
__device__ __forceinline__ void bar_arrive(int id, int n) { asm volatile("bar.arrive %0, %1;" ::"r"(id), "r"(n) : "memory"); }
__device__ __forceinline__ void wg_fence() { asm volatile("wgmma.fence.sync.aligned;" ::: "memory"); }
__device__ __forceinline__ void wg_commit() { asm volatile("wgmma.commit_group.sync.aligned;" ::: "memory"); }
template <int N> __device__ __forceinline__ void wg_wait() { asm volatile("wgmma.wait_group.sync.aligned %0;" ::"n"(N) : "memory"); }
template <int N> __device__ __forceinline__ void pin(float (&d)[N]) {
#pragma unroll
    for (int i = 0; i < N; i++) asm volatile("" : "+f"(d[i])::"memory");
}
__device__ __forceinline__ constexpr uint64_t desc_hi(uint32_t lbo, uint32_t sbo, uint32_t swz) {
    return ((uint64_t)(lbo >> 4) << 16) | ((uint64_t)(sbo >> 4) << 32) | ((uint64_t)swz << 62);
}
__device__ __forceinline__ uint32_t desc_lo(uint32_t addr) { return (addr & 0x3FFFFu) >> 4; }
__device__ __forceinline__ uint32_t pack2(float lo, float hi) { uint32_t r; asm("cvt.rn.bf16x2.f32 %0, %1, %2;" : "=r"(r) : "f"(hi), "f"(lo)); return r; }
__device__ __forceinline__ float bf_lo(uint32_t v) { return __uint_as_float(v << 16); }
__device__ __forceinline__ float bf_hi(uint32_t v) { return __uint_as_float(v & 0xffff0000u); }
__device__ __forceinline__ uint32_t add_bf2(uint32_t a, uint32_t b) { uint32_t r; asm("add.rn.bf16x2 %0, %1, %2;" : "=r"(r) : "r"(a), "r"(b)); return r; }
__device__ __forceinline__ void stsm4(uint32_t a, uint32_t r0, uint32_t r1, uint32_t r2, uint32_t r3) {
    asm volatile("stmatrix.sync.aligned.m8n8.x4.shared.b16 [%0], {%1, %2, %3, %4};" ::"r"(a), "r"(r0), "r"(r1), "r"(r2), "r"(r3) : "memory");
}
__device__ __forceinline__ void stsm2(uint32_t a, uint32_t r0, uint32_t r1) {
    asm volatile("stmatrix.sync.aligned.m8n8.x2.shared.b16 [%0], {%1, %2};" ::"r"(a), "r"(r0), "r"(r1) : "memory");
}
__device__ __forceinline__ void sts2(uint32_t a, uint32_t r0, uint32_t r1) { asm volatile("st.shared.v2.b32 [%0], {%1, %2};" ::"r"(a), "r"(r0), "r"(r1) : "memory"); }
__device__ __forceinline__ void sts4(uint32_t a, uint4 v) { asm volatile("st.shared.v4.b32 [%0], {%1, %2, %3, %4};" ::"r"(a), "r"(v.x), "r"(v.y), "r"(v.z), "r"(v.w) : "memory"); }
__device__ __forceinline__ uint4 lds4(uint32_t a) { uint4 v; asm volatile("ld.shared.v4.b32 {%0, %1, %2, %3}, [%4];" : "=r"(v.x), "=r"(v.y), "=r"(v.z), "=r"(v.w) : "r"(a) : "memory"); return v; }
__device__ __forceinline__ uint2 lds2(uint32_t a) { uint2 v; asm volatile("ld.shared.v2.b32 {%0, %1}, [%2];" : "=r"(v.x), "=r"(v.y) : "r"(a) : "memory"); return v; }
__device__ __forceinline__ float lds1f(uint32_t a) { float v; asm volatile("ld.shared.f32 %0, [%1];" : "=f"(v) : "r"(a) : "memory"); return v; }
__device__ __forceinline__ void ldsm4(uint32_t* r, uint32_t a) {
    asm volatile("ldmatrix.sync.aligned.m8n8.x4.shared.b16 {%0, %1, %2, %3}, [%4];" : "=r"(r[0]), "=r"(r[1]), "=r"(r[2]), "=r"(r[3]) : "r"(a) : "memory");
}
__device__ __forceinline__ void ldsm4t(uint32_t* r, uint32_t a) {
    asm volatile("ldmatrix.sync.aligned.m8n8.x4.trans.shared.b16 {%0, %1, %2, %3}, [%4];" : "=r"(r[0]), "=r"(r[1]), "=r"(r[2]), "=r"(r[3]) : "r"(a) : "memory");
}
__device__ __forceinline__ uint32_t transpose8(uint32_t v) { uint32_t r; asm volatile("movmatrix.sync.aligned.m8n8.trans.b16 %0, %1;" : "=r"(r) : "r"(v)); return r; }
__device__ __forceinline__ void mma16(float (&c)[4], uint32_t a0, uint32_t a1, uint32_t a2, uint32_t a3, uint32_t b0, uint32_t b1) {
    asm volatile("mma.sync.aligned.m16n8k16.row.col.f32.bf16.bf16.f32 {%0, %1, %2, %3}, {%4, %5, %6, %7}, {%8, %9}, {%0, %1, %2, %3};"
                 : "+f"(c[0]), "+f"(c[1]), "+f"(c[2]), "+f"(c[3]) : "r"(a0), "r"(a1), "r"(a2), "r"(a3), "r"(b0), "r"(b1));
}
__device__ __forceinline__ void mma8(float (&c)[4], uint32_t a0, uint32_t a1, uint32_t b0) {
    asm volatile("mma.sync.aligned.m16n8k8.row.col.f32.bf16.bf16.f32 {%0, %1, %2, %3}, {%4, %5}, {%6}, {%0, %1, %2, %3};"
                 : "+f"(c[0]), "+f"(c[1]), "+f"(c[2]), "+f"(c[3]) : "r"(a0), "r"(a1), "r"(b0));
}
__device__ __forceinline__ void st_async4(uint32_t a, uint32_t bar, uint32_t v0, uint32_t v1, uint32_t v2, uint32_t v3) {
    asm volatile("st.async.weak.shared::cluster.mbarrier::complete_tx::bytes.v4.b32 [%0], {%2, %3, %4, %5}, [%1];" ::"r"(a), "r"(bar), "r"(v0), "r"(v1), "r"(v2), "r"(v3) : "memory");
}
__device__ __forceinline__ void st_async2(uint32_t a, uint32_t bar, uint32_t v0, uint32_t v1) {
    asm volatile("st.async.weak.shared::cluster.mbarrier::complete_tx::bytes.v2.b32 [%0], {%2, %3}, [%1];" ::"r"(a), "r"(bar), "r"(v0), "r"(v1) : "memory");
}
__device__ __forceinline__ float quad_max(float v) { v = fmaxf(v, __shfl_xor_sync(~0u, v, 1)); return fmaxf(v, __shfl_xor_sync(~0u, v, 2)); }
__device__ __forceinline__ float quad_sum(float v) { v += __shfl_xor_sync(~0u, v, 1); return v + __shfl_xor_sync(~0u, v, 2); }
__device__ __forceinline__ float ex2(float v) { float r; asm("ex2.approx.ftz.f32 %0, %1;" : "=f"(r) : "f"(v)); return r; }
__device__ __forceinline__ float gelu_tanh(float u) {
    float z = u * fmaf(u * u, 0.044715f * 0.7978845608028654f, 0.7978845608028654f), t;
    asm("tanh.approx.f32 %0, %1;" : "=f"(t) : "f"(z));
    const float hu = 0.5f * u;
    return fmaf(hu, t, hu);
}
__device__ __forceinline__ float oct_sum(float v) {
    v += __shfl_xor_sync(~0u, v, 4); v += __shfl_xor_sync(~0u, v, 8); v += __shfl_xor_sync(~0u, v, 16);
    return v;
}

template <int TA, int TB>
__device__ __forceinline__ void wgmma_n112(float (&d)[56], uint64_t da, uint64_t db, int accumulate) {
    asm volatile("{\n.reg .pred p;\nsetp.ne.b32 p, %58, 0;\n"
        "wgmma.mma_async.sync.aligned.m64n112k16.f32.bf16.bf16 {"
        "%0, %1, %2, %3, %4, %5, %6, %7, %8, %9, %10, %11, %12, %13, %14, %15, "
        "%16, %17, %18, %19, %20, %21, %22, %23, %24, %25, %26, %27, %28, %29, %30, %31, "
        "%32, %33, %34, %35, %36, %37, %38, %39, %40, %41, %42, %43, %44, %45, %46, %47, "
        "%48, %49, %50, %51, %52, %53, %54, %55"
        "}, %56, %57, p, 1, 1, %59, %60;\n}\n"
        : "+f"(d[0]), "+f"(d[1]), "+f"(d[2]), "+f"(d[3]), "+f"(d[4]), "+f"(d[5]), "+f"(d[6]), "+f"(d[7]),
          "+f"(d[8]), "+f"(d[9]), "+f"(d[10]), "+f"(d[11]), "+f"(d[12]), "+f"(d[13]), "+f"(d[14]), "+f"(d[15]),
          "+f"(d[16]), "+f"(d[17]), "+f"(d[18]), "+f"(d[19]), "+f"(d[20]), "+f"(d[21]), "+f"(d[22]), "+f"(d[23]),
          "+f"(d[24]), "+f"(d[25]), "+f"(d[26]), "+f"(d[27]), "+f"(d[28]), "+f"(d[29]), "+f"(d[30]), "+f"(d[31]),
          "+f"(d[32]), "+f"(d[33]), "+f"(d[34]), "+f"(d[35]), "+f"(d[36]), "+f"(d[37]), "+f"(d[38]), "+f"(d[39]),
          "+f"(d[40]), "+f"(d[41]), "+f"(d[42]), "+f"(d[43]), "+f"(d[44]), "+f"(d[45]), "+f"(d[46]), "+f"(d[47]),
          "+f"(d[48]), "+f"(d[49]), "+f"(d[50]), "+f"(d[51]), "+f"(d[52]), "+f"(d[53]), "+f"(d[54]), "+f"(d[55])
        : "l"(da), "l"(db), "r"(accumulate), "n"(TA), "n"(TB));
}

template <int TA, int TB>
__device__ __forceinline__ void wgmma_n184(float (&d)[92], uint64_t da, uint64_t db, int accumulate) {
    asm volatile("{\n.reg .pred p;\nsetp.ne.b32 p, %94, 0;\n"
        "wgmma.mma_async.sync.aligned.m64n184k16.f32.bf16.bf16 {"
        "%0, %1, %2, %3, %4, %5, %6, %7, %8, %9, %10, %11, %12, %13, %14, %15, "
        "%16, %17, %18, %19, %20, %21, %22, %23, %24, %25, %26, %27, %28, %29, %30, %31, "
        "%32, %33, %34, %35, %36, %37, %38, %39, %40, %41, %42, %43, %44, %45, %46, %47, "
        "%48, %49, %50, %51, %52, %53, %54, %55, %56, %57, %58, %59, %60, %61, %62, %63, "
        "%64, %65, %66, %67, %68, %69, %70, %71, %72, %73, %74, %75, %76, %77, %78, %79, "
        "%80, %81, %82, %83, %84, %85, %86, %87, %88, %89, %90, %91"
        "}, %92, %93, p, 1, 1, %95, %96;\n}\n"
        : "+f"(d[0]), "+f"(d[1]), "+f"(d[2]), "+f"(d[3]), "+f"(d[4]), "+f"(d[5]), "+f"(d[6]), "+f"(d[7]),
          "+f"(d[8]), "+f"(d[9]), "+f"(d[10]), "+f"(d[11]), "+f"(d[12]), "+f"(d[13]), "+f"(d[14]), "+f"(d[15]),
          "+f"(d[16]), "+f"(d[17]), "+f"(d[18]), "+f"(d[19]), "+f"(d[20]), "+f"(d[21]), "+f"(d[22]), "+f"(d[23]),
          "+f"(d[24]), "+f"(d[25]), "+f"(d[26]), "+f"(d[27]), "+f"(d[28]), "+f"(d[29]), "+f"(d[30]), "+f"(d[31]),
          "+f"(d[32]), "+f"(d[33]), "+f"(d[34]), "+f"(d[35]), "+f"(d[36]), "+f"(d[37]), "+f"(d[38]), "+f"(d[39]),
          "+f"(d[40]), "+f"(d[41]), "+f"(d[42]), "+f"(d[43]), "+f"(d[44]), "+f"(d[45]), "+f"(d[46]), "+f"(d[47]),
          "+f"(d[48]), "+f"(d[49]), "+f"(d[50]), "+f"(d[51]), "+f"(d[52]), "+f"(d[53]), "+f"(d[54]), "+f"(d[55]),
          "+f"(d[56]), "+f"(d[57]), "+f"(d[58]), "+f"(d[59]), "+f"(d[60]), "+f"(d[61]), "+f"(d[62]), "+f"(d[63]),
          "+f"(d[64]), "+f"(d[65]), "+f"(d[66]), "+f"(d[67]), "+f"(d[68]), "+f"(d[69]), "+f"(d[70]), "+f"(d[71]),
          "+f"(d[72]), "+f"(d[73]), "+f"(d[74]), "+f"(d[75]), "+f"(d[76]), "+f"(d[77]), "+f"(d[78]), "+f"(d[79]),
          "+f"(d[80]), "+f"(d[81]), "+f"(d[82]), "+f"(d[83]), "+f"(d[84]), "+f"(d[85]), "+f"(d[86]), "+f"(d[87]),
          "+f"(d[88]), "+f"(d[89]), "+f"(d[90]), "+f"(d[91])
        : "l"(da), "l"(db), "r"(accumulate), "n"(TA), "n"(TB));
}

struct Ring {
    int slot; uint32_t ph;
    __device__ __forceinline__ void next() { if (++slot == NSLOT) { slot = 0; ph ^= 1; } }
};
__device__ __forceinline__ uint32_t qslot(int i) { return (uint32_t)(i < 2 ? i + 3 : i - 2) * QSLOT; }

constexpr uint64_t HI_WT = desc_hi(8192, 1024, 1);
constexpr uint64_t HI_WQ = desc_hi(4096, 1024, 1);
constexpr uint64_t HI_KM = desc_hi(16, 1024, 1);
constexpr uint64_t HI_TILE = desc_hi(128, 256, 0);
constexpr uint64_t HI_O = desc_hi(1024, 128, 0);

struct Mma {
    uint32_t bars, rel;
    bool lead;
    int wg;
    Ring r;
    int pend;
    __device__ __forceinline__ void release() { if (lead && pend >= 0) mbar_arrive_remote(rel + B_EMPTY + 8 * pend); }
    template <bool WO>
    __device__ __forceinline__ void run(float (&a)[56], int n, int nrel, int lag, int accumulate, uint64_t dA0, uint64_t dB0, int ts) {
#pragma unroll 1
        for (int i = 0; i < n; i++) {
            if (lag && wg == 1 && i == n - lag) bar_sync(7, 256);
            const int s = r.slot;
            mbar_wait(bars + B_FULL + 8 * s, r.ph); r.next();
            const uint64_t dA = dA0 + s * (SLOT >> 4), dB = dB0 + s * (SLOT >> 4);
            wg_fence();
#pragma unroll
            for (int k = 0; k < 4; k++) {
                if (WO) wgmma_n112<0, 1>(a, dA + k * 128 - (k == 3 ? desc_hi(1024, 0, 0) : 0), dB + k * 128, k > 0 || accumulate);
                else wgmma_n112<1, 1>(a, dA + k * 128, dB + k * (SLAB >> 4), k > 0 || accumulate);
                if (k == 1) { wg_commit(); wg_wait<1>(); if (i < nrel) release(); }
            }
            wg_commit();
            accumulate = 1;
            pend = s;
        }
        if (lag && wg == 0) bar_arrive(7, 256);
    }
    __device__ __forceinline__ void drain(float (&a)[56]) { wg_wait<0>(); pin(a); release(); pend = -1; }
};

__global__ void __cluster_dims__(2, 1, 1) __launch_bounds__(NTHREADS, 1)
fused_kernel(const __nv_bfloat16* __restrict__ x, const __nv_bfloat16* __restrict__ b1, const __nv_bfloat16* __restrict__ b2, __nv_bfloat16* out, Scratch* G,
             const __grid_constant__ Params P) {
    extern __shared__ __align__(1024) uint8_t smem[];
    const uint32_t sbase = (uint32_t)__cvta_generic_to_shared(smem);
    const uint32_t bars = sbase + OFF_BAR;
    const int c = blockIdx.x, lane = threadIdx.x & 31;
    const int warp = __shfl_sync(~0u, threadIdx.x >> 5, 0), w = warp & 3;
    const int tb = c & 15, hp = c >> 4;
    const bool has_g1 = c < NG1;
    const int rank = c & 1;
    const int q1 = ((c >> 1) & 7) * 7 + (c >> 4), nt1 = q1 & 3, ft = q1 >> 2;
    const int nt2 = c & 3, mt = (c >> 2) & 15, ks = c >> 6;

    if (warp == 8) {
        if (elect()) {
            TS(0);
#pragma unroll
            for (int i = 0; i < NBAR; i++) mbar_init(bars + 8 * i, i < B_HALO / 8 ? 1 : i < B_QEMPTY / 8 ? 2 : i == B_QEMPTY / 8 ? 7 : 4);
            asm volatile("fence.mbarrier_init.release.cluster;" ::: "memory");
            mbar_expect(bars + B_ROW, TILEB);
            bulk_load(sbase + OFF_Y, x + (tb * 128 + hp * 16) * D_, TILEB, bars + B_ROW);
        }
        __syncwarp();
    }
    asm volatile("barrier.cluster.arrive.relaxed.aligned;\nbarrier.cluster.wait.aligned;" ::: "memory");

    if (warp == 8) {
        if (elect()) {
            int kq = (tb >> 1) == 7 ? 0 : tb >> 1;
            uint32_t due = (uint32_t)clock();
#pragma unroll 1
            for (int i = 0; i < 7; i++) {
                if (i >= 5) mbar_wait(bars + B_QEMPTY + 8 * (i - 5), 0);
                else { while ((int)((uint32_t)clock() - due) < 0) {} due += PACE; }
                mbar_expect(bars + B_QFULL + 8 * i, QSLOT);
                tma3d(sbase + qslot(i), &P.tmX, bars + B_QFULL + 8 * i, kq * 64, tb * 64, 0);
                tma3d_pair(sbase + qslot(i) + 16384 + rank * 12288, &P.tmWqkv, bars + B_QFULL + 8 * i, (hp * 56) & ~15, kq * 64 + rank * 32, 0);
                if (++kq == 7) kq = 0;
                if (i == 0) TS(23);
            }
            mbar_expect(bars + B_X, HALF); mbar_expect(bars + B_X + 8, HALF);
            Ring r{0, 0};
#pragma unroll 1
            for (int j = has_g1 ? 0 : 16; j < 34; j++) {
                const uint32_t dst = sbase + r.slot * SLOT, full = bars + B_FULL + 8 * r.slot;
                mbar_wait(bars + B_EMPTY + 8 * r.slot, r.ph);
                mbar_expect(full, 16384 + TILEB);
                if (j < 16) {
                    tma3d(dst, &P.tmW1, full, 0, (rank * 16 + j) * 64, ft * 2);
                } else if (j < 20) {
                    tma3d(dst + 16384, &P.tmWo, full, nt2 * 112, 0, ks * 4 + j - 16);
                    tma3d(dst + 24576, &P.tmWo, full, nt2 * 112 + 64, 0, ks * 4 + j - 16);
                } else {
                    tma2d_pair(dst + rank * 8192, &P.tmW2, full, mt * 128 + rank * 64, (ks * 14 + (j < 27 ? 2 * j - 40 : 2 * j - 53)) * 64);
                }
                r.next();
            }
        }
    } else if (warp > 8) {
        uint32_t ep = ld_relaxed(&G->epoch[c]);
        if (w == 2) {
            bar_sync(6, 160);
            if (elect()) {
#pragma unroll
                for (int i = 0; i < 4; i++) bulk_store(G->H + (size_t)((tb * 2 + (hp >> 2)) * 4 + i) * TILEB + (hp & 3) * SLAB, sbase + OFF_Y + i * SLAB, SLAB);
                bulk_store(G->stat + 16 + tb * 128 + hp * 16, sbase + OFF_REC, 128);
            }
            __syncwarp();
        }
        {
            mbar_wait(bars + B_QFULL, 0);
            const uint32_t src = sbase + qslot(0) + 16384 + rank * 12288 + (w - 1) * 4096 + lane * 4;
            float s0 = 0.f, s1 = 0.f;
#pragma unroll 1
            for (int i = 0; i < 2; i++) {
                uint32_t v[16];
#pragma unroll
                for (int k = 0; k < 16; k++) v[k] = __float_as_uint(lds1f((src ^ ((k & 7) * 144)) + (k >> 3) * 1024 + i * 2048));
#pragma unroll
                for (int k = 0; k < 16; k++) { s0 += bf_lo(v[k]); s1 += bf_hi(v[k]); }
            }
            sts2(sbase + OFF_REC + 128 + (w - 1) * 256 + lane * 8, __float_as_uint(s0), __float_as_uint(s1));
            fence_async_shared();
            __syncwarp();
            if (w == 1) TSL(24);
            if (tb == 15) *(float2*)(G->colsum[ep & 1][hp] + (w - 1) * 64 + lane * 2) = make_float2(0.f, 0.f);
            ep = inc_late(ep);
            if (elect()) {
                mbar_arrive(bars + B_QEMPTY);
                if (tb < 14)
                    asm volatile("cp.reduce.async.bulk.global.shared::cta.bulk_group.add.f32 [%0], [%1], 256;" ::"l"(G->colsum[ep & 1][hp] + (w - 1) * 64), "r"(sbase + OFF_REC + 128 + (w - 1) * 256) : "memory");
                bulk_commit();
                bulk_wait_all();
                red_after_bulk(&G->flagH[c >> 2]);
                if (w == 2) TS(3);
            }
            __syncwarp();
        }
        if (w == 1) {
            uint32_t it = 0;
            while (!__all_sync(~0u, ld_acquire(&G->flagH[lane]) == 12 * ep)) { __nanosleep(POLL_NS); spin_guard(++it); }
            if (elect()) {
                fence_async_global();
                TS(16);
                mbar_expect(bars + B_REC, 1152 + 768);
                bulk_load(sbase + OFF_CS, G->colsum[ep & 1][hp], 768, bars + B_REC);
                bulk_load(sbase + OFF_ST, G->stat + tb * 128, 1152, bars + B_REC);
                Ring r{0, 0};
#pragma unroll 1
                for (int j = has_g1 ? 0 : 16; j < 34; j++) {
                    if (j == 16 || j == 20 || j == 26) {
                        wait_flag(j == 16 ? G->flagO[mt] : G->flagU[nt2 * 4 + ks * 2 + (j == 26)], (j == 16 ? 8 : 14) * ep);
                        fence_async_global();
                        TS(j == 16 ? 18 : j == 20 ? 17 : j);
                    }
                    const uint32_t dst = sbase + r.slot * SLOT, full = bars + B_FULL + 8 * r.slot;
                    mbar_wait(bars + B_EMPTY + 8 * r.slot, r.ph);
                    if (j >= 16 && j < 20) bulk_load_pair(dst + rank * 8192, G->O + (size_t)((ks * 4 + j - 16) * 16 + mt) * TILEB + rank * HALF, HALF, full);
                    else bulk_load(dst + 16384, G->H + (size_t)(j < 16 ? (rank * 16 + j) * 4 + nt1 : (32 + ks * 14 + (j < 27 ? 2 * j - 40 : 2 * j - 53)) * 4 + nt2) * TILEB, TILEB, full);
                    r.next();
                }
                G->epoch[c] = ep;
            }
        } else {
            bar_sync(3, 320);
            if (w == 2) {
                if (tb > 0) {
                    if (elect()) {
                        mbar_expect(bars + B_HALO, 2 * KV);
                        wait_flag(&G->flagHalo[c - 1], ep);
                        fence_async_global();
                        bulk_load(sbase + OFF_X, G->halo[c - 1], KV, bars + B_HALO);
                        bulk_load(sbase + OFF_X + XW, G->halo[c - 1] + KV, KV, bars + B_HALO);
                        TS(21);
                    }
                } else {
#pragma unroll 1
                    for (int i = lane; i < KV / 16; i += 32) { sts4(sbase + OFF_X + i * 16, make_uint4(0u, 0u, 0u, 0u)); sts4(sbase + OFF_X + XW + i * 16, make_uint4(0u, 0u, 0u, 0u)); }
                    __syncwarp();
                    if (lane == 0) mbar_arrive(bars + B_HALO);
                }
                __syncwarp();
            } else {
                if (elect()) {
                    mbar_arrive(bars + B_HALO);
                    bulk_store(G->halo[c], sbase + OFF_X + 4 * KV, KV);
                    bulk_store(G->halo[c] + KV, sbase + OFF_X + XW + 4 * KV, KV);
                    bulk_commit();
                    bulk_wait_all();
                    red_after_bulk(&G->flagHalo[c]);
                    mbar_expect(bars + B_ROW, TILEB);
                    bulk_load(sbase + OFF_Y, x + (tb * 128 + hp * 16) * D_, TILEB, bars + B_ROW);
                }
                __syncwarp();
                mbar_wait(bars + B_ROW, 1);
                bar_sync(2, 288);
                if (elect()) bulk_store(out + (tb * 128 + hp * 16) * D_, sbase + OFF_Y, TILEB);
                __syncwarp();
                bar_sync(4, 288);
                if (elect()) {
                    bulk_store(G->O + (size_t)c * TILEB, sbase + OFF_X, TILEB);
                    bulk_commit();
                    bulk_wait_all();
                    mbar_arrive_remote(mapa(bars + B_FREE, rank ^ 1));
                    mbar_arrive(bars + B_FREE);
                    red_after_bulk(G->flagO[tb]);
                    TS(22);
                }
                __syncwarp();
            }
            if (has_g1) bar_sync(w + 6, 160);
            if (elect()) {
                if (has_g1) {
                    const int m = w - 2;
#pragma unroll
                    for (int i = 0; i < 4; i++) bulk_store(G->U + (size_t)((ft * 2 + m) * 4 + nt1) * TILEB + i * SLAB + rank * KV, sbase + OFF_Y + m * HALF + i * KV, KV);
                    bulk_commit();
                    bulk_wait_all();
                    red_after_bulk(G->flagU[nt1 * 4 + (ft >= 7) * 2 + m]);
                    TS(5 + w);
                }
                mbar_arrive(bars + B_DONE);
            }
        }
    } else {
        const int wg = warp >> 2;
        const uint32_t t0 = (GATE0 || GATE1 || GATE2) ? now_ns() : 0;
        Mma M{bars, mapa(bars, rank ^ (lane & 1)), (threadIdx.x & 127) < 2, wg, Ring{0, 0}, -1};
        if (wg == 1) {
            const int r16 = w * 4 + (lane & 3), c8 = ((lane >> 2) + 2 * lane) & 7;
            const uint32_t row = sbase + OFF_Y + r16 * (2 * D_) + c8 * 16;
            mbar_wait(bars + B_ROW, 0);
            TS0(67);
            float f[56];
#pragma unroll
            for (int i = 0; i < 7; i++) {
                const uint4 v = lds4(row + i * 128);
                f[8 * i] = bf_lo(v.x); f[8 * i + 1] = bf_hi(v.x); f[8 * i + 2] = bf_lo(v.y); f[8 * i + 3] = bf_hi(v.y);
                f[8 * i + 4] = bf_lo(v.z); f[8 * i + 5] = bf_hi(v.z); f[8 * i + 6] = bf_lo(v.w); f[8 * i + 7] = bf_hi(v.w);
            }
            float s0 = 0.f, s1 = 0.f, s2 = 0.f, s3 = 0.f;
#pragma unroll
            for (int i = 0; i < 56; i += 4) { s0 += f[i]; s1 += f[i + 1]; s2 += f[i + 2]; s3 += f[i + 3]; }
            const float mean = oct_sum((s0 + s1) + (s2 + s3)) * (1.f / D_);
            bar_sync(5, 128);
            s0 = s1 = s2 = s3 = 0.f;
#pragma unroll
            for (int i = 0; i < 56; i += 4) {
                f[i] -= mean; f[i + 1] -= mean; f[i + 2] -= mean; f[i + 3] -= mean;
                s0 = fmaf(f[i], f[i], s0); s1 = fmaf(f[i + 1], f[i + 1], s1); s2 = fmaf(f[i + 2], f[i + 2], s2); s3 = fmaf(f[i + 3], f[i + 3], s3);
            }
            const float var = oct_sum((s0 + s1) + (s2 + s3)) * (1.f / D_);
            const float rstd = rsqrtf(var + LN_EPS);
            const float sc = rstd * rsqrtf(var * rstd * rstd + LN_EPS);
            if (lane < 4) sts2(sbase + OFF_REC + r16 * 8, __float_as_uint(rstd), __float_as_uint(-mean));
            const int sw = tb < 8 ? 0 : 7 * 256;
            const uint32_t hb = sbase + OFF_Y + r16 * 16 + c8 * 256;
#pragma unroll
            for (int i = 0; i < 7; i++) {
                const int lo = (8 * i) % 14;
                const bool up = lo < 7 ? c8 < 7 - lo : c8 >= 14 - lo;
                sts4(hb + (up ? sw : -sw) + i * 2048, make_uint4(pack2(f[8 * i] * sc, f[8 * i + 1] * sc), pack2(f[8 * i + 2] * sc, f[8 * i + 3] * sc),
                                                                  pack2(f[8 * i + 4] * sc, f[8 * i + 5] * sc), pack2(f[8 * i + 6] * sc, f[8 * i + 7] * sc)));
            }
            fence_async_shared();
            TS0(25);
            bar_arrive(6, 160);
        }
        const int r = lane >> 2, t = lane & 3;
        const uint32_t bias0 = ld_u16(b1 + min(ft, 13) * 128 + warp * 16 + r), bias1 = ld_u16(b1 + min(ft, 13) * 128 + warp * 16 + r + 8);
        const uint32_t xw = sbase + OFF_X + (1 - wg) * XW;
        const uint32_t st = sbase + OFF_ST + (16 + w * 32 + wg) * 8;
        uint32_t q[7][2], k0[7], v0[7];
        {
            if (GATE0) gate(t0 + GATE0);
            float acc[92];
            const uint64_t dA0 = HI_KM | desc_lo(sbase + wg * 8192), dB0 = HI_WQ | (desc_lo(sbase + 16384) + (hp & 1));
#pragma unroll 1
            for (int kb = 0; kb < 7; kb++) {
                if (kb == 5 && wg == 1) { wg_wait<0>(); if (M.lead) mbar_arrive_remote(M.rel + B_QEMPTY + 8 * 4); bar_sync(7, 256); }
                mbar_wait(bars + B_QFULL + 8 * kb, 0);
                TS0(68 + wg * 7 + kb);
                const uint64_t dA = dA0 + (qslot(kb) >> 4), dB = dB0 + (qslot(kb) >> 4);
                wg_fence();
#pragma unroll
                for (int k = 0; k < 4; k++) {
                    wgmma_n184<0, 1>(acc, dA + k * 2, dB + (k & 1) * 128 + (k >> 1) * 768, k > 0 || kb > 0);
                    if (k == 0) { wg_commit(); wg_wait<1>(); if (M.lead && kb > 0 && !(kb == 5 && wg == 1)) mbar_arrive_remote(M.rel + B_QEMPTY + 8 * (kb - 1)); }
                }
                wg_commit();
            }
            if (wg == 0) bar_arrive(7, 256);
            mbar_wait(bars + B_REC, 0);
            const float n0 = lds1f(st + r * 16 + 4), n1 = lds1f(st + r * 16 + 132);
            const uint32_t csa = sbase + OFF_CS + t * 8 + (hp & 1) * 32;
            wg_wait<0>();
            pin(acc);
            if (M.lead) { mbar_arrive_remote(M.rel + B_QEMPTY + 8 * 6); mbar_arrive_remote(M.rel + B_QEMPTY + 8 * 7); }
            TS0(4 + 7 * wg);
            uint32_t hi[14];
#pragma unroll
            for (int p = 2; p >= 0; p--) {
#pragma unroll
                for (int g = 0; g < 7; g++) {
                    const uint2 cs = lds2(csa + (p * 8 + g) * 32);
                    const int a = (p * 8 + g) * 4;
                    const float c0 = __uint_as_float(cs.x), c1 = __uint_as_float(cs.y);
                    const uint32_t lo2 = pack2(fmaf(n0, c0, acc[a]), fmaf(n0, c1, acc[a + 1])), hi2 = pack2(fmaf(n1, c0, acc[a + 2]), fmaf(n1, c1, acc[a + 3]));
                    if (p == 0) { q[g][0] = lo2; q[g][1] = hi2; } else { (p == 1 ? k0 : v0)[g] = lo2; hi[(p - 1) * 7 + g] = hi2; }
                }
                if (p == 1) {
                    const uint32_t dst = xw + (w + 1) * KV + lane * 16;
#pragma unroll
                    for (int i = 0; i < 3; i++) stsm4(dst + i * 512, hi[4 * i], hi[4 * i + 1], hi[4 * i + 2], hi[4 * i + 3]);
                    stsm2(dst + 1536, hi[12], hi[13]);
                    if (w == 3) fence_async_shared();
                    bar_arrive(3, 320);
                }
            }
        }
        TS0(9 + 11 * wg);
        float a[56];
        const uint64_t dA0 = HI_WT | desc_lo(sbase + wg * 8192), dB0 = HI_TILE | desc_lo(sbase + 16384);
        const int n1 = PAUSE + (wg == 0 ? LEAD : 0);
        if (has_g1) {
            M.run<false>(a, n1, 16, 0, 0, dA0, dB0, 32);
        } else {
#pragma unroll
            for (int i = 0; i < 56; i++) asm volatile("" : "=f"(a[i]));
        }
        {
            uint32_t kp[8], k1[8], vp[8], v1[8];
            mbar_wait(bars + B_HALO, 0);
            const uint32_t src = xw + w * KV + lane * 16;
            ldsm4(kp, src); ldsm4(kp + 4, src + 512); ldsm4(k1, src + KV); ldsm4(k1 + 4, src + KV + 512);
            ldsm4t(vp, src + 896); ldsm4t(vp + 4, src + 1408); ldsm4t(v1, src + KV + 896); ldsm4t(v1 + 4, src + KV + 1408);
#pragma unroll
            for (int g = 0; g < 7; g++) v0[g] = transpose8(v0[g]);
            const bool e0 = 2 * t > r, e1 = 2 * t + 1 > r;
            const uint32_t ka = st + t * 32 - (e0 ? 128 : 0), kb = st + t * 32 + 16 - (e1 ? 128 : 0);
            const float rk[4] = {lds1f(ka), lds1f(kb), lds1f(ka + 128), lds1f(kb + 128)};
            const float sq0 = lds1f(st + r * 16) * (0.1889822365046136f * 1.4426950408889634f), sq1 = lds1f(st + r * 16 + 128) * (0.1889822365046136f * 1.4426950408889634f);
            const float sc[4] = {sq0 * rk[0], sq0 * rk[1], sq1 * rk[2], sq1 * rk[3]};
            const uint32_t mask = (e0 ? 0xffffu : 0u) | (e1 ? 0xffff0000u : 0u);
            const bool first = tb == 0 && w == 0;
            M.drain(a);
            bar_sync(2, 288);
            TS0(12 + 16 * wg);
            float sv[2][4];
#pragma unroll
            for (int h = 0; h < 2; h++) {
                const uint32_t m0 = (t < 2) == (h == 0) ? q[3][0] : 0u, m1 = (t < 2) == (h == 0) ? q[3][1] : 0u;
                const int ga = h * 4, gb = h * 4 + 1, gc = h * 4 + 2;
                float s[3][4] = {};
                mma16(s[0], q[ga][0], q[ga][1], q[gb][0], q[gb][1], kp[ga], kp[gb]);
                mma16(s[1], q[ga][0], q[ga][1], q[gb][0], q[gb][1], k0[ga], k0[gb]);
                mma16(s[2], q[ga][0], q[ga][1], q[gb][0], q[gb][1], k1[ga], k1[gb]);
                mma16(s[0], q[gc][0], q[gc][1], m0, m1, kp[gc], kp[3]);
                mma16(s[1], q[gc][0], q[gc][1], m0, m1, k0[gc], k0[3]);
                mma16(s[2], q[gc][0], q[gc][1], m0, m1, k1[gc], k1[3]);
                sv[h][0] = e0 ? (first ? -1e30f : s[0][0] * sc[0]) : s[1][0] * sc[0];
                sv[h][1] = e1 ? (first ? -1e30f : s[0][1] * sc[1]) : s[1][1] * sc[1];
                sv[h][2] = (e0 ? s[1][2] : s[2][2]) * sc[2];
                sv[h][3] = (e1 ? s[1][3] : s[2][3]) * sc[3];
            }
            uint32_t pp[2][2];
#pragma unroll
            for (int i = 0; i < 4; i++) {
                float* v = &sv[i >> 1][(i & 1) * 2];
                const float m = quad_max(fmaxf(v[0], v[1]));
                const float p0 = ex2(v[0] - m), p1 = ex2(v[1] - m);
                const float inv = __fdividef(1.f, quad_sum(p0 + p1));
                pp[i >> 1][i & 1] = pack2(p0 * inv * rk[(i & 1) * 2], p1 * inv * rk[(i & 1) * 2 + 1]);
            }
            uint32_t o[8][2];
#pragma unroll
            for (int i = 0; i < 8; i++) {
                const int h = i >> 2, g = i - h;
                float d[4] = {};
                mma16(d, pp[h][0] & mask, 0u, pp[h][0] & ~mask, pp[h][1] & mask, vp[g], v0[g]);
                mma8(d, 0u, pp[h][1] & ~mask, v1[g]);
                o[i][0] = pack2(d[0], d[1]); o[i][1] = pack2(d[2], d[3]);
            }
            if (t >= 2) { o[3][0] = o[4][0]; o[3][1] = o[4][1]; }
            const uint32_t dst = sbase + OFF_X + (w >> 1) * HALF + ((w & 1) * 32 + (lane & 15) * 2 + wg) * 16 + (lane >> 4) * 1024;
            stsm4(dst, o[0][0], o[0][1], o[1][0], o[1][1]);
            stsm4(dst + 2048, o[2][0], o[2][1], o[3][0], o[3][1]);
            stsm4(dst + 4096, o[5][0], o[5][1], o[6][0], o[6][1]);
            stsm2(dst + 6144, o[7][0], o[7][1]);
            fence_async_shared();
            bar_sync(4, 288);
            TS0(10 + 19 * wg);
        }
        if (has_g1) {
            if (GATE1) gate(t0 + GATE1);
            M.run<false>(a, 16 - n1, 16, LAG1, 1, dA0, dB0, 32 + PAUSE + LEAD);
            mbar_wait_cluster(bars + B_FREE, 0);
            const uint32_t xb = xw + (threadIdx.x & 127) * 16;
            const uint32_t rx = mapa(xb, rank ^ 1), rbar = mapa(bars + B_X + 8 * wg, rank ^ 1);
            M.drain(a);
            TS0(5 + wg);
#pragma unroll
            for (int i = 0; i < 3; i++)
                st_async4(rx + i * 2048, rbar, pack2(a[28 + 8 * i], a[29 + 8 * i]), pack2(a[30 + 8 * i], a[31 + 8 * i]), pack2(a[32 + 8 * i], a[33 + 8 * i]), pack2(a[34 + 8 * i], a[35 + 8 * i]));
            st_async2(rx + 6144, rbar, pack2(a[52], a[53]), pack2(a[54], a[55]));
#pragma unroll
            for (int i = 0; i < 28; i++) a[i] += bf_lo((i & 2) ? bias1 : bias0);
            mbar_wait_cluster(bars + B_X + 8 * wg, 0);
            TS0(1 + wg);
            uint32_t u[16];
#pragma unroll
            for (int i = 0; i < 4; i++) { const uint4 v = lds4(xb + i * 2048); u[4 * i] = v.x; u[4 * i + 1] = v.y; u[4 * i + 2] = v.z; u[4 * i + 3] = v.w; }
#pragma unroll
            for (int i = 0; i < 14; i++) u[i] = pack2(gelu_tanh(a[2 * i] + bf_lo(u[i])), gelu_tanh(a[2 * i + 1] + bf_hi(u[i])));
            const uint32_t stg = sbase + OFF_Y + warp * KV + lane * 16;
#pragma unroll
            for (int i = 0; i < 3; i++) stsm4(stg + i * 512, u[4 * i], u[4 * i + 1], u[4 * i + 2], u[4 * i + 3]);
            stsm2(stg + 1536, u[12], u[13]);
            fence_async_shared();
            bar_arrive(8 + wg, 160);
            TS0(30 + wg);
        }
        uint32_t c0 = ld_u16(b2 + mt * 128 + warp * 16 + r), c1 = ld_u16(b2 + mt * 128 + warp * 16 + r + 8);
        M.run<true>(a, 4, 4, 0, 0, HI_O | desc_lo(sbase + wg * 8192), HI_WT | desc_lo(sbase + 16384), 48);
        M.drain(a);
        if (wg == 1) TS0(13);
        c0 *= ks == 0 ? 0x10001u : 0u; c1 *= ks == 0 ? 0x10001u : 0u;
        if (GATE2) gate(t0 + GATE2);
        M.run<false>(a, 14, 15 - NSLOT, LAG2, 1, dA0, dB0, 52);
        mbar_wait(bars + B_DONE, 0);
        const uint32_t stg = sbase + (wg == 0 ? OFF_X : OFF_Y) + w * SLAB;
        const uint32_t sa = stg + (lane & 15) * 224 + (lane >> 4) * 16;
        wg_wait<0>();
        pin(a);
        TS0(14 + wg);
#pragma unroll
        for (int g = 0; g < 7; g++)
            stsm4(sa + g * 32, add_bf2(pack2(a[8 * g], a[8 * g + 1]), c0), add_bf2(pack2(a[8 * g + 2], a[8 * g + 3]), c1), add_bf2(pack2(a[8 * g + 4], a[8 * g + 5]), c0), add_bf2(pack2(a[8 * g + 6], a[8 * g + 7]), c1));
        fence_async_shared();
        __syncwarp();
        if (elect()) {
            asm volatile("cp.reduce.async.bulk.tensor.2d.global.shared::cta.add.tile.bulk_group [%0, {%2, %3}], [%1];" ::"l"(&P.tmOut), "r"(stg), "r"(nt2 * 112), "r"(mt * 128 + warp * 16) : "memory");
            bulk_commit();
            asm volatile("cp.async.bulk.wait_group.read 0;" ::: "memory");
        }
        if (wg == 1) TS0(19);
        TSDUMP();
    }
}

typedef CUresult (*EncodeFn)(CUtensorMap*, CUtensorMapDataType, cuuint32_t, void*, const cuuint64_t*, const cuuint64_t*, const cuuint32_t*, const cuuint32_t*,
                             CUtensorMapInterleave, CUtensorMapSwizzle, CUtensorMapL2promotion, CUtensorMapFloatOOBfill);

void make_map(EncodeFn enc, CUtensorMap* tm, const void* base, bool swizzle, int d0, int d1, int d2, int s1, int s2, int b0, int b1, int b2) {
    const cuuint64_t dims[3] = {(cuuint64_t)d0, (cuuint64_t)d1, (cuuint64_t)d2}, strides[2] = {(cuuint64_t)s1 * 2, (cuuint64_t)s2 * 2};
    const cuuint32_t box[3] = {(cuuint32_t)b0, (cuuint32_t)b1, (cuuint32_t)b2}, es[3] = {1, 1, 1};
    enc(tm, CU_TENSOR_MAP_DATA_TYPE_BFLOAT16, d2 ? 3 : 2, (void*)base, dims, strides, box, es, CU_TENSOR_MAP_INTERLEAVE_NONE,
        swizzle ? CU_TENSOR_MAP_SWIZZLE_128B : CU_TENSOR_MAP_SWIZZLE_NONE, CU_TENSOR_MAP_L2_PROMOTION_L2_128B, CU_TENSOR_MAP_FLOAT_OOB_FILL_NONE);
}

}

extern "C" void kernel_launch(void* const* d_in, const int* in_sizes, int n_in, void* d_out, int out_size) {
    static EncodeFn enc = nullptr;
    static Scratch* scratch = nullptr;
    if (!enc) {
        void* fn = nullptr;
        cudaDriverEntryPointQueryResult qr;
        cudaGetDriverEntryPoint("cuTensorMapEncodeTiled", &fn, cudaEnableDefault, &qr);
        enc = (EncodeFn)fn;
        cudaGetSymbolAddress((void**)&scratch, g_s);
        cudaFuncSetAttribute(fused_kernel, cudaFuncAttributeMaxDynamicSharedMemorySize, SMEM_BYTES);
    }
    Params P;
    const __nv_bfloat16* x = (const __nv_bfloat16*)d_in[0];
    make_map(enc, &P.tmX, x, true, D_, S_ / 2, 2, 2 * D_, D_, 64, 64, 2);
    make_map(enc, &P.tmWqkv, d_in[1], true, D_, D_, 3, 3 * D_, D_, 64, 32, 3);
    make_map(enc, &P.tmW1, d_in[4], true, 64, S_, F_ / 64, F_, 64, 64, 64, 2);
    make_map(enc, &P.tmW2, d_in[6], true, S_, F_, 0, S_, 0, 64, 64, 1);
    make_map(enc, &P.tmWo, d_in[2], true, D_, 56, 8, D_, 56 * D_, 64, 64, 1);
    make_map(enc, &P.tmOut, d_out, false, D_, S_, 0, D_, 0, 112, 16, 1);
    fused_kernel<<<NCTA, NTHREADS, SMEM_BYTES, cudaStreamPerThread>>>(x, (const __nv_bfloat16*)d_in[5], (const __nv_bfloat16*)d_in[7], (__nv_bfloat16*)d_out, scratch, P);
}
```

```cpp
#include <cuda_runtime.h>
#include <cuda_bf16.h>
#include <cuda.h>
#include <stdint.h>

#define POLL_NS 20
#define GATE0 0
#define GATE1 0
#define GATE2 0
#define PACE 800
#define PAUSE 10
#define LEAD 0
#define LAG1 4
#define LAG2 5
#define G1MAP 4
#define G2MAP 1
#define VMAP 1

namespace {

constexpr int S_ = 2048, D_ = 448, F_ = 1792;
constexpr int NCTA = 128, NTHREADS = 384;
constexpr int NSLOT = 6, SLOT = 32768, QSLOT = 40960, TILEB = 14336, SLAB = 3584, HALF = 7168;
constexpr int KV = 1792, XW = 5 * KV;
constexpr int OFF_X = NSLOT * SLOT;
constexpr int OFF_REC = OFF_X + 16384;
constexpr int OFF_Y = OFF_X + 2 * XW;
constexpr int OFF_CS = OFF_Y + TILEB;
constexpr int OFF_ST = OFF_CS + 768;
constexpr int OFF_BAR = OFF_ST + 1152;
constexpr int SMEM_BYTES = OFF_BAR + 1024;
constexpr int B_QFULL = 0, B_FULL = 56, B_REC = 104, B_ROW = 112, B_X = 120, B_HALO = 136, B_FREE = 144, B_DONE = 152, B_QEMPTY = 160, B_EMPTY = 176, NBAR = 28;
constexpr float LN_EPS = 1e-5f;
constexpr int SPIN_LIMIT = 1 << 22;

struct Scratch {
    uint8_t H[32 * 4 * TILEB];
    uint8_t U[28 * 4 * TILEB];
    uint8_t O[NCTA * TILEB];
    uint8_t halo[NCTA][2 * KV];
    float2 stat[16 + S_];
    float colsum[2][8][192];
    uint32_t flagH[32];
    uint32_t flagU[16][32];
    uint32_t flagO[16][32];
    uint32_t flagHalo[NCTA];
    uint32_t epoch[NCTA];
};
__device__ __align__(1024) Scratch g_s;

#define TS(i)
#define TS0(i)
#define TSL(i)
#define TSDEP(i, v)
#define TSDUMP()
#define TSC(i)

struct Params {
    CUtensorMap tmX, tmWqkv, tmW1, tmW2, tmWo, tmOut;
};

__device__ __forceinline__ void spin_guard(uint32_t it) {
    asm volatile("{\n.reg .pred p;\nsetp.gt.u32 p, %0, %1;\n@p st.global.u32 [%2], %0;\n}" ::"r"(it), "n"(SPIN_LIMIT), "l"(0ull) : "memory");
}
__device__ __forceinline__ bool elect() {
    uint32_t p;
    asm volatile("{\n.reg .pred p;\nelect.sync _|p, 0xffffffff;\nselp.u32 %0, 1, 0, p;\n}" : "=r"(p));
    return p;
}
__device__ __forceinline__ uint32_t now_ns() { uint32_t t; asm volatile("mov.u32 %0, %%globaltimer_lo;" : "=r"(t)); return t; }
__device__ __forceinline__ void gate(uint32_t t) { while ((int)(now_ns() - t) < 0) {} }
__device__ __forceinline__ uint32_t inc_late(uint32_t v) { asm volatile("add.u32 %0, %0, 1;" : "+r"(v)); return v; }
__device__ __forceinline__ void mbar_init(uint32_t b, uint32_t c) { asm volatile("mbarrier.init.shared::cta.b64 [%0], %1;" ::"r"(b), "r"(c) : "memory"); }
__device__ __forceinline__ void mbar_expect(uint32_t b, uint32_t tx) { asm volatile("mbarrier.arrive.expect_tx.shared::cta.b64 _, [%0], %1;" ::"r"(b), "r"(tx) : "memory"); }
__device__ __forceinline__ void mbar_arrive(uint32_t b) { asm volatile("mbarrier.arrive.shared::cta.b64 _, [%0];" ::"r"(b) : "memory"); }
__device__ __forceinline__ void mbar_arrive_remote(uint32_t b) { asm volatile("mbarrier.arrive.shared::cluster.b64 _, [%0];" ::"r"(b) : "memory"); }
#define MBAR_WAIT_ASM(SEM)                                                                                   \
    asm volatile("{\n.reg .pred p;\n.reg .u32 n;\nmov.u32 n, 0;\nWAIT:\nadd.u32 n, n, 1;\nsetp.gt.u32 p, n, %2;\n"       \
                 "@p st.global.u32 [%3], n;\nmbarrier.try_wait.parity" SEM ".shared::cta.b64 p, [%0], %1;\n@!p bra WAIT;\n}" \
                 ::"r"(b), "r"(parity), "n"(SPIN_LIMIT), "l"(0ull) : "memory")
__device__ __forceinline__ void mbar_wait(uint32_t b, uint32_t parity) { MBAR_WAIT_ASM(""); }
__device__ __forceinline__ void mbar_wait_cluster(uint32_t b, uint32_t parity) { MBAR_WAIT_ASM(".acquire.cluster"); }
__device__ __forceinline__ uint32_t mapa(uint32_t a, uint32_t rank) { uint32_t r; asm("mapa.shared::cluster.u32 %0, %1, %2;" : "=r"(r) : "r"(a), "r"(rank)); return r; }
__device__ __forceinline__ void tma3d(uint32_t dst, const CUtensorMap* tm, uint32_t bar, int c0, int c1, int c2) {
    asm volatile("cp.async.bulk.tensor.3d.shared::cluster.global.mbarrier::complete_tx::bytes [%0], [%1, {%3, %4, %5}], [%2];" ::"r"(dst), "l"(tm), "r"(bar), "r"(c0), "r"(c1), "r"(c2) : "memory");
}
__device__ __forceinline__ void tma2d_pair(uint32_t dst, const CUtensorMap* tm, uint32_t bar, int c0, int c1) {
    asm volatile("cp.async.bulk.tensor.2d.shared::cluster.global.mbarrier::complete_tx::bytes.multicast::cluster [%0], [%1, {%3, %4}], [%2], %5;" ::"r"(dst), "l"(tm), "r"(bar), "r"(c0), "r"(c1), "h"((uint16_t)3) : "memory");
}
__device__ __forceinline__ void tma3d_pair(uint32_t dst, const CUtensorMap* tm, uint32_t bar, int c0, int c1, int c2) {
    asm volatile("cp.async.bulk.tensor.3d.shared::cluster.global.mbarrier::complete_tx::bytes.multicast::cluster [%0], [%1, {%3, %4, %5}], [%2], %6;" ::"r"(dst), "l"(tm), "r"(bar), "r"(c0), "r"(c1), "r"(c2), "h"((uint16_t)3) : "memory");
}
__device__ __forceinline__ void bulk_load(uint32_t dst, const void* src, uint32_t bytes, uint32_t bar) {
    asm volatile("cp.async.bulk.shared::cluster.global.mbarrier::complete_tx::bytes [%0], [%1], %2, [%3];" ::"r"(dst), "l"(src), "r"(bytes), "r"(bar) : "memory");
}
__device__ __forceinline__ void bulk_load_pair(uint32_t dst, const void* src, uint32_t bytes, uint32_t bar) {
    asm volatile("cp.async.bulk.shared::cluster.global.mbarrier::complete_tx::bytes.multicast::cluster [%0], [%1], %2, [%3], %4;" ::"r"(dst), "l"(src), "r"(bytes), "r"(bar), "h"((uint16_t)3) : "memory");
}
__device__ __forceinline__ void bulk_store(void* dst, uint32_t src, uint32_t bytes) {
    asm volatile("cp.async.bulk.global.shared::cta.bulk_group [%0], [%1], %2;" ::"l"(dst), "r"(src), "r"(bytes) : "memory");
}
__device__ __forceinline__ void bulk_commit() { asm volatile("cp.async.bulk.commit_group;" ::: "memory"); }
__device__ __forceinline__ void bulk_wait_all() { asm volatile("cp.async.bulk.wait_group 0;" ::: "memory"); }
__device__ __forceinline__ uint32_t ld_acquire(const uint32_t* p) { uint32_t v; asm volatile("ld.acquire.gpu.global.u32 %0, [%1];" : "=r"(v) : "l"(p) : "memory"); return v; }
__device__ __forceinline__ uint32_t ld_u16(const void* p) { uint32_t v; asm volatile("ld.global.nc.u16 %0, [%1];" : "=r"(v) : "l"(p)); return v; }
__device__ __forceinline__ uint32_t ld_relaxed(const uint32_t* p) { uint32_t v; asm volatile("ld.relaxed.gpu.global.u32 %0, [%1];" : "=r"(v) : "l"(p) : "memory"); return v; }
__device__ __forceinline__ void red_release(uint32_t* p) { asm volatile("red.release.gpu.global.add.u32 [%0], 1;" ::"l"(p) : "memory"); }
__device__ __forceinline__ void red_after_bulk(uint32_t* p) {
    asm volatile("red.relaxed.gpu.global.add.u32 [%0], 1;" ::"l"(p) : "memory");
}
__device__ __forceinline__ void fence_async_global() { asm volatile("fence.proxy.async.global;" ::: "memory"); }
__device__ __forceinline__ void fence_async_shared() { asm volatile("fence.proxy.async.shared::cta;" ::: "memory"); }
__device__ __forceinline__ void wait_flag(const uint32_t* p, uint32_t target) {
    uint32_t it = 0;
    while (ld_acquire(p) != target) { __nanosleep(POLL_NS); spin_guard(++it); }
}
__device__ __forceinline__ void bar_sync(int id, int n) { asm volatile("bar.sync %0, %1;" ::"r"(id), "r"(n) : "memory"); }
__device__ __forceinline__ void bar_arrive(int id, int n) { asm volatile("bar.arrive %0, %1;" ::"r"(id), "r"(n) : "memory"); }
__device__ __forceinline__ void wg_fence() { asm volatile("wgmma.fence.sync.aligned;" ::: "memory"); }
__device__ __forceinline__ void wg_commit() { asm volatile("wgmma.commit_group.sync.aligned;" ::: "memory"); }
template <int N> __device__ __forceinline__ void wg_wait() { asm volatile("wgmma.wait_group.sync.aligned %0;" ::"n"(N) : "memory"); }
template <int N> __device__ __forceinline__ void pin(float (&d)[N]) {
#pragma unroll
    for (int i = 0; i < N; i++) asm volatile("" : "+f"(d[i])::"memory");
}
__device__ __forceinline__ constexpr uint64_t desc_hi(uint32_t lbo, uint32_t sbo, uint32_t swz) {
    return ((uint64_t)(lbo >> 4) << 16) | ((uint64_t)(sbo >> 4) << 32) | ((uint64_t)swz << 62);
}
__device__ __forceinline__ uint32_t desc_lo(uint32_t addr) { return (addr & 0x3FFFFu) >> 4; }
__device__ __forceinline__ uint32_t pack2(float lo, float hi) { uint32_t r; asm("cvt.rn.bf16x2.f32 %0, %1, %2;" : "=r"(r) : "f"(hi), "f"(lo)); return r; }
__device__ __forceinline__ float bf_lo(uint32_t v) { return __uint_as_float(v << 16); }
__device__ __forceinline__ float bf_hi(uint32_t v) { return __uint_as_float(v & 0xffff0000u); }
__device__ __forceinline__ uint32_t add_bf2(uint32_t a, uint32_t b) { uint32_t r; asm("add.rn.bf16x2 %0, %1, %2;" : "=r"(r) : "r"(a), "r"(b)); return r; }
__device__ __forceinline__ void stsm4(uint32_t a, uint32_t r0, uint32_t r1, uint32_t r2, uint32_t r3) {
    asm volatile("stmatrix.sync.aligned.m8n8.x4.shared.b16 [%0], {%1, %2, %3, %4};" ::"r"(a), "r"(r0), "r"(r1), "r"(r2), "r"(r3) : "memory");
}
__device__ __forceinline__ void stsm2(uint32_t a, uint32_t r0, uint32_t r1) {
    asm volatile("stmatrix.sync.aligned.m8n8.x2.shared.b16 [%0], {%1, %2};" ::"r"(a), "r"(r0), "r"(r1) : "memory");
}
__device__ __forceinline__ void sts2(uint32_t a, uint32_t r0, uint32_t r1) { asm volatile("st.shared.v2.b32 [%0], {%1, %2};" ::"r"(a), "r"(r0), "r"(r1) : "memory"); }
__device__ __forceinline__ void sts4(uint32_t a, uint4 v) { asm volatile("st.shared.v4.b32 [%0], {%1, %2, %3, %4};" ::"r"(a), "r"(v.x), "r"(v.y), "r"(v.z), "r"(v.w) : "memory"); }
__device__ __forceinline__ uint4 lds4(uint32_t a) { uint4 v; asm volatile("ld.shared.v4.b32 {%0, %1, %2, %3}, [%4];" : "=r"(v.x), "=r"(v.y), "=r"(v.z), "=r"(v.w) : "r"(a) : "memory"); return v; }
__device__ __forceinline__ uint2 lds2(uint32_t a) { uint2 v; asm volatile("ld.shared.v2.b32 {%0, %1}, [%2];" : "=r"(v.x), "=r"(v.y) : "r"(a) : "memory"); return v; }
__device__ __forceinline__ float lds1f(uint32_t a) { float v; asm volatile("ld.shared.f32 %0, [%1];" : "=f"(v) : "r"(a) : "memory"); return v; }
__device__ __forceinline__ void ldsm4(uint32_t* r, uint32_t a) {
    asm volatile("ldmatrix.sync.aligned.m8n8.x4.shared.b16 {%0, %1, %2, %3}, [%4];" : "=r"(r[0]), "=r"(r[1]), "=r"(r[2]), "=r"(r[3]) : "r"(a) : "memory");
}
__device__ __forceinline__ void ldsm4t(uint32_t* r, uint32_t a) {
    asm volatile("ldmatrix.sync.aligned.m8n8.x4.trans.shared.b16 {%0, %1, %2, %3}, [%4];" : "=r"(r[0]), "=r"(r[1]), "=r"(r[2]), "=r"(r[3]) : "r"(a) : "memory");
}
__device__ __forceinline__ uint32_t transpose8(uint32_t v) { uint32_t r; asm volatile("movmatrix.sync.aligned.m8n8.trans.b16 %0, %1;" : "=r"(r) : "r"(v)); return r; }
__device__ __forceinline__ void mma16(float (&c)[4], uint32_t a0, uint32_t a1, uint32_t a2, uint32_t a3, uint32_t b0, uint32_t b1) {
    asm volatile("mma.sync.aligned.m16n8k16.row.col.f32.bf16.bf16.f32 {%0, %1, %2, %3}, {%4, %5, %6, %7}, {%8, %9}, {%0, %1, %2, %3};"
                 : "+f"(c[0]), "+f"(c[1]), "+f"(c[2]), "+f"(c[3]) : "r"(a0), "r"(a1), "r"(a2), "r"(a3), "r"(b0), "r"(b1));
}
__device__ __forceinline__ void mma8(float (&c)[4], uint32_t a0, uint32_t a1, uint32_t b0) {
    asm volatile("mma.sync.aligned.m16n8k8.row.col.f32.bf16.bf16.f32 {%0, %1, %2, %3}, {%4, %5}, {%6}, {%0, %1, %2, %3};"
                 : "+f"(c[0]), "+f"(c[1]), "+f"(c[2]), "+f"(c[3]) : "r"(a0), "r"(a1), "r"(b0));
}
__device__ __forceinline__ void st_async4(uint32_t a, uint32_t bar, uint32_t v0, uint32_t v1, uint32_t v2, uint32_t v3) {
    asm volatile("st.async.weak.shared::cluster.mbarrier::complete_tx::bytes.v4.b32 [%0], {%2, %3, %4, %5}, [%1];" ::"r"(a), "r"(bar), "r"(v0), "r"(v1), "r"(v2), "r"(v3) : "memory");
}
__device__ __forceinline__ void st_async2(uint32_t a, uint32_t bar, uint32_t v0, uint32_t v1) {
    asm volatile("st.async.weak.shared::cluster.mbarrier::complete_tx::bytes.v2.b32 [%0], {%2, %3}, [%1];" ::"r"(a), "r"(bar), "r"(v0), "r"(v1) : "memory");
}
__device__ __forceinline__ float quad_max(float v) { v = fmaxf(v, __shfl_xor_sync(~0u, v, 1)); return fmaxf(v, __shfl_xor_sync(~0u, v, 2)); }
__device__ __forceinline__ float quad_sum(float v) { v += __shfl_xor_sync(~0u, v, 1); return v + __shfl_xor_sync(~0u, v, 2); }
__device__ __forceinline__ float ex2(float v) { float r; asm("ex2.approx.ftz.f32 %0, %1;" : "=f"(r) : "f"(v)); return r; }
__device__ __forceinline__ float gelu_tanh(float u) {
    float z = u * fmaf(u * u, 0.044715f * 0.7978845608028654f, 0.7978845608028654f), t;
    asm("tanh.approx.f32 %0, %1;" : "=f"(t) : "f"(z));
    const float hu = 0.5f * u;
    return fmaf(hu, t, hu);
}
__device__ __forceinline__ float oct_sum(float v) {
    v += __shfl_xor_sync(~0u, v, 4); v += __shfl_xor_sync(~0u, v, 8); v += __shfl_xor_sync(~0u, v, 16);
    return v;
}

template <int TA, int TB>
__device__ __forceinline__ void wgmma_n112(float (&d)[56], uint64_t da, uint64_t db, int accumulate) {
    asm volatile("{\n.reg .pred p;\nsetp.ne.b32 p, %58, 0;\n"
        "wgmma.mma_async.sync.aligned.m64n112k16.f32.bf16.bf16 {"
        "%0, %1, %2, %3, %4, %5, %6, %7, %8, %9, %10, %11, %12, %13, %14, %15, "
        "%16, %17, %18, %19, %20, %21, %22, %23, %24, %25, %26, %27, %28, %29, %30, %31, "
        "%32, %33, %34, %35, %36, %37, %38, %39, %40, %41, %42, %43, %44, %45, %46, %47, "
        "%48, %49, %50, %51, %52, %53, %54, %55"
        "}, %56, %57, p, 1, 1, %59, %60;\n}\n"
        : "+f"(d[0]), "+f"(d[1]), "+f"(d[2]), "+f"(d[3]), "+f"(d[4]), "+f"(d[5]), "+f"(d[6]), "+f"(d[7]),
          "+f"(d[8]), "+f"(d[9]), "+f"(d[10]), "+f"(d[11]), "+f"(d[12]), "+f"(d[13]), "+f"(d[14]), "+f"(d[15]),
          "+f"(d[16]), "+f"(d[17]), "+f"(d[18]), "+f"(d[19]), "+f"(d[20]), "+f"(d[21]), "+f"(d[22]), "+f"(d[23]),
          "+f"(d[24]), "+f"(d[25]), "+f"(d[26]), "+f"(d[27]), "+f"(d[28]), "+f"(d[29]), "+f"(d[30]), "+f"(d[31]),
          "+f"(d[32]), "+f"(d[33]), "+f"(d[34]), "+f"(d[35]), "+f"(d[36]), "+f"(d[37]), "+f"(d[38]), "+f"(d[39]),
          "+f"(d[40]), "+f"(d[41]), "+f"(d[42]), "+f"(d[43]), "+f"(d[44]), "+f"(d[45]), "+f"(d[46]), "+f"(d[47]),
          "+f"(d[48]), "+f"(d[49]), "+f"(d[50]), "+f"(d[51]), "+f"(d[52]), "+f"(d[53]), "+f"(d[54]), "+f"(d[55])
        : "l"(da), "l"(db), "r"(accumulate), "n"(TA), "n"(TB));
}

template <int TA, int TB>
__device__ __forceinline__ void wgmma_n184(float (&d)[92], uint64_t da, uint64_t db, int accumulate) {
    asm volatile("{\n.reg .pred p;\nsetp.ne.b32 p, %94, 0;\n"
        "wgmma.mma_async.sync.aligned.m64n184k16.f32.bf16.bf16 {"
        "%0, %1, %2, %3, %4, %5, %6, %7, %8, %9, %10, %11, %12, %13, %14, %15, "
        "%16, %17, %18, %19, %20, %21, %22, %23, %24, %25, %26, %27, %28, %29, %30, %31, "
        "%32, %33, %34, %35, %36, %37, %38, %39, %40, %41, %42, %43, %44, %45, %46, %47, "
        "%48, %49, %50, %51, %52, %53, %54, %55, %56, %57, %58, %59, %60, %61, %62, %63, "
        "%64, %65, %66, %67, %68, %69, %70, %71, %72, %73, %74, %75, %76, %77, %78, %79, "
        "%80, %81, %82, %83, %84, %85, %86, %87, %88, %89, %90, %91"
        "}, %92, %93, p, 1, 1, %95, %96;\n}\n"
        : "+f"(d[0]), "+f"(d[1]), "+f"(d[2]), "+f"(d[3]), "+f"(d[4]), "+f"(d[5]), "+f"(d[6]), "+f"(d[7]),
          "+f"(d[8]), "+f"(d[9]), "+f"(d[10]), "+f"(d[11]), "+f"(d[12]), "+f"(d[13]), "+f"(d[14]), "+f"(d[15]),
          "+f"(d[16]), "+f"(d[17]), "+f"(d[18]), "+f"(d[19]), "+f"(d[20]), "+f"(d[21]), "+f"(d[22]), "+f"(d[23]),
          "+f"(d[24]), "+f"(d[25]), "+f"(d[26]), "+f"(d[27]), "+f"(d[28]), "+f"(d[29]), "+f"(d[30]), "+f"(d[31]),
          "+f"(d[32]), "+f"(d[33]), "+f"(d[34]), "+f"(d[35]), "+f"(d[36]), "+f"(d[37]), "+f"(d[38]), "+f"(d[39]),
          "+f"(d[40]), "+f"(d[41]), "+f"(d[42]), "+f"(d[43]), "+f"(d[44]), "+f"(d[45]), "+f"(d[46]), "+f"(d[47]),
          "+f"(d[48]), "+f"(d[49]), "+f"(d[50]), "+f"(d[51]), "+f"(d[52]), "+f"(d[53]), "+f"(d[54]), "+f"(d[55]),
          "+f"(d[56]), "+f"(d[57]), "+f"(d[58]), "+f"(d[59]), "+f"(d[60]), "+f"(d[61]), "+f"(d[62]), "+f"(d[63]),
          "+f"(d[64]), "+f"(d[65]), "+f"(d[66]), "+f"(d[67]), "+f"(d[68]), "+f"(d[69]), "+f"(d[70]), "+f"(d[71]),
          "+f"(d[72]), "+f"(d[73]), "+f"(d[74]), "+f"(d[75]), "+f"(d[76]), "+f"(d[77]), "+f"(d[78]), "+f"(d[79]),
          "+f"(d[80]), "+f"(d[81]), "+f"(d[82]), "+f"(d[83]), "+f"(d[84]), "+f"(d[85]), "+f"(d[86]), "+f"(d[87]),
          "+f"(d[88]), "+f"(d[89]), "+f"(d[90]), "+f"(d[91])
        : "l"(da), "l"(db), "r"(accumulate), "n"(TA), "n"(TB));
}

struct Ring {
    int slot; uint32_t ph;
    __device__ __forceinline__ void next() { if (++slot == NSLOT) { slot = 0; ph ^= 1; } }
};
__device__ __forceinline__ uint32_t qslot(int i) { return (uint32_t)(i < 2 ? i + 3 : i - 2) * QSLOT; }

constexpr uint64_t HI_WT = desc_hi(8192, 1024, 1);
constexpr uint64_t HI_WQ = desc_hi(4096, 1024, 1);
constexpr uint64_t HI_KM = desc_hi(16, 1024, 1);
constexpr uint64_t HI_TILE = desc_hi(128, 256, 0);
constexpr uint64_t HI_O = desc_hi(1024, 128, 0);

struct Mma {
    uint32_t bars, rel;
    bool lead;
    int wg;
    Ring r;
    int pend;
    __device__ __forceinline__ void release() { if (lead && pend >= 0) mbar_arrive_remote(rel + B_EMPTY + 8 * pend); }
    template <bool WO>
    __device__ __forceinline__ void run(float (&a)[56], int n, int nrel, int lag, int accumulate, uint64_t dA0, uint64_t dB0, int ts) {
#pragma unroll 1
        for (int i = 0; i < n; i++) {
            if (lag && wg == 1 && i == n - lag) bar_sync(7, 256);
            const int s = r.slot;
            mbar_wait(bars + B_FULL + 8 * s, r.ph); r.next();
            const uint64_t dA = dA0 + s * (SLOT >> 4), dB = dB0 + s * (SLOT >> 4);
            wg_fence();
#pragma unroll
            for (int k = 0; k < 4; k++) {
                if (WO) wgmma_n112<0, 1>(a, dA + k * 128 - (k == 3 ? desc_hi(1024, 0, 0) : 0), dB + k * 128, k > 0 || accumulate);
                else wgmma_n112<1, 1>(a, dA + k * 128, dB + k * (SLAB >> 4), k > 0 || accumulate);
                if (k == 1) { wg_commit(); wg_wait<1>(); if (i < nrel) release(); }
            }
            wg_commit();
            accumulate = 1;
            pend = s;
        }
        if (lag && wg == 0) bar_arrive(7, 256);
    }
    __device__ __forceinline__ void drain(float (&a)[56]) { wg_wait<0>(); pin(a); release(); pend = -1; }
};

__global__ void __cluster_dims__(2, 1, 1) __launch_bounds__(NTHREADS, 1)
fused_kernel(const __nv_bfloat16* __restrict__ x, const __nv_bfloat16* __restrict__ b1, const __nv_bfloat16* __restrict__ b2, __nv_bfloat16* out, Scratch* G,
             const __grid_constant__ Params P) {
    extern __shared__ __align__(1024) uint8_t smem[];
    const uint32_t sbase = (uint32_t)__cvta_generic_to_shared(smem);
    const uint32_t bars = sbase + OFF_BAR;
    const int lane = threadIdx.x & 31;
    const int warp = __shfl_sync(~0u, threadIdx.x >> 5, 0), w = warp & 3;
    const int rank = blockIdx.x & 1, pr = blockIdx.x >> 1;
    const int late = (pr - 36) / 7, lj = pr - 36 - late * 7;
    const int gp = pr < 4 ? 0 : pr < 36 ? pr & 7 : lj < 4 ? lj + 4 : lj - 3, hp = pr < 4 ? pr + 4 : pr < 36 ? (pr - 4) >> 3 : late + 4;
    const int tb = gp * 2 + rank, c = hp * 16 + tb;
    const bool has_g1 = gp > 0;
    const int nt1 = hp & 3, ft = max(gp - 1, 0) * 2 + (hp >> 2);
    const int nt2 = c & 3, mt = (gp & 2) * 4 + hp, ks = gp >> 2;

    if (warp == 8) {
        if (elect()) {
            TS(0);
#pragma unroll
            for (int i = 0; i < NBAR; i++) mbar_init(bars + 8 * i, i < B_HALO / 8 ? 1 : i < B_QEMPTY / 8 ? 2 : i == B_QEMPTY / 8 ? 7 : 4);
            asm volatile("fence.mbarrier_init.release.cluster;" ::: "memory");
            mbar_expect(bars + B_ROW, TILEB);
            bulk_load(sbase + OFF_Y, x + (tb * 128 + hp * 16) * D_, TILEB, bars + B_ROW);
        }
        __syncwarp();
    }
    asm volatile("barrier.cluster.arrive.relaxed.aligned;\nbarrier.cluster.wait.aligned;" ::: "memory");

    if (warp == 8) {
        if (elect()) {
            int kq = (tb >> 1) == 7 ? 0 : tb >> 1;
            uint32_t due = (uint32_t)clock();
#pragma unroll 1
            for (int i = 0; i < 7; i++) {
                if (i >= 5) mbar_wait(bars + B_QEMPTY + 8 * (i - 5), 0);
                else { while ((int)((uint32_t)clock() - due) < 0) {} due += PACE; }
                mbar_expect(bars + B_QFULL + 8 * i, QSLOT);
                tma3d(sbase + qslot(i), &P.tmX, bars + B_QFULL + 8 * i, kq * 64, tb * 64, 0);
                tma3d_pair(sbase + qslot(i) + 16384 + rank * 12288, &P.tmWqkv, bars + B_QFULL + 8 * i, (hp * 56) & ~15, kq * 64 + rank * 32, 0);
                if (++kq == 7) kq = 0;
                if (i == 0) TS(23);
            }
            mbar_expect(bars + B_X, HALF); mbar_expect(bars + B_X + 8, HALF);
            Ring r{0, 0};
#pragma unroll 1
            for (int j = has_g1 ? 0 : 16; j < 34; j++) {
                const uint32_t dst = sbase + r.slot * SLOT, full = bars + B_FULL + 8 * r.slot;
                mbar_wait(bars + B_EMPTY + 8 * r.slot, r.ph);
                mbar_expect(full, 16384 + TILEB);
                if (j < 16) {
                    tma3d(dst, &P.tmW1, full, 0, (rank * 16 + j) * 64, ft * 2);
                } else if (j < 20) {
                    tma3d(dst + 16384, &P.tmWo, full, nt2 * 112, 0, ks * 4 + j - 16);
                    tma3d(dst + 24576, &P.tmWo, full, nt2 * 112 + 64, 0, ks * 4 + j - 16);
                } else {
                    tma2d_pair(dst + rank * 8192, &P.tmW2, full, mt * 128 + rank * 64, (ks * 14 + (j < 27 ? 2 * j - 40 : 2 * j - 53)) * 64);
                }
                r.next();
            }
        }
    } else if (warp > 8) {
        uint32_t ep = ld_relaxed(&G->epoch[c]);
        if (w == 2) {
            bar_sync(6, 160);
            if (elect()) {
#pragma unroll
                for (int i = 0; i < 4; i++) bulk_store(G->H + (size_t)((tb * 2 + (hp >> 2)) * 4 + i) * TILEB + (hp & 3) * SLAB, sbase + OFF_Y + i * SLAB, SLAB);
                bulk_store(G->stat + 16 + tb * 128 + hp * 16, sbase + OFF_REC, 128);
            }
            __syncwarp();
        }
        {
            mbar_wait(bars + B_QFULL, 0);
            const uint32_t src = sbase + qslot(0) + 16384 + rank * 12288 + (w - 1) * 4096 + lane * 4;
            float s0 = 0.f, s1 = 0.f;
#pragma unroll 1
            for (int i = 0; i < 2; i++) {
                uint32_t v[16];
#pragma unroll
                for (int k = 0; k < 16; k++) v[k] = __float_as_uint(lds1f((src ^ ((k & 7) * 144)) + (k >> 3) * 1024 + i * 2048));
#pragma unroll
                for (int k = 0; k < 16; k++) { s0 += bf_lo(v[k]); s1 += bf_hi(v[k]); }
            }
            sts2(sbase + OFF_REC + 128 + (w - 1) * 256 + lane * 8, __float_as_uint(s0), __float_as_uint(s1));
            fence_async_shared();
            __syncwarp();
            if (w == 1) TSL(24);
            if (tb == 15) *(float2*)(G->colsum[ep & 1][hp] + (w - 1) * 64 + lane * 2) = make_float2(0.f, 0.f);
            ep = inc_late(ep);
            if (elect()) {
                mbar_arrive(bars + B_QEMPTY);
                if (tb < 14)
                    asm volatile("cp.reduce.async.bulk.global.shared::cta.bulk_group.add.f32 [%0], [%1], 256;" ::"l"(G->colsum[ep & 1][hp] + (w - 1) * 64), "r"(sbase + OFF_REC + 128 + (w - 1) * 256) : "memory");
                bulk_commit();
                bulk_wait_all();
                red_after_bulk(&G->flagH[c >> 2]);
                if (w == 2) TS(3);
            }
            __syncwarp();
        }
        if (w == 1) {
            uint32_t it = 0;
            while (!__all_sync(~0u, ld_acquire(&G->flagH[lane]) == 12 * ep)) { __nanosleep(POLL_NS); spin_guard(++it); }
            if (elect()) {
                fence_async_global();
                TS(16);
                mbar_expect(bars + B_REC, 1152 + 768);
                bulk_load(sbase + OFF_CS, G->colsum[ep & 1][hp], 768, bars + B_REC);
                bulk_load(sbase + OFF_ST, G->stat + tb * 128, 1152, bars + B_REC);
                Ring r{0, 0};
#pragma unroll 1
                for (int j = has_g1 ? 0 : 16; j < 34; j++) {
                    if (j == 16 || j == 20 || j == 26) {
                        wait_flag(j == 16 ? G->flagO[mt] : G->flagU[nt2 * 4 + ks * 2 + (j == 26)], (j == 16 ? 8 : 14) * ep);
                        fence_async_global();
                        TS(j == 16 ? 18 : j == 20 ? 17 : j);
                    }
                    const uint32_t dst = sbase + r.slot * SLOT, full = bars + B_FULL + 8 * r.slot;
                    mbar_wait(bars + B_EMPTY + 8 * r.slot, r.ph);
                    if (j >= 16 && j < 20) bulk_load_pair(dst + rank * 8192, G->O + (size_t)((ks * 4 + j - 16) * 16 + mt) * TILEB + rank * HALF, HALF, full);
                    else bulk_load(dst + 16384, G->H + (size_t)(j < 16 ? (rank * 16 + j) * 4 + nt1 : (32 + ks * 14 + (j < 27 ? 2 * j - 40 : 2 * j - 53)) * 4 + nt2) * TILEB, TILEB, full);
                    r.next();
                }
                G->epoch[c] = ep;
            }
        } else {
            bar_sync(3, 320);
            if (w == 2) {
                if (tb > 0) {
                    if (elect()) {
                        mbar_expect(bars + B_HALO, 2 * KV);
                        wait_flag(&G->flagHalo[c - 1], ep);
                        fence_async_global();
                        bulk_load(sbase + OFF_X, G->halo[c - 1], KV, bars + B_HALO);
                        bulk_load(sbase + OFF_X + XW, G->halo[c - 1] + KV, KV, bars + B_HALO);
                        TS(21);
                    }
                } else {
#pragma unroll 1
                    for (int i = lane; i < KV / 16; i += 32) { sts4(sbase + OFF_X + i * 16, make_uint4(0u, 0u, 0u, 0u)); sts4(sbase + OFF_X + XW + i * 16, make_uint4(0u, 0u, 0u, 0u)); }
                    __syncwarp();
                    if (lane == 0) mbar_arrive(bars + B_HALO);
                }
                __syncwarp();
            } else {
                if (elect()) {
                    mbar_arrive(bars + B_HALO);
                    bulk_store(G->halo[c], sbase + OFF_X + 4 * KV, KV);
                    bulk_store(G->halo[c] + KV, sbase + OFF_X + XW + 4 * KV, KV);
                    bulk_commit();
                    bulk_wait_all();
                    red_after_bulk(&G->flagHalo[c]);
                    mbar_expect(bars + B_ROW, TILEB);
                    bulk_load(sbase + OFF_Y, x + (tb * 128 + hp * 16) * D_, TILEB, bars + B_ROW);
                }
                __syncwarp();
                mbar_wait(bars + B_ROW, 1);
                bar_sync(2, 288);
                if (elect()) bulk_store(out + (tb * 128 + hp * 16) * D_, sbase + OFF_Y, TILEB);
                __syncwarp();
                bar_sync(4, 288);
                if (elect()) {
                    bulk_store(G->O + (size_t)c * TILEB, sbase + OFF_X, TILEB);
                    bulk_commit();
                    bulk_wait_all();
                    mbar_arrive_remote(mapa(bars + B_FREE, rank ^ 1));
                    mbar_arrive(bars + B_FREE);
                    red_after_bulk(G->flagO[tb]);
                    TS(22);
                }
                __syncwarp();
            }
            if (has_g1) bar_sync(w + 6, 160);
            if (elect()) {
                if (has_g1) {
                    const int m = w - 2;
#pragma unroll
                    for (int i = 0; i < 4; i++) bulk_store(G->U + (size_t)((ft * 2 + m) * 4 + nt1) * TILEB + i * SLAB + rank * KV, sbase + OFF_Y + m * HALF + i * KV, KV);
                    bulk_commit();
                    bulk_wait_all();
                    red_after_bulk(G->flagU[nt1 * 4 + (ft >= 7) * 2 + m]);
                    TS(5 + w);
                }
                mbar_arrive(bars + B_DONE);
            }
        }
    } else {
        const int wg = warp >> 2;
        const uint32_t t0 = (GATE0 || GATE1 || GATE2) ? now_ns() : 0;
        Mma M{bars, mapa(bars, rank ^ (lane & 1)), (threadIdx.x & 127) < 2, wg, Ring{0, 0}, -1};
        if (wg == 1) {
            const int r16 = w * 4 + (lane & 3), c8 = ((lane >> 2) + 2 * lane) & 7;
            const uint32_t row = sbase + OFF_Y + r16 * (2 * D_) + c8 * 16;
            mbar_wait(bars + B_ROW, 0);
            TS0(67);
            float f[56];
#pragma unroll
            for (int i = 0; i < 7; i++) {
                const uint4 v = lds4(row + i * 128);
                f[8 * i] = bf_lo(v.x); f[8 * i + 1] = bf_hi(v.x); f[8 * i + 2] = bf_lo(v.y); f[8 * i + 3] = bf_hi(v.y);
                f[8 * i + 4] = bf_lo(v.z); f[8 * i + 5] = bf_hi(v.z); f[8 * i + 6] = bf_lo(v.w); f[8 * i + 7] = bf_hi(v.w);
            }
            float s0 = 0.f, s1 = 0.f, s2 = 0.f, s3 = 0.f;
#pragma unroll
            for (int i = 0; i < 56; i += 4) { s0 += f[i]; s1 += f[i + 1]; s2 += f[i + 2]; s3 += f[i + 3]; }
            const float mean = oct_sum((s0 + s1) + (s2 + s3)) * (1.f / D_);
            bar_sync(5, 128);
            s0 = s1 = s2 = s3 = 0.f;
#pragma unroll
            for (int i = 0; i < 56; i += 4) {
                f[i] -= mean; f[i + 1] -= mean; f[i + 2] -= mean; f[i + 3] -= mean;
                s0 = fmaf(f[i], f[i], s0); s1 = fmaf(f[i + 1], f[i + 1], s1); s2 = fmaf(f[i + 2], f[i + 2], s2); s3 = fmaf(f[i + 3], f[i + 3], s3);
            }
            const float var = oct_sum((s0 + s1) + (s2 + s3)) * (1.f / D_);
            const float rstd = rsqrtf(var + LN_EPS);
            const float sc = rstd * rsqrtf(var * rstd * rstd + LN_EPS);
            if (lane < 4) sts2(sbase + OFF_REC + r16 * 8, __float_as_uint(rstd), __float_as_uint(-mean));
            const int sw = tb < 8 ? 0 : 7 * 256;
            const uint32_t hb = sbase + OFF_Y + r16 * 16 + c8 * 256;
#pragma unroll
            for (int i = 0; i < 7; i++) {
                const int lo = (8 * i) % 14;
                const bool up = lo < 7 ? c8 < 7 - lo : c8 >= 14 - lo;
                sts4(hb + (up ? sw : -sw) + i * 2048, make_uint4(pack2(f[8 * i] * sc, f[8 * i + 1] * sc), pack2(f[8 * i + 2] * sc, f[8 * i + 3] * sc),
                                                                  pack2(f[8 * i + 4] * sc, f[8 * i + 5] * sc), pack2(f[8 * i + 6] * sc, f[8 * i + 7] * sc)));
            }
            fence_async_shared();
            TS0(25);
            bar_arrive(6, 160);
        }
        const int r = lane >> 2, t = lane & 3;
        const uint32_t bias0 = ld_u16(b1 + min(ft, 13) * 128 + warp * 16 + r), bias1 = ld_u16(b1 + min(ft, 13) * 128 + warp * 16 + r + 8);
        const uint32_t xw = sbase + OFF_X + (1 - wg) * XW;
        const uint32_t st = sbase + OFF_ST + (16 + w * 32 + wg) * 8;
        uint32_t q[7][2], k0[7], v0[7];
        {
            if (GATE0) gate(t0 + GATE0);
            float acc[92];
            const uint64_t dA0 = HI_KM | desc_lo(sbase + wg * 8192), dB0 = HI_WQ | (desc_lo(sbase + 16384) + (hp & 1));
#pragma unroll 1
            for (int kb = 0; kb < 7; kb++) {
                if (kb == 5 && wg == 1) { wg_wait<0>(); if (M.lead) mbar_arrive_remote(M.rel + B_QEMPTY + 8 * 4); bar_sync(7, 256); }
                mbar_wait(bars + B_QFULL + 8 * kb, 0);
                TS0(68 + wg * 7 + kb);
                const uint64_t dA = dA0 + (qslot(kb) >> 4), dB = dB0 + (qslot(kb) >> 4);
                wg_fence();
#pragma unroll
                for (int k = 0; k < 4; k++) {
                    wgmma_n184<0, 1>(acc, dA + k * 2, dB + (k & 1) * 128 + (k >> 1) * 768, k > 0 || kb > 0);
                    if (k == 0) { wg_commit(); wg_wait<1>(); if (M.lead && kb > 0 && !(kb == 5 && wg == 1)) mbar_arrive_remote(M.rel + B_QEMPTY + 8 * (kb - 1)); }
                }
                wg_commit();
            }
            if (wg == 0) bar_arrive(7, 256);
            mbar_wait(bars + B_REC, 0);
            const float n0 = lds1f(st + r * 16 + 4), n1 = lds1f(st + r * 16 + 132);
            const uint32_t csa = sbase + OFF_CS + t * 8 + (hp & 1) * 32;
            wg_wait<0>();
            pin(acc);
            if (M.lead) { mbar_arrive_remote(M.rel + B_QEMPTY + 8 * 6); mbar_arrive_remote(M.rel + B_QEMPTY + 8 * 7); }
            TS0(4 + 7 * wg);
            uint32_t hi[14];
#pragma unroll
            for (int p = 2; p >= 0; p--) {
#pragma unroll
                for (int g = 0; g < 7; g++) {
                    const uint2 cs = lds2(csa + (p * 8 + g) * 32);
                    const int a = (p * 8 + g) * 4;
                    const float c0 = __uint_as_float(cs.x), c1 = __uint_as_float(cs.y);
                    const uint32_t lo2 = pack2(fmaf(n0, c0, acc[a]), fmaf(n0, c1, acc[a + 1])), hi2 = pack2(fmaf(n1, c0, acc[a + 2]), fmaf(n1, c1, acc[a + 3]));
                    if (p == 0) { q[g][0] = lo2; q[g][1] = hi2; } else { (p == 1 ? k0 : v0)[g] = lo2; hi[(p - 1) * 7 + g] = hi2; }
                }
                if (p == 1) {
                    const uint32_t dst = xw + (w + 1) * KV + lane * 16;
#pragma unroll
                    for (int i = 0; i < 3; i++) stsm4(dst + i * 512, hi[4 * i], hi[4 * i + 1], hi[4 * i + 2], hi[4 * i + 3]);
                    stsm2(dst + 1536, hi[12], hi[13]);
                    if (w == 3) fence_async_shared();
                    bar_arrive(3, 320);
                }
            }
        }
        TS0(9 + 11 * wg);
        float a[56];
        const uint64_t dA0 = HI_WT | desc_lo(sbase + wg * 8192), dB0 = HI_TILE | desc_lo(sbase + 16384);
        const int n1 = PAUSE + (wg == 0 ? LEAD : 0);
        if (has_g1) {
            M.run<false>(a, n1, 16, 0, 0, dA0, dB0, 32);
        } else {
#pragma unroll
            for (int i = 0; i < 56; i++) asm volatile("" : "=f"(a[i]));
        }
        {
            uint32_t kp[8], k1[8], vp[8], v1[8];
            mbar_wait(bars + B_HALO, 0);
            const uint32_t src = xw + w * KV + lane * 16;
            ldsm4(kp, src); ldsm4(kp + 4, src + 512); ldsm4(k1, src + KV); ldsm4(k1 + 4, src + KV + 512);
            ldsm4t(vp, src + 896); ldsm4t(vp + 4, src + 1408); ldsm4t(v1, src + KV + 896); ldsm4t(v1 + 4, src + KV + 1408);
#pragma unroll
            for (int g = 0; g < 7; g++) v0[g] = transpose8(v0[g]);
            const bool e0 = 2 * t > r, e1 = 2 * t + 1 > r;
            const uint32_t ka = st + t * 32 - (e0 ? 128 : 0), kb = st + t * 32 + 16 - (e1 ? 128 : 0);
            const float rk[4] = {lds1f(ka), lds1f(kb), lds1f(ka + 128), lds1f(kb + 128)};
            const float sq0 = lds1f(st + r * 16) * (0.1889822365046136f * 1.4426950408889634f), sq1 = lds1f(st + r * 16 + 128) * (0.1889822365046136f * 1.4426950408889634f);
            const float sc[4] = {sq0 * rk[0], sq0 * rk[1], sq1 * rk[2], sq1 * rk[3]};
            const uint32_t mask = (e0 ? 0xffffu : 0u) | (e1 ? 0xffff0000u : 0u);
            const bool first = tb == 0 && w == 0;
            M.drain(a);
            bar_sync(2, 288);
            TS0(12 + 16 * wg);
            float sv[2][4];
#pragma unroll
            for (int h = 0; h < 2; h++) {
                const uint32_t m0 = (t < 2) == (h == 0) ? q[3][0] : 0u, m1 = (t < 2) == (h == 0) ? q[3][1] : 0u;
                const int ga = h * 4, gb = h * 4 + 1, gc = h * 4 + 2;
                float s[3][4] = {};
                mma16(s[0], q[ga][0], q[ga][1], q[gb][0], q[gb][1], kp[ga], kp[gb]);
                mma16(s[1], q[ga][0], q[ga][1], q[gb][0], q[gb][1], k0[ga], k0[gb]);
                mma16(s[2], q[ga][0], q[ga][1], q[gb][0], q[gb][1], k1[ga], k1[gb]);
                mma16(s[0], q[gc][0], q[gc][1], m0, m1, kp[gc], kp[3]);
                mma16(s[1], q[gc][0], q[gc][1], m0, m1, k0[gc], k0[3]);
                mma16(s[2], q[gc][0], q[gc][1], m0, m1, k1[gc], k1[3]);
                sv[h][0] = e0 ? (first ? -1e30f : s[0][0] * sc[0]) : s[1][0] * sc[0];
                sv[h][1] = e1 ? (first ? -1e30f : s[0][1] * sc[1]) : s[1][1] * sc[1];
                sv[h][2] = (e0 ? s[1][2] : s[2][2]) * sc[2];
                sv[h][3] = (e1 ? s[1][3] : s[2][3]) * sc[3];
            }
            uint32_t pp[2][2];
#pragma unroll
            for (int i = 0; i < 4; i++) {
                float* v = &sv[i >> 1][(i & 1) * 2];
                const float m = quad_max(fmaxf(v[0], v[1]));
                const float p0 = ex2(v[0] - m), p1 = ex2(v[1] - m);
                const float inv = __fdividef(1.f, quad_sum(p0 + p1));
                pp[i >> 1][i & 1] = pack2(p0 * inv * rk[(i & 1) * 2], p1 * inv * rk[(i & 1) * 2 + 1]);
            }
            uint32_t o[8][2];
#pragma unroll
            for (int i = 0; i < 8; i++) {
                const int h = i >> 2, g = i - h;
                float d[4] = {};
                mma16(d, pp[h][0] & mask, 0u, pp[h][0] & ~mask, pp[h][1] & mask, vp[g], v0[g]);
                mma8(d, 0u, pp[h][1] & ~mask, v1[g]);
                o[i][0] = pack2(d[0], d[1]); o[i][1] = pack2(d[2], d[3]);
            }
            if (t >= 2) { o[3][0] = o[4][0]; o[3][1] = o[4][1]; }
            const uint32_t dst = sbase + OFF_X + (w >> 1) * HALF + ((w & 1) * 32 + (lane & 15) * 2 + wg) * 16 + (lane >> 4) * 1024;
            stsm4(dst, o[0][0], o[0][1], o[1][0], o[1][1]);
            stsm4(dst + 2048, o[2][0], o[2][1], o[3][0], o[3][1]);
            stsm4(dst + 4096, o[5][0], o[5][1], o[6][0], o[6][1]);
            stsm2(dst + 6144, o[7][0], o[7][1]);
            fence_async_shared();
            bar_sync(4, 288);
            TS0(10 + 19 * wg);
        }
        if (has_g1) {
            if (GATE1) gate(t0 + GATE1);
            M.run<false>(a, 16 - n1, 16, LAG1, 1, dA0, dB0, 32 + PAUSE + LEAD);
            mbar_wait_cluster(bars + B_FREE, 0);
            const uint32_t xb = xw + (threadIdx.x & 127) * 16;
            const uint32_t rx = mapa(xb, rank ^ 1), rbar = mapa(bars + B_X + 8 * wg, rank ^ 1);
            M.drain(a);
            TS0(5 + wg);
#pragma unroll
            for (int i = 0; i < 3; i++)
                st_async4(rx + i * 2048, rbar, pack2(a[28 + 8 * i], a[29 + 8 * i]), pack2(a[30 + 8 * i], a[31 + 8 * i]), pack2(a[32 + 8 * i], a[33 + 8 * i]), pack2(a[34 + 8 * i], a[35 + 8 * i]));
            st_async2(rx + 6144, rbar, pack2(a[52], a[53]), pack2(a[54], a[55]));
#pragma unroll
            for (int i = 0; i < 28; i++) a[i] += bf_lo((i & 2) ? bias1 : bias0);
            mbar_wait_cluster(bars + B_X + 8 * wg, 0);
            TS0(1 + wg);
            uint32_t u[16];
#pragma unroll
            for (int i = 0; i < 4; i++) { const uint4 v = lds4(xb + i * 2048); u[4 * i] = v.x; u[4 * i + 1] = v.y; u[4 * i + 2] = v.z; u[4 * i + 3] = v.w; }
#pragma unroll
            for (int i = 0; i < 14; i++) u[i] = pack2(gelu_tanh(a[2 * i] + bf_lo(u[i])), gelu_tanh(a[2 * i + 1] + bf_hi(u[i])));
            const uint32_t stg = sbase + OFF_Y + warp * KV + lane * 16;
#pragma unroll
            for (int i = 0; i < 3; i++) stsm4(stg + i * 512, u[4 * i], u[4 * i + 1], u[4 * i + 2], u[4 * i + 3]);
            stsm2(stg + 1536, u[12], u[13]);
            fence_async_shared();
            bar_arrive(8 + wg, 160);
            TS0(30 + wg);
        }
        uint32_t c0 = ld_u16(b2 + mt * 128 + warp * 16 + r), c1 = ld_u16(b2 + mt * 128 + warp * 16 + r + 8);
        M.run<true>(a, 4, 4, 0, 0, HI_O | desc_lo(sbase + wg * 8192), HI_WT | desc_lo(sbase + 16384), 48);
        M.drain(a);
        if (wg == 1) TS0(13);
        c0 *= ks == 0 ? 0x10001u : 0u; c1 *= ks == 0 ? 0x10001u : 0u;
        if (GATE2) gate(t0 + GATE2);
        M.run<false>(a, 14, 15 - NSLOT, LAG2, 1, dA0, dB0, 52);
        mbar_wait(bars + B_DONE, 0);
        const uint32_t stg = sbase + (wg == 0 ? OFF_X : OFF_Y) + w * SLAB;
        const uint32_t sa = stg + (lane & 15) * 224 + (lane >> 4) * 16;
        wg_wait<0>();
        pin(a);
        TS0(14 + wg);
#pragma unroll
        for (int g = 0; g < 7; g++)
            stsm4(sa + g * 32, add_bf2(pack2(a[8 * g], a[8 * g + 1]), c0), add_bf2(pack2(a[8 * g + 2], a[8 * g + 3]), c1), add_bf2(pack2(a[8 * g + 4], a[8 * g + 5]), c0), add_bf2(pack2(a[8 * g + 6], a[8 * g + 7]), c1));
        fence_async_shared();
        __syncwarp();
        if (elect()) {
            asm volatile("cp.reduce.async.bulk.tensor.2d.global.shared::cta.add.tile.bulk_group [%0, {%2, %3}], [%1];" ::"l"(&P.tmOut), "r"(stg), "r"(nt2 * 112), "r"(mt * 128 + warp * 16) : "memory");
            bulk_commit();
            asm volatile("cp.async.bulk.wait_group.read 0;" ::: "memory");
        }
        if (wg == 1) TS0(19);
        TSDUMP();
    }
}

typedef CUresult (*EncodeFn)(CUtensorMap*, CUtensorMapDataType, cuuint32_t, void*, const cuuint64_t*, const cuuint64_t*, const cuuint32_t*, const cuuint32_t*,
                             CUtensorMapInterleave, CUtensorMapSwizzle, CUtensorMapL2promotion, CUtensorMapFloatOOBfill);

void make_map(EncodeFn enc, CUtensorMap* tm, const void* base, bool swizzle, int d0, int d1, int d2, int s1, int s2, int b0, int b1, int b2) {
    const cuuint64_t dims[3] = {(cuuint64_t)d0, (cuuint64_t)d1, (cuuint64_t)d2}, strides[2] = {(cuuint64_t)s1 * 2, (cuuint64_t)s2 * 2};
    const cuuint32_t box[3] = {(cuuint32_t)b0, (cuuint32_t)b1, (cuuint32_t)b2}, es[3] = {1, 1, 1};
    enc(tm, CU_TENSOR_MAP_DATA_TYPE_BFLOAT16, d2 ? 3 : 2, (void*)base, dims, strides, box, es, CU_TENSOR_MAP_INTERLEAVE_NONE,
        swizzle ? CU_TENSOR_MAP_SWIZZLE_128B : CU_TENSOR_MAP_SWIZZLE_NONE, CU_TENSOR_MAP_L2_PROMOTION_L2_128B, CU_TENSOR_MAP_FLOAT_OOB_FILL_NONE);
}

}

extern "C" void kernel_launch(void* const* d_in, const int* in_sizes, int n_in, void* d_out, int out_size) {
    static EncodeFn enc = nullptr;
    static Scratch* scratch = nullptr;
    if (!enc) {
        void* fn = nullptr;
        cudaDriverEntryPointQueryResult qr;
        cudaGetDriverEntryPoint("cuTensorMapEncodeTiled", &fn, cudaEnableDefault, &qr);
        enc = (EncodeFn)fn;
        cudaGetSymbolAddress((void**)&scratch, g_s);
        cudaFuncSetAttribute(fused_kernel, cudaFuncAttributeMaxDynamicSharedMemorySize, SMEM_BYTES);
    }
    Params P;
    const __nv_bfloat16* x = (const __nv_bfloat16*)d_in[0];
    make_map(enc, &P.tmX, x, true, D_, S_ / 2, 2, 2 * D_, D_, 64, 64, 2);
    make_map(enc, &P.tmWqkv, d_in[1], true, D_, D_, 3, 3 * D_, D_, 64, 32, 3);
    make_map(enc, &P.tmW1, d_in[4], true, 64, S_, F_ / 64, F_, 64, 64, 64, 2);
    make_map(enc, &P.tmW2, d_in[6], true, S_, F_, 0, S_, 0, 64, 64, 1);
    make_map(enc, &P.tmWo, d_in[2], true, D_, 56, 8, D_, 56 * D_, 64, 64, 1);
    make_map(enc, &P.tmOut, d_out, false, D_, S_, 0, D_, 0, 112, 16, 1);
    fused_kernel<<<NCTA, NTHREADS, SMEM_BYTES, cudaStreamPerThread>>>(x, (const __nv_bfloat16*)d_in[5], (const __nv_bfloat16*)d_in[7], (__nv_bfloat16*)d_out, scratch, P);
}
```

```cpp
#include <cuda_runtime.h>
#include <cuda_bf16.h>
#include <cuda.h>
#include <stdint.h>

#define POLL_SLEEP
#define UGAP 0
#define FAST0 1
#define PACE 800
#define PAUSE 10
#define LEAD 0
#define LAG1 4
#define LAG2 5

namespace {

constexpr int S_ = 2048, D_ = 448, F_ = 1792;
constexpr int NCTA = 128, NTHREADS = 384;
constexpr int NSLOT = 6, SLOT = 32768, QSLOT = 40960, TILEB = 14336, SLAB = 3584, HALF = 7168;
constexpr int KV = 1792;
constexpr int OFF_X = NSLOT * SLOT;
constexpr int OFF_Y = OFF_X + 10 * KV;
constexpr int OFF_CS = OFF_Y + TILEB;
constexpr int OFF_ST = OFF_CS + 768;
constexpr int OFF_BAR = OFF_ST + 1152;
constexpr int SMEM_BYTES = OFF_BAR + 1024;
constexpr uint32_t SMEM0 = 1024;
constexpr int B_QFULL = 0, B_FULL = 56, B_REC = 104, B_ROW = 112, B_X = 120, B_CS = 136, B_HALO = 144, B_FREE = 152, B_END = 160, B_QEMPTY = 176, B_EMPTY = 192, NBAR = 30;
constexpr float LN_EPS = 1e-5f;
constexpr int SPIN_LIMIT = 1 << 22;

struct Scratch {
    uint8_t H[4][32][TILEB];
    uint8_t U[4][28][TILEB];
    uint8_t O[16][8][TILEB];
    uint8_t halo[NCTA + 1][2 * KV];
    float2 stat[16 + S_];
    float colsum[2][8][192];
    uint32_t flagH[32];
    uint32_t flag[32][32];
    uint32_t flagHalo[NCTA];
    uint32_t epoch[NCTA];
};
__device__ __align__(1024) Scratch g_s;

#define TS(g, i)
#define TS0(g, i)
#define TSDUMP()

struct Params {
    CUtensorMap tmX, tmWqkv, tmW1, tmW2, tmWo, tmOut;
};

__device__ __forceinline__ bool elect() {
    uint32_t p;
    asm volatile("{\n.reg .pred p;\nelect.sync _|p, 0xffffffff;\nselp.u32 %0, 1, 0, p;\n}" : "=r"(p));
    return p;
}
__device__ __forceinline__ void mbar_init(uint32_t b, uint32_t c) { asm volatile("mbarrier.init.shared::cta.b64 [%0], %1;" ::"r"(b), "r"(c) : "memory"); }
__device__ __forceinline__ void mbar_expect(uint32_t b, uint32_t tx) { asm volatile("mbarrier.arrive.expect_tx.shared::cta.b64 _, [%0], %1;" ::"r"(b), "r"(tx) : "memory"); }
__device__ __forceinline__ void mbar_arrive(uint32_t b) { asm volatile("mbarrier.arrive.shared::cta.b64 _, [%0];" ::"r"(b) : "memory"); }
__device__ __forceinline__ void mbar_arrive_remote(uint32_t b) { asm volatile("mbarrier.arrive.shared::cluster.b64 _, [%0];" ::"r"(b) : "memory"); }
#define MBAR_WAIT_ASM(SEM) \
    asm volatile("{\n.reg .pred p;\nWAIT:\nmbarrier.try_wait.parity" SEM ".shared::cta.b64 p, [%0], %1;\n@!p bra WAIT;\n}" ::"r"(b), "r"(parity) : "memory")
__device__ __forceinline__ void mbar_wait(uint32_t b, uint32_t parity) { MBAR_WAIT_ASM(""); }
__device__ __forceinline__ void mbar_wait_cluster(uint32_t b, uint32_t parity) { MBAR_WAIT_ASM(".acquire.cluster"); }
__device__ __forceinline__ void mbar_wait_bounded(uint32_t b, uint32_t parity, uint32_t& n) {
    asm volatile("{\n.reg .pred p;\nWAIT:\nadd.u32 %0, %0, 1;\nsetp.gt.u32 p, %0, %3;\n@p st.global.u32 [%4], %0;\n"
                 "mbarrier.try_wait.parity.shared::cta.b64 p, [%1], %2;\n@!p bra WAIT;\n}" : "+r"(n) : "r"(b), "r"(parity), "n"(SPIN_LIMIT), "l"(0ull) : "memory");
}
__device__ __forceinline__ uint32_t mapa(uint32_t a, uint32_t rank) { uint32_t r; asm("mapa.shared::cluster.u32 %0, %1, %2;" : "=r"(r) : "r"(a), "r"(rank)); return r; }
__device__ __forceinline__ void tma3d(uint32_t dst, const CUtensorMap* tm, uint32_t bar, int c0, int c1, int c2) {
    asm volatile("cp.async.bulk.tensor.3d.shared::cluster.global.mbarrier::complete_tx::bytes [%0], [%1, {%3, %4, %5}], [%2];" ::"r"(dst), "l"(tm), "r"(bar), "r"(c0), "r"(c1), "r"(c2) : "memory");
}
__device__ __forceinline__ void tma2d_pair(uint32_t dst, const CUtensorMap* tm, uint32_t bar, int c0, int c1) {
    asm volatile("cp.async.bulk.tensor.2d.shared::cluster.global.mbarrier::complete_tx::bytes.multicast::cluster [%0], [%1, {%3, %4}], [%2], %5;" ::"r"(dst), "l"(tm), "r"(bar), "r"(c0), "r"(c1), "h"((uint16_t)3) : "memory");
}
__device__ __forceinline__ void tma3d_pair(uint32_t dst, const CUtensorMap* tm, uint32_t bar, int c0, int c1, int c2) {
    asm volatile("cp.async.bulk.tensor.3d.shared::cluster.global.mbarrier::complete_tx::bytes.multicast::cluster [%0], [%1, {%3, %4, %5}], [%2], %6;" ::"r"(dst), "l"(tm), "r"(bar), "r"(c0), "r"(c1), "r"(c2), "h"((uint16_t)3) : "memory");
}
__device__ __forceinline__ void bulk_load(uint32_t dst, const void* src, uint32_t bytes, uint32_t bar) {
    asm volatile("cp.async.bulk.shared::cluster.global.mbarrier::complete_tx::bytes [%0], [%1], %2, [%3];" ::"r"(dst), "l"(src), "r"(bytes), "r"(bar) : "memory");
}
__device__ __forceinline__ void bulk_load_pair(uint32_t dst, const void* src, uint32_t bytes, uint32_t bar) {
    asm volatile("cp.async.bulk.shared::cluster.global.mbarrier::complete_tx::bytes.multicast::cluster [%0], [%1], %2, [%3], %4;" ::"r"(dst), "l"(src), "r"(bytes), "r"(bar), "h"((uint16_t)3) : "memory");
}
__device__ __forceinline__ void bulk_store(void* dst, uint32_t src, uint32_t bytes) {
    asm volatile("cp.async.bulk.global.shared::cta.bulk_group [%0], [%1], %2;" ::"l"(dst), "r"(src), "r"(bytes) : "memory");
}
__device__ __forceinline__ uint32_t ld_u16(const void* p) { uint32_t v; asm volatile("ld.global.nc.u16 %0, [%1];" : "=r"(v) : "l"(p)); return v; }
__device__ __forceinline__ uint32_t ld_relaxed(const uint32_t* p) { uint32_t v; asm volatile("ld.relaxed.gpu.global.u32 %0, [%1];" : "=r"(v) : "l"(p) : "memory"); return v; }
__device__ __forceinline__ void bulk_flush() { asm volatile("cp.async.bulk.commit_group;\ncp.async.bulk.wait_group 0;" ::: "memory"); }
__device__ __forceinline__ void signal(uint32_t* flag) { asm volatile("red.release.gpu.global.add.u32 [%0], 1;" ::"l"(flag) : "memory"); }
__device__ __forceinline__ void stg1(void* p, uint32_t v) { asm volatile("st.global.b32 [%0], %1;" ::"l"(p), "r"(v) : "memory"); }
__device__ __forceinline__ void fence_async_shared() { asm volatile("fence.proxy.async.shared::cta;" ::: "memory"); }
__device__ __forceinline__ void wait_flag(const uint32_t* p, uint32_t target) {
    asm volatile("{\n.reg .pred p;\n.reg .u32 v;\nPOLL:\nld.acquire.gpu.global.u32 v, [%0];\nsetp.ne.u32 p, v, %1;\n" POLL_SLEEP "@p bra POLL;\nfence.proxy.async.global;\n}" ::"l"(p), "r"(target) : "memory");
}
__device__ __forceinline__ void bar_sync(int id, int n) { asm volatile("bar.sync %0, %1;" ::"r"(id), "r"(n) : "memory"); }
__device__ __forceinline__ void bar_arrive(int id, int n) { asm volatile("bar.arrive %0, %1;" ::"r"(id), "r"(n) : "memory"); }
__device__ __forceinline__ void wg_fence() { asm volatile("wgmma.fence.sync.aligned;" ::: "memory"); }
__device__ __forceinline__ void wg_commit() { asm volatile("wgmma.commit_group.sync.aligned;" ::: "memory"); }
template <int N> __device__ __forceinline__ void wg_wait() { asm volatile("wgmma.wait_group.sync.aligned %0;" ::"n"(N) : "memory"); }
template <int N> __device__ __forceinline__ void pin(float (&d)[N]) {
#pragma unroll
    for (int i = 0; i < N; i++) asm volatile("" : "+f"(d[i])::"memory");
}
__host__ __device__ constexpr uint32_t desc_hi(uint32_t sbo, uint32_t swz) { return (sbo >> 4) | (swz << 30); }
__host__ __device__ constexpr uint32_t desc_lo(uint32_t off, uint32_t lbo) { return ((SMEM0 + off) >> 4) | ((lbo >> 4) << 16); }
__device__ __forceinline__ uint32_t pack2(float lo, float hi) { uint32_t r; asm("cvt.rn.bf16x2.f32 %0, %1, %2;" : "=r"(r) : "f"(hi), "f"(lo)); return r; }
__device__ __forceinline__ float bf_lo(uint32_t v) { return __uint_as_float(v << 16); }
__device__ __forceinline__ float bf_hi(uint32_t v) { return __uint_as_float(v & 0xffff0000u); }
__device__ __forceinline__ uint32_t half_plus(uint32_t a, uint32_t b) { uint32_t r; asm("fma.rn.bf16x2 %0, %1, %2, %3;" : "=r"(r) : "r"(a), "r"(0x3f003f00u), "r"(b)); return r; }
__device__ __forceinline__ void stsm4(uint32_t a, uint32_t r0, uint32_t r1, uint32_t r2, uint32_t r3) {
    asm volatile("stmatrix.sync.aligned.m8n8.x4.shared.b16 [%0], {%1, %2, %3, %4};" ::"r"(a), "r"(r0), "r"(r1), "r"(r2), "r"(r3) : "memory");
}
__device__ __forceinline__ void stsm2(uint32_t a, uint32_t r0, uint32_t r1) {
    asm volatile("stmatrix.sync.aligned.m8n8.x2.shared.b16 [%0], {%1, %2};" ::"r"(a), "r"(r0), "r"(r1) : "memory");
}
__device__ __forceinline__ uint4 lds4(uint32_t a) { uint4 v; asm volatile("ld.shared.v4.b32 {%0, %1, %2, %3}, [%4];" : "=r"(v.x), "=r"(v.y), "=r"(v.z), "=r"(v.w) : "r"(a) : "memory"); return v; }
__device__ __forceinline__ uint2 lds2(uint32_t a) { uint2 v; asm volatile("ld.shared.v2.b32 {%0, %1}, [%2];" : "=r"(v.x), "=r"(v.y) : "r"(a) : "memory"); return v; }
__device__ __forceinline__ float lds1f(uint32_t a) { float v; asm volatile("ld.shared.f32 %0, [%1];" : "=f"(v) : "r"(a) : "memory"); return v; }
__device__ __forceinline__ void ldsm4(uint32_t* r, uint32_t a) {
    asm volatile("ldmatrix.sync.aligned.m8n8.x4.shared.b16 {%0, %1, %2, %3}, [%4];" : "=r"(r[0]), "=r"(r[1]), "=r"(r[2]), "=r"(r[3]) : "r"(a) : "memory");
}
__device__ __forceinline__ void ldsm4t(uint32_t* r, uint32_t a) {
    asm volatile("ldmatrix.sync.aligned.m8n8.x4.trans.shared.b16 {%0, %1, %2, %3}, [%4];" : "=r"(r[0]), "=r"(r[1]), "=r"(r[2]), "=r"(r[3]) : "r"(a) : "memory");
}
__device__ __forceinline__ uint32_t transpose8(uint32_t v) { uint32_t r; asm volatile("movmatrix.sync.aligned.m8n8.trans.b16 %0, %1;" : "=r"(r) : "r"(v)); return r; }
__device__ __forceinline__ void mma16(float (&c)[4], uint32_t a0, uint32_t a1, uint32_t a2, uint32_t a3, uint32_t b0, uint32_t b1) {
    asm volatile("mma.sync.aligned.m16n8k16.row.col.f32.bf16.bf16.f32 {%0, %1, %2, %3}, {%4, %5, %6, %7}, {%8, %9}, {%0, %1, %2, %3};"
                 : "+f"(c[0]), "+f"(c[1]), "+f"(c[2]), "+f"(c[3]) : "r"(a0), "r"(a1), "r"(a2), "r"(a3), "r"(b0), "r"(b1));
}
__device__ __forceinline__ void mma8(float (&c)[4], uint32_t a0, uint32_t a1, uint32_t b0) {
    asm volatile("mma.sync.aligned.m16n8k8.row.col.f32.bf16.bf16.f32 {%0, %1, %2, %3}, {%4, %5}, {%6}, {%0, %1, %2, %3};"
                 : "+f"(c[0]), "+f"(c[1]), "+f"(c[2]), "+f"(c[3]) : "r"(a0), "r"(a1), "r"(b0));
}
__device__ __forceinline__ void st_async4(uint32_t a, uint32_t bar, uint32_t v0, uint32_t v1, uint32_t v2, uint32_t v3) {
    asm volatile("st.async.weak.shared::cluster.mbarrier::complete_tx::bytes.v4.b32 [%0], {%2, %3, %4, %5}, [%1];" ::"r"(a), "r"(bar), "r"(v0), "r"(v1), "r"(v2), "r"(v3) : "memory");
}
__device__ __forceinline__ void st_async2(uint32_t a, uint32_t bar, uint32_t v0, uint32_t v1) {
    asm volatile("st.async.weak.shared::cluster.mbarrier::complete_tx::bytes.v2.b32 [%0], {%2, %3}, [%1];" ::"r"(a), "r"(bar), "r"(v0), "r"(v1) : "memory");
}
__device__ __forceinline__ float quad_max(float v) { v = fmaxf(v, __shfl_xor_sync(~0u, v, 1)); return fmaxf(v, __shfl_xor_sync(~0u, v, 2)); }
__device__ __forceinline__ float quad_sum(float v) { v += __shfl_xor_sync(~0u, v, 1); return v + __shfl_xor_sync(~0u, v, 2); }
__device__ __forceinline__ float ex2(float v) { float r; asm("ex2.approx.ftz.f32 %0, %1;" : "=f"(r) : "f"(v)); return r; }
__device__ __forceinline__ float rcp(float v) { float r; asm("rcp.approx.ftz.f32 %0, %1;" : "=f"(r) : "f"(v)); return r; }
__device__ __forceinline__ float rsq(float v) { float r; asm("rsqrt.approx.ftz.f32 %0, %1;" : "=f"(r) : "f"(v)); return r; }
__device__ __forceinline__ float gelu2(float u) {
    float z = u * fmaf(u * u, 0.044715f * 0.7978845608028654f, 0.7978845608028654f), t;
    asm("tanh.approx.f32 %0, %1;" : "=f"(t) : "f"(z));
    return fmaf(u, t, u);
}
__device__ __forceinline__ float oct_sum(float v) {
    v += __shfl_xor_sync(~0u, v, 4); v += __shfl_xor_sync(~0u, v, 8); v += __shfl_xor_sync(~0u, v, 16);
    return v;
}

template <int TA, int TB, uint32_t HA, uint32_t HB>
__device__ __forceinline__ void wgmma_n112(float (&d)[56], uint32_t da, uint32_t db, int accumulate) {
    asm volatile("{\n.reg .pred p;\n.reg .b64 a, b;\nmov.b64 a, {%56, %61};\nmov.b64 b, {%57, %62};\nsetp.ne.b32 p, %58, 0;\n"
        "wgmma.mma_async.sync.aligned.m64n112k16.f32.bf16.bf16 {"
        "%0, %1, %2, %3, %4, %5, %6, %7, %8, %9, %10, %11, %12, %13, %14, %15, "
        "%16, %17, %18, %19, %20, %21, %22, %23, %24, %25, %26, %27, %28, %29, %30, %31, "
        "%32, %33, %34, %35, %36, %37, %38, %39, %40, %41, %42, %43, %44, %45, %46, %47, "
        "%48, %49, %50, %51, %52, %53, %54, %55"
        "}, a, b, p, 1, 1, %59, %60;\n}\n"
        : "+f"(d[0]), "+f"(d[1]), "+f"(d[2]), "+f"(d[3]), "+f"(d[4]), "+f"(d[5]), "+f"(d[6]), "+f"(d[7]),
          "+f"(d[8]), "+f"(d[9]), "+f"(d[10]), "+f"(d[11]), "+f"(d[12]), "+f"(d[13]), "+f"(d[14]), "+f"(d[15]),
          "+f"(d[16]), "+f"(d[17]), "+f"(d[18]), "+f"(d[19]), "+f"(d[20]), "+f"(d[21]), "+f"(d[22]), "+f"(d[23]),
          "+f"(d[24]), "+f"(d[25]), "+f"(d[26]), "+f"(d[27]), "+f"(d[28]), "+f"(d[29]), "+f"(d[30]), "+f"(d[31]),
          "+f"(d[32]), "+f"(d[33]), "+f"(d[34]), "+f"(d[35]), "+f"(d[36]), "+f"(d[37]), "+f"(d[38]), "+f"(d[39]),
          "+f"(d[40]), "+f"(d[41]), "+f"(d[42]), "+f"(d[43]), "+f"(d[44]), "+f"(d[45]), "+f"(d[46]), "+f"(d[47]),
          "+f"(d[48]), "+f"(d[49]), "+f"(d[50]), "+f"(d[51]), "+f"(d[52]), "+f"(d[53]), "+f"(d[54]), "+f"(d[55])
        : "r"(da), "r"(db), "r"(accumulate), "n"(TA), "n"(TB), "n"(HA), "n"(HB));
}

template <int TA, int TB, uint32_t HA, uint32_t HB>
__device__ __forceinline__ void wgmma_n184(float (&d)[92], uint32_t da, uint32_t db, int accumulate) {
    asm volatile("{\n.reg .pred p;\n.reg .b64 a, b;\nmov.b64 a, {%92, %97};\nmov.b64 b, {%93, %98};\nsetp.ne.b32 p, %94, 0;\n"
        "wgmma.mma_async.sync.aligned.m64n184k16.f32.bf16.bf16 {"
        "%0, %1, %2, %3, %4, %5, %6, %7, %8, %9, %10, %11, %12, %13, %14, %15, "
        "%16, %17, %18, %19, %20, %21, %22, %23, %24, %25, %26, %27, %28, %29, %30, %31, "
        "%32, %33, %34, %35, %36, %37, %38, %39, %40, %41, %42, %43, %44, %45, %46, %47, "
        "%48, %49, %50, %51, %52, %53, %54, %55, %56, %57, %58, %59, %60, %61, %62, %63, "
        "%64, %65, %66, %67, %68, %69, %70, %71, %72, %73, %74, %75, %76, %77, %78, %79, "
        "%80, %81, %82, %83, %84, %85, %86, %87, %88, %89, %90, %91"
        "}, a, b, p, 1, 1, %95, %96;\n}\n"
        : "+f"(d[0]), "+f"(d[1]), "+f"(d[2]), "+f"(d[3]), "+f"(d[4]), "+f"(d[5]), "+f"(d[6]), "+f"(d[7]),
          "+f"(d[8]), "+f"(d[9]), "+f"(d[10]), "+f"(d[11]), "+f"(d[12]), "+f"(d[13]), "+f"(d[14]), "+f"(d[15]),
          "+f"(d[16]), "+f"(d[17]), "+f"(d[18]), "+f"(d[19]), "+f"(d[20]), "+f"(d[21]), "+f"(d[22]), "+f"(d[23]),
          "+f"(d[24]), "+f"(d[25]), "+f"(d[26]), "+f"(d[27]), "+f"(d[28]), "+f"(d[29]), "+f"(d[30]), "+f"(d[31]),
          "+f"(d[32]), "+f"(d[33]), "+f"(d[34]), "+f"(d[35]), "+f"(d[36]), "+f"(d[37]), "+f"(d[38]), "+f"(d[39]),
          "+f"(d[40]), "+f"(d[41]), "+f"(d[42]), "+f"(d[43]), "+f"(d[44]), "+f"(d[45]), "+f"(d[46]), "+f"(d[47]),
          "+f"(d[48]), "+f"(d[49]), "+f"(d[50]), "+f"(d[51]), "+f"(d[52]), "+f"(d[53]), "+f"(d[54]), "+f"(d[55]),
          "+f"(d[56]), "+f"(d[57]), "+f"(d[58]), "+f"(d[59]), "+f"(d[60]), "+f"(d[61]), "+f"(d[62]), "+f"(d[63]),
          "+f"(d[64]), "+f"(d[65]), "+f"(d[66]), "+f"(d[67]), "+f"(d[68]), "+f"(d[69]), "+f"(d[70]), "+f"(d[71]),
          "+f"(d[72]), "+f"(d[73]), "+f"(d[74]), "+f"(d[75]), "+f"(d[76]), "+f"(d[77]), "+f"(d[78]), "+f"(d[79]),
          "+f"(d[80]), "+f"(d[81]), "+f"(d[82]), "+f"(d[83]), "+f"(d[84]), "+f"(d[85]), "+f"(d[86]), "+f"(d[87]),
          "+f"(d[88]), "+f"(d[89]), "+f"(d[90]), "+f"(d[91])
        : "r"(da), "r"(db), "r"(accumulate), "n"(TA), "n"(TB), "n"(HA), "n"(HB));
}

struct Ring {
    uint32_t slot, ph;
    __device__ __forceinline__ void next() { if (++slot == NSLOT) { slot = 0; ph ^= 1; } }
};
__device__ __forceinline__ uint32_t xslot(int i) { return __byte_perm(0x04130e0cu, 0x00130e0cu, 0x7770 + i); }
__device__ __forceinline__ uint32_t wslot(int i) { return __byte_perm(0x06001510u, 0x00151009u, 0x7770 + i); }

constexpr uint32_t HI_SW = desc_hi(1024, 1);

struct Mma {
    uint32_t bars, rel;
    bool lead;
    int wg, w;
    Ring r;
    __device__ __forceinline__ void release(uint32_t s) { if (lead) mbar_arrive_remote(rel + B_EMPTY + 8 * s); }
    template <int KIND>
    __device__ __forceinline__ uint32_t run(float (&a)[56], int n, int nrel, int lag, int accumulate, int ts) {
        uint32_t prev = 0;
#pragma unroll 1
        for (int i = 0; i < n; i++) {
            if (lag && i == (wg ? n - lag : -1)) bar_sync(7, 256);
            const uint32_t s = r.slot;
            mbar_wait(bars + B_FULL + 8 * s, r.ph); r.next();
            if (wg == 0) TS0(KIND ? 8 : 2, ts + i);
            const uint32_t dB = s * (SLOT >> 4), dA = dB + wg * 512;
            wg_fence();
#pragma unroll
            for (int k = 0; k < 4; k++) {
                const int acc = k > 0 || accumulate || i > 0;
                if (KIND == 0) wgmma_n112<1, 1, HI_SW, desc_hi(256, 0)>(a, dA + desc_lo(k * 2048, 8192), dB + desc_lo(16384 + k * SLAB, 128), acc);
                if (KIND == 1) wgmma_n112<0, 1, desc_hi(128, 0), HI_SW>(a, dA + desc_lo(k * 2048, k < 3 ? 1024 : 0), dB + desc_lo(16384 + k * 2048, 8192), acc);
                if (KIND == 2) wgmma_n112<1, 1, HI_SW, desc_hi(1024, 0)>(a, dA + desc_lo(k * 2048, 8192), dB + desc_lo(16384 + k * 256, 128), acc);
                if (k == 1) {
                    wg_commit(); wg_wait<1>();
                    if ((uint32_t)(i - 1) < (uint32_t)nrel) release(prev);
                    if (lag && i == (wg ? -1 : n - 1)) bar_arrive(7, 256);
                }
            }
            wg_commit();
            prev = s;
        }
        return prev;
    }
};

__global__ void __cluster_dims__(2, 1, 1) __launch_bounds__(NTHREADS, 1)
fused_kernel(const __nv_bfloat16* __restrict__ x, const __nv_bfloat16* __restrict__ b1, const __nv_bfloat16* __restrict__ b2, __nv_bfloat16* out, Scratch* G,
             const __grid_constant__ Params P) {
    extern __shared__ __align__(1024) uint8_t smem[];
    const uint32_t sbase = (uint32_t)__cvta_generic_to_shared(smem);
    const uint32_t bars = sbase + OFF_BAR;
    const int lane = threadIdx.x & 31;
    const int warp = __shfl_sync(~0u, threadIdx.x >> 5, 0), w = warp & 3;
    const uint32_t rank = blockIdx.x & 1, pr = blockIdx.x >> 1;
    const uint32_t pv = pr < 4 ? pr * 8 + 36 : pr < 40 ? pr - 4 : pr - 3 + (((pr - 40) * 37) >> 8);
    const uint32_t gp = (pv + 4) & 7, hp = pv >> 3;
    const uint32_t tb = gp * 2 + rank, c = hp * 16 + tb, row0 = (tb * 8 + hp) * 16;
    const bool has_g1 = gp > 0;
    const uint32_t nt1 = hp & 3, ft = max((int)gp - 1, 0) * 2 + (hp >> 2);
    const uint32_t nt2 = tb & 3, mt = (gp & 2) * 4 + hp, ks = gp >> 2;

    if (warp < NBAR / 3 && elect()) {
        if (warp == 0) TS(15, 0);
#pragma unroll
        for (int i = 0; i < 3; i++) mbar_init(bars + warp * 24 + 8 * i, 1u << ((0xaaa55000u >> (2 * max(warp * 3 + i - 12, 0)) & 3) | (warp == 9 ? 2 : 0)));
        asm volatile("fence.mbarrier_init.release.cluster;" ::: "memory");
        if (warp == B_ROW / 24) {
            mbar_expect(bars + B_ROW, TILEB);
            bulk_load(sbase + OFF_Y, x + row0 * D_, TILEB, bars + B_ROW);
        }
        const uint32_t k0 = gp == 7 ? 0 : gp * 64;
        if (FAST0 >= 2 && warp == 8) asm volatile("cp.async.bulk.prefetch.tensor.3d.L2.global [%0, {%1, %2, %3}];" ::"l"(&P.tmWqkv), "r"((hp * 56) & ~15), "r"(k0 + rank * 32), "r"(0) : "memory");
        if (FAST0 >= 3 && warp == 0) tma3d(sbase + 12 * 8192, &P.tmX, bars + B_QFULL, k0, tb * 64, 0);
    }
    __syncwarp();
    asm volatile("barrier.cluster.arrive.relaxed.aligned;\nbarrier.cluster.wait.aligned;" ::: "memory");

    if (warp == 8) {
        if (elect()) {
            uint32_t spins = (sbase & 0xffffffu) == SMEM0 ? 0 : SPIN_LIMIT;
            uint32_t kw = gp * 64, kx = kw;
            uint32_t due = (uint32_t)clock();
#pragma unroll 1
            for (int i = 0; i < 8; i++) {
                if (i >= 5) mbar_wait_bounded(bars + B_QEMPTY + 8 * (i - 5), 0, spins);
                else { while ((int)((uint32_t)clock() - due) < 0) {} due += PACE; }
                if (kw == D_) kw = 0;
                if (i < 4) kx = kw;
                const int ix = i - (i > 4);
                if (i < 7) mbar_expect(bars + B_QFULL + 8 * i, QSLOT);
                if (i != 4 && (FAST0 < 3 || i > 0)) tma3d(sbase + xslot(ix) * 8192, &P.tmX, bars + B_QFULL + 8 * ix, kx, tb * 64, 0);
                if (i == 5) mbar_wait_bounded(bars + B_CS, 0, spins);
                if (i < 7) tma3d_pair(sbase + wslot(i) * 8192 + rank * 12288, &P.tmWqkv, bars + B_QFULL + 8 * i, (hp * 56) & ~15, kw + rank * 32, 0);
                kx = kw; kw += 64;
                if (i == 0) TS(1, 23);
            }
            mbar_expect(bars + B_X, HALF); mbar_expect(bars + B_X + 8, HALF);
            Ring r{0, 0};
#pragma unroll 1
            for (int j = has_g1 ? 0 : 16; j < 34; j++) {
                const uint32_t dst = sbase + r.slot * SLOT, full = bars + B_FULL + 8 * r.slot;
                mbar_wait_bounded(bars + B_EMPTY + 8 * r.slot, r.ph, spins);
                mbar_expect(full, 16384 + TILEB);
                if (j < 16) {
                    tma3d(dst, &P.tmW1, full, 0, rank * 1024 + j * 64, ft * 2);
                } else if (j < 20) {
                    tma3d(dst + 16384, &P.tmWo, full, nt2 * 112, 0, ks * 4 + j - 16);
                    tma3d(dst + 24576, &P.tmWo, full, nt2 * 112 + 64, 0, ks * 4 + j - 16);
                } else {
                    tma2d_pair(dst + rank * 8192, &P.tmW2, full, mt * 128 + rank * 64, ks * 896 + j * 128 - (j < 27 ? 2560 : 3392));
                }
                r.next();
            }
            mbar_wait_bounded(bars + B_END, 0, spins);
        }
    } else if (warp > 8) {
        uint32_t ep = ld_relaxed(&G->epoch[c]);
        float* cs;
        {
            uint32_t src = sbase + 16 * 8192 - 4096 + rank * 12288 + w * 4096 + lane * 4;
            float s0 = 0.f, s1 = 0.f, s2 = 0.f, s3 = 0.f;
            mbar_wait(bars + B_QFULL, 0);
#pragma unroll 1
            for (int i = 0; i < 2; i++) {
                uint32_t v[16];
#pragma unroll
                for (int k = 0; k < 16; k++) v[k] = __float_as_uint(lds1f((src ^ ((k & 7) * 144)) + (k >> 3) * 1024));
#pragma unroll
                for (int k = 0; k < 16; k += 2) { s0 += bf_lo(v[k]); s1 += bf_hi(v[k]); s2 += bf_lo(v[k + 1]); s3 += bf_hi(v[k + 1]); }
                src += 2048;
            }
            cs = G->colsum[ep & 1][hp];
            if (tb < 14) asm volatile("red.relaxed.gpu.global.add.v2.f32 [%0], {%1, %2};" ::"l"(cs + w * 64 - 64 + lane * 2), "f"(s0 + s2), "f"(s1 + s3) : "memory");
            if (tb == 15) *(float2*)(G->colsum[~ep & 1][hp] + w * 64 - 64 + lane * 2) = make_float2(0.f, 0.f);
            ep++;
            if (w == 1) TS(1, 24);
            if (w == 2) {
                bar_sync(6, 224);
                if (elect()) { mbar_arrive(bars + B_CS); signal(&G->flagH[c >> 2]); TS(1, 3); }
                __syncwarp();
            } else {
                bar_arrive(6, 224);
            }
        }
        if (w == 1) {
            wait_flag(&G->flagH[lane], 4 * ep);
            __syncwarp();
            if (elect()) {
                TS(1, 16);
                mbar_expect(bars + B_REC, 1152 + 768);
                bulk_load(sbase + OFF_CS, cs, 768, bars + B_REC);
                bulk_load(sbase + OFF_ST, G->stat + tb * 128, 1152, bars + B_REC);
                G->epoch[c] = ep;
                Ring r{0, 0};
                const uint8_t* src = G->H[nt1][rank * 16];
#pragma unroll 1
                for (int j = has_g1 ? 0 : 16; j < 34; j++) {
                    if (j == 16) src = G->O[mt][ks * 4] + rank * HALF;
                    if (j == 20) src = G->U[nt2][ks * 14];
                    if ((0x4110000ull >> j) & 1) {
                        wait_flag(G->flag[j == 16 ? 16 + mt : nt2 * 4 + ks * 2 + (j == 26)], (j == 16 ? 8 : 14) * ep);
                        TS(4, j == 16 ? 18 : j == 20 ? 17 : j);
                    }
                    const uint32_t dst = sbase + r.slot * SLOT, full = bars + B_FULL + 8 * r.slot;
                    mbar_wait(bars + B_EMPTY + 8 * r.slot, r.ph);
                    if ((j >> 2) == 4) bulk_load_pair(dst + rank * 8192, src, HALF, full);
                    else bulk_load(dst + 16384, src, TILEB, full);
                    src += TILEB;
                    if (UGAP && j == 20) __nanosleep(UGAP);
                    r.next();
                }
            }
        } else {
            bar_sync(3, 320);
            if (w == 2) {
                if (elect()) {
                    mbar_expect(bars + B_HALO, 2 * KV);
                    if (tb > 0) wait_flag(&G->flagHalo[c - 1], ep);
                    bulk_load(sbase + OFF_X, G->halo[tb > 0 ? c - 1 : NCTA], 2 * KV, bars + B_HALO);
                    TS(2, 21);
                }
            } else {
                if (elect()) { mbar_arrive(bars + B_HALO); signal(&G->flagHalo[c]); }
                __syncwarp();
                bar_sync(2, 288);
                if (elect()) bulk_store(out + row0 * D_, sbase + OFF_Y, TILEB);
                __syncwarp();
                bar_sync(4, 288);
                if (elect()) {
                    bulk_store(G->O[tb][hp], sbase + OFF_X, TILEB);
                    bulk_flush();
                    mbar_arrive_remote(mapa(bars + B_FREE, rank ^ 1));
                    mbar_arrive(bars + B_FREE);
                    signal(G->flag[16 + tb]);
                    TS(2, 22);
                }
            }
            __syncwarp();
            if (has_g1) {
                bar_sync(w + 6, 160);
                if (elect()) { signal(G->flag[nt1 * 4 + (ft >= 7) * 2 + w - 2]); TS(4, 5 + w); }
            }
        }
    } else {
        const int wg = warp >> 2;
        Mma M{bars, mapa(bars, rank ^ (lane & 1)), (threadIdx.x & 127) < 2, wg, w, Ring{0, 0}};
        const int r = lane >> 2, t = lane & 3;
        const uint32_t bias0 = ld_u16(b1 + ft * 128 + warp * 16 + r), bias1 = ld_u16(b1 + ft * 128 + warp * 16 + r + 8);
        if (wg == 1) {
            const int r16 = w * 4 + t, c8 = (r + 2 * t) & 7;
            const uint32_t row = sbase + OFF_Y + r16 * (2 * D_) + c8 * 16;
            mbar_wait(bars + B_ROW, 0);
            TS0(1, 67);
            float f[56];
#pragma unroll
            for (int i = 0; i < 7; i++) {
                const uint4 v = lds4(row + i * 128);
                f[8 * i] = bf_lo(v.x); f[8 * i + 1] = bf_hi(v.x); f[8 * i + 2] = bf_lo(v.y); f[8 * i + 3] = bf_hi(v.y);
                f[8 * i + 4] = bf_lo(v.z); f[8 * i + 5] = bf_hi(v.z); f[8 * i + 6] = bf_lo(v.w); f[8 * i + 7] = bf_hi(v.w);
            }
            float s0 = f[0], s1 = f[1], s2 = f[2], s3 = f[3];
#pragma unroll
            for (int i = 4; i < 56; i += 4) { s0 += f[i]; s1 += f[i + 1]; s2 += f[i + 2]; s3 += f[i + 3]; }
            const float nmean = oct_sum((s0 + s1) + (s2 + s3)) * (-1.f / D_);
            s0 = s1 = s2 = s3 = 0.f;
#pragma unroll
            for (int i = 0; i < 56; i += 4) {
                f[i] += nmean; f[i + 1] += nmean; f[i + 2] += nmean; f[i + 3] += nmean;
                s0 = fmaf(f[i], f[i], s0); s1 = fmaf(f[i + 1], f[i + 1], s1); s2 = fmaf(f[i + 2], f[i + 2], s2); s3 = fmaf(f[i + 3], f[i + 3], s3);
            }
            const float var = oct_sum((s0 + s1) + (s2 + s3)) * (1.f / D_);
            const float rstd = rsq(var + LN_EPS);
            const float sc = rstd * rsq(fmaf(var * rstd, rstd, LN_EPS));
            if (lane < 4) G->stat[16 + row0 + r16] = make_float2(rstd + rstd, nmean);
            uint8_t* hb = G->H[0][0] + row0 * (SLAB / 16) + r16 * 16 + c8 * 256;
            const int sw = tb < 8 ? 0 : 7 * 256;
#pragma unroll
            for (int i = 0; i < 7; i++) {
                const int lo = (8 * i) % 14, nt = (8 * i) / 14, next = 32 * TILEB - SLAB;
                const int off = lo < 7 ? (c8 < 7 - lo ? sw : -sw) : (c8 >= 14 - lo ? sw + next : -sw);
                *(uint4*)(hb + off + i * 2048 + nt * next) = make_uint4(pack2(f[8 * i] * sc, f[8 * i + 1] * sc), pack2(f[8 * i + 2] * sc, f[8 * i + 3] * sc),
                                                                        pack2(f[8 * i + 4] * sc, f[8 * i + 5] * sc), pack2(f[8 * i + 6] * sc, f[8 * i + 7] * sc));
            }
            TS0(1, 25);
            bar_arrive(6, 224);
        }
        const uint32_t kv = sbase + OFF_X + (w * 2 + wg) * KV + lane * 16;
        const uint32_t st = sbase + OFF_ST + (16 + w * 32 + wg) * 8;
        uint32_t q[7][2], k0[7], v0[7];
        {
            float acc[92];
#pragma unroll 1
            for (int kb = 0; kb < 7; kb++) {
                const bool held = kb == (wg ? 5 : -1);
                if (held) { wg_wait<0>(); if (M.lead) mbar_arrive_remote(M.rel + B_QEMPTY + 8 * 4); bar_sync(7, 256); }
                mbar_wait(bars + B_QFULL + 8 * kb, 0);
                TS0(1, 68 + wg * 7 + kb);
                const uint32_t dA = (xslot(kb) + wg) * 512, dB = wslot(kb) * 512 + (hp & 1);
                wg_fence();
#pragma unroll
                for (int k = 0; k < 4; k++) {
                    wgmma_n184<0, 1, HI_SW, HI_SW>(acc, dA + desc_lo(k * 32, 16), dB + desc_lo((k & 1) * 2048 + (k >> 1) * 12288, 4096), k > 0 || kb > 0);
                    if (k == 0) { wg_commit(); wg_wait<1>(); if (M.lead && kb > 0 && !held) mbar_arrive_remote(M.rel + B_QEMPTY + 8 * (kb - 1)); }
                }
                wg_commit();
            }
            if (wg == 0) bar_arrive(7, 256);
            mbar_wait(bars + B_REC, 0);
            const float n0 = lds1f(st + r * 16 + 4), n1 = lds1f(st + r * 16 + 132);
            const uint32_t csa = sbase + OFF_CS + t * 8 + (hp & 1) * 32;
            wg_wait<0>();
            pin(acc);
            M.release(4); M.release(5);
            TS0(1, 4 + 7 * wg);
            uint32_t hi[14];
#pragma unroll
            for (int p = 2; p >= 0; p--) {
#pragma unroll
                for (int g = 0; g < 7; g++) {
                    const uint2 cs = lds2(csa + (p * 8 + g) * 32);
                    const int a = (p * 8 + g) * 4;
                    const float c0 = __uint_as_float(cs.x), c1 = __uint_as_float(cs.y);
                    const uint32_t lo2 = pack2(fmaf(n0, c0, acc[a]), fmaf(n0, c1, acc[a + 1])), hi2 = pack2(fmaf(n1, c0, acc[a + 2]), fmaf(n1, c1, acc[a + 3]));
                    if (p == 0) { q[g][0] = lo2; q[g][1] = hi2; } else { (p == 1 ? k0 : v0)[g] = lo2; hi[(p - 1) * 7 + g] = hi2; }
                }
                if (p == 1) {
#pragma unroll
                    for (int i = 0; i < 3; i++) stsm4(kv + 2 * KV + i * 512, hi[4 * i], hi[4 * i + 1], hi[4 * i + 2], hi[4 * i + 3]);
                    stsm2(kv + 2 * KV + 1536, hi[12], hi[13]);
                    if (w == 3) {
#pragma unroll
                        for (int i = 0; i < 14; i++) stg1(G->halo[c] + wg * KV + lane * 4 + i * 128, hi[i]);
                    }
                    bar_arrive(3, 320);
                }
            }
        }
        TS0(1, 9 + 11 * wg);
        float a[56];
#pragma unroll
        for (int i = 0; i < 56; i++) asm volatile("" : "=f"(a[i]));
        const int n1 = PAUSE + (wg == 0 ? LEAD : 0);
        uint32_t last = M.run<0>(a, has_g1 ? n1 : 0, 16, 0, 0, 32);
        {
            uint32_t kp[8], k1[8], vp[8], v1[8];
            mbar_wait(bars + B_HALO, 0);
            ldsm4(kp, kv); ldsm4(kp + 4, kv + 512); ldsm4(k1, kv + 2 * KV); ldsm4(k1 + 4, kv + 2 * KV + 512);
            ldsm4t(vp, kv + 896); ldsm4t(vp + 4, kv + 1408); ldsm4t(v1, kv + 2 * KV + 896); ldsm4t(v1 + 4, kv + 2 * KV + 1408);
#pragma unroll
            for (int g = 0; g < 7; g++) v0[g] = transpose8(v0[g]);
            const bool e0 = 2 * t > r, e1 = 2 * t >= r;
            const uint32_t ka = st + t * 32 - (e0 ? 128 : 0), kb = st + t * 32 + 16 - (e1 ? 128 : 0);
            const float rk[4] = {lds1f(ka), lds1f(kb), lds1f(ka + 128), lds1f(kb + 128)};
            const float sq0 = lds1f(st + r * 16) * (0.25f * 0.1889822365046136f * 1.4426950408889634f), sq1 = lds1f(st + r * 16 + 128) * (0.25f * 0.1889822365046136f * 1.4426950408889634f);
            float sc[6] = {sq0 * rk[0], sq0 * rk[1], sq1 * rk[2], sq1 * rk[3], 0.f, 0.f};
            if (tb == 0 && w == 0) { sc[4] = e0 ? -1e30f : 0.f; sc[5] = e1 ? -1e30f : 0.f; }
            uint32_t mk[6] = {(e0 ? 0xffffu : 0u) | (e1 ? 0xffff0000u : 0u), 0u, t < 2 ? q[3][0] : 0u, t < 2 ? q[3][1] : 0u, t < 2 ? 0u : q[3][0], t < 2 ? 0u : q[3][1]};
            wg_wait<0>();
            pin(a);
            if (has_g1) M.release(last);
            bar_sync(2, 288);
            mbar_wait(bars + B_HALO, 0);
            TS0(2, 12 + 16 * wg);
            float sv[2][4];
#pragma unroll
            for (int h = 0; h < 2; h++) {
                const int ga = h * 4, gb = h * 4 + 1, gc = h * 4 + 2;
                float s[3][4] = {};
                mma16(s[0], q[ga][0], q[ga][1], q[gb][0], q[gb][1], kp[ga], kp[gb]);
                mma16(s[1], q[ga][0], q[ga][1], q[gb][0], q[gb][1], k0[ga], k0[gb]);
                mma16(s[2], q[ga][0], q[ga][1], q[gb][0], q[gb][1], k1[ga], k1[gb]);
                mma16(s[0], q[gc][0], q[gc][1], mk[2 + 2 * h], mk[3 + 2 * h], kp[gc], kp[3]);
                mma16(s[1], q[gc][0], q[gc][1], mk[2 + 2 * h], mk[3 + 2 * h], k0[gc], k0[3]);
                mma16(s[2], q[gc][0], q[gc][1], mk[2 + 2 * h], mk[3 + 2 * h], k1[gc], k1[3]);
                sv[h][0] = fmaf(e0 ? s[0][0] : s[1][0], sc[0], sc[4]);
                sv[h][1] = fmaf(e1 ? s[0][1] : s[1][1], sc[1], sc[5]);
                sv[h][2] = (e0 ? s[1][2] : s[2][2]) * sc[2];
                sv[h][3] = (e1 ? s[1][3] : s[2][3]) * sc[3];
            }
            uint32_t pp[2][2];
#pragma unroll
            for (int i = 0; i < 4; i++) {
                float* v = &sv[i >> 1][(i & 1) * 2];
                const float m = quad_max(fmaxf(v[0], v[1]));
                const float p0 = ex2(v[0] - m), p1 = ex2(v[1] - m);
                const float inv = rcp(quad_sum(p0 + p1));
                pp[i >> 1][i & 1] = pack2(p0 * rk[(i & 1) * 2] * inv, p1 * rk[(i & 1) * 2 + 1] * inv);
            }
            uint32_t o[8][2];
#pragma unroll
            for (int i = 0; i < 8; i++) {
                const int h = i >> 2, g = i - h;
                float d[4] = {};
                mma16(d, pp[h][0] & mk[0], 0u, pp[h][0] & ~mk[0], pp[h][1] & mk[0], vp[g], v0[g]);
                mma8(d, 0u, pp[h][1] & ~mk[0], v1[g]);
                o[i][0] = pack2(d[0], d[1]); o[i][1] = pack2(d[2], d[3]);
            }
            if (t >= 2) { o[3][0] = o[4][0]; o[3][1] = o[4][1]; }
            const uint32_t dst = sbase + OFF_X + (w >> 1) * HALF + ((w & 1) * 32 + (lane & 15) * 2 + wg) * 16 + (lane >> 4) * 1024;
            stsm4(dst, o[0][0], o[0][1], o[1][0], o[1][1]);
            stsm4(dst + 2048, o[2][0], o[2][1], o[3][0], o[3][1]);
            stsm4(dst + 4096, o[5][0], o[5][1], o[6][0], o[6][1]);
            stsm2(dst + 6144, o[7][0], o[7][1]);
            fence_async_shared();
            bar_sync(4, 288);
            TS0(2, 10 + 19 * wg);
        }
        if (has_g1) {
            last = M.run<0>(a, 16 - n1, 16, LAG1, 1, 32 + PAUSE + LEAD);
            mbar_wait_cluster(bars + B_FREE, 0);
            const uint32_t xb = sbase + OFF_X + wg * 8192 + (threadIdx.x & 127) * 16;
            const uint32_t rx = mapa(xb, rank ^ 1), rbar = mapa(bars + B_X + 8 * wg, rank ^ 1);
            wg_wait<0>();
            pin(a);
            M.release(last);
            TS0(4, 5 + wg);
#pragma unroll
            for (int i = 0; i < 3; i++)
                st_async4(rx + i * 2048, rbar, pack2(a[28 + 8 * i], a[29 + 8 * i]), pack2(a[30 + 8 * i], a[31 + 8 * i]), pack2(a[32 + 8 * i], a[33 + 8 * i]), pack2(a[34 + 8 * i], a[35 + 8 * i]));
            st_async2(rx + 6144, rbar, pack2(a[52], a[53]), pack2(a[54], a[55]));
#pragma unroll
            for (int i = 0; i < 28; i++) a[i] += bf_lo((i & 2) ? bias1 : bias0);
            mbar_wait_cluster(bars + B_X + 8 * wg, 0);
            TS0(4, 1 + wg);
            uint32_t u[16];
#pragma unroll
            for (int i = 0; i < 4; i++) { const uint4 v = lds4(xb + i * 2048); u[4 * i] = v.x; u[4 * i + 1] = v.y; u[4 * i + 2] = v.z; u[4 * i + 3] = v.w; }
            uint8_t* dst = G->U[nt1][((ft >= 7) + wg) * 7 + ft] + rank * HALF + w * 256 + lane * 4;
#pragma unroll
            for (int i = 0; i < 14; i++) stg1(dst + (i >> 1) * 1024 + (i & 1) * 128, pack2(gelu2(a[2 * i] + bf_lo(u[i])), gelu2(a[2 * i + 1] + bf_hi(u[i]))));
            bar_arrive(8 + wg, 160);
            TS0(4, 30 + wg);
        }
        uint32_t c0 = ld_u16(b2 + mt * 128 + warp * 16 + r), c1 = ld_u16(b2 + mt * 128 + warp * 16 + r + 8);
        last = M.run<1>(a, 4, 4, 0, 0, 48);
        wg_wait<0>();
        M.release(last);
        if (wg == 1) TS0(4, 13);
        c0 *= ks == 0 ? 0x10001u : 0u; c1 *= ks == 0 ? 0x10001u : 0u;
        M.run<2>(a, 14, 14 - NSLOT, LAG2, 1, 52);
        mbar_wait(bars + B_FREE, 0);
        const uint32_t stg = sbase + OFF_X + wg * (OFF_Y - OFF_X) + w * SLAB;
        const uint32_t sa = stg + (lane & 15) * 224 + (lane >> 4) * 16;
        wg_wait<0>();
        pin(a);
        TS0(8, 14 + wg);
#pragma unroll
        for (int g = 0; g < 7; g++)
            stsm4(sa + g * 32, half_plus(pack2(a[8 * g], a[8 * g + 1]), c0), half_plus(pack2(a[8 * g + 2], a[8 * g + 3]), c1),
                  half_plus(pack2(a[8 * g + 4], a[8 * g + 5]), c0), half_plus(pack2(a[8 * g + 6], a[8 * g + 7]), c1));
        fence_async_shared();
        __syncwarp();
        if (elect()) {
            asm volatile("cp.reduce.async.bulk.tensor.2d.global.shared::cta.add.tile.bulk_group [%0, {%2, %3}], [%1];\ncp.async.bulk.commit_group;" ::"l"(&P.tmOut), "r"(stg), "r"(nt2 * 112), "r"(mt * 128 + warp * 16) : "memory");
            if (w == 0) mbar_arrive(bars + B_END);
            asm volatile("cp.async.bulk.wait_group.read 0;" ::: "memory");
        }
        if (wg == 1) TS0(15, 19);
        TSDUMP();
    }
}

typedef CUresult (*EncodeFn)(CUtensorMap*, CUtensorMapDataType, cuuint32_t, void*, const cuuint64_t*, const cuuint64_t*, const cuuint32_t*, const cuuint32_t*,
                             CUtensorMapInterleave, CUtensorMapSwizzle, CUtensorMapL2promotion, CUtensorMapFloatOOBfill);

void make_map(EncodeFn enc, CUtensorMap* tm, const void* base, bool swizzle, int d0, int d1, int d2, int s1, int s2, int b0, int b1, int b2) {
    const cuuint64_t dims[3] = {(cuuint64_t)d0, (cuuint64_t)d1, (cuuint64_t)d2}, strides[2] = {(cuuint64_t)s1 * 2, (cuuint64_t)s2 * 2};
    const cuuint32_t box[3] = {(cuuint32_t)b0, (cuuint32_t)b1, (cuuint32_t)b2}, es[3] = {1, 1, 1};
    enc(tm, CU_TENSOR_MAP_DATA_TYPE_BFLOAT16, d2 ? 3 : 2, (void*)base, dims, strides, box, es, CU_TENSOR_MAP_INTERLEAVE_NONE,
        swizzle ? CU_TENSOR_MAP_SWIZZLE_128B : CU_TENSOR_MAP_SWIZZLE_NONE, CU_TENSOR_MAP_L2_PROMOTION_L2_128B, CU_TENSOR_MAP_FLOAT_OOB_FILL_NONE);
}

}

extern "C" void kernel_launch(void* const* d_in, const int* in_sizes, int n_in, void* d_out, int out_size) {
    static EncodeFn enc = nullptr;
    static Scratch* scratch = nullptr;
    if (!enc) {
        void* fn = nullptr;
        cudaDriverEntryPointQueryResult qr;
        cudaGetDriverEntryPoint("cuTensorMapEncodeTiled", &fn, cudaEnableDefault, &qr);
        enc = (EncodeFn)fn;
        cudaGetSymbolAddress((void**)&scratch, g_s);
        cudaFuncSetAttribute(fused_kernel, cudaFuncAttributeMaxDynamicSharedMemorySize, SMEM_BYTES);
    }
    Params P;
    const __nv_bfloat16* x = (const __nv_bfloat16*)d_in[0];
    make_map(enc, &P.tmX, x, true, D_, S_ / 2, 2, 2 * D_, D_, 64, 64, 2);
    make_map(enc, &P.tmWqkv, d_in[1], true, D_, D_, 3, 3 * D_, D_, 64, 32, 3);
    make_map(enc, &P.tmW1, d_in[4], true, 64, S_, F_ / 64, F_, 64, 64, 64, 2);
    make_map(enc, &P.tmW2, d_in[6], true, S_, F_, 0, S_, 0, 64, 64, 1);
    make_map(enc, &P.tmWo, d_in[2], true, D_, 56, 8, D_, 56 * D_, 64, 64, 1);
    make_map(enc, &P.tmOut, d_out, false, D_, S_, 0, D_, 0, 112, 16, 1);
    fused_kernel<<<NCTA, NTHREADS, SMEM_BYTES, cudaStreamPerThread>>>(x, (const __nv_bfloat16*)d_in[5], (const __nv_bfloat16*)d_in[7], (__nv_bfloat16*)d_out, scratch, P);
}
```

```cpp
#include <cuda_runtime.h>
#include <cuda_bf16.h>
#include <cuda.h>
#include <stdint.h>

#define POLL_SLEEP
#define HALO_NS 300
#define PACE 800
#define PAUSE 8
#define LEAD 0
#define LAG1 4
#define LAG2 5

namespace {

constexpr int S_ = 2048, D_ = 448, F_ = 1792;
constexpr int NCTA = 128, NTHREADS = 384;
constexpr int NSLOT = 6, SLOT = 32768, QSLOT = 40960, TILEB = 14336, SLAB = 3584, HALF = 7168;
constexpr int KV = 1792;
constexpr int OFF_X = NSLOT * SLOT;
constexpr int OFF_Y = OFF_X + 10 * KV;
constexpr int OFF_CS = OFF_Y + TILEB;
constexpr int OFF_ST = OFF_CS + 768;
constexpr int OFF_BAR = OFF_ST + 1152;
constexpr int SMEM_BYTES = OFF_BAR + 1024;
constexpr uint32_t SMEM0 = 1024;
constexpr int B_QFULL = 0, B_FULL = 56, B_REC = 104, B_ROW = 112, B_X = 120, B_CS = 136, B_HALO = 144, B_FREE = 152, B_END = 160, B_UDONE = 168, B_QEMPTY = 176, B_EMPTY = 192, NBAR = 30;
constexpr float LN_EPS = 1e-5f;
constexpr int SPIN_LIMIT = 1 << 22;

struct Scratch {
    uint8_t H[4][32][TILEB];
    uint8_t U[4][28][TILEB];
    uint8_t O[16][8][TILEB];
    uint8_t halo[NCTA][2 * KV];
    float2 stat[16 + S_];
    float colsum[2][8][192];
    uint32_t flagH[32];
    uint32_t flag[32][32];
    uint32_t epoch[NCTA];
};
__device__ __align__(1024) Scratch g_s;

#define TS(g, i)
#define TS0(g, i)
#define TSDUMP()

struct Params {
    CUtensorMap tmX, tmWqkv, tmW1, tmW2, tmWo, tmOut;
};

__device__ __forceinline__ bool elect() {
    uint32_t p;
    asm volatile("{\n.reg .pred p;\nelect.sync _|p, 0xffffffff;\nselp.u32 %0, 1, 0, p;\n}" : "=r"(p));
    return p;
}
__device__ __forceinline__ void mbar_init(uint32_t b, uint32_t c) { asm volatile("mbarrier.init.shared::cta.b64 [%0], %1;" ::"r"(b), "r"(c) : "memory"); }
__device__ __forceinline__ void mbar_expect(uint32_t b, uint32_t tx) { asm volatile("mbarrier.arrive.expect_tx.shared::cta.b64 _, [%0], %1;" ::"r"(b), "r"(tx) : "memory"); }
__device__ __forceinline__ void mbar_arrive(uint32_t b) { asm volatile("mbarrier.arrive.shared::cta.b64 _, [%0];" ::"r"(b) : "memory"); }
__device__ __forceinline__ void mbar_arrive_remote(uint32_t b) { asm volatile("mbarrier.arrive.shared::cluster.b64 _, [%0];" ::"r"(b) : "memory"); }
#define MBAR_WAIT_ASM(SEM) \
    asm volatile("{\n.reg .pred p;\nWAIT:\nmbarrier.try_wait.parity" SEM ".shared::cta.b64 p, [%0], %1;\n@!p bra WAIT;\n}" ::"r"(b), "r"(parity) : "memory")
__device__ __forceinline__ void mbar_wait(uint32_t b, uint32_t parity) { MBAR_WAIT_ASM(""); }
__device__ __forceinline__ void mbar_wait_cluster(uint32_t b, uint32_t parity) { MBAR_WAIT_ASM(".acquire.cluster"); }
__device__ __forceinline__ void mbar_wait_bounded(uint32_t b, uint32_t parity, uint32_t& n) {
    asm volatile("{\n.reg .pred p;\nWAIT:\nadd.u32 %0, %0, 1;\nsetp.gt.u32 p, %0, %3;\n@p st.global.u32 [%4], %0;\n"
                 "mbarrier.try_wait.parity.shared::cta.b64 p, [%1], %2;\n@!p bra WAIT;\n}" : "+r"(n) : "r"(b), "r"(parity), "n"(SPIN_LIMIT), "l"(0ull) : "memory");
}
__device__ __forceinline__ uint32_t mapa(uint32_t a, uint32_t rank) { uint32_t r; asm("mapa.shared::cluster.u32 %0, %1, %2;" : "=r"(r) : "r"(a), "r"(rank)); return r; }
__device__ __forceinline__ void tma3d(uint32_t dst, const CUtensorMap* tm, uint32_t bar, int c0, int c1, int c2) {
    asm volatile("cp.async.bulk.tensor.3d.shared::cluster.global.mbarrier::complete_tx::bytes [%0], [%1, {%3, %4, %5}], [%2];" ::"r"(dst), "l"(tm), "r"(bar), "r"(c0), "r"(c1), "r"(c2) : "memory");
}
__device__ __forceinline__ void tma2d_pair(uint32_t dst, const CUtensorMap* tm, uint32_t bar, int c0, int c1) {
    asm volatile("cp.async.bulk.tensor.2d.shared::cluster.global.mbarrier::complete_tx::bytes.multicast::cluster [%0], [%1, {%3, %4}], [%2], %5;" ::"r"(dst), "l"(tm), "r"(bar), "r"(c0), "r"(c1), "h"((uint16_t)3) : "memory");
}
__device__ __forceinline__ void tma3d_pair(uint32_t dst, const CUtensorMap* tm, uint32_t bar, int c0, int c1, int c2) {
    asm volatile("cp.async.bulk.tensor.3d.shared::cluster.global.mbarrier::complete_tx::bytes.multicast::cluster [%0], [%1, {%3, %4, %5}], [%2], %6;" ::"r"(dst), "l"(tm), "r"(bar), "r"(c0), "r"(c1), "r"(c2), "h"((uint16_t)3) : "memory");
}
__device__ __forceinline__ void bulk_load(uint32_t dst, const void* src, uint32_t bytes, uint32_t bar) {
    asm volatile("cp.async.bulk.shared::cluster.global.mbarrier::complete_tx::bytes [%0], [%1], %2, [%3];" ::"r"(dst), "l"(src), "r"(bytes), "r"(bar) : "memory");
}
__device__ __forceinline__ void bulk_load_pair(uint32_t dst, const void* src, uint32_t bytes, uint32_t bar) {
    asm volatile("cp.async.bulk.shared::cluster.global.mbarrier::complete_tx::bytes.multicast::cluster [%0], [%1], %2, [%3], %4;" ::"r"(dst), "l"(src), "r"(bytes), "r"(bar), "h"((uint16_t)3) : "memory");
}
__device__ __forceinline__ void bulk_store(void* dst, uint32_t src, uint32_t bytes) {
    asm volatile("cp.async.bulk.global.shared::cta.bulk_group [%0], [%1], %2;" ::"l"(dst), "r"(src), "r"(bytes) : "memory");
}
__device__ __forceinline__ uint32_t ld_u16(const void* p) { uint32_t v; asm volatile("ld.global.nc.u16 %0, [%1];" : "=r"(v) : "l"(p)); return v; }
__device__ __forceinline__ uint32_t ld_relaxed(const uint32_t* p) { uint32_t v; asm volatile("ld.relaxed.gpu.global.u32 %0, [%1];" : "=r"(v) : "l"(p) : "memory"); return v; }
__device__ __forceinline__ void bulk_flush() { asm volatile("cp.async.bulk.commit_group;\ncp.async.bulk.wait_group 0;" ::: "memory"); }
__device__ __forceinline__ void signal(uint32_t* flag) { asm volatile("red.release.gpu.global.add.u32 [%0], 1;" ::"l"(flag) : "memory"); }
__device__ __forceinline__ uint32_t tag(uint32_t v, uint32_t mask, uint32_t parity) { return (v & ~mask) | (parity & mask); }
__device__ __forceinline__ uint32_t or_diff(uint32_t acc, uint32_t v, uint32_t parity) { asm("lop3.b32 %0, %0, %1, %2, 0xf6;" : "+r"(acc) : "r"(v), "r"(parity)); return acc; }
__device__ __forceinline__ uint4 ld_relaxed4(const void* p) {
    uint4 v;
    asm volatile("ld.relaxed.gpu.global.v4.u32 {%0, %1, %2, %3}, [%4];" : "=r"(v.x), "=r"(v.y), "=r"(v.z), "=r"(v.w) : "l"(p) : "memory");
    return v;
}
__device__ __forceinline__ void sts4(uint32_t a, uint4 v) { asm volatile("st.shared.v4.b32 [%0], {%1, %2, %3, %4};" ::"r"(a), "r"(v.x), "r"(v.y), "r"(v.z), "r"(v.w) : "memory"); }
__device__ __forceinline__ void stg1(void* p, uint32_t v) { asm volatile("st.global.b32 [%0], %1;" ::"l"(p), "r"(v) : "memory"); }
__device__ __forceinline__ void fence_async_shared() { asm volatile("fence.proxy.async.shared::cta;" ::: "memory"); }
__device__ __forceinline__ void wait_flag(const uint32_t* p, uint32_t target) {
    asm volatile("{\n.reg .pred p;\n.reg .u32 v;\nPOLL:\nld.acquire.gpu.global.u32 v, [%0];\nsetp.ne.u32 p, v, %1;\n" POLL_SLEEP "@p bra POLL;\nfence.proxy.async.global;\n}" ::"l"(p), "r"(target) : "memory");
}
__device__ __forceinline__ void bar_sync(int id, int n) { asm volatile("bar.sync %0, %1;" ::"r"(id), "r"(n) : "memory"); }
__device__ __forceinline__ void bar_arrive(int id, int n) { asm volatile("bar.arrive %0, %1;" ::"r"(id), "r"(n) : "memory"); }
__device__ __forceinline__ void wg_fence() { asm volatile("wgmma.fence.sync.aligned;" ::: "memory"); }
__device__ __forceinline__ void wg_commit() { asm volatile("wgmma.commit_group.sync.aligned;" ::: "memory"); }
template <int N> __device__ __forceinline__ void wg_wait() { asm volatile("wgmma.wait_group.sync.aligned %0;" ::"n"(N) : "memory"); }
template <int N> __device__ __forceinline__ void pin(float (&d)[N]) {
#pragma unroll
    for (int i = 0; i < N; i++) asm volatile("" : "+f"(d[i])::"memory");
}
__host__ __device__ constexpr uint32_t desc_hi(uint32_t sbo, uint32_t swz) { return (sbo >> 4) | (swz << 30); }
__host__ __device__ constexpr uint32_t desc_lo(uint32_t off, uint32_t lbo) { return ((SMEM0 + off) >> 4) | ((lbo >> 4) << 16); }
__device__ __forceinline__ uint32_t pack2(float lo, float hi) { uint32_t r; asm("cvt.rn.bf16x2.f32 %0, %1, %2;" : "=r"(r) : "f"(hi), "f"(lo)); return r; }
__device__ __forceinline__ float bf_lo(uint32_t v) { return __uint_as_float(v << 16); }
__device__ __forceinline__ float bf_hi(uint32_t v) { return __uint_as_float(v & 0xffff0000u); }
__device__ __forceinline__ uint32_t half_plus(uint32_t a, uint32_t b) { uint32_t r; asm("fma.rn.bf16x2 %0, %1, %2, %3;" : "=r"(r) : "r"(a), "r"(0x3f003f00u), "r"(b)); return r; }
__device__ __forceinline__ void stsm4(uint32_t a, uint32_t r0, uint32_t r1, uint32_t r2, uint32_t r3) {
    asm volatile("stmatrix.sync.aligned.m8n8.x4.shared.b16 [%0], {%1, %2, %3, %4};" ::"r"(a), "r"(r0), "r"(r1), "r"(r2), "r"(r3) : "memory");
}
__device__ __forceinline__ void stsm2(uint32_t a, uint32_t r0, uint32_t r1) {
    asm volatile("stmatrix.sync.aligned.m8n8.x2.shared.b16 [%0], {%1, %2};" ::"r"(a), "r"(r0), "r"(r1) : "memory");
}
__device__ __forceinline__ uint4 lds4(uint32_t a) { uint4 v; asm volatile("ld.shared.v4.b32 {%0, %1, %2, %3}, [%4];" : "=r"(v.x), "=r"(v.y), "=r"(v.z), "=r"(v.w) : "r"(a) : "memory"); return v; }
__device__ __forceinline__ uint2 lds2(uint32_t a) { uint2 v; asm volatile("ld.shared.v2.b32 {%0, %1}, [%2];" : "=r"(v.x), "=r"(v.y) : "r"(a) : "memory"); return v; }
__device__ __forceinline__ float lds1f(uint32_t a) { float v; asm volatile("ld.shared.f32 %0, [%1];" : "=f"(v) : "r"(a) : "memory"); return v; }
__device__ __forceinline__ void ldsm4(uint32_t* r, uint32_t a) {
    asm volatile("ldmatrix.sync.aligned.m8n8.x4.shared.b16 {%0, %1, %2, %3}, [%4];" : "=r"(r[0]), "=r"(r[1]), "=r"(r[2]), "=r"(r[3]) : "r"(a) : "memory");
}
__device__ __forceinline__ void ldsm4t(uint32_t* r, uint32_t a) {
    asm volatile("ldmatrix.sync.aligned.m8n8.x4.trans.shared.b16 {%0, %1, %2, %3}, [%4];" : "=r"(r[0]), "=r"(r[1]), "=r"(r[2]), "=r"(r[3]) : "r"(a) : "memory");
}
__device__ __forceinline__ uint32_t transpose8(uint32_t v) { uint32_t r; asm volatile("movmatrix.sync.aligned.m8n8.trans.b16 %0, %1;" : "=r"(r) : "r"(v)); return r; }
__device__ __forceinline__ void mma16(float (&c)[4], uint32_t a0, uint32_t a1, uint32_t a2, uint32_t a3, uint32_t b0, uint32_t b1) {
    asm volatile("mma.sync.aligned.m16n8k16.row.col.f32.bf16.bf16.f32 {%0, %1, %2, %3}, {%4, %5, %6, %7}, {%8, %9}, {%0, %1, %2, %3};"
                 : "+f"(c[0]), "+f"(c[1]), "+f"(c[2]), "+f"(c[3]) : "r"(a0), "r"(a1), "r"(a2), "r"(a3), "r"(b0), "r"(b1));
}
__device__ __forceinline__ void mma8(float (&c)[4], uint32_t a0, uint32_t a1, uint32_t b0) {
    asm volatile("mma.sync.aligned.m16n8k8.row.col.f32.bf16.bf16.f32 {%0, %1, %2, %3}, {%4, %5}, {%6}, {%0, %1, %2, %3};"
                 : "+f"(c[0]), "+f"(c[1]), "+f"(c[2]), "+f"(c[3]) : "r"(a0), "r"(a1), "r"(b0));
}
__device__ __forceinline__ void st_async4(uint32_t a, uint32_t bar, uint32_t v0, uint32_t v1, uint32_t v2, uint32_t v3) {
    asm volatile("st.async.weak.shared::cluster.mbarrier::complete_tx::bytes.v4.b32 [%0], {%2, %3, %4, %5}, [%1];" ::"r"(a), "r"(bar), "r"(v0), "r"(v1), "r"(v2), "r"(v3) : "memory");
}
__device__ __forceinline__ void st_async2(uint32_t a, uint32_t bar, uint32_t v0, uint32_t v1) {
    asm volatile("st.async.weak.shared::cluster.mbarrier::complete_tx::bytes.v2.b32 [%0], {%2, %3}, [%1];" ::"r"(a), "r"(bar), "r"(v0), "r"(v1) : "memory");
}
__device__ __forceinline__ float quad_max(float v) { v = fmaxf(v, __shfl_xor_sync(~0u, v, 1)); return fmaxf(v, __shfl_xor_sync(~0u, v, 2)); }
__device__ __forceinline__ float quad_sum(float v) { v += __shfl_xor_sync(~0u, v, 1); return v + __shfl_xor_sync(~0u, v, 2); }
__device__ __forceinline__ float ex2(float v) { float r; asm("ex2.approx.ftz.f32 %0, %1;" : "=f"(r) : "f"(v)); return r; }
__device__ __forceinline__ float rcp(float v) { float r; asm("rcp.approx.ftz.f32 %0, %1;" : "=f"(r) : "f"(v)); return r; }
__device__ __forceinline__ float rsq(float v) { float r; asm("rsqrt.approx.ftz.f32 %0, %1;" : "=f"(r) : "f"(v)); return r; }
__device__ __forceinline__ float gelu2(float u) {
    float z = u * fmaf(u * u, 0.044715f * 0.7978845608028654f, 0.7978845608028654f), t;
    asm("tanh.approx.f32 %0, %1;" : "=f"(t) : "f"(z));
    return fmaf(u, t, u);
}
__device__ __forceinline__ float oct_sum(float v) {
    v += __shfl_xor_sync(~0u, v, 4); v += __shfl_xor_sync(~0u, v, 8); v += __shfl_xor_sync(~0u, v, 16);
    return v;
}

template <int TA, int TB, uint32_t HA, uint32_t HB>
__device__ __forceinline__ void wgmma_n112(float (&d)[56], uint32_t da, uint32_t db, int accumulate) {
    asm volatile("{\n.reg .pred p;\n.reg .b64 a, b;\nmov.b64 a, {%56, %61};\nmov.b64 b, {%57, %62};\nsetp.ne.b32 p, %58, 0;\n"
        "wgmma.mma_async.sync.aligned.m64n112k16.f32.bf16.bf16 {"
        "%0, %1, %2, %3, %4, %5, %6, %7, %8, %9, %10, %11, %12, %13, %14, %15, "
        "%16, %17, %18, %19, %20, %21, %22, %23, %24, %25, %26, %27, %28, %29, %30, %31, "
        "%32, %33, %34, %35, %36, %37, %38, %39, %40, %41, %42, %43, %44, %45, %46, %47, "
        "%48, %49, %50, %51, %52, %53, %54, %55"
        "}, a, b, p, 1, 1, %59, %60;\n}\n"
        : "+f"(d[0]), "+f"(d[1]), "+f"(d[2]), "+f"(d[3]), "+f"(d[4]), "+f"(d[5]), "+f"(d[6]), "+f"(d[7]),
          "+f"(d[8]), "+f"(d[9]), "+f"(d[10]), "+f"(d[11]), "+f"(d[12]), "+f"(d[13]), "+f"(d[14]), "+f"(d[15]),
          "+f"(d[16]), "+f"(d[17]), "+f"(d[18]), "+f"(d[19]), "+f"(d[20]), "+f"(d[21]), "+f"(d[22]), "+f"(d[23]),
          "+f"(d[24]), "+f"(d[25]), "+f"(d[26]), "+f"(d[27]), "+f"(d[28]), "+f"(d[29]), "+f"(d[30]), "+f"(d[31]),
          "+f"(d[32]), "+f"(d[33]), "+f"(d[34]), "+f"(d[35]), "+f"(d[36]), "+f"(d[37]), "+f"(d[38]), "+f"(d[39]),
          "+f"(d[40]), "+f"(d[41]), "+f"(d[42]), "+f"(d[43]), "+f"(d[44]), "+f"(d[45]), "+f"(d[46]), "+f"(d[47]),
          "+f"(d[48]), "+f"(d[49]), "+f"(d[50]), "+f"(d[51]), "+f"(d[52]), "+f"(d[53]), "+f"(d[54]), "+f"(d[55])
        : "r"(da), "r"(db), "r"(accumulate), "n"(TA), "n"(TB), "n"(HA), "n"(HB));
}

template <int TA, int TB, uint32_t HA, uint32_t HB>
__device__ __forceinline__ void wgmma_n184(float (&d)[92], uint32_t da, uint32_t db, int accumulate) {
    asm volatile("{\n.reg .pred p;\n.reg .b64 a, b;\nmov.b64 a, {%92, %97};\nmov.b64 b, {%93, %98};\nsetp.ne.b32 p, %94, 0;\n"
        "wgmma.mma_async.sync.aligned.m64n184k16.f32.bf16.bf16 {"
        "%0, %1, %2, %3, %4, %5, %6, %7, %8, %9, %10, %11, %12, %13, %14, %15, "
        "%16, %17, %18, %19, %20, %21, %22, %23, %24, %25, %26, %27, %28, %29, %30, %31, "
        "%32, %33, %34, %35, %36, %37, %38, %39, %40, %41, %42, %43, %44, %45, %46, %47, "
        "%48, %49, %50, %51, %52, %53, %54, %55, %56, %57, %58, %59, %60, %61, %62, %63, "
        "%64, %65, %66, %67, %68, %69, %70, %71, %72, %73, %74, %75, %76, %77, %78, %79, "
        "%80, %81, %82, %83, %84, %85, %86, %87, %88, %89, %90, %91"
        "}, a, b, p, 1, 1, %95, %96;\n}\n"
        : "+f"(d[0]), "+f"(d[1]), "+f"(d[2]), "+f"(d[3]), "+f"(d[4]), "+f"(d[5]), "+f"(d[6]), "+f"(d[7]),
          "+f"(d[8]), "+f"(d[9]), "+f"(d[10]), "+f"(d[11]), "+f"(d[12]), "+f"(d[13]), "+f"(d[14]), "+f"(d[15]),
          "+f"(d[16]), "+f"(d[17]), "+f"(d[18]), "+f"(d[19]), "+f"(d[20]), "+f"(d[21]), "+f"(d[22]), "+f"(d[23]),
          "+f"(d[24]), "+f"(d[25]), "+f"(d[26]), "+f"(d[27]), "+f"(d[28]), "+f"(d[29]), "+f"(d[30]), "+f"(d[31]),
          "+f"(d[32]), "+f"(d[33]), "+f"(d[34]), "+f"(d[35]), "+f"(d[36]), "+f"(d[37]), "+f"(d[38]), "+f"(d[39]),
          "+f"(d[40]), "+f"(d[41]), "+f"(d[42]), "+f"(d[43]), "+f"(d[44]), "+f"(d[45]), "+f"(d[46]), "+f"(d[47]),
          "+f"(d[48]), "+f"(d[49]), "+f"(d[50]), "+f"(d[51]), "+f"(d[52]), "+f"(d[53]), "+f"(d[54]), "+f"(d[55]),
          "+f"(d[56]), "+f"(d[57]), "+f"(d[58]), "+f"(d[59]), "+f"(d[60]), "+f"(d[61]), "+f"(d[62]), "+f"(d[63]),
          "+f"(d[64]), "+f"(d[65]), "+f"(d[66]), "+f"(d[67]), "+f"(d[68]), "+f"(d[69]), "+f"(d[70]), "+f"(d[71]),
          "+f"(d[72]), "+f"(d[73]), "+f"(d[74]), "+f"(d[75]), "+f"(d[76]), "+f"(d[77]), "+f"(d[78]), "+f"(d[79]),
          "+f"(d[80]), "+f"(d[81]), "+f"(d[82]), "+f"(d[83]), "+f"(d[84]), "+f"(d[85]), "+f"(d[86]), "+f"(d[87]),
          "+f"(d[88]), "+f"(d[89]), "+f"(d[90]), "+f"(d[91])
        : "r"(da), "r"(db), "r"(accumulate), "n"(TA), "n"(TB), "n"(HA), "n"(HB));
}

struct Ring {
    uint32_t slot, ph;
    __device__ __forceinline__ void next() { if (++slot == NSLOT) { slot = 0; ph ^= 1; } }
};
__device__ __forceinline__ uint32_t xslot(int i) { return __byte_perm(0x04130e0cu, 0x00130e0cu, 0x7770 + i); }
__device__ __forceinline__ uint32_t wslot(int i) { return __byte_perm(0x06001510u, 0x00151009u, 0x7770 + i); }

constexpr uint32_t HI_SW = desc_hi(1024, 1);

struct Mma {
    uint32_t bars, rel;
    bool lead;
    int wg, w;
    Ring r;
    __device__ __forceinline__ void release(uint32_t s) { if (lead) mbar_arrive_remote(rel + B_EMPTY + 8 * s); }
    template <int KIND>
    __device__ __forceinline__ uint32_t run(float (&a)[56], int n, int nrel, int lag, int accumulate, int ts) {
        uint32_t prev = 0;
#pragma unroll 1
        for (int i = 0; i < n; i++) {
            if (lag && i == (wg ? n - lag : -1)) bar_sync(7, 256);
            const uint32_t s = r.slot;
            mbar_wait(bars + B_FULL + 8 * s, r.ph); r.next();
            if (wg == 0) TS0(KIND ? 8 : 2, ts + i);
            const uint32_t dB = s * (SLOT >> 4), dA = dB + wg * 512;
            wg_fence();
#pragma unroll
            for (int k = 0; k < 4; k++) {
                const int acc = k > 0 || accumulate || i > 0;
                if (KIND == 0) wgmma_n112<1, 1, HI_SW, desc_hi(256, 0)>(a, dA + desc_lo(k * 2048, 8192), dB + desc_lo(16384 + k * SLAB, 128), acc);
                if (KIND == 1) wgmma_n112<0, 1, desc_hi(128, 0), HI_SW>(a, dA + desc_lo(k * 2048, k < 3 ? 1024 : 0), dB + desc_lo(16384 + k * 2048, 8192), acc);
                if (KIND == 2) wgmma_n112<1, 1, HI_SW, desc_hi(1024, 0)>(a, dA + desc_lo(k * 2048, 8192), dB + desc_lo(16384 + k * 256, 128), acc);
                if (k == 1) {
                    wg_commit(); wg_wait<1>();
                    if ((uint32_t)(i - 1) < (uint32_t)nrel) release(prev);
                    if (lag && i == (wg ? -1 : n - 1)) bar_arrive(7, 256);
                }
            }
            wg_commit();
            prev = s;
        }
        return prev;
    }
};

__global__ void __cluster_dims__(2, 1, 1) __launch_bounds__(NTHREADS, 1)
fused_kernel(const __nv_bfloat16* __restrict__ x, const __nv_bfloat16* __restrict__ b1, const __nv_bfloat16* __restrict__ b2, __nv_bfloat16* out, Scratch* G,
             const __grid_constant__ Params P) {
    extern __shared__ __align__(1024) uint8_t smem[];
    const uint32_t sbase = (uint32_t)__cvta_generic_to_shared(smem);
    const uint32_t bars = sbase + OFF_BAR;
    const int lane = threadIdx.x & 31;
    const int warp = __shfl_sync(~0u, threadIdx.x >> 5, 0), w = warp & 3;
    const uint32_t rank = blockIdx.x & 1, pr = blockIdx.x >> 1;
    const uint32_t pv = pr < 4 ? pr * 8 + 36 : pr < 40 ? pr - 4 : pr - 3 + (((pr - 40) * 37) >> 8);
    const uint32_t gp = (pv + 4) & 7, hp = pv >> 3;
    const uint32_t tb = gp * 2 + rank, c = hp * 16 + tb, row0 = (tb * 8 + hp) * 16;
    const bool has_g1 = gp > 0;
    const uint32_t nt1 = hp & 3, ft = max((int)gp - 1, 0) * 2 + (hp >> 2);
    const uint32_t nt2 = tb & 3, mt = (gp & 2) * 4 + hp, ks = gp >> 2;

    if (warp < NBAR / 3 && elect()) {
        if (warp == 0) TS(15, 0);
#pragma unroll
        for (int i = 0; i < 3; i++) mbar_init(bars + warp * 24 + 8 * i, 1u << ((0xaaad4000u >> (2 * max(warp * 3 + i - 12, 0)) & 3) | (warp == 9 ? 2 : 0)));
        asm volatile("fence.mbarrier_init.release.cluster;" ::: "memory");
        if (warp == B_ROW / 24) {
            mbar_expect(bars + B_ROW, TILEB);
            bulk_load(sbase + OFF_Y, x + row0 * D_, TILEB, bars + B_ROW);
        }
    }
    __syncwarp();
    asm volatile("barrier.cluster.arrive.relaxed.aligned;\nbarrier.cluster.wait.aligned;" ::: "memory");

    if (warp == 8) {
        if (elect()) {
            uint32_t spins = (sbase & 0xffffffu) == SMEM0 ? 0 : SPIN_LIMIT;
            uint32_t kw = gp * 64, kx = kw;
            uint32_t due = (uint32_t)clock();
#pragma unroll 1
            for (int i = 0; i < 8; i++) {
                if (i >= 5) mbar_wait_bounded(bars + B_QEMPTY + 8 * (i - 5), 0, spins);
                else { while ((int)((uint32_t)clock() - due) < 0) {} due += PACE; }
                if (kw == D_) kw = 0;
                if (i < 4) kx = kw;
                const int ix = i - (i > 4);
                if (i < 7) mbar_expect(bars + B_QFULL + 8 * i, QSLOT);
                if (i != 4) tma3d(sbase + xslot(ix) * 8192, &P.tmX, bars + B_QFULL + 8 * ix, kx, tb * 64, 0);
                if (i == 5) mbar_wait_bounded(bars + B_CS, 0, spins);
                if (i < 7) tma3d_pair(sbase + wslot(i) * 8192 + rank * 12288, &P.tmWqkv, bars + B_QFULL + 8 * i, (hp * 56) & ~15, kw + rank * 32, 0);
                kx = kw; kw += 64;
                if (i == 0) TS(1, 23);
            }
            mbar_expect(bars + B_X, HALF); mbar_expect(bars + B_X + 8, HALF);
            Ring r{0, 0};
#pragma unroll 1
            for (int j = has_g1 ? 0 : 16; j < 34; j++) {
                const uint32_t dst = sbase + r.slot * SLOT, full = bars + B_FULL + 8 * r.slot;
                mbar_wait_bounded(bars + B_EMPTY + 8 * r.slot, r.ph, spins);
                if (j < 20 || j >= 26) mbar_expect(full, 16384 + TILEB);
                if (j < 16) {
                    tma3d(dst, &P.tmW1, full, 0, rank * 1024 + j * 64, ft * 2);
                } else if (j < 20) {
                    tma3d(dst + 16384, &P.tmWo, full, nt2 * 112, 0, ks * 4 + j - 16);
                    tma3d(dst + 24576, &P.tmWo, full, nt2 * 112 + 64, 0, ks * 4 + j - 16);
                } else {
                    tma2d_pair(dst + rank * 8192, &P.tmW2, full, mt * 128 + rank * 64, ks * 896 + j * 128 - (j < 27 ? 2560 : 3392));
                }
                r.next();
            }
            mbar_wait_bounded(bars + B_END, 0, spins);
        }
    } else if (warp > 8) {
        uint32_t ep = ld_relaxed(&G->epoch[c]);
        float* cs;
        {
            uint32_t src = sbase + 16 * 8192 - 4096 + rank * 12288 + w * 4096 + lane * 4;
            float s0 = 0.f, s1 = 0.f, s2 = 0.f, s3 = 0.f;
            mbar_wait(bars + B_QFULL, 0);
#pragma unroll 1
            for (int i = 0; i < 2; i++) {
                uint32_t v[16];
#pragma unroll
                for (int k = 0; k < 16; k++) v[k] = __float_as_uint(lds1f((src ^ ((k & 7) * 144)) + (k >> 3) * 1024));
#pragma unroll
                for (int k = 0; k < 16; k += 2) { s0 += bf_lo(v[k]); s1 += bf_hi(v[k]); s2 += bf_lo(v[k + 1]); s3 += bf_hi(v[k + 1]); }
                src += 2048;
            }
            cs = G->colsum[ep & 1][hp];
            if (tb < 14) asm volatile("red.relaxed.gpu.global.add.v2.f32 [%0], {%1, %2};" ::"l"(cs + w * 64 - 64 + lane * 2), "f"(s0 + s2), "f"(s1 + s3) : "memory");
            if (tb == 15) *(float2*)(G->colsum[~ep & 1][hp] + w * 64 - 64 + lane * 2) = make_float2(0.f, 0.f);
            ep++;
            if (w == 1) TS(1, 24);
            if (w == 2) {
                bar_sync(6, 224);
                if (elect()) { mbar_arrive(bars + B_CS); signal(&G->flagH[c >> 2]); TS(1, 3); }
                __syncwarp();
            } else {
                bar_arrive(6, 224);
            }
        }
        if (w == 1) {
            wait_flag(&G->flagH[lane], 4 * ep);
            __syncwarp();
            if (elect()) {
                TS(1, 16);
                asm volatile("st.shared.u32 [%0], %1;" ::"r"(bars + 8 * NBAR), "r"(ep) : "memory");
                mbar_expect(bars + B_REC, 1152 + 768);
                bulk_load(sbase + OFF_CS, cs, 768, bars + B_REC);
                bulk_load(sbase + OFF_ST, G->stat + tb * 128, 1152, bars + B_REC);
                Ring r{0, 0};
                const uint8_t* src = G->H[nt1][rank * 16];
#pragma unroll 1
                for (int j = has_g1 ? 0 : 16; j < 34; j++) {
                    if (j == 20) {
                        if (has_g1) { mbar_wait(bars + B_UDONE, 0); signal(G->flag[nt1 * 2 + (ft >= 7)]); TS(4, 8); }
                        j += NSLOT; r.ph ^= 1;
                    }
                    if (j == 16 || j == 26) {
                        src = j == 16 ? G->O[mt][ks * 4] + rank * HALF : G->U[nt2][ks * 14 + 6];
                        wait_flag(G->flag[j == 16 ? 16 + mt : nt2 * 2 + ks], (j == 16 ? 8 : 14) * ep);
                        TS(4, j == 16 ? 18 : j);
                        mbar_wait(bars + B_CS, j == 26);
                    }
                    const uint32_t dst = sbase + r.slot * SLOT, full = bars + B_FULL + 8 * r.slot;
                    mbar_wait(bars + B_EMPTY + 8 * r.slot, r.ph);
                    if ((j >> 2) == 4) bulk_load_pair(dst + rank * 8192, src, HALF, full);
                    else bulk_load(dst + 16384, src, TILEB, full);
                    src += TILEB;
                    r.next();
                }
                G->epoch[c] = ep;
            }
        } else {
            Ring r{has_g1 ? 20u % NSLOT : 4u, has_g1};
            const uint8_t* src = G->U[nt2][ks * 14];
            if (w == 2) {
                bar_sync(3, 288);
                __nanosleep(HALO_NS);
                uint4 v[7];
                uint32_t bad;
                do {
                    bad = 0;
#pragma unroll
                    for (int i = 0; i < 7; i++) { v[i] = ld_relaxed4(G->halo[c - (tb > 0)] + i * 512 + lane * 16); bad = or_diff(bad, v[i].x, ep); }
                } while (bad & 1);
#pragma unroll
                for (int i = 0; i < 7; i++) sts4(sbase + OFF_X + i * 512 + lane * 16, v[i]);
                __syncwarp();
                if (elect()) { mbar_arrive(bars + B_HALO); TS(2, 21); }
                uint32_t ph = 1;
#pragma unroll 1
                for (int i = 0; i < NSLOT;) {
                    const uint32_t dst = sbase + r.slot * SLOT + 16384;
                    mbar_wait(bars + B_QFULL + 8 * i, ph);
                    TS(4, 86 + i);
                    bad = 0;
#pragma unroll
                    for (int k = 0; k < 14; k++) bad = or_diff(bad, __float_as_uint(lds1f(dst + k * 1024 + lane * 32 + (lane >> 2) * 4)), ep);
                    if (__any_sync(~0u, bad & 1)) {
                        if (elect()) {
                            fence_async_shared();
                            mbar_expect(bars + B_QFULL + 8 * i, TILEB);
                            bulk_load(dst, src, TILEB, bars + B_QFULL + 8 * i);
                        }
                        ph ^= 1;
                        TS(4, 84);
                    } else {
                        if (elect()) mbar_expect(bars + B_FULL + 8 * r.slot, 16384);
                        ph = 1; i++; src += TILEB; r.next();
                    }
                }
            } else {
                bar_sync(2, 288);
                if (elect()) bulk_store(out + row0 * D_, sbase + OFF_Y, TILEB);
                __syncwarp();
                bar_sync(4, 288);
                if (elect()) {
                    bulk_store(G->O[tb][hp], sbase + OFF_X, TILEB);
                    bulk_flush();
                    mbar_arrive_remote(mapa(bars + B_FREE, rank ^ 1));
                    mbar_arrive(bars + B_FREE);
                    signal(G->flag[16 + tb]);
                    TS(2, 22);
                }
                __syncwarp();
                uint32_t late = ~0u;
#pragma unroll 1
                for (int i = 0; i < NSLOT; i++) {
                    while ((late >> i) & 1) late = __ballot_sync(~0u, ld_relaxed(G->flag[8 + nt2 * 2 + ks] + lane) != 8 * ep);
                    if (i == 0) { TS(4, 17); mbar_wait(bars + (has_g1 ? B_UDONE : B_FREE), 0); }
                    mbar_wait(bars + B_EMPTY + 8 * r.slot, r.ph);
                    if (elect()) {
                        mbar_expect(bars + B_QFULL + 8 * i, TILEB);
                        bulk_load(sbase + r.slot * SLOT + 16384, src, TILEB, bars + B_QFULL + 8 * i);
                    }
                    src += TILEB; r.next();
                }
                if (elect()) mbar_arrive(bars + B_CS);
            }
        }
    } else {
        const int wg = warp >> 2;
        Mma M{bars, mapa(bars, rank ^ (lane & 1)), (threadIdx.x & 127) < 2, wg, w, Ring{0, 0}};
        const int r = lane >> 2, t = lane & 3;
        uint32_t ep;
        const uint32_t bias0 = ld_u16(b1 + ft * 128 + warp * 16 + r), bias1 = ld_u16(b1 + ft * 128 + warp * 16 + r + 8);
        if (wg == 1) {
            const int r16 = w * 4 + t, c8 = (r + 2 * t) & 7;
            const uint32_t row = sbase + OFF_Y + r16 * (2 * D_) + c8 * 16;
            mbar_wait(bars + B_ROW, 0);
            TS0(1, 67);
            float f[56];
#pragma unroll
            for (int i = 0; i < 7; i++) {
                const uint4 v = lds4(row + i * 128);
                f[8 * i] = bf_lo(v.x); f[8 * i + 1] = bf_hi(v.x); f[8 * i + 2] = bf_lo(v.y); f[8 * i + 3] = bf_hi(v.y);
                f[8 * i + 4] = bf_lo(v.z); f[8 * i + 5] = bf_hi(v.z); f[8 * i + 6] = bf_lo(v.w); f[8 * i + 7] = bf_hi(v.w);
            }
            float s0 = f[0], s1 = f[1], s2 = f[2], s3 = f[3];
#pragma unroll
            for (int i = 4; i < 56; i += 4) { s0 += f[i]; s1 += f[i + 1]; s2 += f[i + 2]; s3 += f[i + 3]; }
            const float nmean = oct_sum((s0 + s1) + (s2 + s3)) * (-1.f / D_);
            s0 = s1 = s2 = s3 = 0.f;
#pragma unroll
            for (int i = 0; i < 56; i += 4) {
                f[i] += nmean; f[i + 1] += nmean; f[i + 2] += nmean; f[i + 3] += nmean;
                s0 = fmaf(f[i], f[i], s0); s1 = fmaf(f[i + 1], f[i + 1], s1); s2 = fmaf(f[i + 2], f[i + 2], s2); s3 = fmaf(f[i + 3], f[i + 3], s3);
            }
            const float var = oct_sum((s0 + s1) + (s2 + s3)) * (1.f / D_);
            const float rstd = rsq(var + LN_EPS);
            const float sc = rstd * rsq(fmaf(var * rstd, rstd, LN_EPS));
            if (lane < 4) G->stat[16 + row0 + r16] = make_float2(rstd + rstd, nmean);
            uint8_t* hb = G->H[0][0] + row0 * (SLAB / 16) + r16 * 16 + c8 * 256;
            const int sw = tb < 8 ? 0 : 7 * 256;
#pragma unroll
            for (int i = 0; i < 7; i++) {
                const int lo = (8 * i) % 14, nt = (8 * i) / 14, next = 32 * TILEB - SLAB;
                const int off = lo < 7 ? (c8 < 7 - lo ? sw : -sw) : (c8 >= 14 - lo ? sw + next : -sw);
                *(uint4*)(hb + off + i * 2048 + nt * next) = make_uint4(pack2(f[8 * i] * sc, f[8 * i + 1] * sc), pack2(f[8 * i + 2] * sc, f[8 * i + 3] * sc),
                                                                        pack2(f[8 * i + 4] * sc, f[8 * i + 5] * sc), pack2(f[8 * i + 6] * sc, f[8 * i + 7] * sc));
            }
            TS0(1, 25);
            bar_arrive(6, 224);
        }
        const uint32_t kv = sbase + OFF_X + (w * 2 + wg) * KV + lane * 16;
        const uint32_t st = sbase + OFF_ST + (16 + w * 32 + wg) * 8;
        uint32_t q[7][2], k0[7], v0[7];
        {
            float acc[92];
#pragma unroll 1
            for (int kb = 0; kb < 7; kb++) {
                const bool held = kb == (wg ? 5 : -1);
                if (held) { wg_wait<0>(); if (M.lead) mbar_arrive_remote(M.rel + B_QEMPTY + 8 * 4); bar_sync(7, 256); }
                mbar_wait(bars + B_QFULL + 8 * kb, 0);
                TS0(1, 68 + wg * 7 + kb);
                const uint32_t dA = (xslot(kb) + wg) * 512, dB = wslot(kb) * 512 + (hp & 1);
                wg_fence();
#pragma unroll
                for (int k = 0; k < 4; k++) {
                    wgmma_n184<0, 1, HI_SW, HI_SW>(acc, dA + desc_lo(k * 32, 16), dB + desc_lo((k & 1) * 2048 + (k >> 1) * 12288, 4096), k > 0 || kb > 0);
                    if (k == 0) { wg_commit(); wg_wait<1>(); if (M.lead && kb > 0 && !held) mbar_arrive_remote(M.rel + B_QEMPTY + 8 * (kb - 1)); }
                }
                wg_commit();
            }
            if (wg == 0) bar_arrive(7, 256);
            mbar_wait(bars + B_REC, 0);
            ep = __float_as_uint(lds1f(bars + 8 * NBAR));
            const float n0 = lds1f(st + r * 16 + 4), n1 = lds1f(st + r * 16 + 132);
            const uint32_t csa = sbase + OFF_CS + t * 8 + (hp & 1) * 32;
            wg_wait<0>();
            pin(acc);
            M.release(4); M.release(5);
            TS0(1, 4 + 7 * wg);
            uint32_t hi[14];
#pragma unroll
            for (int p = 2; p >= 0; p--) {
#pragma unroll
                for (int g = 0; g < 7; g++) {
                    const uint2 cs = lds2(csa + (p * 8 + g) * 32);
                    const int a = (p * 8 + g) * 4;
                    const float c0 = __uint_as_float(cs.x), c1 = __uint_as_float(cs.y);
                    const uint32_t lo2 = pack2(fmaf(n0, c0, acc[a]), fmaf(n0, c1, acc[a + 1])), hi2 = pack2(fmaf(n1, c0, acc[a + 2]), fmaf(n1, c1, acc[a + 3]));
                    if (p == 0) { q[g][0] = lo2; q[g][1] = hi2; } else { (p == 1 ? k0 : v0)[g] = lo2; hi[(p - 1) * 7 + g] = hi2; }
                }
                if (p == 1) {
#pragma unroll
                    for (int i = 0; i < 3; i++) stsm4(kv + 2 * KV + i * 512, hi[4 * i], hi[4 * i + 1], hi[4 * i + 2], hi[4 * i + 3]);
                    stsm2(kv + 2 * KV + 1536, hi[12], hi[13]);
                    if (w == 3) {
#pragma unroll
                        for (int i = 0; i < 14; i++) stg1(G->halo[c] + wg * KV + lane * 4 + i * 128, tag(hi[i], t == 0, ep));
                    }
                    bar_arrive(3, 288);
                }
            }
        }
        TS0(1, 9 + 11 * wg);
        float a[56];
#pragma unroll
        for (int i = 0; i < 56; i++) asm volatile("" : "=f"(a[i]));
        const int n1 = PAUSE + (wg == 0 ? LEAD : 0);
        uint32_t last = M.run<0>(a, has_g1 ? n1 : 0, 16, 0, 0, 32);
        {
            uint32_t kp[8], k1[8], vp[8], v1[8];
            mbar_wait(bars + B_HALO, 0);
            ldsm4(kp, kv); ldsm4(kp + 4, kv + 512); ldsm4(k1, kv + 2 * KV); ldsm4(k1 + 4, kv + 2 * KV + 512);
            ldsm4t(vp, kv + 896); ldsm4t(vp + 4, kv + 1408); ldsm4t(v1, kv + 2 * KV + 896); ldsm4t(v1 + 4, kv + 2 * KV + 1408);
#pragma unroll
            for (int g = 0; g < 7; g++) v0[g] = transpose8(v0[g]);
            const bool e0 = 2 * t > r, e1 = 2 * t >= r;
            const uint32_t ka = st + t * 32 - (e0 ? 128 : 0), kb = st + t * 32 + 16 - (e1 ? 128 : 0);
            const float rk[4] = {lds1f(ka), lds1f(kb), lds1f(ka + 128), lds1f(kb + 128)};
            const float sq0 = lds1f(st + r * 16) * (0.25f * 0.1889822365046136f * 1.4426950408889634f), sq1 = lds1f(st + r * 16 + 128) * (0.25f * 0.1889822365046136f * 1.4426950408889634f);
            float sc[6] = {sq0 * rk[0], sq0 * rk[1], sq1 * rk[2], sq1 * rk[3], 0.f, 0.f};
            if (tb == 0 && w == 0) { sc[4] = e0 ? -1e30f : 0.f; sc[5] = e1 ? -1e30f : 0.f; }
            uint32_t mk[6] = {(e0 ? 0xffffu : 0u) | (e1 ? 0xffff0000u : 0u), 0u, t < 2 ? q[3][0] : 0u, t < 2 ? q[3][1] : 0u, t < 2 ? 0u : q[3][0], t < 2 ? 0u : q[3][1]};
            wg_wait<0>();
            pin(a);
            if (has_g1) M.release(last);
            bar_sync(2, 288);
            mbar_wait(bars + B_HALO, 0);
            TS0(2, 12 + 16 * wg);
            float sv[2][4];
#pragma unroll
            for (int h = 0; h < 2; h++) {
                const int ga = h * 4, gb = h * 4 + 1, gc = h * 4 + 2;
                float s[3][4] = {};
                mma16(s[0], q[ga][0], q[ga][1], q[gb][0], q[gb][1], kp[ga], kp[gb]);
                mma16(s[1], q[ga][0], q[ga][1], q[gb][0], q[gb][1], k0[ga], k0[gb]);
                mma16(s[2], q[ga][0], q[ga][1], q[gb][0], q[gb][1], k1[ga], k1[gb]);
                mma16(s[0], q[gc][0], q[gc][1], mk[2 + 2 * h], mk[3 + 2 * h], kp[gc], kp[3]);
                mma16(s[1], q[gc][0], q[gc][1], mk[2 + 2 * h], mk[3 + 2 * h], k0[gc], k0[3]);
                mma16(s[2], q[gc][0], q[gc][1], mk[2 + 2 * h], mk[3 + 2 * h], k1[gc], k1[3]);
                sv[h][0] = fmaf(e0 ? s[0][0] : s[1][0], sc[0], sc[4]);
                sv[h][1] = fmaf(e1 ? s[0][1] : s[1][1], sc[1], sc[5]);
                sv[h][2] = (e0 ? s[1][2] : s[2][2]) * sc[2];
                sv[h][3] = (e1 ? s[1][3] : s[2][3]) * sc[3];
            }
            uint32_t pp[2][2];
#pragma unroll
            for (int i = 0; i < 4; i++) {
                float* v = &sv[i >> 1][(i & 1) * 2];
                const float m = quad_max(fmaxf(v[0], v[1]));
                const float p0 = ex2(v[0] - m), p1 = ex2(v[1] - m);
                const float inv = rcp(quad_sum(p0 + p1));
                pp[i >> 1][i & 1] = pack2(p0 * rk[(i & 1) * 2] * inv, p1 * rk[(i & 1) * 2 + 1] * inv);
            }
            uint32_t o[8][2];
#pragma unroll
            for (int i = 0; i < 8; i++) {
                const int h = i >> 2, g = i - h;
                float d[4] = {};
                mma16(d, pp[h][0] & mk[0], 0u, pp[h][0] & ~mk[0], pp[h][1] & mk[0], vp[g], v0[g]);
                mma8(d, 0u, pp[h][1] & ~mk[0], v1[g]);
                o[i][0] = pack2(d[0], d[1]); o[i][1] = pack2(d[2], d[3]);
            }
            if (t >= 2) { o[3][0] = o[4][0]; o[3][1] = o[4][1]; }
            const uint32_t dst = sbase + OFF_X + (w >> 1) * HALF + ((w & 1) * 32 + (lane & 15) * 2 + wg) * 16 + (lane >> 4) * 1024;
            stsm4(dst, o[0][0], o[0][1], o[1][0], o[1][1]);
            stsm4(dst + 2048, o[2][0], o[2][1], o[3][0], o[3][1]);
            stsm4(dst + 4096, o[5][0], o[5][1], o[6][0], o[6][1]);
            stsm2(dst + 6144, o[7][0], o[7][1]);
            fence_async_shared();
            bar_sync(4, 288);
            TS0(2, 10 + 19 * wg);
        }
        if (has_g1) {
            last = M.run<0>(a, 16 - n1, 16, LAG1, 1, 32 + PAUSE + LEAD);
            mbar_wait_cluster(bars + B_FREE, 0);
            const uint32_t xb = sbase + OFF_X + wg * 8192 + (threadIdx.x & 127) * 16;
            const uint32_t rx = mapa(xb, rank ^ 1), rbar = mapa(bars + B_X + 8 * wg, rank ^ 1);
            wg_wait<0>();
            pin(a);
            M.release(last);
            TS0(4, 5 + wg);
#pragma unroll
            for (int i = 0; i < 3; i++)
                st_async4(rx + i * 2048, rbar, pack2(a[28 + 8 * i], a[29 + 8 * i]), pack2(a[30 + 8 * i], a[31 + 8 * i]), pack2(a[32 + 8 * i], a[33 + 8 * i]), pack2(a[34 + 8 * i], a[35 + 8 * i]));
            st_async2(rx + 6144, rbar, pack2(a[52], a[53]), pack2(a[54], a[55]));
#pragma unroll
            for (int i = 0; i < 28; i++) a[i] += bf_lo((i & 2) ? bias1 : bias0);
            mbar_wait_cluster(bars + B_X + 8 * wg, 0);
            TS0(4, 1 + wg);
            uint32_t u[16];
#pragma unroll
            for (int i = 0; i < 4; i++) { const uint4 v = lds4(xb + i * 2048); u[4 * i] = v.x; u[4 * i + 1] = v.y; u[4 * i + 2] = v.z; u[4 * i + 3] = v.w; }
            uint8_t* dst = G->U[nt1][((ft >= 7) + wg) * 7 + ft] + rank * HALF + w * 256 + lane * 4;
#pragma unroll
            for (int i = 0; i < 14; i++)
                stg1(dst + (i >> 1) * 1024 + (i & 1) * 128, tag(pack2(gelu2(a[2 * i] + bf_lo(u[i])), gelu2(a[2 * i + 1] + bf_hi(u[i]))), (lane & 7) == warp * 2 + (i & 1), ep));
            __syncwarp();
            if (lane == 0) {
                if (wg == 0) asm volatile("red.relaxed.gpu.global.add.u32 [%0], 1;" ::"l"(G->flag[8 + nt1 * 2] + ft + (ft >= 7) * 25) : "memory");
                mbar_arrive(bars + B_UDONE);
            }
            TS0(4, 30 + wg);
        }
        uint32_t c0 = ld_u16(b2 + mt * 128 + warp * 16 + r), c1 = ld_u16(b2 + mt * 128 + warp * 16 + r + 8);
        last = M.run<1>(a, 4, 4, 0, 0, 48);
        wg_wait<0>();
        M.release(last);
        if (wg == 1) TS0(4, 13);
        c0 *= ks == 0 ? 0x10001u : 0u; c1 *= ks == 0 ? 0x10001u : 0u;
        M.run<2>(a, 14, 14 - NSLOT, LAG2, 1, 52);
        mbar_wait(bars + B_FREE, 0);
        const uint32_t stg = sbase + OFF_X + wg * (OFF_Y - OFF_X) + w * SLAB;
        const uint32_t sa = stg + (lane & 15) * 224 + (lane >> 4) * 16;
        wg_wait<0>();
        pin(a);
        TS0(8, 14 + wg);
#pragma unroll
        for (int g = 0; g < 7; g++)
            stsm4(sa + g * 32, half_plus(pack2(a[8 * g], a[8 * g + 1]), c0), half_plus(pack2(a[8 * g + 2], a[8 * g + 3]), c1),
                  half_plus(pack2(a[8 * g + 4], a[8 * g + 5]), c0), half_plus(pack2(a[8 * g + 6], a[8 * g + 7]), c1));
        fence_async_shared();
        __syncwarp();
        if (elect()) {
            asm volatile("cp.reduce.async.bulk.tensor.2d.global.shared::cta.add.tile.bulk_group [%0, {%2, %3}], [%1];\ncp.async.bulk.commit_group;" ::"l"(&P.tmOut), "r"(stg), "r"(nt2 * 112), "r"(mt * 128 + warp * 16) : "memory");
            if (w == 0) mbar_arrive(bars + B_END);
            asm volatile("cp.async.bulk.wait_group.read 0;" ::: "memory");
        }
        if (wg == 1) TS0(15, 19);
        TSDUMP();
    }
}

typedef CUresult (*EncodeFn)(CUtensorMap*, CUtensorMapDataType, cuuint32_t, void*, const cuuint64_t*, const cuuint64_t*, const cuuint32_t*, const cuuint32_t*,
                             CUtensorMapInterleave, CUtensorMapSwizzle, CUtensorMapL2promotion, CUtensorMapFloatOOBfill);

void make_map(EncodeFn enc, CUtensorMap* tm, const void* base, bool swizzle, int d0, int d1, int d2, int s1, int s2, int b0, int b1, int b2) {
    const cuuint64_t dims[3] = {(cuuint64_t)d0, (cuuint64_t)d1, (cuuint64_t)d2}, strides[2] = {(cuuint64_t)s1 * 2, (cuuint64_t)s2 * 2};
    const cuuint32_t box[3] = {(cuuint32_t)b0, (cuuint32_t)b1, (cuuint32_t)b2}, es[3] = {1, 1, 1};
    enc(tm, CU_TENSOR_MAP_DATA_TYPE_BFLOAT16, d2 ? 3 : 2, (void*)base, dims, strides, box, es, CU_TENSOR_MAP_INTERLEAVE_NONE,
        swizzle ? CU_TENSOR_MAP_SWIZZLE_128B : CU_TENSOR_MAP_SWIZZLE_NONE, CU_TENSOR_MAP_L2_PROMOTION_L2_128B, CU_TENSOR_MAP_FLOAT_OOB_FILL_NONE);
}

}

extern "C" void kernel_launch(void* const* d_in, const int* in_sizes, int n_in, void* d_out, int out_size) {
    static EncodeFn enc = nullptr;
    static Scratch* scratch = nullptr;
    if (!enc) {
        void* fn = nullptr;
        cudaDriverEntryPointQueryResult qr;
        cudaGetDriverEntryPoint("cuTensorMapEncodeTiled", &fn, cudaEnableDefault, &qr);
        enc = (EncodeFn)fn;
        cudaGetSymbolAddress((void**)&scratch, g_s);
        cudaFuncSetAttribute(fused_kernel, cudaFuncAttributeMaxDynamicSharedMemorySize, SMEM_BYTES);
    }
    Params P;
    const __nv_bfloat16* x = (const __nv_bfloat16*)d_in[0];
    make_map(enc, &P.tmX, x, true, D_, S_ / 2, 2, 2 * D_, D_, 64, 64, 2);
    make_map(enc, &P.tmWqkv, d_in[1], true, D_, D_, 3, 3 * D_, D_, 64, 32, 3);
    make_map(enc, &P.tmW1, d_in[4], true, 64, S_, F_ / 64, F_, 64, 64, 64, 2);
    make_map(enc, &P.tmW2, d_in[6], true, S_, F_, 0, S_, 0, 64, 64, 1);
    make_map(enc, &P.tmWo, d_in[2], true, D_, 56, 8, D_, 56 * D_, 64, 64, 1);
    make_map(enc, &P.tmOut, d_out, false, D_, S_, 0, D_, 0, 112, 16, 1);
    fused_kernel<<<NCTA, NTHREADS, SMEM_BYTES, cudaStreamPerThread>>>(x, (const __nv_bfloat16*)d_in[5], (const __nv_bfloat16*)d_in[7], (__nv_bfloat16*)d_out, scratch, P);
}
```

```cpp
#include <cuda_runtime.h>
#include <cuda_bf16.h>
#include <cuda.h>
#include <stdint.h>

#define POLL_SLEEP
#define HALO_NS 300
#define PACE 800
#define PAUSE 7
#define LEAD 0
#define LAG1 4
#define LAG2 5

namespace {

constexpr int S_ = 2048, D_ = 448, F_ = 1792;
constexpr int NCTA = 128, NTHREADS = 384;
constexpr int NSLOT = 6, SLOT = 32768, QSLOT = 40960, TILEB = 14336, SLAB = 3584, HALF = 7168;
constexpr int KV = 1792;
constexpr int OFF_X = NSLOT * SLOT;
constexpr int OFF_Y = OFF_X + 10 * KV;
constexpr int OFF_CS = OFF_Y + TILEB;
constexpr int OFF_ST = OFF_CS + 768;
constexpr int OFF_BAR = OFF_ST + 1152;
constexpr int SMEM_BYTES = OFF_BAR + 1024;
constexpr uint32_t SMEM0 = 1024;
constexpr int B_QFULL = 0, B_FULL = 56, B_REC = 104, B_ROW = 112, B_X = 120, B_CS = 136, B_HALO = 144, B_FREE = 152, B_END = 160, B_UDONE = 168, B_QEMPTY = 176, B_EMPTY = 192, NBAR = 30;
constexpr float LN_EPS = 1e-5f;
constexpr int SPIN_LIMIT = 1 << 22;

struct Scratch {
    uint8_t H[4][32][TILEB];
    uint8_t U[4][28][TILEB];
    uint8_t O[16][8][TILEB];
    uint8_t Wo[4][8][TILEB];
    uint8_t halo[NCTA][2 * KV];
    float2 stat[16 + S_];
    float colsum[2][8][192];
    uint32_t flagH[32];
    uint32_t flag[32][32];
    uint32_t epoch[NCTA];
};
__device__ __align__(1024) Scratch g_s;

#define TS(g, i)
#define TS0(g, i)
#define TSDUMP()

struct Params {
    CUtensorMap tmX, tmWqkv, tmW1, tmW2, tmOut;
};

__device__ __forceinline__ bool elect() {
    uint32_t p;
    asm volatile("{\n.reg .pred p;\nelect.sync _|p, 0xffffffff;\nselp.u32 %0, 1, 0, p;\n}" : "=r"(p));
    return p;
}
__device__ __forceinline__ void mbar_init(uint32_t b, uint32_t c) { asm volatile("mbarrier.init.shared::cta.b64 [%0], %1;" ::"r"(b), "r"(c) : "memory"); }
__device__ __forceinline__ void mbar_expect(uint32_t b, uint32_t tx) { asm volatile("mbarrier.arrive.expect_tx.shared::cta.b64 _, [%0], %1;" ::"r"(b), "r"(tx) : "memory"); }
__device__ __forceinline__ void mbar_arrive(uint32_t b) { asm volatile("mbarrier.arrive.shared::cta.b64 _, [%0];" ::"r"(b) : "memory"); }
__device__ __forceinline__ void mbar_arrive_remote(uint32_t b) { asm volatile("mbarrier.arrive.shared::cluster.b64 _, [%0];" ::"r"(b) : "memory"); }
#define MBAR_WAIT_ASM(SEM) \
    asm volatile("{\n.reg .pred p;\nWAIT:\nmbarrier.try_wait.parity" SEM ".shared::cta.b64 p, [%0], %1;\n@!p bra WAIT;\n}" ::"r"(b), "r"(parity) : "memory")
__device__ __forceinline__ void mbar_wait(uint32_t b, uint32_t parity) { MBAR_WAIT_ASM(""); }
__device__ __forceinline__ void mbar_wait_cluster(uint32_t b, uint32_t parity) { MBAR_WAIT_ASM(".acquire.cluster"); }
__device__ __forceinline__ void mbar_wait_bounded(uint32_t b, uint32_t parity, uint32_t& n) {
    asm volatile("{\n.reg .pred p;\nWAIT:\nadd.u32 %0, %0, 1;\nsetp.gt.u32 p, %0, %3;\n@p st.global.u32 [%4], %0;\n"
                 "mbarrier.try_wait.parity.shared::cta.b64 p, [%1], %2;\n@!p bra WAIT;\n}" : "+r"(n) : "r"(b), "r"(parity), "n"(SPIN_LIMIT), "l"(0ull) : "memory");
}
__device__ __forceinline__ uint32_t mapa(uint32_t a, uint32_t rank) { uint32_t r; asm("mapa.shared::cluster.u32 %0, %1, %2;" : "=r"(r) : "r"(a), "r"(rank)); return r; }
__device__ __forceinline__ void tma3d(uint32_t dst, const CUtensorMap* tm, uint32_t bar, int c0, int c1, int c2) {
    asm volatile("cp.async.bulk.tensor.3d.shared::cluster.global.mbarrier::complete_tx::bytes [%0], [%1, {%3, %4, %5}], [%2];" ::"r"(dst), "l"(tm), "r"(bar), "r"(c0), "r"(c1), "r"(c2) : "memory");
}
__device__ __forceinline__ void tma2d_pair(uint32_t dst, const CUtensorMap* tm, uint32_t bar, int c0, int c1) {
    asm volatile("cp.async.bulk.tensor.2d.shared::cluster.global.mbarrier::complete_tx::bytes.multicast::cluster [%0], [%1, {%3, %4}], [%2], %5;" ::"r"(dst), "l"(tm), "r"(bar), "r"(c0), "r"(c1), "h"((uint16_t)3) : "memory");
}
__device__ __forceinline__ void tma3d_pair(uint32_t dst, const CUtensorMap* tm, uint32_t bar, int c0, int c1, int c2) {
    asm volatile("cp.async.bulk.tensor.3d.shared::cluster.global.mbarrier::complete_tx::bytes.multicast::cluster [%0], [%1, {%3, %4, %5}], [%2], %6;" ::"r"(dst), "l"(tm), "r"(bar), "r"(c0), "r"(c1), "r"(c2), "h"((uint16_t)3) : "memory");
}
__device__ __forceinline__ void bulk_load(uint32_t dst, const void* src, uint32_t bytes, uint32_t bar) {
    asm volatile("cp.async.bulk.shared::cluster.global.mbarrier::complete_tx::bytes [%0], [%1], %2, [%3];" ::"r"(dst), "l"(src), "r"(bytes), "r"(bar) : "memory");
}
__device__ __forceinline__ void bulk_load_pair(uint32_t dst, const void* src, uint32_t bytes, uint32_t bar) {
    asm volatile("cp.async.bulk.shared::cluster.global.mbarrier::complete_tx::bytes.multicast::cluster [%0], [%1], %2, [%3], %4;" ::"r"(dst), "l"(src), "r"(bytes), "r"(bar), "h"((uint16_t)3) : "memory");
}
__device__ __forceinline__ void bulk_store(void* dst, uint32_t src, uint32_t bytes) {
    asm volatile("cp.async.bulk.global.shared::cta.bulk_group [%0], [%1], %2;" ::"l"(dst), "r"(src), "r"(bytes) : "memory");
}
__device__ __forceinline__ uint32_t ld_u16(const void* p) { uint32_t v; asm volatile("ld.global.nc.u16 %0, [%1];" : "=r"(v) : "l"(p)); return v; }
__device__ __forceinline__ uint32_t ld_relaxed(const uint32_t* p) { uint32_t v; asm volatile("ld.relaxed.gpu.global.u32 %0, [%1];" : "=r"(v) : "l"(p) : "memory"); return v; }
__device__ __forceinline__ void bulk_flush() { asm volatile("cp.async.bulk.commit_group;\ncp.async.bulk.wait_group 0;" ::: "memory"); }
__device__ __forceinline__ void signal(uint32_t* flag) { asm volatile("fence.acq_rel.gpu;\nred.relaxed.gpu.global.add.u32 [%0], 1;" ::"l"(flag) : "memory"); }
__device__ __forceinline__ uint32_t tag(uint32_t v, uint32_t mask, uint32_t parity) { return (v & ~mask) | (parity & mask); }
__device__ __forceinline__ uint32_t or_diff(uint32_t acc, uint32_t v, uint32_t parity) { asm("lop3.b32 %0, %0, %1, %2, 0xf6;" : "+r"(acc) : "r"(v), "r"(parity)); return acc; }
__device__ __forceinline__ uint4 ld_relaxed4(const void* p) {
    uint4 v;
    asm volatile("ld.relaxed.gpu.global.v4.u32 {%0, %1, %2, %3}, [%4];" : "=r"(v.x), "=r"(v.y), "=r"(v.z), "=r"(v.w) : "l"(p) : "memory");
    return v;
}
__device__ __forceinline__ void sts4(uint32_t a, uint4 v) { asm volatile("st.shared.v4.b32 [%0], {%1, %2, %3, %4};" ::"r"(a), "r"(v.x), "r"(v.y), "r"(v.z), "r"(v.w) : "memory"); }
__device__ __forceinline__ void stg1(void* p, uint32_t v) { asm volatile("st.global.b32 [%0], %1;" ::"l"(p), "r"(v) : "memory"); }
__device__ __forceinline__ void fence_async_shared() { asm volatile("fence.proxy.async.shared::cta;" ::: "memory"); }
__device__ __forceinline__ void wait_flag(const uint32_t* p, uint32_t target) {
    asm volatile("{\n.reg .pred p;\n.reg .u32 v;\nPOLL:\nld.acquire.gpu.global.u32 v, [%0];\nsetp.ne.u32 p, v, %1;\n" POLL_SLEEP "@p bra POLL;\nfence.proxy.async.global;\n}" ::"l"(p), "r"(target) : "memory");
}
__device__ __forceinline__ void bar_sync(int id, int n) { asm volatile("bar.sync %0, %1;" ::"r"(id), "r"(n) : "memory"); }
__device__ __forceinline__ void bar_arrive(int id, int n) { asm volatile("bar.arrive %0, %1;" ::"r"(id), "r"(n) : "memory"); }
__device__ __forceinline__ void wg_fence() { asm volatile("wgmma.fence.sync.aligned;" ::: "memory"); }
__device__ __forceinline__ void wg_commit() { asm volatile("wgmma.commit_group.sync.aligned;" ::: "memory"); }
template <int N> __device__ __forceinline__ void wg_wait() { asm volatile("wgmma.wait_group.sync.aligned %0;" ::"n"(N) : "memory"); }
template <int N> __device__ __forceinline__ void pin(float (&d)[N]) {
#pragma unroll
    for (int i = 0; i < N; i++) asm volatile("" : "+f"(d[i])::"memory");
}
__host__ __device__ constexpr uint32_t desc_hi(uint32_t sbo, uint32_t swz) { return (sbo >> 4) | (swz << 30); }
__host__ __device__ constexpr uint32_t desc_lo(uint32_t off, uint32_t lbo) { return ((SMEM0 + off) >> 4) | ((lbo >> 4) << 16); }
__device__ __forceinline__ uint32_t pack2(float lo, float hi) { uint32_t r; asm("cvt.rn.bf16x2.f32 %0, %1, %2;" : "=r"(r) : "f"(hi), "f"(lo)); return r; }
__device__ __forceinline__ float bf_lo(uint32_t v) { return __uint_as_float(v << 16); }
__device__ __forceinline__ float bf_hi(uint32_t v) { return __uint_as_float(v & 0xffff0000u); }
__device__ __forceinline__ uint32_t half_plus(uint32_t a, uint32_t b) { uint32_t r; asm("fma.rn.bf16x2 %0, %1, %2, %3;" : "=r"(r) : "r"(a), "r"(0x3f003f00u), "r"(b)); return r; }
__device__ __forceinline__ void stsm4(uint32_t a, uint32_t r0, uint32_t r1, uint32_t r2, uint32_t r3) {
    asm volatile("stmatrix.sync.aligned.m8n8.x4.shared.b16 [%0], {%1, %2, %3, %4};" ::"r"(a), "r"(r0), "r"(r1), "r"(r2), "r"(r3) : "memory");
}
__device__ __forceinline__ void stsm2(uint32_t a, uint32_t r0, uint32_t r1) {
    asm volatile("stmatrix.sync.aligned.m8n8.x2.shared.b16 [%0], {%1, %2};" ::"r"(a), "r"(r0), "r"(r1) : "memory");
}
__device__ __forceinline__ uint4 lds4(uint32_t a) { uint4 v; asm volatile("ld.shared.v4.b32 {%0, %1, %2, %3}, [%4];" : "=r"(v.x), "=r"(v.y), "=r"(v.z), "=r"(v.w) : "r"(a) : "memory"); return v; }
__device__ __forceinline__ uint2 lds2(uint32_t a) { uint2 v; asm volatile("ld.shared.v2.b32 {%0, %1}, [%2];" : "=r"(v.x), "=r"(v.y) : "r"(a) : "memory"); return v; }
__device__ __forceinline__ float lds1f(uint32_t a) { float v; asm volatile("ld.shared.f32 %0, [%1];" : "=f"(v) : "r"(a) : "memory"); return v; }
__device__ __forceinline__ void ldsm4(uint32_t* r, uint32_t a) {
    asm volatile("ldmatrix.sync.aligned.m8n8.x4.shared.b16 {%0, %1, %2, %3}, [%4];" : "=r"(r[0]), "=r"(r[1]), "=r"(r[2]), "=r"(r[3]) : "r"(a) : "memory");
}
__device__ __forceinline__ void ldsm4t(uint32_t* r, uint32_t a) {
    asm volatile("ldmatrix.sync.aligned.m8n8.x4.trans.shared.b16 {%0, %1, %2, %3}, [%4];" : "=r"(r[0]), "=r"(r[1]), "=r"(r[2]), "=r"(r[3]) : "r"(a) : "memory");
}
__device__ __forceinline__ uint32_t transpose8(uint32_t v) { uint32_t r; asm volatile("movmatrix.sync.aligned.m8n8.trans.b16 %0, %1;" : "=r"(r) : "r"(v)); return r; }
__device__ __forceinline__ void mma16(float (&c)[4], uint32_t a0, uint32_t a1, uint32_t a2, uint32_t a3, uint32_t b0, uint32_t b1) {
    asm volatile("mma.sync.aligned.m16n8k16.row.col.f32.bf16.bf16.f32 {%0, %1, %2, %3}, {%4, %5, %6, %7}, {%8, %9}, {%0, %1, %2, %3};"
                 : "+f"(c[0]), "+f"(c[1]), "+f"(c[2]), "+f"(c[3]) : "r"(a0), "r"(a1), "r"(a2), "r"(a3), "r"(b0), "r"(b1));
}
__device__ __forceinline__ void mma8(float (&c)[4], uint32_t a0, uint32_t a1, uint32_t b0) {
    asm volatile("mma.sync.aligned.m16n8k8.row.col.f32.bf16.bf16.f32 {%0, %1, %2, %3}, {%4, %5}, {%6}, {%0, %1, %2, %3};"
                 : "+f"(c[0]), "+f"(c[1]), "+f"(c[2]), "+f"(c[3]) : "r"(a0), "r"(a1), "r"(b0));
}
__device__ __forceinline__ void st_async4(uint32_t a, uint32_t bar, uint32_t v0, uint32_t v1, uint32_t v2, uint32_t v3) {
    asm volatile("st.async.weak.shared::cluster.mbarrier::complete_tx::bytes.v4.b32 [%0], {%2, %3, %4, %5}, [%1];" ::"r"(a), "r"(bar), "r"(v0), "r"(v1), "r"(v2), "r"(v3) : "memory");
}
__device__ __forceinline__ void st_async2(uint32_t a, uint32_t bar, uint32_t v0, uint32_t v1) {
    asm volatile("st.async.weak.shared::cluster.mbarrier::complete_tx::bytes.v2.b32 [%0], {%2, %3}, [%1];" ::"r"(a), "r"(bar), "r"(v0), "r"(v1) : "memory");
}
__device__ __forceinline__ float quad_max(float v) { v = fmaxf(v, __shfl_xor_sync(~0u, v, 1)); return fmaxf(v, __shfl_xor_sync(~0u, v, 2)); }
__device__ __forceinline__ float quad_sum(float v) { v += __shfl_xor_sync(~0u, v, 1); return v + __shfl_xor_sync(~0u, v, 2); }
__device__ __forceinline__ float ex2(float v) { float r; asm("ex2.approx.ftz.f32 %0, %1;" : "=f"(r) : "f"(v)); return r; }
__device__ __forceinline__ float rcp(float v) { float r; asm("rcp.approx.ftz.f32 %0, %1;" : "=f"(r) : "f"(v)); return r; }
__device__ __forceinline__ float rsq(float v) { float r; asm("rsqrt.approx.ftz.f32 %0, %1;" : "=f"(r) : "f"(v)); return r; }
__device__ __forceinline__ float gelu2(float u) {
    float z = u * fmaf(u * u, 0.044715f * 0.7978845608028654f, 0.7978845608028654f), t;
    asm("tanh.approx.f32 %0, %1;" : "=f"(t) : "f"(z));
    return fmaf(u, t, u);
}
__device__ __forceinline__ float oct_sum(float v) {
    v += __shfl_xor_sync(~0u, v, 4); v += __shfl_xor_sync(~0u, v, 8); v += __shfl_xor_sync(~0u, v, 16);
    return v;
}

template <int TA, int TB, uint32_t HA, uint32_t HB>
__device__ __forceinline__ void wgmma_n112(float (&d)[56], uint32_t da, uint32_t db, int accumulate) {
    asm volatile("{\n.reg .pred p;\n.reg .b64 a, b;\nmov.b64 a, {%56, %61};\nmov.b64 b, {%57, %62};\nsetp.ne.b32 p, %58, 0;\n"
        "wgmma.mma_async.sync.aligned.m64n112k16.f32.bf16.bf16 {"
        "%0, %1, %2, %3, %4, %5, %6, %7, %8, %9, %10, %11, %12, %13, %14, %15, "
        "%16, %17, %18, %19, %20, %21, %22, %23, %24, %25, %26, %27, %28, %29, %30, %31, "
        "%32, %33, %34, %35, %36, %37, %38, %39, %40, %41, %42, %43, %44, %45, %46, %47, "
        "%48, %49, %50, %51, %52, %53, %54, %55"
        "}, a, b, p, 1, 1, %59, %60;\n}\n"
        : "+f"(d[0]), "+f"(d[1]), "+f"(d[2]), "+f"(d[3]), "+f"(d[4]), "+f"(d[5]), "+f"(d[6]), "+f"(d[7]),
          "+f"(d[8]), "+f"(d[9]), "+f"(d[10]), "+f"(d[11]), "+f"(d[12]), "+f"(d[13]), "+f"(d[14]), "+f"(d[15]),
          "+f"(d[16]), "+f"(d[17]), "+f"(d[18]), "+f"(d[19]), "+f"(d[20]), "+f"(d[21]), "+f"(d[22]), "+f"(d[23]),
          "+f"(d[24]), "+f"(d[25]), "+f"(d[26]), "+f"(d[27]), "+f"(d[28]), "+f"(d[29]), "+f"(d[30]), "+f"(d[31]),
          "+f"(d[32]), "+f"(d[33]), "+f"(d[34]), "+f"(d[35]), "+f"(d[36]), "+f"(d[37]), "+f"(d[38]), "+f"(d[39]),
          "+f"(d[40]), "+f"(d[41]), "+f"(d[42]), "+f"(d[43]), "+f"(d[44]), "+f"(d[45]), "+f"(d[46]), "+f"(d[47]),
          "+f"(d[48]), "+f"(d[49]), "+f"(d[50]), "+f"(d[51]), "+f"(d[52]), "+f"(d[53]), "+f"(d[54]), "+f"(d[55])
        : "r"(da), "r"(db), "r"(accumulate), "n"(TA), "n"(TB), "n"(HA), "n"(HB));
}

template <int TA, int TB, uint32_t HA, uint32_t HB>
__device__ __forceinline__ void wgmma_n184(float (&d)[92], uint32_t da, uint32_t db, int accumulate) {
    asm volatile("{\n.reg .pred p;\n.reg .b64 a, b;\nmov.b64 a, {%92, %97};\nmov.b64 b, {%93, %98};\nsetp.ne.b32 p, %94, 0;\n"
        "wgmma.mma_async.sync.aligned.m64n184k16.f32.bf16.bf16 {"
        "%0, %1, %2, %3, %4, %5, %6, %7, %8, %9, %10, %11, %12, %13, %14, %15, "
        "%16, %17, %18, %19, %20, %21, %22, %23, %24, %25, %26, %27, %28, %29, %30, %31, "
        "%32, %33, %34, %35, %36, %37, %38, %39, %40, %41, %42, %43, %44, %45, %46, %47, "
        "%48, %49, %50, %51, %52, %53, %54, %55, %56, %57, %58, %59, %60, %61, %62, %63, "
        "%64, %65, %66, %67, %68, %69, %70, %71, %72, %73, %74, %75, %76, %77, %78, %79, "
        "%80, %81, %82, %83, %84, %85, %86, %87, %88, %89, %90, %91"
        "}, a, b, p, 1, 1, %95, %96;\n}\n"
        : "+f"(d[0]), "+f"(d[1]), "+f"(d[2]), "+f"(d[3]), "+f"(d[4]), "+f"(d[5]), "+f"(d[6]), "+f"(d[7]),
          "+f"(d[8]), "+f"(d[9]), "+f"(d[10]), "+f"(d[11]), "+f"(d[12]), "+f"(d[13]), "+f"(d[14]), "+f"(d[15]),
          "+f"(d[16]), "+f"(d[17]), "+f"(d[18]), "+f"(d[19]), "+f"(d[20]), "+f"(d[21]), "+f"(d[22]), "+f"(d[23]),
          "+f"(d[24]), "+f"(d[25]), "+f"(d[26]), "+f"(d[27]), "+f"(d[28]), "+f"(d[29]), "+f"(d[30]), "+f"(d[31]),
          "+f"(d[32]), "+f"(d[33]), "+f"(d[34]), "+f"(d[35]), "+f"(d[36]), "+f"(d[37]), "+f"(d[38]), "+f"(d[39]),
          "+f"(d[40]), "+f"(d[41]), "+f"(d[42]), "+f"(d[43]), "+f"(d[44]), "+f"(d[45]), "+f"(d[46]), "+f"(d[47]),
          "+f"(d[48]), "+f"(d[49]), "+f"(d[50]), "+f"(d[51]), "+f"(d[52]), "+f"(d[53]), "+f"(d[54]), "+f"(d[55]),
          "+f"(d[56]), "+f"(d[57]), "+f"(d[58]), "+f"(d[59]), "+f"(d[60]), "+f"(d[61]), "+f"(d[62]), "+f"(d[63]),
          "+f"(d[64]), "+f"(d[65]), "+f"(d[66]), "+f"(d[67]), "+f"(d[68]), "+f"(d[69]), "+f"(d[70]), "+f"(d[71]),
          "+f"(d[72]), "+f"(d[73]), "+f"(d[74]), "+f"(d[75]), "+f"(d[76]), "+f"(d[77]), "+f"(d[78]), "+f"(d[79]),
          "+f"(d[80]), "+f"(d[81]), "+f"(d[82]), "+f"(d[83]), "+f"(d[84]), "+f"(d[85]), "+f"(d[86]), "+f"(d[87]),
          "+f"(d[88]), "+f"(d[89]), "+f"(d[90]), "+f"(d[91])
        : "r"(da), "r"(db), "r"(accumulate), "n"(TA), "n"(TB), "n"(HA), "n"(HB));
}

struct Ring {
    uint32_t slot, ph;
    __device__ __forceinline__ void next() { if (++slot == NSLOT) { slot = 0; ph ^= 1; } }
};
__device__ __forceinline__ uint32_t xslot(int i) { return __byte_perm(0x04130e0cu, 0x00130e0cu, 0x7770 + i); }
__device__ __forceinline__ uint32_t wslot(int i) { return __byte_perm(0x06001510u, 0x00151009u, 0x7770 + i); }

constexpr uint32_t HI_SW = desc_hi(1024, 1);

struct Mma {
    uint32_t bars, rel;
    bool lead;
    int wg, w;
    Ring r;
    __device__ __forceinline__ void release(uint32_t s) { if (lead) mbar_arrive_remote(rel + B_EMPTY + 8 * s); }
    template <int KIND>
    __device__ __forceinline__ uint32_t run(float (&a)[56], int n, int nrel, int lag, int accumulate, int ts) {
        uint32_t prev = 0;
#pragma unroll 1
        for (int i = 0; i < n; i++) {
            if (lag && i == (wg ? n - lag : -1)) bar_sync(7, 256);
            const uint32_t s = r.slot;
            mbar_wait(bars + B_FULL + 8 * s, r.ph); r.next();
            if (wg == 0) TS0(KIND ? 8 : 2, ts + i);
            const uint32_t dB = s * (SLOT >> 4), dA = dB + wg * 512;
            wg_fence();
#pragma unroll
            for (int k = 0; k < 4; k++) {
                const int acc = k > 0 || accumulate || i > 0;
                if (KIND == 0) wgmma_n112<1, 1, HI_SW, desc_hi(256, 0)>(a, dA + desc_lo(k * 2048, 8192), dB + desc_lo(16384 + k * SLAB, 128), acc);
                if (KIND == 1) wgmma_n112<0, 1, desc_hi(128, 0), desc_hi(1024, 0)>(a, dA + desc_lo(k * 2048, k < 3 ? 1024 : 0), dB + desc_lo(16384 + k * 256, 128), acc);
                if (KIND == 2) wgmma_n112<1, 1, HI_SW, desc_hi(1024, 0)>(a, dA + desc_lo(k * 2048, 8192), dB + desc_lo(16384 + k * 256, 128), acc);
                if (k == 1) {
                    wg_commit(); wg_wait<1>();
                    if ((uint32_t)(i - 1) < (uint32_t)nrel) release(prev);
                    if (lag && i == (wg ? -1 : n - 1)) bar_arrive(7, 256);
                }
            }
            wg_commit();
            prev = s;
        }
        return prev;
    }
};

__global__ void __cluster_dims__(2, 1, 1) __launch_bounds__(NTHREADS, 1)
fused_kernel(const __nv_bfloat16* __restrict__ x, const __nv_bfloat16* __restrict__ b1, const __nv_bfloat16* __restrict__ b2, const __nv_bfloat16* __restrict__ wo, __nv_bfloat16* out, Scratch* G,
             const __grid_constant__ Params P) {
    extern __shared__ __align__(1024) uint8_t smem[];
    const uint32_t sbase = (uint32_t)__cvta_generic_to_shared(smem);
    const uint32_t bars = sbase + OFF_BAR;
    const int lane = threadIdx.x & 31;
    const int warp = __shfl_sync(~0u, threadIdx.x >> 5, 0), w = warp & 3;
    const uint32_t rank = blockIdx.x & 1, pr = blockIdx.x >> 1;
    const uint32_t pv = pr < 4 ? pr * 8 + 36 : pr < 40 ? pr - 4 : pr - 3 + (((pr - 40) * 37) >> 8);
    const uint32_t gp = (pv + 4) & 7, hp = pv >> 3;
    const uint32_t tb = gp * 2 + rank, c = hp * 16 + tb, row0 = (tb * 8 + hp) * 16;
    const bool has_g1 = gp > 0;
    const uint32_t nt1 = hp & 3, ft = max((int)gp - 1, 0) * 2 + (hp >> 2);
    const uint32_t nt2 = tb & 3, mt = (gp & 2) * 4 + hp, ks = gp >> 2;

    if (warp < NBAR / 3 && elect()) {
        if (warp == 0) TS(15, 0);
#pragma unroll
        for (int i = 0; i < 3; i++) mbar_init(bars + warp * 24 + 8 * i, 1u << ((0xaaad4000u >> (2 * max(warp * 3 + i - 12, 0)) & 3) | (warp == 9 ? 2 : 0)));
        asm volatile("fence.mbarrier_init.release.cluster;" ::: "memory");
        if (warp == B_ROW / 24) {
            mbar_expect(bars + B_ROW, TILEB);
            bulk_load(sbase + OFF_Y, x + row0 * D_, TILEB, bars + B_ROW);
        }
    }
    __syncwarp();
    asm volatile("barrier.cluster.arrive.relaxed.aligned;\nbarrier.cluster.wait.aligned;" ::: "memory");

    if (warp == 8) {
        if (elect()) {
            uint32_t spins = (sbase & 0xffffffu) == SMEM0 ? 0 : SPIN_LIMIT;
            uint32_t kw = gp * 64, kx = kw;
            uint32_t due = (uint32_t)clock();
#pragma unroll 1
            for (int i = 0; i < 8; i++) {
                if (i >= 5) mbar_wait_bounded(bars + B_QEMPTY + 8 * (i - 5), 0, spins);
                else { while ((int)((uint32_t)clock() - due) < 0) {} due += PACE; }
                if (kw == D_) kw = 0;
                if (i < 4) kx = kw;
                const int ix = i - (i > 4);
                if (i < 7) mbar_expect(bars + B_QFULL + 8 * i, QSLOT);
                if (i != 4) tma3d(sbase + xslot(ix) * 8192, &P.tmX, bars + B_QFULL + 8 * ix, kx, tb * 64, 0);
                if (i == 5) mbar_wait_bounded(bars + B_CS, 0, spins);
                if (i < 7) tma3d_pair(sbase + wslot(i) * 8192 + rank * 12288, &P.tmWqkv, bars + B_QFULL + 8 * i, (hp * 56) & ~15, kw + rank * 32, 0);
                kx = kw; kw += 64;
                if (i == 0) TS(1, 23);
            }
            mbar_expect(bars + B_X, HALF); mbar_expect(bars + B_X + 8, HALF);
            Ring r{0, 0};
#pragma unroll 1
            for (int j = has_g1 ? 0 : 16; j < 34; j++) {
                const uint32_t dst = sbase + r.slot * SLOT, full = bars + B_FULL + 8 * r.slot;
                mbar_wait_bounded(bars + B_EMPTY + 8 * r.slot, r.ph, spins);
                if (j < 20 || j >= 26) mbar_expect(full, ((j >> 2) == 4 ? TILEB : 16384) + TILEB);
                if (j < 16) tma3d(dst, &P.tmW1, full, 0, rank * 1024 + j * 64, ft * 2);
                else if (j < 20) { mbar_wait_bounded(bars + B_ROW, 1, spins); bulk_load(dst + 16384, G->Wo[nt2][ks * 4 + j - 16], TILEB, full); }
                else tma2d_pair(dst + rank * 8192, &P.tmW2, full, mt * 128 + rank * 64, ks * 896 + j * 128 - (j < 27 ? 2560 : 3392));
                r.next();
            }
            mbar_wait_bounded(bars + B_END, 0, spins);
        }
    } else if (warp > 8) {
        uint32_t ep = ld_relaxed(&G->epoch[c]);
        float* cs;
        {
            uint32_t src = sbase + 16 * 8192 - 4096 + rank * 12288 + w * 4096 + lane * 4;
            float s0 = 0.f, s1 = 0.f, s2 = 0.f, s3 = 0.f;
            mbar_wait(bars + B_QFULL, 0);
#pragma unroll 1
            for (int i = 0; i < 2; i++) {
                uint32_t v[16];
#pragma unroll
                for (int k = 0; k < 16; k++) v[k] = __float_as_uint(lds1f((src ^ ((k & 7) * 144)) + (k >> 3) * 1024));
#pragma unroll
                for (int k = 0; k < 16; k += 2) { s0 += bf_lo(v[k]); s1 += bf_hi(v[k]); s2 += bf_lo(v[k + 1]); s3 += bf_hi(v[k + 1]); }
                src += 2048;
            }
            cs = G->colsum[ep & 1][hp];
            if (tb < 14) asm volatile("red.relaxed.gpu.global.add.v2.f32 [%0], {%1, %2};" ::"l"(cs + w * 64 - 64 + lane * 2), "f"(s0 + s2), "f"(s1 + s3) : "memory");
            if (tb == 15) *(float2*)(G->colsum[~ep & 1][hp] + w * 64 - 64 + lane * 2) = make_float2(0.f, 0.f);
            ep++;
            if (w == 1) TS(1, 24);
            if (w == 2) {
                bar_sync(6, 224);
                if (elect()) { mbar_arrive(bars + B_CS); signal(&G->flagH[c >> 2]); TS(1, 3); }
                __syncwarp();
            } else {
                bar_arrive(6, 224);
            }
        }
        if (w == 1) {
            wait_flag(&G->flagH[lane], 4 * ep);
            __syncwarp();
            if (elect()) {
                TS(1, 16);
                asm volatile("st.shared.u32 [%0], %1;" ::"r"(bars + 8 * NBAR), "r"(ep) : "memory");
                mbar_expect(bars + B_REC, 1152 + 768);
                bulk_load(sbase + OFF_CS, cs, 768, bars + B_REC);
                bulk_load(sbase + OFF_ST, G->stat + tb * 128, 1152, bars + B_REC);
                Ring r{0, 0};
                const uint8_t* src = G->H[nt1][rank * 16];
#pragma unroll 1
                for (int j = has_g1 ? 0 : 16; j < 34; j++) {
                    if (j == 20) {
                        if (has_g1) { mbar_wait(bars + B_UDONE, 0); signal(G->flag[nt1 * 2 + (ft >= 7)]); TS(4, 8); }
                        j += NSLOT; r.ph ^= 1;
                    }
                    if (j == 16 || j == 26) {
                        src = j == 16 ? G->O[mt][ks * 4] + rank * HALF : G->U[nt2][ks * 14 + 6];
                        wait_flag(G->flag[j == 16 ? 16 + mt : nt2 * 2 + ks], (j == 16 ? 8 : 14) * ep);
                        TS(4, j == 16 ? 18 : j);
                        mbar_wait(bars + B_CS, j == 26);
                    }
                    const uint32_t dst = sbase + r.slot * SLOT, full = bars + B_FULL + 8 * r.slot;
                    mbar_wait(bars + B_EMPTY + 8 * r.slot, r.ph);
                    if ((j >> 2) == 4) bulk_load_pair(dst + rank * 8192, src, HALF, full);
                    else bulk_load(dst + 16384, src, TILEB, full);
                    src += TILEB;
                    r.next();
                }
                G->epoch[c] = ep;
            }
        } else {
            Ring r{has_g1 ? 20u % NSLOT : 4u, has_g1};
            const uint8_t* src = G->U[nt2][ks * 14];
            if (w == 2) {
                bar_sync(3, 288);
                __nanosleep(HALO_NS);
                uint4 v[7];
                uint32_t bad;
                do {
                    bad = 0;
#pragma unroll
                    for (int i = 0; i < 7; i++) { v[i] = ld_relaxed4(G->halo[c - (tb > 0)] + i * 512 + lane * 16); bad = or_diff(bad, v[i].x, ep); }
                } while (bad & 1);
#pragma unroll
                for (int i = 0; i < 7; i++) sts4(sbase + OFF_X + i * 512 + lane * 16, v[i]);
                __syncwarp();
                if (elect()) {
                    mbar_arrive(bars + B_HALO);
                    TS(2, 21);
                    __nanosleep(1500);
                    wait_flag(G->flag[(nt2 & 2) + ks] + 1, 4 * ep);
                    mbar_arrive(bars + B_ROW);
                    TS(2, 27);
                }
                __syncwarp();
                uint32_t ph = 1;
#pragma unroll 1
                for (int i = 0; i < NSLOT;) {
                    const uint32_t dst = sbase + r.slot * SLOT + 16384;
                    mbar_wait(bars + B_QFULL + 8 * i, ph);
                    TS(4, 86 + i);
                    bad = 0;
#pragma unroll
                    for (int k = 0; k < 14; k++) bad = or_diff(bad, __float_as_uint(lds1f(dst + k * 1024 + lane * 32 + (lane >> 2) * 4)), ep);
                    if (__any_sync(~0u, bad & 1)) {
                        if (elect()) {
                            fence_async_shared();
                            mbar_expect(bars + B_QFULL + 8 * i, TILEB);
                            bulk_load(dst, src, TILEB, bars + B_QFULL + 8 * i);
                        }
                        ph ^= 1;
                        TS(4, 84);
                    } else {
                        if (elect()) mbar_expect(bars + B_FULL + 8 * r.slot, 16384);
                        ph = 1; i++; src += TILEB; r.next();
                    }
                }
            } else {
                bar_sync(2, 288);
                if (elect()) bulk_store(out + row0 * D_, sbase + OFF_Y, TILEB);
                __syncwarp();
                bar_sync(4, 288);
                if (elect()) {
                    bulk_store(G->O[tb][hp], sbase + OFF_X, TILEB);
                    bulk_flush();
                    mbar_arrive_remote(mapa(bars + B_FREE, rank ^ 1));
                    mbar_arrive(bars + B_FREE);
                    signal(G->flag[16 + tb]);
                    if (!has_g1) asm volatile("red.relaxed.gpu.global.add.u32 [%0], 1;" ::"l"(G->flag[rank * 2 + (hp >> 2)] + 1) : "memory");
                    TS(2, 22);
                }
                __syncwarp();
                uint32_t late = ~0u;
#pragma unroll 1
                for (int i = 0; i < NSLOT; i++) {
                    while ((late >> i) & 1) late = __ballot_sync(~0u, ld_relaxed(G->flag[8 + nt2 * 2 + ks] + lane) != 8 * ep);
                    if (i == 0) { TS(4, 17); mbar_wait(bars + (has_g1 ? B_UDONE : B_FREE), 0); }
                    mbar_wait(bars + B_EMPTY + 8 * r.slot, r.ph);
                    if (elect()) {
                        mbar_expect(bars + B_QFULL + 8 * i, TILEB);
                        bulk_load(sbase + r.slot * SLOT + 16384, src, TILEB, bars + B_QFULL + 8 * i);
                    }
                    src += TILEB; r.next();
                }
                if (elect()) mbar_arrive(bars + B_CS);
            }
        }
    } else {
        const int wg = warp >> 2;
        Mma M{bars, mapa(bars, rank ^ (lane & 1)), (threadIdx.x & 127) < 2, wg, w, Ring{0, 0}};
        const int r = lane >> 2, t = lane & 3;
        uint32_t ep;
        const uint32_t bias0 = ld_u16(b1 + ft * 128 + warp * 16 + r), bias1 = ld_u16(b1 + ft * 128 + warp * 16 + r + 8);
        if (wg == 1) {
            const int r16 = w * 4 + t, c8 = (r + 2 * t) & 7;
            const uint32_t row = sbase + OFF_Y + r16 * (2 * D_) + c8 * 16;
            mbar_wait(bars + B_ROW, 0);
            TS0(1, 67);
            float f[56];
#pragma unroll
            for (int i = 0; i < 7; i++) {
                const uint4 v = lds4(row + i * 128);
                f[8 * i] = bf_lo(v.x); f[8 * i + 1] = bf_hi(v.x); f[8 * i + 2] = bf_lo(v.y); f[8 * i + 3] = bf_hi(v.y);
                f[8 * i + 4] = bf_lo(v.z); f[8 * i + 5] = bf_hi(v.z); f[8 * i + 6] = bf_lo(v.w); f[8 * i + 7] = bf_hi(v.w);
            }
            float s0 = f[0], s1 = f[1], s2 = f[2], s3 = f[3];
#pragma unroll
            for (int i = 4; i < 56; i += 4) { s0 += f[i]; s1 += f[i + 1]; s2 += f[i + 2]; s3 += f[i + 3]; }
            const float nmean = oct_sum((s0 + s1) + (s2 + s3)) * (-1.f / D_);
            s0 = s1 = s2 = s3 = 0.f;
#pragma unroll
            for (int i = 0; i < 56; i += 4) {
                f[i] += nmean; f[i + 1] += nmean; f[i + 2] += nmean; f[i + 3] += nmean;
                s0 = fmaf(f[i], f[i], s0); s1 = fmaf(f[i + 1], f[i + 1], s1); s2 = fmaf(f[i + 2], f[i + 2], s2); s3 = fmaf(f[i + 3], f[i + 3], s3);
            }
            const float var = oct_sum((s0 + s1) + (s2 + s3)) * (1.f / D_);
            const float rstd = rsq(var + LN_EPS);
            const float sc = rstd * rsq(fmaf(var * rstd, rstd, LN_EPS));
            if (lane < 4) G->stat[16 + row0 + r16] = make_float2(rstd + rstd, nmean);
            uint8_t* hb = G->H[0][0] + row0 * (SLAB / 16) + r16 * 16 + c8 * 256;
            const int sw = tb < 8 ? 0 : 7 * 256;
#pragma unroll
            for (int i = 0; i < 7; i++) {
                const int lo = (8 * i) % 14, nt = (8 * i) / 14, next = 32 * TILEB - SLAB;
                const int off = lo < 7 ? (c8 < 7 - lo ? sw : -sw) : (c8 >= 14 - lo ? sw + next : -sw);
                *(uint4*)(hb + off + i * 2048 + nt * next) = make_uint4(pack2(f[8 * i] * sc, f[8 * i + 1] * sc), pack2(f[8 * i + 2] * sc, f[8 * i + 3] * sc),
                                                                        pack2(f[8 * i + 4] * sc, f[8 * i + 5] * sc), pack2(f[8 * i + 6] * sc, f[8 * i + 7] * sc));
            }
            TS0(1, 25);
            bar_arrive(6, 224);
        }
        const uint32_t kv = sbase + OFF_X + (w * 2 + wg) * KV + lane * 16;
        const uint32_t st = sbase + OFF_ST + (16 + w * 32 + wg) * 8;
        uint32_t q[7][2], k0[7], v0[7];
        {
            float acc[92];
#pragma unroll 1
            for (int kb = 0; kb < 7; kb++) {
                const bool held = kb == (wg ? 5 : -1);
                if (held) { wg_wait<0>(); if (M.lead) mbar_arrive_remote(M.rel + B_QEMPTY + 8 * 4); bar_sync(7, 256); }
                mbar_wait(bars + B_QFULL + 8 * kb, 0);
                TS0(1, 68 + wg * 7 + kb);
                const uint32_t dA = (xslot(kb) + wg) * 512, dB = wslot(kb) * 512 + (hp & 1);
                wg_fence();
#pragma unroll
                for (int k = 0; k < 4; k++) {
                    wgmma_n184<0, 1, HI_SW, HI_SW>(acc, dA + desc_lo(k * 32, 16), dB + desc_lo((k & 1) * 2048 + (k >> 1) * 12288, 4096), k > 0 || kb > 0);
                    if (k == 0) { wg_commit(); wg_wait<1>(); if (M.lead && kb > 0 && !held) mbar_arrive_remote(M.rel + B_QEMPTY + 8 * (kb - 1)); }
                }
                wg_commit();
            }
            if (wg == 0) bar_arrive(7, 256);
            mbar_wait(bars + B_REC, 0);
            ep = __float_as_uint(lds1f(bars + 8 * NBAR));
            const float n0 = lds1f(st + r * 16 + 4), n1 = lds1f(st + r * 16 + 132);
            const uint32_t csa = sbase + OFF_CS + t * 8 + (hp & 1) * 32;
            wg_wait<0>();
            pin(acc);
            M.release(4); M.release(5);
            TS0(1, 4 + 7 * wg);
            uint32_t hi[14];
#pragma unroll
            for (int p = 2; p >= 0; p--) {
#pragma unroll
                for (int g = 0; g < 7; g++) {
                    const uint2 cs = lds2(csa + (p * 8 + g) * 32);
                    const int a = (p * 8 + g) * 4;
                    const float c0 = __uint_as_float(cs.x), c1 = __uint_as_float(cs.y);
                    const uint32_t lo2 = pack2(fmaf(n0, c0, acc[a]), fmaf(n0, c1, acc[a + 1])), hi2 = pack2(fmaf(n1, c0, acc[a + 2]), fmaf(n1, c1, acc[a + 3]));
                    if (p == 0) { q[g][0] = lo2; q[g][1] = hi2; } else { (p == 1 ? k0 : v0)[g] = lo2; hi[(p - 1) * 7 + g] = hi2; }
                }
                if (p == 1) {
#pragma unroll
                    for (int i = 0; i < 3; i++) stsm4(kv + 2 * KV + i * 512, hi[4 * i], hi[4 * i + 1], hi[4 * i + 2], hi[4 * i + 3]);
                    stsm2(kv + 2 * KV + 1536, hi[12], hi[13]);
                    if (w == 3) {
#pragma unroll
                        for (int i = 0; i < 14; i++) stg1(G->halo[c] + wg * KV + lane * 4 + i * 128, tag(hi[i], t == 0, ep));
                    }
                    bar_arrive(3, 288);
                }
            }
        }
        TS0(1, 9 + 11 * wg);
        float a[56];
#pragma unroll
        for (int i = 0; i < 56; i++) asm volatile("" : "=f"(a[i]));
        const int n1 = PAUSE + (wg == 0 ? LEAD : 0);
        if (!has_g1) {
            const int g = min(lane >> 1, 13), k = w * 16 + (lane & 1), nt = rank * 2 + wg;
            const uint4* src = (const uint4*)(wo + (hp * 56 + k) * D_ + nt * 112) + g;
            uint4 v[8] = {};
#pragma unroll
            for (int i = 0; i < 8; i++) if (i < 4 || w < 3) v[i] = __ldg(src + i * (D_ / 4));
#pragma unroll
            for (int i = 0; i < 8; i++) ((uint4*)G->Wo[nt][hp])[g * 64 + k + 2 * i] = v[i];
        }
        uint32_t last = M.run<0>(a, has_g1 ? n1 : 0, 16, 0, 0, 32);
        {
            uint32_t kp[8], k1[8], vp[8], v1[8];
            mbar_wait(bars + B_HALO, 0);
            ldsm4(kp, kv); ldsm4(kp + 4, kv + 512); ldsm4(k1, kv + 2 * KV); ldsm4(k1 + 4, kv + 2 * KV + 512);
            ldsm4t(vp, kv + 896); ldsm4t(vp + 4, kv + 1408); ldsm4t(v1, kv + 2 * KV + 896); ldsm4t(v1 + 4, kv + 2 * KV + 1408);
#pragma unroll
            for (int g = 0; g < 7; g++) v0[g] = transpose8(v0[g]);
            const bool e0 = 2 * t > r, e1 = 2 * t >= r;
            const uint32_t ka = st + t * 32 - (e0 ? 128 : 0), kb = st + t * 32 + 16 - (e1 ? 128 : 0);
            const float rk[4] = {lds1f(ka), lds1f(kb), lds1f(ka + 128), lds1f(kb + 128)};
            const float sq0 = lds1f(st + r * 16) * (0.25f * 0.1889822365046136f * 1.4426950408889634f), sq1 = lds1f(st + r * 16 + 128) * (0.25f * 0.1889822365046136f * 1.4426950408889634f);
            float sc[6] = {sq0 * rk[0], sq0 * rk[1], sq1 * rk[2], sq1 * rk[3], 0.f, 0.f};
            if (tb == 0 && w == 0) { sc[4] = e0 ? -1e30f : 0.f; sc[5] = e1 ? -1e30f : 0.f; }
            uint32_t mk[6] = {(e0 ? 0xffffu : 0u) | (e1 ? 0xffff0000u : 0u), 0u, t < 2 ? q[3][0] : 0u, t < 2 ? q[3][1] : 0u, t < 2 ? 0u : q[3][0], t < 2 ? 0u : q[3][1]};
            wg_wait<0>();
            pin(a);
            if (has_g1) M.release(last);
            bar_sync(2, 288);
            mbar_wait(bars + B_HALO, 0);
            TS0(2, 12 + 16 * wg);
            float sv[2][4];
#pragma unroll
            for (int h = 0; h < 2; h++) {
                const int ga = h * 4, gb = h * 4 + 1, gc = h * 4 + 2;
                float s[3][4] = {};
                mma16(s[0], q[ga][0], q[ga][1], q[gb][0], q[gb][1], kp[ga], kp[gb]);
                mma16(s[1], q[ga][0], q[ga][1], q[gb][0], q[gb][1], k0[ga], k0[gb]);
                mma16(s[2], q[ga][0], q[ga][1], q[gb][0], q[gb][1], k1[ga], k1[gb]);
                mma16(s[0], q[gc][0], q[gc][1], mk[2 + 2 * h], mk[3 + 2 * h], kp[gc], kp[3]);
                mma16(s[1], q[gc][0], q[gc][1], mk[2 + 2 * h], mk[3 + 2 * h], k0[gc], k0[3]);
                mma16(s[2], q[gc][0], q[gc][1], mk[2 + 2 * h], mk[3 + 2 * h], k1[gc], k1[3]);
                sv[h][0] = fmaf(e0 ? s[0][0] : s[1][0], sc[0], sc[4]);
                sv[h][1] = fmaf(e1 ? s[0][1] : s[1][1], sc[1], sc[5]);
                sv[h][2] = (e0 ? s[1][2] : s[2][2]) * sc[2];
                sv[h][3] = (e1 ? s[1][3] : s[2][3]) * sc[3];
            }
            uint32_t pp[2][2];
#pragma unroll
            for (int i = 0; i < 4; i++) {
                float* v = &sv[i >> 1][(i & 1) * 2];
                const float m = quad_max(fmaxf(v[0], v[1]));
                const float p0 = ex2(v[0] - m), p1 = ex2(v[1] - m);
                const float inv = rcp(quad_sum(p0 + p1));
                pp[i >> 1][i & 1] = pack2(p0 * rk[(i & 1) * 2] * inv, p1 * rk[(i & 1) * 2 + 1] * inv);
            }
            uint32_t o[8][2];
#pragma unroll
            for (int i = 0; i < 8; i++) {
                const int h = i >> 2, g = i - h;
                float d[4] = {};
                mma16(d, pp[h][0] & mk[0], 0u, pp[h][0] & ~mk[0], pp[h][1] & mk[0], vp[g], v0[g]);
                mma8(d, 0u, pp[h][1] & ~mk[0], v1[g]);
                o[i][0] = pack2(d[0], d[1]); o[i][1] = pack2(d[2], d[3]);
            }
            if (t >= 2) { o[3][0] = o[4][0]; o[3][1] = o[4][1]; }
            const uint32_t dst = sbase + OFF_X + (w >> 1) * HALF + ((w & 1) * 32 + (lane & 15) * 2 + wg) * 16 + (lane >> 4) * 1024;
            stsm4(dst, o[0][0], o[0][1], o[1][0], o[1][1]);
            stsm4(dst + 2048, o[2][0], o[2][1], o[3][0], o[3][1]);
            stsm4(dst + 4096, o[5][0], o[5][1], o[6][0], o[6][1]);
            stsm2(dst + 6144, o[7][0], o[7][1]);
            fence_async_shared();
            bar_sync(4, 288);
            TS0(2, 10 + 19 * wg);
        }
        if (has_g1) {
            last = M.run<0>(a, 16 - n1, 16, LAG1, 1, 32 + PAUSE + LEAD);
            mbar_wait_cluster(bars + B_FREE, 0);
            const uint32_t xb = sbase + OFF_X + wg * 8192 + (threadIdx.x & 127) * 16;
            const uint32_t rx = mapa(xb, rank ^ 1), rbar = mapa(bars + B_X + 8 * wg, rank ^ 1);
            wg_wait<0>();
            pin(a);
            M.release(last);
            TS0(4, 5 + wg);
#pragma unroll
            for (int i = 0; i < 3; i++)
                st_async4(rx + i * 2048, rbar, pack2(a[28 + 8 * i], a[29 + 8 * i]), pack2(a[30 + 8 * i], a[31 + 8 * i]), pack2(a[32 + 8 * i], a[33 + 8 * i]), pack2(a[34 + 8 * i], a[35 + 8 * i]));
            st_async2(rx + 6144, rbar, pack2(a[52], a[53]), pack2(a[54], a[55]));
#pragma unroll
            for (int i = 0; i < 28; i++) a[i] += bf_lo((i & 2) ? bias1 : bias0);
            mbar_wait_cluster(bars + B_X + 8 * wg, 0);
            TS0(4, 1 + wg);
            uint32_t u[16];
#pragma unroll
            for (int i = 0; i < 4; i++) { const uint4 v = lds4(xb + i * 2048); u[4 * i] = v.x; u[4 * i + 1] = v.y; u[4 * i + 2] = v.z; u[4 * i + 3] = v.w; }
            uint8_t* dst = G->U[nt1][((ft >= 7) + wg) * 7 + ft] + rank * HALF + w * 256 + lane * 4;
#pragma unroll
            for (int i = 0; i < 14; i++)
                stg1(dst + (i >> 1) * 1024 + (i & 1) * 128, tag(pack2(gelu2(a[2 * i] + bf_lo(u[i])), gelu2(a[2 * i + 1] + bf_hi(u[i]))), (lane & 7) == warp * 2 + (i & 1), ep));
            __syncwarp();
            if (lane == 0) {
                if (wg == 0) asm volatile("red.relaxed.gpu.global.add.u32 [%0], 1;" ::"l"(G->flag[8 + nt1 * 2] + ft + (ft >= 7) * 25) : "memory");
                mbar_arrive(bars + B_UDONE);
            }
            TS0(4, 30 + wg);
        }
        uint32_t c0 = ld_u16(b2 + mt * 128 + warp * 16 + r), c1 = ld_u16(b2 + mt * 128 + warp * 16 + r + 8);
        last = M.run<1>(a, 4, 4, 0, 0, 48);
        wg_wait<0>();
        M.release(last);
        if (wg == 1) TS0(4, 13);
        c0 *= ks == 0 ? 0x10001u : 0u; c1 *= ks == 0 ? 0x10001u : 0u;
        M.run<2>(a, 14, 14 - NSLOT, LAG2, 1, 52);
        mbar_wait(bars + B_FREE, 0);
        const uint32_t stg = sbase + OFF_X + wg * (OFF_Y - OFF_X) + w * SLAB;
        const uint32_t sa = stg + (lane & 15) * 224 + (lane >> 4) * 16;
        wg_wait<0>();
        pin(a);
        TS0(8, 14 + wg);
#pragma unroll
        for (int g = 0; g < 7; g++)
            stsm4(sa + g * 32, half_plus(pack2(a[8 * g], a[8 * g + 1]), c0), half_plus(pack2(a[8 * g + 2], a[8 * g + 3]), c1),
                  half_plus(pack2(a[8 * g + 4], a[8 * g + 5]), c0), half_plus(pack2(a[8 * g + 6], a[8 * g + 7]), c1));
        fence_async_shared();
        __syncwarp();
        if (elect()) {
            asm volatile("cp.reduce.async.bulk.tensor.2d.global.shared::cta.add.tile.bulk_group [%0, {%2, %3}], [%1];\ncp.async.bulk.commit_group;" ::"l"(&P.tmOut), "r"(stg), "r"(nt2 * 112), "r"(mt * 128 + warp * 16) : "memory");
            if (w == 0) mbar_arrive(bars + B_END);
            asm volatile("cp.async.bulk.wait_group.read 0;" ::: "memory");
        }
        if (wg == 1) TS0(15, 19);
        TSDUMP();
    }
}

typedef CUresult (*EncodeFn)(CUtensorMap*, CUtensorMapDataType, cuuint32_t, void*, const cuuint64_t*, const cuuint64_t*, const cuuint32_t*, const cuuint32_t*,
                             CUtensorMapInterleave, CUtensorMapSwizzle, CUtensorMapL2promotion, CUtensorMapFloatOOBfill);

void make_map(EncodeFn enc, CUtensorMap* tm, const void* base, bool swizzle, int d0, int d1, int d2, int s1, int s2, int b0, int b1, int b2) {
    const cuuint64_t dims[3] = {(cuuint64_t)d0, (cuuint64_t)d1, (cuuint64_t)d2}, strides[2] = {(cuuint64_t)s1 * 2, (cuuint64_t)s2 * 2};
    const cuuint32_t box[3] = {(cuuint32_t)b0, (cuuint32_t)b1, (cuuint32_t)b2}, es[3] = {1, 1, 1};
    enc(tm, CU_TENSOR_MAP_DATA_TYPE_BFLOAT16, d2 ? 3 : 2, (void*)base, dims, strides, box, es, CU_TENSOR_MAP_INTERLEAVE_NONE,
        swizzle ? CU_TENSOR_MAP_SWIZZLE_128B : CU_TENSOR_MAP_SWIZZLE_NONE, CU_TENSOR_MAP_L2_PROMOTION_L2_128B, CU_TENSOR_MAP_FLOAT_OOB_FILL_NONE);
}

}

extern "C" void kernel_launch(void* const* d_in, const int* in_sizes, int n_in, void* d_out, int out_size) {
    static EncodeFn enc = nullptr;
    static Scratch* scratch = nullptr;
    if (!enc) {
        void* fn = nullptr;
        cudaDriverEntryPointQueryResult qr;
        cudaGetDriverEntryPoint("cuTensorMapEncodeTiled", &fn, cudaEnableDefault, &qr);
        enc = (EncodeFn)fn;
        cudaGetSymbolAddress((void**)&scratch, g_s);
        cudaFuncSetAttribute(fused_kernel, cudaFuncAttributeMaxDynamicSharedMemorySize, SMEM_BYTES);
    }
    Params P;
    const __nv_bfloat16* x = (const __nv_bfloat16*)d_in[0];
    make_map(enc, &P.tmX, x, true, D_, S_ / 2, 2, 2 * D_, D_, 64, 64, 2);
    make_map(enc, &P.tmWqkv, d_in[1], true, D_, D_, 3, 3 * D_, D_, 64, 32, 3);
    make_map(enc, &P.tmW1, d_in[4], true, 64, S_, F_ / 64, F_, 64, 64, 64, 2);
    make_map(enc, &P.tmW2, d_in[6], true, S_, F_, 0, S_, 0, 64, 64, 1);
    make_map(enc, &P.tmOut, d_out, false, D_, S_, 0, D_, 0, 112, 16, 1);
    fused_kernel<<<NCTA, NTHREADS, SMEM_BYTES, cudaStreamPerThread>>>(x, (const __nv_bfloat16*)d_in[5], (const __nv_bfloat16*)d_in[7], (const __nv_bfloat16*)d_in[2], (__nv_bfloat16*)d_out, scratch, P);
}
```

```cpp
#include <cuda_runtime.h>
#include <cuda_bf16.h>
#include <cuda.h>
#include <stdint.h>

#define HALO_NS 300
#define HINT 4
#define CHUNK 2
#define WOFIRST 0
#define SPLIT 4
#define EARLYREL 0
#define REC_NS 0
#define ADELAY 0
#define BDELAY 0
#define HOLD 2
#define ROT 4
#define LATEREL 0
#define PF 400
#define PF0 2
#define PF1 8
#define PACE 800
#define PAUSE 7
#define LEAD 0
#define LAG1 4
#define LAG2 4

namespace {

constexpr int S_ = 2048, D_ = 448, F_ = 1792;
constexpr int NCTA = 128, NTHREADS = 384;
constexpr int NSLOT = 6, SLOT = 32768, QSLOT = 40960, TILEB = 14336, SLAB = 3584, HALF = 7168;
constexpr int KV = 1792;
constexpr int OFF_X = NSLOT * SLOT;
constexpr int OFF_Y = OFF_X + 10 * KV;
constexpr int OFF_ST = OFF_Y + TILEB;
constexpr int OFF_BAR = OFF_ST + 1152;
constexpr int SMEM_BYTES = OFF_BAR + 1024;
constexpr uint32_t SMEM0 = 1024;
constexpr int B_QFULL = 0, B_FULL = 56, B_H = 104, B_ROW = 112, B_CS = 120, B_HALO = 128, B_X = 136, B_FREE = 208, B_END = 216, B_QEMPTY = 224, B_EMPTY = 240, NBAR = 36;
constexpr float LN_EPS = 1e-5f;
constexpr int SPIN_LIMIT = 1 << 22;

struct Scratch {
    uint8_t H[4][32][TILEB];
    uint8_t U[4][28][TILEB];
    uint8_t O[16][8][TILEB];
    uint8_t Wo[4][8][TILEB];
    uint8_t halo[NCTA][2 * KV];
    uint2 stat[S_];
    uint2 colsum[8][8][96];
    uint32_t flag[32][32];
    uint32_t epoch[NCTA];
};
__device__ __align__(1024) Scratch g_s;

#define TS(g, i)
#define TS0(g, i)
#define TSDUMP()

struct Params {
    CUtensorMap tmX, tmWqkv, tmW1, tmW2, tmOut;
};

__device__ __forceinline__ bool elect() {
    uint32_t p;
    asm volatile("{\n.reg .pred p;\nelect.sync _|p, 0xffffffff;\nselp.u32 %0, 1, 0, p;\n}" : "=r"(p));
    return p;
}
__device__ __forceinline__ void mbar_init(uint32_t b, uint32_t c) { asm volatile("mbarrier.init.shared::cta.b64 [%0], %1;" ::"r"(b), "r"(c) : "memory"); }
__device__ __forceinline__ void mbar_expect(uint32_t b, uint32_t tx) { asm volatile("mbarrier.arrive.expect_tx.shared::cta.b64 _, [%0], %1;" ::"r"(b), "r"(tx) : "memory"); }
__device__ __forceinline__ void mbar_arrive(uint32_t b) { asm volatile("mbarrier.arrive.shared::cta.b64 _, [%0];" ::"r"(b) : "memory"); }
__device__ __forceinline__ void mbar_arrive_remote(uint32_t b) { asm volatile("mbarrier.arrive.shared::cluster.b64 _, [%0];" ::"r"(b) : "memory"); }
#define MBAR_WAIT_ASM(SEM) \
    asm volatile("{\n.reg .pred p;\nWAIT:\nmbarrier.try_wait.parity" SEM ".shared::cta.b64 p, [%0], %1;\n@!p bra WAIT;\n}" ::"r"(b), "r"(parity) : "memory")
__device__ __forceinline__ void mbar_wait(uint32_t b, uint32_t parity) { MBAR_WAIT_ASM(""); }
__device__ __forceinline__ void mbar_wait_bounded(uint32_t b, uint32_t parity, uint32_t& n) {
    asm volatile("{\n.reg .pred p;\nWAIT:\nadd.u32 %0, %0, 1;\nsetp.gt.u32 p, %0, %3;\n@p st.global.u32 [%4], %0;\n"
                 "mbarrier.try_wait.parity.shared::cta.b64 p, [%1], %2;\n@!p bra WAIT;\n}" : "+r"(n) : "r"(b), "r"(parity), "n"(SPIN_LIMIT), "l"(0ull) : "memory");
}
__device__ __forceinline__ uint32_t mapa(uint32_t a, uint32_t rank) { uint32_t r; asm("mapa.shared::cluster.u32 %0, %1, %2;" : "=r"(r) : "r"(a), "r"(rank)); return r; }
__device__ __forceinline__ void tma3d(uint32_t dst, const CUtensorMap* tm, uint32_t bar, int c0, int c1, int c2) {
    asm volatile("cp.async.bulk.tensor.3d.shared::cluster.global.mbarrier::complete_tx::bytes [%0], [%1, {%3, %4, %5}], [%2];" ::"r"(dst), "l"(tm), "r"(bar), "r"(c0), "r"(c1), "r"(c2) : "memory");
}
__device__ __forceinline__ void tma2d_pair(uint32_t dst, const CUtensorMap* tm, uint32_t bar, int c0, int c1) {
    asm volatile("cp.async.bulk.tensor.2d.shared::cluster.global.mbarrier::complete_tx::bytes.multicast::cluster [%0], [%1, {%3, %4}], [%2], %5;" ::"r"(dst), "l"(tm), "r"(bar), "r"(c0), "r"(c1), "h"((uint16_t)3) : "memory");
}
__device__ __forceinline__ void tma3d_pair(uint32_t dst, const CUtensorMap* tm, uint32_t bar, int c0, int c1, int c2) {
    asm volatile("cp.async.bulk.tensor.3d.shared::cluster.global.mbarrier::complete_tx::bytes.multicast::cluster [%0], [%1, {%3, %4, %5}], [%2], %6;" ::"r"(dst), "l"(tm), "r"(bar), "r"(c0), "r"(c1), "r"(c2), "h"((uint16_t)3) : "memory");
}
__device__ __forceinline__ void bulk_load(uint32_t dst, const void* src, uint32_t bytes, uint32_t bar) {
    asm volatile("cp.async.bulk.shared::cluster.global.mbarrier::complete_tx::bytes [%0], [%1], %2, [%3];" ::"r"(dst), "l"(src), "r"(bytes), "r"(bar) : "memory");
}
__device__ __forceinline__ void bulk_load_pair(uint32_t dst, const void* src, uint32_t bytes, uint32_t bar) {
    asm volatile("cp.async.bulk.shared::cluster.global.mbarrier::complete_tx::bytes.multicast::cluster [%0], [%1], %2, [%3], %4;" ::"r"(dst), "l"(src), "r"(bytes), "r"(bar), "h"((uint16_t)3) : "memory");
}
__device__ __forceinline__ void bulk_store(void* dst, uint32_t src, uint32_t bytes) {
    asm volatile("cp.async.bulk.global.shared::cta.bulk_group [%0], [%1], %2;" ::"l"(dst), "r"(src), "r"(bytes) : "memory");
}
__device__ __forceinline__ uint32_t ld_u16(const void* p) { uint32_t v; asm volatile("ld.global.nc.u16 %0, [%1];" : "=r"(v) : "l"(p)); return v; }
__device__ __forceinline__ uint32_t ld_relaxed(const uint32_t* p) { uint32_t v; asm volatile("ld.relaxed.gpu.global.u32 %0, [%1];" : "=r"(v) : "l"(p) : "memory"); return v; }
__device__ __forceinline__ void bulk_flush() { asm volatile("cp.async.bulk.commit_group;\ncp.async.bulk.wait_group 0;" ::: "memory"); }
__device__ __forceinline__ void signal(uint32_t* flag) { asm volatile("fence.acq_rel.gpu;\nred.relaxed.gpu.global.add.u32 [%0], 1;" ::"l"(flag) : "memory"); }
__device__ __forceinline__ void hint(uint32_t* flag) { asm volatile("red.relaxed.gpu.global.add.u32 [%0], 1;" ::"l"(flag) : "memory"); }
__device__ __forceinline__ uint32_t tag(uint32_t v, uint32_t mask, uint32_t parity) { return (v & ~mask) | (parity & mask); }
__device__ __forceinline__ uint32_t or_diff(uint32_t acc, uint32_t v, uint32_t parity) { asm("lop3.b32 %0, %0, %1, %2, 0xf6;" : "+r"(acc) : "r"(v), "r"(parity)); return acc; }
__device__ __forceinline__ uint4 ld_relaxed4(const void* p) {
    uint4 v;
    asm volatile("ld.relaxed.gpu.global.v4.u32 {%0, %1, %2, %3}, [%4];" : "=r"(v.x), "=r"(v.y), "=r"(v.z), "=r"(v.w) : "l"(p) : "memory");
    return v;
}
__device__ __forceinline__ uint2 ld_relaxed2(const void* p) { uint2 v; asm volatile("ld.relaxed.gpu.global.v2.u32 {%0, %1}, [%2];" : "=r"(v.x), "=r"(v.y) : "l"(p) : "memory"); return v; }
__device__ __forceinline__ void sts2(uint32_t a, uint2 v) { asm volatile("st.shared.v2.b32 [%0], {%1, %2};" ::"r"(a), "r"(v.x), "r"(v.y) : "memory"); }
__device__ __forceinline__ void sts4(uint32_t a, uint4 v) { asm volatile("st.shared.v4.b32 [%0], {%1, %2, %3, %4};" ::"r"(a), "r"(v.x), "r"(v.y), "r"(v.z), "r"(v.w) : "memory"); }
__device__ __forceinline__ void stg1(void* p, uint32_t v) { asm volatile("st.global.b32 [%0], %1;" ::"l"(p), "r"(v) : "memory"); }
__device__ __forceinline__ void fence_async_shared() { asm volatile("fence.proxy.async.shared::cta;" ::: "memory"); }
#define BOUND "add.u32 %0, %0, 16;\nsetp.gt.u32 p, %0, %1;\n@p st.global.u32 [%2], %0;\n"
__device__ __forceinline__ void wait_flag(const uint32_t* p, uint32_t target, uint32_t& n) {
    asm volatile("{\n.reg .pred p;\n.reg .u32 v;\nPOLL:\n" BOUND "ld.acquire.gpu.global.u32 v, [%3];\nsetp.ne.u32 p, v, %4;\n@p bra POLL;\nfence.proxy.async.global;\n}"
                 : "+r"(n) : "n"(SPIN_LIMIT), "l"(0ull), "l"(p), "r"(target) : "memory");
}
__device__ __forceinline__ void wait_flag2(const uint32_t* h, uint32_t th, const uint32_t* p, uint32_t target, uint32_t& n) {
    asm volatile("{\n.reg .pred p;\n.reg .u32 u, v;\nPOLL:\n" BOUND "ld.relaxed.gpu.global.u32 u, [%3];\nld.acquire.gpu.global.u32 v, [%5];\nsetp.ne.u32 p, u, %4;\nsetp.ne.or.u32 p, v, %6, p;\n@p bra POLL;\nfence.proxy.async.global;\n}"
                 : "+r"(n) : "n"(SPIN_LIMIT), "l"(0ull), "l"(h), "r"(th), "l"(p), "r"(target) : "memory");
}
__device__ __forceinline__ void bar_sync(int id, int n) { asm volatile("bar.sync %0, %1;" ::"r"(id), "r"(n) : "memory"); }
__device__ __forceinline__ void bar_arrive(int id, int n) { asm volatile("bar.arrive %0, %1;" ::"r"(id), "r"(n) : "memory"); }
__device__ __forceinline__ void wg_fence() { asm volatile("wgmma.fence.sync.aligned;" ::: "memory"); }
__device__ __forceinline__ void wg_commit() { asm volatile("wgmma.commit_group.sync.aligned;" ::: "memory"); }
template <int N> __device__ __forceinline__ void wg_wait() { asm volatile("wgmma.wait_group.sync.aligned %0;" ::"n"(N) : "memory"); }
template <int N> __device__ __forceinline__ void pin(float (&d)[N]) {
#pragma unroll
    for (int i = 0; i < N; i++) asm volatile("" : "+f"(d[i])::"memory");
}
__host__ __device__ constexpr uint32_t desc_hi(uint32_t sbo, uint32_t swz) { return (sbo >> 4) | (swz << 30); }
__host__ __device__ constexpr uint32_t desc_lo(uint32_t off, uint32_t lbo) { return ((SMEM0 + off) >> 4) | ((lbo >> 4) << 16); }
__device__ __forceinline__ uint32_t pack2(float lo, float hi) { uint32_t r; asm("cvt.rn.bf16x2.f32 %0, %1, %2;" : "=r"(r) : "f"(hi), "f"(lo)); return r; }
__device__ __forceinline__ float bf_lo(uint32_t v) { return __uint_as_float(v << 16); }
__device__ __forceinline__ float bf_hi(uint32_t v) { return __uint_as_float(v & 0xffff0000u); }
__device__ __forceinline__ uint32_t half_plus(uint32_t a, uint32_t b) { uint32_t r; asm("fma.rn.bf16x2 %0, %1, %2, %3;" : "=r"(r) : "r"(a), "r"(0x3f003f00u), "r"(b)); return r; }
__device__ __forceinline__ void stsm4(uint32_t a, uint32_t r0, uint32_t r1, uint32_t r2, uint32_t r3) {
    asm volatile("stmatrix.sync.aligned.m8n8.x4.shared.b16 [%0], {%1, %2, %3, %4};" ::"r"(a), "r"(r0), "r"(r1), "r"(r2), "r"(r3) : "memory");
}
__device__ __forceinline__ void stsm2(uint32_t a, uint32_t r0, uint32_t r1) {
    asm volatile("stmatrix.sync.aligned.m8n8.x2.shared.b16 [%0], {%1, %2};" ::"r"(a), "r"(r0), "r"(r1) : "memory");
}
__device__ __forceinline__ uint4 lds4(uint32_t a) { uint4 v; asm volatile("ld.shared.v4.b32 {%0, %1, %2, %3}, [%4];" : "=r"(v.x), "=r"(v.y), "=r"(v.z), "=r"(v.w) : "r"(a) : "memory"); return v; }
__device__ __forceinline__ uint2 lds2(uint32_t a) { uint2 v; asm volatile("ld.shared.v2.b32 {%0, %1}, [%2];" : "=r"(v.x), "=r"(v.y) : "r"(a) : "memory"); return v; }
__device__ __forceinline__ float lds1f(uint32_t a) { float v; asm volatile("ld.shared.f32 %0, [%1];" : "=f"(v) : "r"(a) : "memory"); return v; }
__device__ __forceinline__ void ldsm4(uint32_t* r, uint32_t a) {
    asm volatile("ldmatrix.sync.aligned.m8n8.x4.shared.b16 {%0, %1, %2, %3}, [%4];" : "=r"(r[0]), "=r"(r[1]), "=r"(r[2]), "=r"(r[3]) : "r"(a) : "memory");
}
__device__ __forceinline__ void ldsm4t(uint32_t* r, uint32_t a) {
    asm volatile("ldmatrix.sync.aligned.m8n8.x4.trans.shared.b16 {%0, %1, %2, %3}, [%4];" : "=r"(r[0]), "=r"(r[1]), "=r"(r[2]), "=r"(r[3]) : "r"(a) : "memory");
}
__device__ __forceinline__ uint32_t transpose8(uint32_t v) { uint32_t r; asm volatile("movmatrix.sync.aligned.m8n8.trans.b16 %0, %1;" : "=r"(r) : "r"(v)); return r; }
__device__ __forceinline__ void mma16(float (&c)[4], uint32_t a0, uint32_t a1, uint32_t a2, uint32_t a3, uint32_t b0, uint32_t b1) {
    asm volatile("mma.sync.aligned.m16n8k16.row.col.f32.bf16.bf16.f32 {%0, %1, %2, %3}, {%4, %5, %6, %7}, {%8, %9}, {%0, %1, %2, %3};"
                 : "+f"(c[0]), "+f"(c[1]), "+f"(c[2]), "+f"(c[3]) : "r"(a0), "r"(a1), "r"(a2), "r"(a3), "r"(b0), "r"(b1));
}
__device__ __forceinline__ void mma8(float (&c)[4], uint32_t a0, uint32_t a1, uint32_t b0) {
    asm volatile("mma.sync.aligned.m16n8k8.row.col.f32.bf16.bf16.f32 {%0, %1, %2, %3}, {%4, %5}, {%6}, {%0, %1, %2, %3};"
                 : "+f"(c[0]), "+f"(c[1]), "+f"(c[2]), "+f"(c[3]) : "r"(a0), "r"(a1), "r"(b0));
}
__device__ __forceinline__ void st_async4(uint32_t a, uint32_t bar, uint32_t v0, uint32_t v1, uint32_t v2, uint32_t v3) {
    asm volatile("st.async.weak.shared::cluster.mbarrier::complete_tx::bytes.v4.b32 [%0], {%2, %3, %4, %5}, [%1];" ::"r"(a), "r"(bar), "r"(v0), "r"(v1), "r"(v2), "r"(v3) : "memory");
}
__device__ __forceinline__ void st_async2(uint32_t a, uint32_t bar, uint32_t v0, uint32_t v1) {
    asm volatile("st.async.weak.shared::cluster.mbarrier::complete_tx::bytes.v2.b32 [%0], {%2, %3}, [%1];" ::"r"(a), "r"(bar), "r"(v0), "r"(v1) : "memory");
}
__device__ __forceinline__ float quad_max(float v) { v = fmaxf(v, __shfl_xor_sync(~0u, v, 1)); return fmaxf(v, __shfl_xor_sync(~0u, v, 2)); }
__device__ __forceinline__ float quad_sum(float v) { v += __shfl_xor_sync(~0u, v, 1); return v + __shfl_xor_sync(~0u, v, 2); }
__device__ __forceinline__ float ex2(float v) { float r; asm("ex2.approx.ftz.f32 %0, %1;" : "=f"(r) : "f"(v)); return r; }
__device__ __forceinline__ float rcp(float v) { float r; asm("rcp.approx.ftz.f32 %0, %1;" : "=f"(r) : "f"(v)); return r; }
__device__ __forceinline__ float rsq(float v) { float r; asm("rsqrt.approx.ftz.f32 %0, %1;" : "=f"(r) : "f"(v)); return r; }
__device__ __forceinline__ float gelu2(float u) {
    float z = u * fmaf(u * u, 0.044715f * 0.7978845608028654f, 0.7978845608028654f), t;
    asm("tanh.approx.f32 %0, %1;" : "=f"(t) : "f"(z));
    return fmaf(u, t, u);
}
__device__ __forceinline__ float oct_sum(float v) {
    v += __shfl_xor_sync(~0u, v, 4); v += __shfl_xor_sync(~0u, v, 8); v += __shfl_xor_sync(~0u, v, 16);
    return v;
}

template <int TA, int TB, uint32_t HA, uint32_t HB>
__device__ __forceinline__ void wgmma_n112(float (&d)[56], uint32_t da, uint32_t db, int accumulate) {
    asm volatile("{\n.reg .pred p;\n.reg .b64 a, b;\nmov.b64 a, {%56, %61};\nmov.b64 b, {%57, %62};\nsetp.ne.b32 p, %58, 0;\n"
        "wgmma.mma_async.sync.aligned.m64n112k16.f32.bf16.bf16 {"
        "%0, %1, %2, %3, %4, %5, %6, %7, %8, %9, %10, %11, %12, %13, %14, %15, "
        "%16, %17, %18, %19, %20, %21, %22, %23, %24, %25, %26, %27, %28, %29, %30, %31, "
        "%32, %33, %34, %35, %36, %37, %38, %39, %40, %41, %42, %43, %44, %45, %46, %47, "
        "%48, %49, %50, %51, %52, %53, %54, %55"
        "}, a, b, p, 1, 1, %59, %60;\n}\n"
        : "+f"(d[0]), "+f"(d[1]), "+f"(d[2]), "+f"(d[3]), "+f"(d[4]), "+f"(d[5]), "+f"(d[6]), "+f"(d[7]),
          "+f"(d[8]), "+f"(d[9]), "+f"(d[10]), "+f"(d[11]), "+f"(d[12]), "+f"(d[13]), "+f"(d[14]), "+f"(d[15]),
          "+f"(d[16]), "+f"(d[17]), "+f"(d[18]), "+f"(d[19]), "+f"(d[20]), "+f"(d[21]), "+f"(d[22]), "+f"(d[23]),
          "+f"(d[24]), "+f"(d[25]), "+f"(d[26]), "+f"(d[27]), "+f"(d[28]), "+f"(d[29]), "+f"(d[30]), "+f"(d[31]),
          "+f"(d[32]), "+f"(d[33]), "+f"(d[34]), "+f"(d[35]), "+f"(d[36]), "+f"(d[37]), "+f"(d[38]), "+f"(d[39]),
          "+f"(d[40]), "+f"(d[41]), "+f"(d[42]), "+f"(d[43]), "+f"(d[44]), "+f"(d[45]), "+f"(d[46]), "+f"(d[47]),
          "+f"(d[48]), "+f"(d[49]), "+f"(d[50]), "+f"(d[51]), "+f"(d[52]), "+f"(d[53]), "+f"(d[54]), "+f"(d[55])
        : "r"(da), "r"(db), "r"(accumulate), "n"(TA), "n"(TB), "n"(HA), "n"(HB));
}

template <int TA, int TB, uint32_t HA, uint32_t HB>
__device__ __forceinline__ void wgmma_n184(float (&d)[92], uint32_t da, uint32_t db, int accumulate) {
    asm volatile("{\n.reg .pred p;\n.reg .b64 a, b;\nmov.b64 a, {%92, %97};\nmov.b64 b, {%93, %98};\nsetp.ne.b32 p, %94, 0;\n"
        "wgmma.mma_async.sync.aligned.m64n184k16.f32.bf16.bf16 {"
        "%0, %1, %2, %3, %4, %5, %6, %7, %8, %9, %10, %11, %12, %13, %14, %15, "
        "%16, %17, %18, %19, %20, %21, %22, %23, %24, %25, %26, %27, %28, %29, %30, %31, "
        "%32, %33, %34, %35, %36, %37, %38, %39, %40, %41, %42, %43, %44, %45, %46, %47, "
        "%48, %49, %50, %51, %52, %53, %54, %55, %56, %57, %58, %59, %60, %61, %62, %63, "
        "%64, %65, %66, %67, %68, %69, %70, %71, %72, %73, %74, %75, %76, %77, %78, %79, "
        "%80, %81, %82, %83, %84, %85, %86, %87, %88, %89, %90, %91"
        "}, a, b, p, 1, 1, %95, %96;\n}\n"
        : "+f"(d[0]), "+f"(d[1]), "+f"(d[2]), "+f"(d[3]), "+f"(d[4]), "+f"(d[5]), "+f"(d[6]), "+f"(d[7]),
          "+f"(d[8]), "+f"(d[9]), "+f"(d[10]), "+f"(d[11]), "+f"(d[12]), "+f"(d[13]), "+f"(d[14]), "+f"(d[15]),
          "+f"(d[16]), "+f"(d[17]), "+f"(d[18]), "+f"(d[19]), "+f"(d[20]), "+f"(d[21]), "+f"(d[22]), "+f"(d[23]),
          "+f"(d[24]), "+f"(d[25]), "+f"(d[26]), "+f"(d[27]), "+f"(d[28]), "+f"(d[29]), "+f"(d[30]), "+f"(d[31]),
          "+f"(d[32]), "+f"(d[33]), "+f"(d[34]), "+f"(d[35]), "+f"(d[36]), "+f"(d[37]), "+f"(d[38]), "+f"(d[39]),
          "+f"(d[40]), "+f"(d[41]), "+f"(d[42]), "+f"(d[43]), "+f"(d[44]), "+f"(d[45]), "+f"(d[46]), "+f"(d[47]),
          "+f"(d[48]), "+f"(d[49]), "+f"(d[50]), "+f"(d[51]), "+f"(d[52]), "+f"(d[53]), "+f"(d[54]), "+f"(d[55]),
          "+f"(d[56]), "+f"(d[57]), "+f"(d[58]), "+f"(d[59]), "+f"(d[60]), "+f"(d[61]), "+f"(d[62]), "+f"(d[63]),
          "+f"(d[64]), "+f"(d[65]), "+f"(d[66]), "+f"(d[67]), "+f"(d[68]), "+f"(d[69]), "+f"(d[70]), "+f"(d[71]),
          "+f"(d[72]), "+f"(d[73]), "+f"(d[74]), "+f"(d[75]), "+f"(d[76]), "+f"(d[77]), "+f"(d[78]), "+f"(d[79]),
          "+f"(d[80]), "+f"(d[81]), "+f"(d[82]), "+f"(d[83]), "+f"(d[84]), "+f"(d[85]), "+f"(d[86]), "+f"(d[87]),
          "+f"(d[88]), "+f"(d[89]), "+f"(d[90]), "+f"(d[91])
        : "r"(da), "r"(db), "r"(accumulate), "n"(TA), "n"(TB), "n"(HA), "n"(HB));
}

template <uint32_t HB>
__device__ __forceinline__ void wgmma_rs_n184(float (&d)[92], uint32_t a0, uint32_t a1, uint32_t db) {
    asm volatile("{\n.reg .b64 b;\nmov.b64 b, {%94, %96};\n"
        "wgmma.mma_async.sync.aligned.m64n184k16.f32.bf16.bf16 {"
        "%0, %1, %2, %3, %4, %5, %6, %7, %8, %9, %10, %11, %12, %13, %14, %15, "
        "%16, %17, %18, %19, %20, %21, %22, %23, %24, %25, %26, %27, %28, %29, %30, %31, "
        "%32, %33, %34, %35, %36, %37, %38, %39, %40, %41, %42, %43, %44, %45, %46, %47, "
        "%48, %49, %50, %51, %52, %53, %54, %55, %56, %57, %58, %59, %60, %61, %62, %63, "
        "%64, %65, %66, %67, %68, %69, %70, %71, %72, %73, %74, %75, %76, %77, %78, %79, "
        "%80, %81, %82, %83, %84, %85, %86, %87, %88, %89, %90, %91"
        "}, {%92, %93, %95, %95}, b, 1, 1, 1, 0;\n}\n"
        : "+f"(d[0]), "+f"(d[1]), "+f"(d[2]), "+f"(d[3]), "+f"(d[4]), "+f"(d[5]), "+f"(d[6]), "+f"(d[7]),
          "+f"(d[8]), "+f"(d[9]), "+f"(d[10]), "+f"(d[11]), "+f"(d[12]), "+f"(d[13]), "+f"(d[14]), "+f"(d[15]),
          "+f"(d[16]), "+f"(d[17]), "+f"(d[18]), "+f"(d[19]), "+f"(d[20]), "+f"(d[21]), "+f"(d[22]), "+f"(d[23]),
          "+f"(d[24]), "+f"(d[25]), "+f"(d[26]), "+f"(d[27]), "+f"(d[28]), "+f"(d[29]), "+f"(d[30]), "+f"(d[31]),
          "+f"(d[32]), "+f"(d[33]), "+f"(d[34]), "+f"(d[35]), "+f"(d[36]), "+f"(d[37]), "+f"(d[38]), "+f"(d[39]),
          "+f"(d[40]), "+f"(d[41]), "+f"(d[42]), "+f"(d[43]), "+f"(d[44]), "+f"(d[45]), "+f"(d[46]), "+f"(d[47]),
          "+f"(d[48]), "+f"(d[49]), "+f"(d[50]), "+f"(d[51]), "+f"(d[52]), "+f"(d[53]), "+f"(d[54]), "+f"(d[55]),
          "+f"(d[56]), "+f"(d[57]), "+f"(d[58]), "+f"(d[59]), "+f"(d[60]), "+f"(d[61]), "+f"(d[62]), "+f"(d[63]),
          "+f"(d[64]), "+f"(d[65]), "+f"(d[66]), "+f"(d[67]), "+f"(d[68]), "+f"(d[69]), "+f"(d[70]), "+f"(d[71]),
          "+f"(d[72]), "+f"(d[73]), "+f"(d[74]), "+f"(d[75]), "+f"(d[76]), "+f"(d[77]), "+f"(d[78]), "+f"(d[79]),
          "+f"(d[80]), "+f"(d[81]), "+f"(d[82]), "+f"(d[83]), "+f"(d[84]), "+f"(d[85]), "+f"(d[86]), "+f"(d[87]),
          "+f"(d[88]), "+f"(d[89]), "+f"(d[90]), "+f"(d[91])
        : "r"(a0), "r"(a1), "r"(db), "r"(0), "n"(HB));
}

struct Ring {
    uint32_t slot, ph;
    __device__ __forceinline__ void next() { if (++slot == NSLOT) { slot = 0; ph ^= 1; } }
};
__device__ __forceinline__ uint32_t xslot(int i) { return __byte_perm(0x04130e0cu, 0x00130e0cu, 0x7770 + i); }
__device__ __forceinline__ uint32_t wslot(int i) { return __byte_perm(0x06001510u, 0x00151009u, 0x7770 + i); }

constexpr uint32_t HI_SW = desc_hi(1024, 1);

struct Mma {
    uint32_t bars, rel;
    bool lead;
    int wg, w;
    Ring r;
    __device__ __forceinline__ void release(uint32_t s) { if (lead) mbar_arrive_remote(rel + B_EMPTY + 8 * s); }
    template <int KIND>
    __device__ __forceinline__ uint32_t run(float (&a)[56], int n, int nrel, int lag, int accumulate, int ts) {
        uint32_t prev = 0;
#pragma unroll 1
        for (int i = 0; i < n; i++) {
            const bool held = lag && i == (wg ? n - lag : -1);
            if (held) { if (KIND == 0 && EARLYREL) { wg_wait<0>(); release(prev); } bar_sync(7, 256); }
            const uint32_t s = r.slot;
            mbar_wait(bars + B_FULL + 8 * s, r.ph); r.next();
            TS0(KIND ? 8 : 2, ts + i + wg * 68);
            const uint32_t dB = s * (SLOT >> 4), dA = dB + wg * 512;
            wg_fence();
#pragma unroll
            for (int k = 0; k < 4; k++) {
                const int acc = k > 0 || accumulate || i > 0;
                if (KIND == 0) wgmma_n112<1, 1, HI_SW, desc_hi(256, 0)>(a, dA + desc_lo(k * 2048, 8192), dB + desc_lo(16384 + k * SLAB, 128), acc);
                if (KIND == 1) wgmma_n112<0, 1, desc_hi(128, 0), desc_hi(1024, 0)>(a, dA + desc_lo(k * 2048, k < 3 ? 1024 : 0), dB + desc_lo(16384 + k * 256, 128), acc);
                if (KIND == 2) wgmma_n112<1, 1, HI_SW, desc_hi(1024, 0)>(a, dA + desc_lo(k * 2048, 8192), dB + desc_lo(16384 + k * 256, 128), acc);
                if (k == 1) {
                    wg_commit(); wg_wait<1>();
                    if ((uint32_t)(i - 1) < (uint32_t)nrel && !(KIND == 0 && EARLYREL && held)) release(prev);
                    if (lag && i == (wg ? -1 : n - 1)) bar_arrive(7, 256);
                }
            }
            wg_commit();
            prev = s;
        }
        return prev;
    }
};

__global__ void __cluster_dims__(2, 1, 1) __launch_bounds__(NTHREADS, 1)
fused_kernel(const __nv_bfloat16* __restrict__ x, const __nv_bfloat16* __restrict__ b1, const __nv_bfloat16* __restrict__ b2, const __nv_bfloat16* __restrict__ wo, __nv_bfloat16* out, Scratch* G,
             const __nv_bfloat16* __restrict__ w1, const __nv_bfloat16* __restrict__ w2,
             const __grid_constant__ Params P) {
    extern __shared__ __align__(1024) uint8_t smem[];
    const uint32_t sbase = (uint32_t)__cvta_generic_to_shared(smem);
    const uint32_t bars = sbase + OFF_BAR;
    const int lane = threadIdx.x & 31;
    const int warp = __shfl_sync(~0u, threadIdx.x >> 5, 0), w = warp & 3;
    const uint32_t rank = blockIdx.x & 1, pr = blockIdx.x >> 1;
    const uint32_t pv = pr < 4 ? pr * 8 + 36 : pr < 40 ? pr - 4 : pr - 3 + (((pr - 40) * 37) >> 8);
    const uint32_t gp = (pv + 4) & 7, hp = pv >> 3;
    const uint32_t tb = gp * 2 + rank, c = hp * 16 + tb, row0 = (tb * 8 + hp) * 16;
    const bool has_g1 = gp > 0;
    const uint32_t nt1 = hp & 3, ft = max((int)gp - 1, 0) * 2 + (hp >> 2);
    const uint32_t nt2 = tb & 3, mt = (gp & 2) * 4 + hp, ks = gp >> 2;

    if (elect()) {
        if (warp == 0) TS(15, 0);
#pragma unroll
        for (int i = 0; i < 3; i++) mbar_init(bars + warp * 24 + 8 * i, warp * 24 + 8 * i < B_FREE ? 1 : warp * 24 + 8 * i < B_QEMPTY ? 2 : 4);
        asm volatile("fence.mbarrier_init.release.cluster;" ::: "memory");
        if (warp == B_ROW / 24) {
            mbar_expect(bars + B_ROW, TILEB);
            bulk_load(sbase + OFF_Y, x + row0 * D_, TILEB, bars + B_ROW);
        }
    }
    __syncwarp();
    asm volatile("barrier.cluster.arrive.relaxed.aligned;\nbarrier.cluster.wait.aligned;" ::: "memory");

    if (warp == 8) {
        if (elect()) {
            uint32_t spins = (sbase & 0xffffffu) == SMEM0 ? 0 : SPIN_LIMIT;
            uint32_t kw = gp % ROT * (512 / ROT), kx = kw;
            uint32_t due = (uint32_t)clock(), ep = 0;
#pragma unroll 1
            for (int i = 0; i < 8; i++) {
                if (i >= 5) mbar_wait_bounded(bars + B_QEMPTY + 8 * (i - 5), 0, spins);
                else { while ((int)((uint32_t)clock() - due) < 0) {} due += PACE; }
                if (kw == D_) kw = 0;
                if (i < 4) kx = kw;
                const int ix = i - (i > 4);
                if (i < 7) mbar_expect(bars + B_QFULL + 8 * i, QSLOT);
                if (i != 4) tma3d(sbase + xslot(ix) * 8192, &P.tmX, bars + B_QFULL + 8 * ix, kx, tb * 64, 0);
                if (i == 5) mbar_wait_bounded(bars + B_CS, 0, spins);
                if (i < 7) tma3d_pair(sbase + wslot(i) * 8192 + rank * 12288, &P.tmWqkv, bars + B_QFULL + 8 * i, (hp * 56) & ~15, kw + rank * 32, 0);
                kx = kw; kw += 64;
                if (i == 0) { TS(1, 23); ep = ld_relaxed(&G->epoch[c]); }
            }
            ep++;
            if (PF && !has_g1) {
                due = (uint32_t)clock();
#pragma unroll 1
                for (int j = PF0; j < PF1; j++) {
                    const __nv_bfloat16* p = j < 16 ? w1 + (rank * 1024 + j * 64 + hp * 8) * F_ : w2 + (rank * 896 + j * 128 - (j < 23 ? 2048 : 2880) + hp * 8) * S_;
                    asm volatile("cp.async.bulk.prefetch.L2.global [%0], %1;" ::"l"(p), "r"(j < 16 ? 16 * F_ : 16 * S_) : "memory");
                    due += PF;
                    while ((int)((uint32_t)clock() - due) < 0) {}
                }
            }
            Ring r{0, 0};
            const uint8_t* src = G->H[nt1][rank * 16];
#pragma unroll 1
            for (int j = has_g1 ? 0 : 16; j < 34; j++) {
                const uint32_t dst = sbase + r.slot * SLOT, landed = bars + B_QFULL + 8 * r.slot, full = landed + (B_FULL - B_QFULL);
                if (j == 4) mbar_wait_bounded(bars + B_H, 0, spins);
                if (j == 16) {
                    src = G->Wo[nt2][ks * 4];
                    wait_flag2(G->flag[16 + mt], 8 * ep, G->flag[0], 16 * ep, spins);
                    TS(4, 18);
                }
                mbar_wait_bounded(bars + B_EMPTY + 8 * r.slot, r.ph, spins);
                if ((j >> 3) == 1) mbar_expect(bars + B_X + 8 * 15 - 8 * j, (j & 3) ? 2048 : 1024);
                if (j < 14) TS(2, 146 + j);
                if (j < 16) { mbar_expect(full, 16384 + TILEB); tma3d(dst, &P.tmW1, full, 0, rank * 1024 + j * 64, ft * 2); }
                else if (j < 20) { mbar_expect(landed, TILEB); bulk_load_pair(dst + rank * 8192, G->O[mt][ks * 4 + j - 16] + rank * HALF, HALF, landed); }
                else tma2d_pair(dst + rank * 8192, &P.tmW2, full, mt * 128 + rank * 64, ks * 896 + j * 128 - (j < 27 ? 2560 : 3392));
                if (j == 0) { wait_flag(G->flag[1] + rank * 2, 16 * ep, spins); TS(1, 16); }
                if (j < 20) bulk_load(dst + 16384, src, TILEB, full);
                src += TILEB;
                r.next();
            }
            mbar_wait_bounded(bars + B_END, 0, spins);
        }
    } else if (warp > 8) {
        const uint32_t ep = ld_relaxed(&G->epoch[c]) + 1;
        {
            const uint32_t src = (sbase + wslot(gp / ROT) * 8192 - 4096 + w * 4096 + rank * 64 + (lane & 15) * 4 + (lane >> 4) * 12288) ^ ((lane >> 4) * 576);
            float s0 = 0.f, s1 = 0.f, s2 = 0.f, s3 = 0.f;
            mbar_wait(bars + B_QFULL + 8 * (gp / ROT), 0);
            if (w == 1) TS(1, 66);
            uint32_t v[32];
#pragma unroll
            for (int k = 0; k < 32; k++) v[k] = __float_as_uint(lds1f((src ^ ((k & 7) * 144)) + (k >> 3) * 1024));
#pragma unroll
            for (int k = 0; k < 32; k += 2) { s0 += bf_lo(v[k]); s1 += bf_hi(v[k]); s2 += bf_lo(v[k + 1]); s3 += bf_hi(v[k + 1]); }
            s0 += s2; s1 += s3;
            s0 += __shfl_xor_sync(~0u, s0, 16); s1 += __shfl_xor_sync(~0u, s1, 16);
            uint2* cs = G->colsum[hp][0] + w * 32 - 32;
            if (lane < 16) cs[gp * 96 + rank * 16 + lane] = make_uint2(tag(__float_as_uint(s0), 1, ep), __float_as_uint(s1));
            if (w == 1) TS(1, 24);
            if (w == 2) {
                bar_sync(6, 224);
                TS(1, 8);
                if (elect()) { mbar_arrive(bars + B_CS); signal(G->flag[1] + (gp >> 2) * 2 + ((gp & 3) > 0)); TS(1, 3); }
                __syncwarp();
            } else {
                bar_arrive(6, 224);
            }
            bar_sync(1, 96);
            if (REC_NS) __nanosleep(REC_NS);
            const int i0 = threadIdx.x - 288, i1 = min(i0 + 96, 143);
            uint2 u[9];
            uint32_t bad;
            do {
                bad = 0;
#pragma unroll
                for (int i = 0; i < 9; i++) {
                    u[i] = ld_relaxed2(i < 7 ? cs + i * 96 + lane : G->stat + max((int)tb * 128 - 16 + (i == 7 ? i0 : i1), 0));
                    bad = or_diff(bad, u[i].x, ep);
                }
            } while (bad & 1);
            sts2(sbase + OFF_ST + i0 * 8, u[7]); sts2(sbase + OFF_ST + i1 * 8, u[8]);
#pragma unroll
            for (int e = 0; e < 2; e++) {
                float f = 0.f;
#pragma unroll
                for (int i = 0; i < 7; i++) f += __uint_as_float(e ? u[i].y : u[i].x);
                const uint32_t hi = pack2(f, f);
                sts4(sbase + OFF_X + i0 * 32 + e * 16, make_uint4(hi, pack2(f - bf_hi(hi), f - bf_hi(hi)), 0, 0));
            }
            asm volatile("st.shared.u32 [%0], %1;" ::"r"(bars + 8 * NBAR), "r"(ep) : "memory");
            fence_async_shared();
            __syncwarp();
            bar_arrive(8, 224); bar_arrive(9, 224);
            TS(1, 90 + w);
        }
        if (w == 1) {
            if (elect()) {
                uint32_t spins = 0;
                wait_flag(G->flag[1] + rank * 2 + 1, 48 * ep, spins);
                mbar_arrive(bars + B_H);
                TS(1, 96);
                __nanosleep(5000);
                wait_flag(G->flag[16 + mt] + 1, 8 * ep, spins);
                mbar_arrive(bars + B_ROW);
                TS(2, 27);
                G->epoch[c] = ep;
            }
        } else {
            const uint8_t* src = G->U[nt2][ks * 14];
            if (w == 2) {
                bar_sync(3, 288);
                __nanosleep(HALO_NS);
                uint4 v[7];
                uint32_t bad;
                do {
                    bad = 0;
#pragma unroll
                    for (int i = 0; i < 7; i++) { v[i] = ld_relaxed4(G->halo[c - (tb > 0)] + i * 512 + lane * 16); bad = or_diff(bad, v[i].x, ep); }
                } while (bad & 1);
#pragma unroll
                for (int i = 0; i < 7; i++) sts4(sbase + OFF_X + i * 512 + lane * 16, v[i]);
                __syncwarp();
                if (elect()) mbar_arrive(bars + B_HALO);
                TS(2, 21);
                if (!has_g1) { bar_sync(5, 288); if (elect()) signal(G->flag[0]); __syncwarp(); TS(2, 26); }
                const uint8_t* cur = G->O[mt][ks * 4];
                uint32_t slot = has_g1 ? 16 % NSLOT : 0, ph = ~0u;
#pragma unroll 1
                for (int i = 0; i < 18;) {
                    const uint32_t d0 = sbase + slot * SLOT + (i < 4 ? 0 : 16384), d1 = d0 + (i < 4 ? 8192 : HALF), landed = bars + B_QFULL + 8 * slot;
                    mbar_wait(landed, (ph >> slot) & 1);
                    ph ^= 1 << slot;
                    if (i < 8) TS(4, 82 + i);
                    bad = 0;
#pragma unroll
                    for (int k = 0; k < 14; k++) bad = or_diff(bad, __float_as_uint(lds1f((k < 7 ? d0 : d1) + k % 7 * 1024 + lane * 32 + (lane >> 2) * 4)), ep);
                    if (__any_sync(~0u, bad & 1)) {
                        if (elect()) {
                            fence_async_shared();
                            mbar_expect(landed, TILEB);
                            bulk_load(d0, cur, HALF, landed);
                            bulk_load(d1, cur + HALF, HALF, landed);
                        }
                        TS(4, i < 4 ? 94 : 95);
                    } else {
                        if (elect()) mbar_expect(landed + (B_FULL - B_QFULL), i < 4 ? TILEB : 16384);
                        cur = ++i == 4 ? src : cur + TILEB;
                        if (++slot == NSLOT) slot = 0;
                    }
                }
            } else {
                bar_sync(2, 288);
                if (elect()) bulk_store(out + row0 * D_, sbase + OFF_Y, TILEB);
                __syncwarp();
                bar_sync(4, 288);
                if (elect()) {
                    bulk_store(G->O[tb][hp], sbase + OFF_X, TILEB);
                    bulk_flush();
                    TS(2, 7);
                    mbar_arrive_remote(mapa(bars + B_FREE, rank ^ 1));
                    mbar_arrive(bars + B_FREE);
                    hint(G->flag[16 + tb]);
                    signal(G->flag[16 + tb] + 1);
                    TS(2, 22);
                }
                __syncwarp();
                uint32_t late = ~0u;
                Ring r{has_g1 ? 20u % NSLOT : 4u, has_g1};
#pragma unroll 1
                for (int i = 0; i < 14; i++) {
                    while ((late >> i) & 1) late = __ballot_sync(~0u, ld_relaxed(G->flag[8 + nt2 * 2 + ks] + lane) != 2 * ep) & 127;
                    if (i == 0) { TS(4, 17); mbar_wait(bars + (has_g1 ? B_X : B_FREE), 0); }
                    mbar_wait(bars + B_EMPTY + 8 * r.slot, r.ph);
                    if (elect()) {
                        mbar_expect(bars + B_QFULL + 8 * r.slot, TILEB);
                        bulk_load(sbase + r.slot * SLOT + 16384, src, TILEB, bars + B_QFULL + 8 * r.slot);
                    }
                    src += TILEB; r.next();
                }
            }
        }
    } else {
        const int wg = warp >> 2;
        Mma M{bars, mapa(bars, rank ^ (lane & 1)), (threadIdx.x & 127) < 2, wg, w, Ring{0, 0}};
        const int r = lane >> 2, t = lane & 3;
        uint32_t ep;
        const uint32_t bias0 = ld_u16(b1 + ft * 128 + warp * 16 + r), bias1 = ld_u16(b1 + ft * 128 + warp * 16 + r + 8);
        if (wg == 1) {
            ep = ld_relaxed(&G->epoch[c]);
            const int r16 = w * 4 + t, c8 = (r + 2 * t) & 7;
            const uint32_t row = sbase + OFF_Y + r16 * (2 * D_) + c8 * 16;
            mbar_wait(bars + B_ROW, 0);
            TS0(1, 67);
            float f[56];
#pragma unroll
            for (int i = 0; i < 7; i++) {
                const uint4 v = lds4(row + i * 128);
                f[8 * i] = bf_lo(v.x); f[8 * i + 1] = bf_hi(v.x); f[8 * i + 2] = bf_lo(v.y); f[8 * i + 3] = bf_hi(v.y);
                f[8 * i + 4] = bf_lo(v.z); f[8 * i + 5] = bf_hi(v.z); f[8 * i + 6] = bf_lo(v.w); f[8 * i + 7] = bf_hi(v.w);
            }
            float s0 = f[0], s1 = f[1], s2 = f[2], s3 = f[3];
#pragma unroll
            for (int i = 4; i < 56; i += 4) { s0 += f[i]; s1 += f[i + 1]; s2 += f[i + 2]; s3 += f[i + 3]; }
            const float nmean = oct_sum((s0 + s1) + (s2 + s3)) * (-1.f / D_);
            s0 = s1 = s2 = s3 = 0.f;
#pragma unroll
            for (int i = 0; i < 56; i += 4) {
                f[i] += nmean; f[i + 1] += nmean; f[i + 2] += nmean; f[i + 3] += nmean;
                s0 = fmaf(f[i], f[i], s0); s1 = fmaf(f[i + 1], f[i + 1], s1); s2 = fmaf(f[i + 2], f[i + 2], s2); s3 = fmaf(f[i + 3], f[i + 3], s3);
            }
            const float var = oct_sum((s0 + s1) + (s2 + s3)) * (1.f / D_);
            const float rstd = rsq(var + LN_EPS);
            const float sc = rstd * rsq(fmaf(var * rstd, rstd, LN_EPS));
            if (lane < 4) G->stat[row0 + r16] = make_uint2(tag(__float_as_uint(rstd + rstd), 1, ~ep), pack2(nmean, nmean - bf_hi(pack2(nmean, nmean))));
            uint8_t* hb = G->H[0][0] + row0 * (SLAB / 16) + r16 * 16 + c8 * 256;
            const int sw = tb < 8 ? 0 : 7 * 256;
#pragma unroll
            for (int i = 0; i < 7; i++) {
                const int lo = (8 * i) % 14, nt = (8 * i) / 14, next = 32 * TILEB - SLAB;
                const int off = lo < 7 ? (c8 < 7 - lo ? sw : -sw) : (c8 >= 14 - lo ? sw + next : -sw);
                *(uint4*)(hb + off + i * 2048 + nt * next) = make_uint4(pack2(f[8 * i] * sc, f[8 * i + 1] * sc), pack2(f[8 * i + 2] * sc, f[8 * i + 3] * sc),
                                                                        pack2(f[8 * i + 4] * sc, f[8 * i + 5] * sc), pack2(f[8 * i + 6] * sc, f[8 * i + 7] * sc));
            }
            TS0(1, 25);
            bar_arrive(6, 224);
        }
        const uint32_t kv = sbase + OFF_X + (w * 2 + wg) * KV + lane * 16;
        const uint32_t st = sbase + OFF_ST + (16 + w * 32 + wg) * 8;
        uint32_t q[7][2], k0[7], v0[7];
        {
            float acc[92];
            if (ADELAY) { mbar_wait(bars + B_QFULL, 0); if (wg == 0 || BDELAY) { const uint32_t t0 = clock(); while ((uint32_t)clock() - t0 < ADELAY) {} } }
#pragma unroll 1
            for (int kb = 0; kb < 7; kb++) {
                const bool held = kb == (wg ? 7 - HOLD : -1);
                if (held) { wg_wait<0>(); if (M.lead) mbar_arrive_remote(M.rel + B_QEMPTY + 8 * (6 - HOLD)); bar_sync(7, 256); }
                mbar_wait(bars + B_QFULL + 8 * kb, 0);
                TS0(1, 68 + wg * 7 + kb);
                const uint32_t dA = (xslot(kb) + wg) * 512, dB = wslot(kb) * 512 + (hp & 1);
                wg_fence();
#pragma unroll
                for (int k = 0; k < 4; k++) {
                    wgmma_n184<0, 1, HI_SW, HI_SW>(acc, dA + desc_lo(k * 32, 16), dB + desc_lo((k & 1) * 2048 + (k >> 1) * 12288, 4096), k > 0 || kb > 0);
                    if (k == 0) { wg_commit(); wg_wait<1>(); if (M.lead && kb > 0 && !held) mbar_arrive_remote(M.rel + B_QEMPTY + 8 * (kb - 1)); }
                }
                wg_commit();
            }
            if (wg == 0 && !LATEREL) bar_arrive(7, 256);
            bar_sync(8 + wg, 224);
            ep = __float_as_uint(lds1f(bars + 8 * NBAR));
            const uint32_t n0 = __float_as_uint(lds1f(st + r * 16 + 4)), n1 = __float_as_uint(lds1f(st + r * 16 + 132));
            const uint32_t a0 = t < 2 ? n0 : 0, a1 = t < 2 ? n1 : 0;
            wg_fence();
            wgmma_rs_n184<desc_hi(128, 0)>(acc, a0, a1, desc_lo(OFF_X, 0) + (hp & 1) * 8);
            wg_commit();
            if (wg == 0 && LATEREL) bar_arrive(7, 256);
            wg_wait<0>();
            pin(acc);
            M.release(4); M.release(5);
            mbar_wait(bars + B_QFULL, 0);
            TS0(1, 4 + 7 * wg);
            uint32_t hi[14];
#pragma unroll
            for (int p = 2; p >= 0; p--) {
#pragma unroll
                for (int g = 0; g < 7; g++) {
                    const int a = (p * 8 + g) * 4;
                    const uint32_t lo2 = pack2(acc[a], acc[a + 1]), hi2 = pack2(acc[a + 2], acc[a + 3]);
                    if (p == 0) { q[g][0] = lo2; q[g][1] = hi2; } else { (p == 1 ? k0 : v0)[g] = lo2; hi[(p - 1) * 7 + g] = hi2; }
                }
                if (p == 1) {
#pragma unroll
                    for (int i = 0; i < 3; i++) stsm4(kv + 2 * KV + i * 512, hi[4 * i], hi[4 * i + 1], hi[4 * i + 2], hi[4 * i + 3]);
                    stsm2(kv + 2 * KV + 1536, hi[12], hi[13]);
                    if (w == 3) {
#pragma unroll
                        for (int i = 0; i < 14; i++) stg1(G->halo[c] + wg * KV + lane * 4 + i * 128, tag(hi[i], t == 0, ep));
                    }
                    bar_arrive(3, 288);
                }
            }
        }
        TS0(1, 9 + 11 * wg);
        float a[56];
#pragma unroll
        for (int i = 0; i < 56; i++) asm volatile("" : "=f"(a[i]));
        const int n1 = PAUSE + (wg == 0 ? LEAD : 0);
        if (__builtin_expect(!has_g1, 0)) {
            const int g = min(lane >> 1, 13), k = w * 16 + (lane & 1), nt = rank * 2 + wg;
            const uint4* src = (const uint4*)(wo + (hp * 56 + k) * D_ + nt * 112) + g;
            uint4 v[8] = {};
#pragma unroll
            for (int i = 0; i < 8; i++) if (i < 4 || w < 3) v[i] = __ldg(src + i * (D_ / 4));
#pragma unroll
            for (int i = 0; i < 8; i++) ((uint4*)G->Wo[nt][hp])[g * 64 + k + 2 * i] = v[i];
            bar_arrive(5, 288);
        }
        uint32_t last = M.run<0>(a, has_g1 ? n1 : 0, 16, 0, 0, 32);
        {
            uint32_t kp[8], k1[8], vp[8], v1[8];
            TS0(2, 140 + wg);
            mbar_wait(bars + B_HALO, 0);
            TS0(2, 142 + wg);
            ldsm4(kp, kv); ldsm4(kp + 4, kv + 512); ldsm4(k1, kv + 2 * KV); ldsm4(k1 + 4, kv + 2 * KV + 512);
            ldsm4t(vp, kv + 896); ldsm4t(vp + 4, kv + 1408); ldsm4t(v1, kv + 2 * KV + 896); ldsm4t(v1 + 4, kv + 2 * KV + 1408);
#pragma unroll
            for (int g = 0; g < 7; g++) v0[g] = transpose8(v0[g]);
            const bool e0 = 2 * t > r, e1 = 2 * t >= r;
            const uint32_t ka = st + t * 32 - (e0 ? 128 : 0), kb = st + t * 32 + 16 - (e1 ? 128 : 0);
            const float rk[4] = {lds1f(ka), lds1f(kb), lds1f(ka + 128), lds1f(kb + 128)};
            const float sq0 = lds1f(st + r * 16) * (0.25f * 0.1889822365046136f * 1.4426950408889634f), sq1 = lds1f(st + r * 16 + 128) * (0.25f * 0.1889822365046136f * 1.4426950408889634f);
            float sc[6] = {sq0 * rk[0], sq0 * rk[1], sq1 * rk[2], sq1 * rk[3], 0.f, 0.f};
            if (tb == 0 && w == 0) { sc[4] = e0 ? -1e30f : 0.f; sc[5] = e1 ? -1e30f : 0.f; }
            uint32_t mk[6] = {(e0 ? 0xffffu : 0u) | (e1 ? 0xffff0000u : 0u), 0u, t < 2 ? q[3][0] : 0u, t < 2 ? q[3][1] : 0u, t < 2 ? 0u : q[3][0], t < 2 ? 0u : q[3][1]};
            wg_wait<0>();
            pin(a);
            if (has_g1) M.release(last);
            TS0(2, 144 + wg);
            bar_sync(2, 288);
            mbar_wait(bars + B_HALO, 0);
            TS0(2, 12 + 16 * wg);
            float sv[2][4];
#pragma unroll
            for (int h = 0; h < 2; h++) {
                const int ga = h * 4, gb = h * 4 + 1, gc = h * 4 + 2;
                float s[3][4] = {};
                mma16(s[0], q[ga][0], q[ga][1], q[gb][0], q[gb][1], kp[ga], kp[gb]);
                mma16(s[1], q[ga][0], q[ga][1], q[gb][0], q[gb][1], k0[ga], k0[gb]);
                mma16(s[2], q[ga][0], q[ga][1], q[gb][0], q[gb][1], k1[ga], k1[gb]);
                mma16(s[0], q[gc][0], q[gc][1], mk[2 + 2 * h], mk[3 + 2 * h], kp[gc], kp[3]);
                mma16(s[1], q[gc][0], q[gc][1], mk[2 + 2 * h], mk[3 + 2 * h], k0[gc], k0[3]);
                mma16(s[2], q[gc][0], q[gc][1], mk[2 + 2 * h], mk[3 + 2 * h], k1[gc], k1[3]);
                sv[h][0] = fmaf(e0 ? s[0][0] : s[1][0], sc[0], sc[4]);
                sv[h][1] = fmaf(e1 ? s[0][1] : s[1][1], sc[1], sc[5]);
                sv[h][2] = (e0 ? s[1][2] : s[2][2]) * sc[2];
                sv[h][3] = (e1 ? s[1][3] : s[2][3]) * sc[3];
            }
            uint32_t pp[2][2];
#pragma unroll
            for (int i = 0; i < 4; i++) {
                float* v = &sv[i >> 1][(i & 1) * 2];
                const float m = quad_max(fmaxf(v[0], v[1]));
                const float p0 = ex2(v[0] - m), p1 = ex2(v[1] - m);
                const float inv = rcp(quad_sum(p0 + p1));
                pp[i >> 1][i & 1] = pack2(p0 * rk[(i & 1) * 2] * inv, p1 * rk[(i & 1) * 2 + 1] * inv);
            }
            uint32_t o[8][2];
#pragma unroll
            for (int i = 0; i < 8; i++) {
                const int h = i >> 2, g = i - h;
                float d[4] = {};
                mma16(d, pp[h][0] & mk[0], 0u, pp[h][0] & ~mk[0], pp[h][1] & mk[0], vp[g], v0[g]);
                mma8(d, 0u, pp[h][1] & ~mk[0], v1[g]);
                o[i][0] = pack2(d[0], d[1]); o[i][1] = pack2(d[2], d[3]);
            }
            if (t >= 2) { o[3][0] = o[4][0]; o[3][1] = o[4][1]; }
            const int word = wg * 4 + t - (w & 1) * 4 - (r >> 2);
#pragma unroll
            for (int i = 0; i < 8; i++) { o[i][0] = tag(o[i][0], word == 0, ep); o[i][1] = tag(o[i][1], word == 2, ep); }
            const uint32_t dst = sbase + OFF_X + (w >> 1) * HALF + ((w & 1) * 32 + (lane & 15) * 2 + wg) * 16 + (lane >> 4) * 1024;
            stsm4(dst, o[0][0], o[0][1], o[1][0], o[1][1]);
            stsm4(dst + 2048, o[2][0], o[2][1], o[3][0], o[3][1]);
            stsm4(dst + 4096, o[5][0], o[5][1], o[6][0], o[6][1]);
            stsm2(dst + 6144, o[7][0], o[7][1]);
            fence_async_shared();
            bar_sync(4, 288);
            TS0(2, 10 + 19 * wg);
        }
        float g[56];
#pragma unroll
        for (int i = 0; i < 56; i++) asm volatile("" : "=f"(g[i]));
        if (has_g1) {
            last = M.run<0>(a, 16 - n1, 16, LAG1, 1, 32 + PAUSE + LEAD);
            mbar_wait(bars + B_FREE, 0);
            const uint32_t xb = sbase + OFF_X + wg * 8192 + (threadIdx.x & 127) * 16, xbar = bars + B_X + 32 * wg;
            const uint32_t rx = mapa(xb, rank ^ 1), rbar = mapa(xbar, rank ^ 1);
            wg_wait<0>();
            pin(a);
            M.release(last);
            TS0(4, 5 + wg);
#pragma unroll
            for (int i = 0; i < 3; i++)
                st_async4(rx + i * 2048, rbar + 8 * i, pack2(a[28 + 8 * i], a[29 + 8 * i]), pack2(a[30 + 8 * i], a[31 + 8 * i]), pack2(a[32 + 8 * i], a[33 + 8 * i]), pack2(a[34 + 8 * i], a[35 + 8 * i]));
            const uint32_t tail = 6144 - (threadIdx.x & 127) * 8;
            st_async2(rx + tail, rbar + 24, pack2(a[52], a[53]), pack2(a[54], a[55]));
            if (WOFIRST) {
                last = M.run<1>(g, wg * WOFIRST, 4, 0, 0, 48);
                wg_wait<0>();
                if (wg) M.release(last);
            }
            uint8_t* dst = G->U[nt1][((ft >= 7) + wg) * 7 + ft] + rank * HALF + w * 256 + lane * 4;
            uint32_t u[14];
#pragma unroll
            for (int i = 0; i < 14; i++) {
                if (i == 0 || i == CHUNK * 4) {
#pragma unroll
                    for (int k = i / 4; k < (i ? 4 : CHUNK); k++) mbar_wait(xbar + 8 * k, 0);
                    if (i == 0) TS0(4, 1 + wg);
#pragma unroll
                    for (int k = i / 4; k < (i ? 4 : CHUNK); k++) {
                        if (k < 3) { const uint4 v = lds4(xb + k * 2048); u[4 * k] = v.x; u[4 * k + 1] = v.y; u[4 * k + 2] = v.z; u[4 * k + 3] = v.w; }
                        else { const uint2 v = lds2(xb + tail); u[12] = v.x; u[13] = v.y; }
                    }
                } else if (i % SPLIT == 0) mbar_wait(xbar, 0);
                if (i == HINT && threadIdx.x == 0) hint(G->flag[8 + nt1 * 2] + ft + (ft >= 7) * 25);
                const float bias = bf_lo((i & 1) ? bias1 : bias0);
                stg1(dst + (i >> 1) * 1024 + (i & 1) * 128, tag(pack2(gelu2(a[2 * i] + bias + bf_lo(u[i])), gelu2(a[2 * i + 1] + bias + bf_hi(u[i]))), (lane & 7) == w * 2 + (i & 1), ep));
            }
            TS0(4, 30 + wg);
        }
        uint32_t c0 = ld_u16(b2 + mt * 128 + warp * 16 + r), c1 = ld_u16(b2 + mt * 128 + warp * 16 + r + 8);
        const int done = has_g1 ? wg * WOFIRST : 0;
        last = M.run<1>(g, 4 - done, 4, 0, done, 48);
        wg_wait<0>();
        M.release(last);
        if (wg == 1) TS0(4, 13);
        c0 *= ks == 0 ? 0x10001u : 0u; c1 *= ks == 0 ? 0x10001u : 0u;
        M.run<2>(g, 14, 14 - NSLOT, LAG2, 1, 52);
        mbar_wait(bars + B_FREE, 0);
        mbar_wait(bars + B_ROW, 1);
        const uint32_t stg = sbase + OFF_X + wg * (OFF_Y - OFF_X) + w * SLAB;
        const uint32_t sa = stg + (lane & 15) * 224 + (lane >> 4) * 16;
        wg_wait<0>();
        pin(g);
        TS0(8, 14 + wg);
#pragma unroll
        for (int i = 0; i < 7; i++)
            stsm4(sa + i * 32, half_plus(pack2(g[8 * i], g[8 * i + 1]), c0), half_plus(pack2(g[8 * i + 2], g[8 * i + 3]), c1),
                  half_plus(pack2(g[8 * i + 4], g[8 * i + 5]), c0), half_plus(pack2(g[8 * i + 6], g[8 * i + 7]), c1));
        fence_async_shared();
        __syncwarp();
        if (elect()) {
            asm volatile("cp.reduce.async.bulk.tensor.2d.global.shared::cta.add.tile.bulk_group [%0, {%2, %3}], [%1];\ncp.async.bulk.commit_group;" ::"l"(&P.tmOut), "r"(stg), "r"(nt2 * 112), "r"(mt * 128 + warp * 16) : "memory");
            if (w == 0) mbar_arrive(bars + B_END);
            asm volatile("cp.async.bulk.wait_group.read 0;" ::: "memory");
        }
        if (wg == 1) TS0(15, 19);
        TSDUMP();
    }
}

typedef CUresult (*EncodeFn)(CUtensorMap*, CUtensorMapDataType, cuuint32_t, void*, const cuuint64_t*, const cuuint64_t*, const cuuint32_t*, const cuuint32_t*,
                             CUtensorMapInterleave, CUtensorMapSwizzle, CUtensorMapL2promotion, CUtensorMapFloatOOBfill);

void make_map(EncodeFn enc, CUtensorMap* tm, const void* base, bool swizzle, int d0, int d1, int d2, int s1, int s2, int b0, int b1, int b2) {
    const cuuint64_t dims[3] = {(cuuint64_t)d0, (cuuint64_t)d1, (cuuint64_t)d2}, strides[2] = {(cuuint64_t)s1 * 2, (cuuint64_t)s2 * 2};
    const cuuint32_t box[3] = {(cuuint32_t)b0, (cuuint32_t)b1, (cuuint32_t)b2}, es[3] = {1, 1, 1};
    enc(tm, CU_TENSOR_MAP_DATA_TYPE_BFLOAT16, d2 ? 3 : 2, (void*)base, dims, strides, box, es, CU_TENSOR_MAP_INTERLEAVE_NONE,
        swizzle ? CU_TENSOR_MAP_SWIZZLE_128B : CU_TENSOR_MAP_SWIZZLE_NONE, CU_TENSOR_MAP_L2_PROMOTION_L2_128B, CU_TENSOR_MAP_FLOAT_OOB_FILL_NONE);
}

}

extern "C" void kernel_launch(void* const* d_in, const int* in_sizes, int n_in, void* d_out, int out_size) {
    static EncodeFn enc = nullptr;
    static Scratch* scratch = nullptr;
    if (!enc) {
        void* fn = nullptr;
        cudaDriverEntryPointQueryResult qr;
        cudaGetDriverEntryPoint("cuTensorMapEncodeTiled", &fn, cudaEnableDefault, &qr);
        enc = (EncodeFn)fn;
        cudaGetSymbolAddress((void**)&scratch, g_s);
        cudaFuncSetAttribute(fused_kernel, cudaFuncAttributeMaxDynamicSharedMemorySize, SMEM_BYTES);
    }
    Params P;
    const __nv_bfloat16* x = (const __nv_bfloat16*)d_in[0];
    make_map(enc, &P.tmX, x, true, D_, S_ / 2, 2, 2 * D_, D_, 64, 64, 2);
    make_map(enc, &P.tmWqkv, d_in[1], true, D_, D_, 3, 3 * D_, D_, 64, 32, 3);
    make_map(enc, &P.tmW1, d_in[4], true, 64, S_, F_ / 64, F_, 64, 64, 64, 2);
    make_map(enc, &P.tmW2, d_in[6], true, S_, F_, 0, S_, 0, 64, 64, 1);
    make_map(enc, &P.tmOut, d_out, false, D_, S_, 0, D_, 0, 112, 16, 1);
    fused_kernel<<<NCTA, NTHREADS, SMEM_BYTES, cudaStreamPerThread>>>(x, (const __nv_bfloat16*)d_in[5], (const __nv_bfloat16*)d_in[7], (const __nv_bfloat16*)d_in[2], (__nv_bfloat16*)d_out, scratch,
                                                                      (const __nv_bfloat16*)d_in[4], (const __nv_bfloat16*)d_in[6], P);
}
```

```cpp
#include <cuda_runtime.h>
#include <cuda_bf16.h>
#include <cuda.h>
#include <stdint.h>

#define HALO_NS 300
#define HINT 4
#define SPLIT 4
#define HOLD 2
#define ROT 4
#define LATEREL 0
#define PF 400
#define PF0 2
#define PF1 8
#define ENDBAR 1
#define PG0 2
#define PG1 4
#define PACE 800
#define PAUSE 8
#define LAG1 4
#define LAG2 5

namespace {

constexpr int S_ = 2048, D_ = 448, F_ = 1792;
constexpr int NCTA = 128, NTHREADS = 384;
constexpr int NSLOT = 6, SLOT = 32768, QSLOT = 40960, TILEB = 14336, SLAB = 3584, HALF = 7168;
constexpr int KV = 1792;
constexpr int OFF_X = NSLOT * SLOT;
constexpr int OFF_Y = OFF_X + 10 * KV;
constexpr int OFF_ST = OFF_Y + TILEB;
constexpr int OFF_BAR = OFF_ST + 1024;
constexpr int SMEM_BYTES = OFF_BAR + 1280;
constexpr uint32_t SMEM0 = 1024;
constexpr int B_QFULL = 0, B_FULL = 56, B_ROW = 112, B_CS = 120, B_HALO = 128, B_X = 136, B_FREE = 208, B_END = 216, B_QEMPTY = 224, B_EMPTY = 240, NBAR = 36;
constexpr float LN_EPS = 1e-5f;
constexpr int SPIN_LIMIT = 1 << 22;

struct Scratch {
    uint8_t H[4][32][TILEB];
    uint8_t U[4][28][TILEB];
    uint8_t O[16][8][TILEB];
    uint8_t Wo[4][8][TILEB];
    uint8_t halo[NCTA][2 * KV];
    uint2 stat[S_];
    uint2 colsum[8][8][96];
    uint32_t flag[32][32];
    uint32_t epoch[NCTA];
};
__device__ __align__(1024) Scratch g_s;

#define TS(g, i)
#define TS0(g, i)
#define TSDUMP()

struct Params {
    CUtensorMap tmX, tmWqkv, tmW1, tmW2, tmOut;
};

__device__ __forceinline__ bool elect() {
    uint32_t p;
    asm volatile("{\n.reg .pred p;\nelect.sync _|p, 0xffffffff;\nselp.u32 %0, 1, 0, p;\n}" : "=r"(p));
    return p;
}
__device__ __forceinline__ void mbar_init(uint32_t b, uint32_t c) { asm volatile("mbarrier.init.shared::cta.b64 [%0], %1;" ::"r"(b), "r"(c) : "memory"); }
__device__ __forceinline__ void mbar_expect(uint32_t b, uint32_t tx) { asm volatile("mbarrier.arrive.expect_tx.shared::cta.b64 _, [%0], %1;" ::"r"(b), "r"(tx) : "memory"); }
__device__ __forceinline__ void mbar_arrive(uint32_t b) { asm volatile("mbarrier.arrive.shared::cta.b64 _, [%0];" ::"r"(b) : "memory"); }
__device__ __forceinline__ void mbar_arrive_remote(uint32_t b) { asm volatile("mbarrier.arrive.shared::cluster.b64 _, [%0];" ::"r"(b) : "memory"); }
#define MBAR_WAIT_ASM(SEM) \
    asm volatile("{\n.reg .pred p;\nWAIT:\nmbarrier.try_wait.parity" SEM ".shared::cta.b64 p, [%0], %1;\n@!p bra WAIT;\n}" ::"r"(b), "r"(parity) : "memory")
__device__ __forceinline__ void mbar_wait(uint32_t b, uint32_t parity) { MBAR_WAIT_ASM(""); }
__device__ __forceinline__ void mbar_wait_bounded(uint32_t b, uint32_t parity, uint32_t& n) {
    asm volatile("{\n.reg .pred p;\nWAIT:\nadd.u32 %0, %0, 1;\nsetp.gt.u32 p, %0, %3;\n@p st.global.u32 [%4], %0;\n"
                 "mbarrier.try_wait.parity.shared::cta.b64 p, [%1], %2;\n@!p bra WAIT;\n}" : "+r"(n) : "r"(b), "r"(parity), "n"(SPIN_LIMIT), "l"(0ull) : "memory");
}
__device__ __forceinline__ uint32_t mapa(uint32_t a, uint32_t rank) { uint32_t r; asm("mapa.shared::cluster.u32 %0, %1, %2;" : "=r"(r) : "r"(a), "r"(rank)); return r; }
__device__ __forceinline__ void tma3d(uint32_t dst, const CUtensorMap* tm, uint32_t bar, int c0, int c1, int c2) {
    asm volatile("cp.async.bulk.tensor.3d.shared::cluster.global.mbarrier::complete_tx::bytes [%0], [%1, {%3, %4, %5}], [%2];" ::"r"(dst), "l"(tm), "r"(bar), "r"(c0), "r"(c1), "r"(c2) : "memory");
}
__device__ __forceinline__ void tma2d_pair(uint32_t dst, const CUtensorMap* tm, uint32_t bar, int c0, int c1) {
    asm volatile("cp.async.bulk.tensor.2d.shared::cluster.global.mbarrier::complete_tx::bytes.multicast::cluster [%0], [%1, {%3, %4}], [%2], %5;" ::"r"(dst), "l"(tm), "r"(bar), "r"(c0), "r"(c1), "h"((uint16_t)3) : "memory");
}
__device__ __forceinline__ void tma3d_pair(uint32_t dst, const CUtensorMap* tm, uint32_t bar, int c0, int c1, int c2) {
    asm volatile("cp.async.bulk.tensor.3d.shared::cluster.global.mbarrier::complete_tx::bytes.multicast::cluster [%0], [%1, {%3, %4, %5}], [%2], %6;" ::"r"(dst), "l"(tm), "r"(bar), "r"(c0), "r"(c1), "r"(c2), "h"((uint16_t)3) : "memory");
}
__device__ __forceinline__ void bulk_load(uint32_t dst, const void* src, uint32_t bytes, uint32_t bar) {
    asm volatile("cp.async.bulk.shared::cluster.global.mbarrier::complete_tx::bytes [%0], [%1], %2, [%3];" ::"r"(dst), "l"(src), "r"(bytes), "r"(bar) : "memory");
}
__device__ __forceinline__ void bulk_load_pair(uint32_t dst, const void* src, uint32_t bytes, uint32_t bar) {
    asm volatile("cp.async.bulk.shared::cluster.global.mbarrier::complete_tx::bytes.multicast::cluster [%0], [%1], %2, [%3], %4;" ::"r"(dst), "l"(src), "r"(bytes), "r"(bar), "h"((uint16_t)3) : "memory");
}
__device__ __forceinline__ void bulk_store(void* dst, uint32_t src, uint32_t bytes) {
    asm volatile("cp.async.bulk.global.shared::cta.bulk_group [%0], [%1], %2;" ::"l"(dst), "r"(src), "r"(bytes) : "memory");
}
__device__ __forceinline__ uint32_t ld_u16(const void* p) { uint32_t v; asm volatile("ld.global.nc.u16 %0, [%1];" : "=r"(v) : "l"(p)); return v; }
__device__ __forceinline__ uint32_t ld_relaxed(const uint32_t* p) { uint32_t v; asm volatile("ld.relaxed.gpu.global.u32 %0, [%1];" : "=r"(v) : "l"(p) : "memory"); return v; }
__device__ __forceinline__ void bulk_flush() { asm volatile("cp.async.bulk.commit_group;\ncp.async.bulk.wait_group 0;" ::: "memory"); }
__device__ __forceinline__ void signal(uint32_t* flag) { asm volatile("fence.acq_rel.gpu;\nred.relaxed.gpu.global.add.u32 [%0], 1;" ::"l"(flag) : "memory"); }
__device__ __forceinline__ void hint(uint32_t* flag) { asm volatile("red.relaxed.gpu.global.add.u32 [%0], 1;" ::"l"(flag) : "memory"); }
__device__ __forceinline__ uint32_t tag(uint32_t v, uint32_t mask, uint32_t parity) { return (v & ~mask) | (parity & mask); }
__device__ __forceinline__ uint32_t or_diff(uint32_t acc, uint32_t v, uint32_t parity) { asm("lop3.b32 %0, %0, %1, %2, 0xf6;" : "+r"(acc) : "r"(v), "r"(parity)); return acc; }
__device__ __forceinline__ uint4 ld_relaxed4(const void* p) {
    uint4 v;
    asm volatile("ld.relaxed.gpu.global.v4.u32 {%0, %1, %2, %3}, [%4];" : "=r"(v.x), "=r"(v.y), "=r"(v.z), "=r"(v.w) : "l"(p) : "memory");
    return v;
}
__device__ __forceinline__ uint2 ld_relaxed2(const void* p) { uint2 v; asm volatile("ld.relaxed.gpu.global.v2.u32 {%0, %1}, [%2];" : "=r"(v.x), "=r"(v.y) : "l"(p) : "memory"); return v; }
__device__ __forceinline__ void sts4(uint32_t a, uint4 v) { asm volatile("st.shared.v4.b32 [%0], {%1, %2, %3, %4};" ::"r"(a), "r"(v.x), "r"(v.y), "r"(v.z), "r"(v.w) : "memory"); }
__device__ __forceinline__ void stg1(void* p, uint32_t v) { asm volatile("st.global.b32 [%0], %1;" ::"l"(p), "r"(v) : "memory"); }
__device__ __forceinline__ void fence_async_shared() { asm volatile("fence.proxy.async.shared::cta;" ::: "memory"); }
#define BOUND "add.u32 %0, %0, 16;\nsetp.gt.u32 p, %0, %1;\n@p st.global.u32 [%2], %0;\n"
__device__ __forceinline__ void wait_flag(const uint32_t* p, uint32_t target, uint32_t& n) {
    asm volatile("{\n.reg .pred p;\n.reg .u32 v;\nPOLL:\n" BOUND "ld.acquire.gpu.global.u32 v, [%3];\nsetp.ne.u32 p, v, %4;\n@p bra POLL;\nfence.proxy.async.global;\n}"
                 : "+r"(n) : "n"(SPIN_LIMIT), "l"(0ull), "l"(p), "r"(target) : "memory");
}
__device__ __forceinline__ void wait_flag2(const uint32_t* h, uint32_t th, const uint32_t* p, uint32_t target, uint32_t& n) {
    asm volatile("{\n.reg .pred p;\n.reg .u32 u, v;\nPOLL:\n" BOUND "ld.relaxed.gpu.global.u32 u, [%3];\nld.acquire.gpu.global.u32 v, [%5];\nsetp.ne.u32 p, u, %4;\nsetp.ne.or.u32 p, v, %6, p;\n@p bra POLL;\nfence.proxy.async.global;\n}"
                 : "+r"(n) : "n"(SPIN_LIMIT), "l"(0ull), "l"(h), "r"(th), "l"(p), "r"(target) : "memory");
}
__device__ __forceinline__ void bar_sync(int id, int n) { asm volatile("bar.sync %0, %1;" ::"r"(id), "r"(n) : "memory"); }
__device__ __forceinline__ void bar_arrive(int id, int n) { asm volatile("bar.arrive %0, %1;" ::"r"(id), "r"(n) : "memory"); }
__device__ __forceinline__ void wg_fence() { asm volatile("wgmma.fence.sync.aligned;" ::: "memory"); }
__device__ __forceinline__ void wg_commit() { asm volatile("wgmma.commit_group.sync.aligned;" ::: "memory"); }
template <int N> __device__ __forceinline__ void wg_wait() { asm volatile("wgmma.wait_group.sync.aligned %0;" ::"n"(N) : "memory"); }
template <int N> __device__ __forceinline__ void pin(float (&d)[N]) {
#pragma unroll
    for (int i = 0; i < N; i++) asm volatile("" : "+f"(d[i])::"memory");
}
__host__ __device__ constexpr uint32_t desc_hi(uint32_t sbo, uint32_t swz) { return (sbo >> 4) | (swz << 30); }
__host__ __device__ constexpr uint32_t desc_lo(uint32_t off, uint32_t lbo) { return ((SMEM0 + off) >> 4) | ((lbo >> 4) << 16); }
__device__ __forceinline__ uint32_t pack2(float lo, float hi) { uint32_t r; asm("cvt.rn.bf16x2.f32 %0, %1, %2;" : "=r"(r) : "f"(hi), "f"(lo)); return r; }
__device__ __forceinline__ float bf_lo(uint32_t v) { return __uint_as_float(v << 16); }
__device__ __forceinline__ float bf_hi(uint32_t v) { return __uint_as_float(v & 0xffff0000u); }
__device__ __forceinline__ uint32_t half_plus(uint32_t a, uint32_t b) { uint32_t r; asm("fma.rn.bf16x2 %0, %1, %2, %3;" : "=r"(r) : "r"(a), "r"(0x3f003f00u), "r"(b)); return r; }
__device__ __forceinline__ void stsm4(uint32_t a, uint32_t r0, uint32_t r1, uint32_t r2, uint32_t r3) {
    asm volatile("stmatrix.sync.aligned.m8n8.x4.shared.b16 [%0], {%1, %2, %3, %4};" ::"r"(a), "r"(r0), "r"(r1), "r"(r2), "r"(r3) : "memory");
}
__device__ __forceinline__ void stsm2(uint32_t a, uint32_t r0, uint32_t r1) {
    asm volatile("stmatrix.sync.aligned.m8n8.x2.shared.b16 [%0], {%1, %2};" ::"r"(a), "r"(r0), "r"(r1) : "memory");
}
__device__ __forceinline__ uint4 lds4(uint32_t a) { uint4 v; asm volatile("ld.shared.v4.b32 {%0, %1, %2, %3}, [%4];" : "=r"(v.x), "=r"(v.y), "=r"(v.z), "=r"(v.w) : "r"(a) : "memory"); return v; }
__device__ __forceinline__ uint2 lds2(uint32_t a) { uint2 v; asm volatile("ld.shared.v2.b32 {%0, %1}, [%2];" : "=r"(v.x), "=r"(v.y) : "r"(a) : "memory"); return v; }
__device__ __forceinline__ float lds1f(uint32_t a) { float v; asm volatile("ld.shared.f32 %0, [%1];" : "=f"(v) : "r"(a) : "memory"); return v; }
__device__ __forceinline__ void ldsm4(uint32_t* r, uint32_t a) {
    asm volatile("ldmatrix.sync.aligned.m8n8.x4.shared.b16 {%0, %1, %2, %3}, [%4];" : "=r"(r[0]), "=r"(r[1]), "=r"(r[2]), "=r"(r[3]) : "r"(a) : "memory");
}
__device__ __forceinline__ void ldsm4t(uint32_t* r, uint32_t a) {
    asm volatile("ldmatrix.sync.aligned.m8n8.x4.trans.shared.b16 {%0, %1, %2, %3}, [%4];" : "=r"(r[0]), "=r"(r[1]), "=r"(r[2]), "=r"(r[3]) : "r"(a) : "memory");
}
__device__ __forceinline__ void ldsm2t(uint32_t* r, uint32_t a) {
    asm volatile("ldmatrix.sync.aligned.m8n8.x2.trans.shared.b16 {%0, %1}, [%2];" : "=r"(r[0]), "=r"(r[1]) : "r"(a) : "memory");
}
__device__ __forceinline__ uint32_t transpose8(uint32_t v) { uint32_t r; asm volatile("movmatrix.sync.aligned.m8n8.trans.b16 %0, %1;" : "=r"(r) : "r"(v)); return r; }
__device__ __forceinline__ void mma16(float (&c)[4], uint32_t a0, uint32_t a1, uint32_t a2, uint32_t a3, uint32_t b0, uint32_t b1) {
    asm volatile("mma.sync.aligned.m16n8k16.row.col.f32.bf16.bf16.f32 {%0, %1, %2, %3}, {%4, %5, %6, %7}, {%8, %9}, {%0, %1, %2, %3};"
                 : "+f"(c[0]), "+f"(c[1]), "+f"(c[2]), "+f"(c[3]) : "r"(a0), "r"(a1), "r"(a2), "r"(a3), "r"(b0), "r"(b1));
}
__device__ __forceinline__ void mma8(float (&c)[4], uint32_t a0, uint32_t a1, uint32_t b0) {
    asm volatile("mma.sync.aligned.m16n8k8.row.col.f32.bf16.bf16.f32 {%0, %1, %2, %3}, {%4, %5}, {%6}, {%0, %1, %2, %3};"
                 : "+f"(c[0]), "+f"(c[1]), "+f"(c[2]), "+f"(c[3]) : "r"(a0), "r"(a1), "r"(b0));
}
__device__ __forceinline__ void st_async4(uint32_t a, uint32_t bar, uint32_t v0, uint32_t v1, uint32_t v2, uint32_t v3) {
    asm volatile("st.async.weak.shared::cluster.mbarrier::complete_tx::bytes.v4.b32 [%0], {%2, %3, %4, %5}, [%1];" ::"r"(a), "r"(bar), "r"(v0), "r"(v1), "r"(v2), "r"(v3) : "memory");
}
__device__ __forceinline__ void st_async2(uint32_t a, uint32_t bar, uint32_t v0, uint32_t v1) {
    asm volatile("st.async.weak.shared::cluster.mbarrier::complete_tx::bytes.v2.b32 [%0], {%2, %3}, [%1];" ::"r"(a), "r"(bar), "r"(v0), "r"(v1) : "memory");
}
__device__ __forceinline__ float quad_max(float v) { v = fmaxf(v, __shfl_xor_sync(~0u, v, 1)); return fmaxf(v, __shfl_xor_sync(~0u, v, 2)); }
__device__ __forceinline__ float quad_sum(float v) { v += __shfl_xor_sync(~0u, v, 1); return v + __shfl_xor_sync(~0u, v, 2); }
__device__ __forceinline__ float ex2(float v) { float r; asm("ex2.approx.ftz.f32 %0, %1;" : "=f"(r) : "f"(v)); return r; }
__device__ __forceinline__ float rcp(float v) { float r; asm("rcp.approx.ftz.f32 %0, %1;" : "=f"(r) : "f"(v)); return r; }
__device__ __forceinline__ float rsq(float v) { float r; asm("rsqrt.approx.ftz.f32 %0, %1;" : "=f"(r) : "f"(v)); return r; }
__device__ __forceinline__ float gelu2(float u) {
    float z = u * fmaf(u * u, 0.044715f * 0.7978845608028654f, 0.7978845608028654f), t;
    asm("tanh.approx.f32 %0, %1;" : "=f"(t) : "f"(z));
    return fmaf(u, t, u);
}
__device__ __forceinline__ float oct_sum(float v) {
    v += __shfl_xor_sync(~0u, v, 4); v += __shfl_xor_sync(~0u, v, 8); v += __shfl_xor_sync(~0u, v, 16);
    return v;
}

template <int TA, int TB, uint32_t HA, uint32_t HB>
__device__ __forceinline__ void wgmma_n112(float (&d)[56], uint32_t da, uint32_t db, int accumulate) {
    asm volatile("{\n.reg .pred p;\n.reg .b64 a, b;\nmov.b64 a, {%56, %61};\nmov.b64 b, {%57, %62};\nsetp.ne.b32 p, %58, 0;\n"
        "wgmma.mma_async.sync.aligned.m64n112k16.f32.bf16.bf16 {"
        "%0, %1, %2, %3, %4, %5, %6, %7, %8, %9, %10, %11, %12, %13, %14, %15, "
        "%16, %17, %18, %19, %20, %21, %22, %23, %24, %25, %26, %27, %28, %29, %30, %31, "
        "%32, %33, %34, %35, %36, %37, %38, %39, %40, %41, %42, %43, %44, %45, %46, %47, "
        "%48, %49, %50, %51, %52, %53, %54, %55"
        "}, a, b, p, 1, 1, %59, %60;\n}\n"
        : "+f"(d[0]), "+f"(d[1]), "+f"(d[2]), "+f"(d[3]), "+f"(d[4]), "+f"(d[5]), "+f"(d[6]), "+f"(d[7]),
          "+f"(d[8]), "+f"(d[9]), "+f"(d[10]), "+f"(d[11]), "+f"(d[12]), "+f"(d[13]), "+f"(d[14]), "+f"(d[15]),
          "+f"(d[16]), "+f"(d[17]), "+f"(d[18]), "+f"(d[19]), "+f"(d[20]), "+f"(d[21]), "+f"(d[22]), "+f"(d[23]),
          "+f"(d[24]), "+f"(d[25]), "+f"(d[26]), "+f"(d[27]), "+f"(d[28]), "+f"(d[29]), "+f"(d[30]), "+f"(d[31]),
          "+f"(d[32]), "+f"(d[33]), "+f"(d[34]), "+f"(d[35]), "+f"(d[36]), "+f"(d[37]), "+f"(d[38]), "+f"(d[39]),
          "+f"(d[40]), "+f"(d[41]), "+f"(d[42]), "+f"(d[43]), "+f"(d[44]), "+f"(d[45]), "+f"(d[46]), "+f"(d[47]),
          "+f"(d[48]), "+f"(d[49]), "+f"(d[50]), "+f"(d[51]), "+f"(d[52]), "+f"(d[53]), "+f"(d[54]), "+f"(d[55])
        : "r"(da), "r"(db), "r"(accumulate), "n"(TA), "n"(TB), "n"(HA), "n"(HB));
}

template <int TA, int TB, uint32_t HA, uint32_t HB>
__device__ __forceinline__ void wgmma_n184(float (&d)[92], uint32_t da, uint32_t db, int accumulate) {
    asm volatile("{\n.reg .pred p;\n.reg .b64 a, b;\nmov.b64 a, {%92, %97};\nmov.b64 b, {%93, %98};\nsetp.ne.b32 p, %94, 0;\n"
        "wgmma.mma_async.sync.aligned.m64n184k16.f32.bf16.bf16 {"
        "%0, %1, %2, %3, %4, %5, %6, %7, %8, %9, %10, %11, %12, %13, %14, %15, "
        "%16, %17, %18, %19, %20, %21, %22, %23, %24, %25, %26, %27, %28, %29, %30, %31, "
        "%32, %33, %34, %35, %36, %37, %38, %39, %40, %41, %42, %43, %44, %45, %46, %47, "
        "%48, %49, %50, %51, %52, %53, %54, %55, %56, %57, %58, %59, %60, %61, %62, %63, "
        "%64, %65, %66, %67, %68, %69, %70, %71, %72, %73, %74, %75, %76, %77, %78, %79, "
        "%80, %81, %82, %83, %84, %85, %86, %87, %88, %89, %90, %91"
        "}, a, b, p, 1, 1, %95, %96;\n}\n"
        : "+f"(d[0]), "+f"(d[1]), "+f"(d[2]), "+f"(d[3]), "+f"(d[4]), "+f"(d[5]), "+f"(d[6]), "+f"(d[7]),
          "+f"(d[8]), "+f"(d[9]), "+f"(d[10]), "+f"(d[11]), "+f"(d[12]), "+f"(d[13]), "+f"(d[14]), "+f"(d[15]),
          "+f"(d[16]), "+f"(d[17]), "+f"(d[18]), "+f"(d[19]), "+f"(d[20]), "+f"(d[21]), "+f"(d[22]), "+f"(d[23]),
          "+f"(d[24]), "+f"(d[25]), "+f"(d[26]), "+f"(d[27]), "+f"(d[28]), "+f"(d[29]), "+f"(d[30]), "+f"(d[31]),
          "+f"(d[32]), "+f"(d[33]), "+f"(d[34]), "+f"(d[35]), "+f"(d[36]), "+f"(d[37]), "+f"(d[38]), "+f"(d[39]),
          "+f"(d[40]), "+f"(d[41]), "+f"(d[42]), "+f"(d[43]), "+f"(d[44]), "+f"(d[45]), "+f"(d[46]), "+f"(d[47]),
          "+f"(d[48]), "+f"(d[49]), "+f"(d[50]), "+f"(d[51]), "+f"(d[52]), "+f"(d[53]), "+f"(d[54]), "+f"(d[55]),
          "+f"(d[56]), "+f"(d[57]), "+f"(d[58]), "+f"(d[59]), "+f"(d[60]), "+f"(d[61]), "+f"(d[62]), "+f"(d[63]),
          "+f"(d[64]), "+f"(d[65]), "+f"(d[66]), "+f"(d[67]), "+f"(d[68]), "+f"(d[69]), "+f"(d[70]), "+f"(d[71]),
          "+f"(d[72]), "+f"(d[73]), "+f"(d[74]), "+f"(d[75]), "+f"(d[76]), "+f"(d[77]), "+f"(d[78]), "+f"(d[79]),
          "+f"(d[80]), "+f"(d[81]), "+f"(d[82]), "+f"(d[83]), "+f"(d[84]), "+f"(d[85]), "+f"(d[86]), "+f"(d[87]),
          "+f"(d[88]), "+f"(d[89]), "+f"(d[90]), "+f"(d[91])
        : "r"(da), "r"(db), "r"(accumulate), "n"(TA), "n"(TB), "n"(HA), "n"(HB));
}

template <uint32_t HB>
__device__ __forceinline__ void wgmma_rs_n184(float (&d)[92], uint32_t a0, uint32_t a1, uint32_t db) {
    asm volatile("{\n.reg .b64 b;\nmov.b64 b, {%94, %96};\n"
        "wgmma.mma_async.sync.aligned.m64n184k16.f32.bf16.bf16 {"
        "%0, %1, %2, %3, %4, %5, %6, %7, %8, %9, %10, %11, %12, %13, %14, %15, "
        "%16, %17, %18, %19, %20, %21, %22, %23, %24, %25, %26, %27, %28, %29, %30, %31, "
        "%32, %33, %34, %35, %36, %37, %38, %39, %40, %41, %42, %43, %44, %45, %46, %47, "
        "%48, %49, %50, %51, %52, %53, %54, %55, %56, %57, %58, %59, %60, %61, %62, %63, "
        "%64, %65, %66, %67, %68, %69, %70, %71, %72, %73, %74, %75, %76, %77, %78, %79, "
        "%80, %81, %82, %83, %84, %85, %86, %87, %88, %89, %90, %91"
        "}, {%92, %93, %95, %95}, b, 1, 1, 1, 0;\n}\n"
        : "+f"(d[0]), "+f"(d[1]), "+f"(d[2]), "+f"(d[3]), "+f"(d[4]), "+f"(d[5]), "+f"(d[6]), "+f"(d[7]),
          "+f"(d[8]), "+f"(d[9]), "+f"(d[10]), "+f"(d[11]), "+f"(d[12]), "+f"(d[13]), "+f"(d[14]), "+f"(d[15]),
          "+f"(d[16]), "+f"(d[17]), "+f"(d[18]), "+f"(d[19]), "+f"(d[20]), "+f"(d[21]), "+f"(d[22]), "+f"(d[23]),
          "+f"(d[24]), "+f"(d[25]), "+f"(d[26]), "+f"(d[27]), "+f"(d[28]), "+f"(d[29]), "+f"(d[30]), "+f"(d[31]),
          "+f"(d[32]), "+f"(d[33]), "+f"(d[34]), "+f"(d[35]), "+f"(d[36]), "+f"(d[37]), "+f"(d[38]), "+f"(d[39]),
          "+f"(d[40]), "+f"(d[41]), "+f"(d[42]), "+f"(d[43]), "+f"(d[44]), "+f"(d[45]), "+f"(d[46]), "+f"(d[47]),
          "+f"(d[48]), "+f"(d[49]), "+f"(d[50]), "+f"(d[51]), "+f"(d[52]), "+f"(d[53]), "+f"(d[54]), "+f"(d[55]),
          "+f"(d[56]), "+f"(d[57]), "+f"(d[58]), "+f"(d[59]), "+f"(d[60]), "+f"(d[61]), "+f"(d[62]), "+f"(d[63]),
          "+f"(d[64]), "+f"(d[65]), "+f"(d[66]), "+f"(d[67]), "+f"(d[68]), "+f"(d[69]), "+f"(d[70]), "+f"(d[71]),
          "+f"(d[72]), "+f"(d[73]), "+f"(d[74]), "+f"(d[75]), "+f"(d[76]), "+f"(d[77]), "+f"(d[78]), "+f"(d[79]),
          "+f"(d[80]), "+f"(d[81]), "+f"(d[82]), "+f"(d[83]), "+f"(d[84]), "+f"(d[85]), "+f"(d[86]), "+f"(d[87]),
          "+f"(d[88]), "+f"(d[89]), "+f"(d[90]), "+f"(d[91])
        : "r"(a0), "r"(a1), "r"(db), "r"(0), "n"(HB));
}

struct Ring {
    uint32_t slot, ph;
    __device__ __forceinline__ void next() { if (++slot == NSLOT) { slot = 0; ph ^= 1; } }
};
struct Slot {
    uint32_t dst, bar, ph;
    __device__ __forceinline__ void next(uint32_t bars) {
        dst += SLOT; bar += 8;
        if (bar == bars + 8 * NSLOT) { dst -= NSLOT * SLOT; bar = bars; ph ^= 1; }
    }
};
__device__ __forceinline__ uint32_t xslot(int i) { return __byte_perm(0x04130e0cu, 0x00130e0cu, 0x7770 + i); }
__device__ __forceinline__ uint32_t wslot(int i) { return __byte_perm(0x06001510u, 0x00151009u, 0x7770 + i); }

constexpr uint32_t HI_SW = desc_hi(1024, 1);

struct Mma {
    uint32_t bars, rel;
    bool lead;
    int wg, w;
    Ring r;
    uint32_t prev;
    __device__ __forceinline__ void release(uint32_t s) { if (lead) mbar_arrive_remote(rel + B_EMPTY + 8 * s); }
    template <bool G1>
    __device__ __forceinline__ void run(float (&a)[56], int n, int first, int last, int lag, int accumulate, int ts) {
#pragma unroll 1
        for (int i = 0; i < n; i++) {
            if (lag && i == (wg ? n - lag : -1)) bar_sync(7, 256);
            const uint32_t s = r.slot;
            mbar_wait(bars + B_FULL + 8 * s, r.ph); r.next();
            TS0(G1 ? 2 : 8, ts + i + wg * 68);
            const uint32_t dB = s * (SLOT >> 4), dA = dB + wg * 512;
            wg_fence();
#pragma unroll
            for (int k = 0; k < 4; k++) {
                wgmma_n112<1, 1, HI_SW, desc_hi(G1 ? 256 : 1024, 0)>(a, dA + desc_lo(k * 2048, 8192), dB + desc_lo(16384 + k * (G1 ? SLAB : 256), 128), k > 0 || accumulate || i > 0);
                if (k == 1) {
                    wg_commit(); wg_wait<1>();
                    if ((uint32_t)(i - first) < (uint32_t)(last - first)) release(prev);
                    if (lag && i == (wg ? -1 : n - 1)) bar_arrive(7, 256);
                }
            }
            wg_commit();
            prev = s;
        }
    }
    __device__ __forceinline__ void run_o(float (&a)[56]) {
#pragma unroll 1
        for (int i = 0; i < 2; i++) {
            const uint32_t s = r.slot, dB = s * (SLOT >> 4), dA = dB + wg * 512;
            mbar_wait(bars + B_FULL + 8 * s, r.ph);
            TS0(8, 48 + 2 * i + wg * 68);
            wg_fence();
#pragma unroll
            for (int k = 0; k < 7; k++) {
                if (k == 3) { mbar_wait(bars + B_FULL + 8 * s + 8, r.ph); wg_fence(); }
                wgmma_n112<0, 1, desc_hi(128, 0), desc_hi(256, 0)>(a, dA + desc_lo(k * 2048 + (k > 3) * (SLOT - HALF), k == 3 ? SLOT - 6144 : 1024),
                                                                   dB + desc_lo(16384 + k * SLAB + (k > 2) * (SLOT - 3 * SLAB), 128), k > 0 || i > 0);
                if (k & 1) wg_commit();
                if (k == 1) { wg_wait<1>(); if (i) release(prev); }
                if (k == 5) { wg_wait<1>(); release(s); }
            }
            wg_commit();
            prev = s + 1;
            r.next(); r.next();
        }
    }
};

__global__ void __cluster_dims__(2, 1, 1) __launch_bounds__(NTHREADS, 1)
fused_kernel(const __nv_bfloat16* __restrict__ x, const __nv_bfloat16* __restrict__ b1, const __nv_bfloat16* __restrict__ b2, const __nv_bfloat16* __restrict__ wo, __nv_bfloat16* out, Scratch* G,
             const __nv_bfloat16* __restrict__ w1, const __nv_bfloat16* __restrict__ w2,
             const __grid_constant__ Params P) {
    extern __shared__ __align__(1024) uint8_t smem[];
    const uint32_t sbase = (uint32_t)__cvta_generic_to_shared(smem);
    const uint32_t bars = sbase + OFF_BAR;
    const int lane = threadIdx.x & 31;
    const int warp = __shfl_sync(~0u, threadIdx.x >> 5, 0), w = warp & 3;
    const uint32_t rank = blockIdx.x & 1, pr = blockIdx.x >> 1;
    const uint32_t pv = pr < 4 ? pr * 8 + 36 : pr < 40 ? pr - 4 : pr - 3 + (((pr - 40) * 37) >> 8);
    const uint32_t gp = (pv + 4) & 7, hp = pv >> 3;
    const uint32_t tb = gp * 2 + rank, c = hp * 16 + tb, row0 = (tb * 8 + hp) * 16;
    const bool has_g1 = gp > 0;
    const uint32_t nt1 = hp & 3, ft = max((int)gp - 1, 0) * 2 + (hp >> 2);
    const uint32_t nt2 = tb & 3, mt = (gp & 2) * 4 + hp, ks = gp >> 2;

    if (elect()) {
        if (warp == 0) TS(15, 0);
#pragma unroll
        for (int i = 0; i < 3; i++) mbar_init(bars + warp * 24 + 8 * i, warp * 24 + 8 * i < B_FREE ? 1 : warp * 24 + 8 * i < B_QEMPTY ? 2 : 4);
        asm volatile("fence.mbarrier_init.release.cluster;" ::: "memory");
        if (warp == B_ROW / 24) {
            mbar_expect(bars + B_ROW, TILEB);
            bulk_load(sbase + OFF_Y, x + row0 * D_, TILEB, bars + B_ROW);
        }
    }
    __syncwarp();
    asm volatile("barrier.cluster.arrive.relaxed.aligned;\nbarrier.cluster.wait.aligned;" ::: "memory");

    if (warp == 8) {
        if (elect()) {
            uint32_t spins = (sbase & 0xffffffu) == SMEM0 ? 0 : SPIN_LIMIT;
            uint32_t kw = gp % ROT * (512 / ROT), kx = kw;
            uint32_t due = (uint32_t)clock(), ep = 0;
#pragma unroll 1
            for (int i = 0; i < 8; i++) {
                if (i >= 5) mbar_wait_bounded(bars + B_QEMPTY + 8 * (i - 5), 0, spins);
                else { while ((int)((uint32_t)clock() - due) < 0) {} due += PACE; }
                if (kw == D_) kw = 0;
                if (i < 4) kx = kw;
                const int ix = i - (i > 4);
                if (i < 7) mbar_expect(bars + B_QFULL + 8 * i, QSLOT);
                if (i != 4) tma3d(sbase + xslot(ix) * 8192, &P.tmX, bars + B_QFULL + 8 * ix, kx, tb * 64, 0);
                if (i == 5) mbar_wait_bounded(bars + B_CS, 0, spins);
                if (i < 7) tma3d_pair(sbase + wslot(i) * 8192 + rank * 12288, &P.tmWqkv, bars + B_QFULL + 8 * i, (hp * 56) & ~15, kw + rank * 32, 0);
                kx = kw; kw += 64;
                if (i == 0) { TS(1, 23); ep = ld_relaxed(&G->epoch[c]); }
            }
            ep++;
            Slot r{sbase, bars, 0};
            if (has_g1) {
                const uint8_t* src = G->H[nt1][rank * 16];
                const int row = rank * 1024;
                mbar_expect(bars + B_FULL, 16384 + TILEB);
                tma3d(sbase, &P.tmW1, bars + B_FULL, 0, row, ft * 2);
                wait_flag(G->flag[1] + rank * 2, 20 * ep, spins);
                TS(1, 16);
#pragma unroll 1
                for (int j = 64;; j += 64) {
                    bulk_load(r.dst + 16384, src, TILEB, r.bar + B_FULL);
                    src += TILEB;
                    r.next(bars);
                    if (j == 1024) break;
                    mbar_wait_bounded(r.bar + B_EMPTY, r.ph, spins);
                    if (j < 14 * 64) TS(2, 146 + j / 64);
                    mbar_expect(r.bar + B_FULL, 16384 + TILEB);
                    tma3d(r.dst, &P.tmW1, r.bar + B_FULL, 0, row + j, ft * 2);
                }
#pragma unroll
                for (int i = 0; i < 4; i++) mbar_expect(bars + B_X + 8 * i, (i & 1) ? 3072 : 4096);
            } else {
                due = (uint32_t)clock();
#pragma unroll 1
                for (int j = PF0; j < PF1; j++) {
                    asm volatile("cp.async.bulk.prefetch.L2.global [%0], %1;" ::"l"(w1 + (rank * 1024 + j * 64 + hp * 8) * F_), "n"(16 * F_) : "memory");
                    due += PF;
                    while ((int)((uint32_t)clock() - due) < 0) {}
                }
            }
            const uint8_t *so = G->O[mt][ks * 4] + rank * HALF, *sw = G->Wo[nt2][ks * 4];
            wait_flag2(G->flag[16 + mt], 8 * ep, G->flag[0], 16 * ep, spins);
            TS(4, 18);
#pragma unroll 1
            for (int j = 0; j < 4 * TILEB; j += TILEB) {
                mbar_wait_bounded(r.bar + B_EMPTY, r.ph, spins);
                mbar_expect(r.bar + B_QFULL, TILEB);
                bulk_load_pair(r.dst + rank * 8192, so + j, HALF, r.bar + B_QFULL);
                bulk_load(r.dst + 16384, sw + j, (r.bar & 8) ? TILEB : 3 * SLAB, r.bar + B_FULL);
                r.next(bars);
            }
            if (!has_g1) {
#pragma unroll 1
                for (int j = PG0; j < PG1; j++)
                    asm volatile("cp.async.bulk.prefetch.L2.global [%0], %1;" ::"l"(w2 + (rank * 896 + j * 128 + hp * 8) * S_), "n"(16 * S_) : "memory");
            }
#pragma unroll 1
            for (int j = 0; j < 14 * 128; j += 128) {
                mbar_wait_bounded(r.bar + B_EMPTY, r.ph, spins);
                TS(8, 176 + j / 128);
                tma2d_pair(r.dst + rank * 8192, &P.tmW2, r.bar + B_FULL, mt * 128 + rank * 64, ks * 896 + j - (j < 896 ? 0 : 832));
                r.next(bars);
            }
            mbar_wait_bounded(bars + B_END, 0, spins);
        }
    } else if (warp > 8) {
        const uint32_t ep = ld_relaxed(&G->epoch[c]) + 1;
        {
            const uint32_t src = (sbase + wslot(gp / ROT) * 8192 - 4096 + w * 4096 + rank * 64 + (lane & 15) * 4 + (lane >> 4) * 12288) ^ ((lane >> 4) * 576);
            float s0 = 0.f, s1 = 0.f, s2 = 0.f, s3 = 0.f;
            mbar_wait(bars + B_QFULL + 8 * (gp / ROT), 0);
            if (w == 1) TS(1, 66);
            uint32_t v[32];
#pragma unroll
            for (int k = 0; k < 32; k++) v[k] = __float_as_uint(lds1f((src ^ ((k & 7) * 144)) + (k >> 3) * 1024));
#pragma unroll
            for (int k = 0; k < 32; k += 2) { s0 += bf_lo(v[k]); s1 += bf_hi(v[k]); s2 += bf_lo(v[k + 1]); s3 += bf_hi(v[k + 1]); }
            s0 += s2; s1 += s3;
            s0 += __shfl_xor_sync(~0u, s0, 16); s1 += __shfl_xor_sync(~0u, s1, 16);
            uint2* cs = G->colsum[hp][0] + w * 32 - 32;
            if (lane < 16) cs[gp * 96 + rank * 16 + lane] = make_uint2(tag(__float_as_uint(s0), 1, ep), __float_as_uint(s1));
            if (w == 1) TS(1, 24);
            if (w == 2) {
                bar_sync(6, 224);
                TS(1, 8);
                if (elect()) { mbar_arrive(bars + B_CS); signal(G->flag[1] + (gp >> 2) * 2 + ((row0 & 1023) >= 320)); TS(1, 3); }
                __syncwarp();
            } else {
                bar_arrive(6, 224);
            }
            bar_sync(1, 96);
            const int i0 = threadIdx.x - 288;
            uint2 u[7];
            uint4 sv;
            uint32_t bad;
            do {
                sv = ld_relaxed4(G->stat + tb * 128 + (i0 & 63) * 2);
                bad = or_diff(sv.x ^ ep, sv.z, ep);
#pragma unroll
                for (int i = 0; i < 7; i++) { u[i] = ld_relaxed2(cs + i * 96 + lane); bad = or_diff(bad, u[i].x, ep); }
            } while (bad & 1);
            if (w < 3) sts4(sbase + OFF_ST + i0 * 16, sv);
#pragma unroll
            for (int e = 0; e < 2; e++) {
                float f = 0.f;
#pragma unroll
                for (int i = 0; i < 7; i++) f += __uint_as_float(e ? u[i].y : u[i].x);
                const uint32_t hi = pack2(f, f);
                sts4(sbase + OFF_X + i0 * 32 + e * 16, make_uint4(hi, pack2(f - bf_hi(hi), f - bf_hi(hi)), 0, 0));
            }
            asm volatile("st.shared.u32 [%0], %1;" ::"r"(bars + 8 * NBAR), "r"(ep) : "memory");
            fence_async_shared();
            __syncwarp();
            bar_arrive(8, 224); bar_arrive(9, 224);
            TS(1, 90 + w);
        }
        const uint8_t* src = G->U[nt2][ks * 14];
        uint32_t spins = 0;
        if (w < 3) {
            uint32_t bad;
            if (w == 1) {
                if (elect()) {
                    wait_flag(G->flag[1] + rank * 2 + 1, 44 * ep, spins);
                    asm volatile("mbarrier.arrive.shared::cta.b64 _, [%0], 4;" ::"r"(bars + B_EMPTY + 8 * 5) : "memory");
                    TS(1, 96);
                }
                __syncwarp();
                if (!has_g1) { bar_sync(5, 288); if (elect()) signal(G->flag[0]); __syncwarp(); TS(2, 26); }
            } else {
                bar_sync(3, 288);
                __nanosleep(HALO_NS);
                uint4 v[7];
                do {
                    bad = 0;
#pragma unroll
                    for (int i = 0; i < 7; i++) { v[i] = ld_relaxed4(G->halo[c - (tb > 0)] + i * 512 + lane * 16); bad = or_diff(bad, v[i].x, ep); }
                } while (bad & 1);
#pragma unroll
                for (int i = 0; i < 7; i++) sts4(sbase + OFF_X + i * 512 + lane * 16, v[i]);
                __syncwarp();
                if (elect()) mbar_arrive(bars + B_HALO);
                TS(2, 21);
            }
            mbar_wait(bars + B_HALO, 0);
            uint32_t slot = (has_g1 ? 16 % NSLOT : 0) + w - 1, ph = ~0u;
#pragma unroll 1
            for (int i = w - 1; i < 18;) {
                const uint32_t d0 = sbase + slot * SLOT + (i < 4 ? 0 : 16384), d1 = d0 + (i < 4 ? 8192 : HALF), landed = bars + B_QFULL + 8 * slot;
                mbar_wait(landed, (ph >> slot) & 1);
                ph ^= 1 << slot;
                if (i < 8) TS(4, 82 + i);
                if (i >= 4) TS(8, 156 + i);
                bad = 0;
#pragma unroll
                for (int k = 0; k < 14; k++) bad = or_diff(bad, __float_as_uint(lds1f((k < 7 ? d0 : d1) + k % 7 * 1024 + lane * 32 + (lane >> 2) * 4)), ep);
                if (__any_sync(~0u, bad & 1)) {
                    if (elect()) {
                        const uint8_t* cur = (i < 4 ? G->O[mt][ks * 4] : src - 4 * TILEB) + i * TILEB;
                        fence_async_shared();
                        mbar_expect(landed, TILEB);
                        bulk_load(d0, cur, HALF, landed);
                        bulk_load(d1, cur + HALF, HALF, landed);
                    }
                    TS(4, i < 4 ? 94 : 95);
                } else {
                    if (elect()) mbar_expect(landed + (B_FULL - B_QFULL), i < 4 ? (2 + w) * SLAB : 16384);
                    i += 2;
                    slot += slot < NSLOT - 2 ? 2 : 2 - NSLOT;
                }
            }
        } else {
            bar_sync(2, 288);
            if (elect()) bulk_store(out + row0 * D_, sbase + OFF_Y, TILEB);
            __syncwarp();
            bar_sync(4, 288);
            if (elect()) {
                fence_async_shared();
                bulk_store(G->O[tb][hp], sbase + OFF_X, TILEB);
                bulk_flush();
                TS(2, 7);
                mbar_arrive_remote(mapa(bars + B_FREE, rank ^ 1));
                mbar_arrive(bars + B_FREE);
                hint(G->flag[16 + tb]);
                signal(G->flag[16 + tb] + 1);
                TS(2, 22);
            }
            __syncwarp();
            uint32_t late = ~0u;
            Ring r{has_g1 ? 20u % NSLOT : 4u, has_g1};
#pragma unroll 1
            for (int i = 0; i < 14; i++) {
                while ((late >> i) & 1) late = __ballot_sync(~0u, ld_relaxed(G->flag[8 + nt2 * 2 + ks] + lane) != 2 * ep) & 127;
                if (i == 0) { TS(4, 17); mbar_wait(bars + (has_g1 ? B_X : B_FREE), 0); }
                mbar_wait(bars + B_EMPTY + 8 * r.slot, r.ph);
                TS(8, 192 + i);
                if (elect()) {
                    mbar_expect(bars + B_QFULL + 8 * r.slot, TILEB);
                    bulk_load(sbase + r.slot * SLOT + 16384, src, TILEB, bars + B_QFULL + 8 * r.slot);
                }
                src += TILEB; r.next();
            }
            if (elect()) {
                wait_flag(G->flag[16 + mt] + 1, 8 * ep, spins);
                mbar_arrive(bars + B_ROW);
                TS(2, 27);
                G->epoch[c] = ep;
            }
        }
    } else {
        const int wg = warp >> 2;
        Mma M{bars, mapa(bars, rank ^ (lane & 1)), (threadIdx.x & 127) < 2, wg, w, Ring{0, 0}, 0};
        const int r = lane >> 2, t = lane & 3;
        uint32_t ep;
        const uint32_t bias0 = ld_u16(b1 + ft * 128 + warp * 16 + r), bias1 = ld_u16(b1 + ft * 128 + warp * 16 + r + 8);
        if (wg == 1) {
            ep = ld_relaxed(&G->epoch[c]);
            const int r16 = w * 4 + t, c8 = (r + 2 * t) & 7;
            const uint32_t row = sbase + OFF_Y + r16 * (2 * D_) + c8 * 16;
            mbar_wait(bars + B_ROW, 0);
            TS0(1, 67);
            float f[56];
#pragma unroll
            for (int i = 0; i < 7; i++) {
                const uint4 v = lds4(row + i * 128);
                f[8 * i] = bf_lo(v.x); f[8 * i + 1] = bf_hi(v.x); f[8 * i + 2] = bf_lo(v.y); f[8 * i + 3] = bf_hi(v.y);
                f[8 * i + 4] = bf_lo(v.z); f[8 * i + 5] = bf_hi(v.z); f[8 * i + 6] = bf_lo(v.w); f[8 * i + 7] = bf_hi(v.w);
            }
            float s0 = f[0], s1 = f[1], s2 = f[2], s3 = f[3];
#pragma unroll
            for (int i = 4; i < 56; i += 4) { s0 += f[i]; s1 += f[i + 1]; s2 += f[i + 2]; s3 += f[i + 3]; }
            const float nmean = oct_sum((s0 + s1) + (s2 + s3)) * (-1.f / D_);
            s0 = s1 = s2 = s3 = 0.f;
#pragma unroll
            for (int i = 0; i < 56; i += 4) {
                f[i] += nmean; f[i + 1] += nmean; f[i + 2] += nmean; f[i + 3] += nmean;
                s0 = fmaf(f[i], f[i], s0); s1 = fmaf(f[i + 1], f[i + 1], s1); s2 = fmaf(f[i + 2], f[i + 2], s2); s3 = fmaf(f[i + 3], f[i + 3], s3);
            }
            const float var = oct_sum((s0 + s1) + (s2 + s3)) * (1.f / D_);
            const float rstd = rsq(var + LN_EPS);
            const float sc = rstd * rsq(fmaf(var * rstd, rstd, LN_EPS));
            if (lane < 4) G->stat[row0 + r16] = make_uint2(tag(__float_as_uint(rstd), 1, ~ep), pack2(nmean, nmean - bf_hi(pack2(nmean, nmean))));
            uint8_t* hb = G->H[0][0] + row0 * (SLAB / 16) + r16 * 16 + c8 * 256;
            const int sw = tb < 8 ? 0 : 7 * 256;
#pragma unroll
            for (int i = 0; i < 7; i++) {
                const int lo = (8 * i) % 14, nt = (8 * i) / 14, next = 32 * TILEB - SLAB;
                const int off = lo < 7 ? (c8 < 7 - lo ? sw : -sw) : (c8 >= 14 - lo ? sw + next : -sw);
                *(uint4*)(hb + off + i * 2048 + nt * next) = make_uint4(pack2(f[8 * i] * sc, f[8 * i + 1] * sc), pack2(f[8 * i + 2] * sc, f[8 * i + 3] * sc),
                                                                        pack2(f[8 * i + 4] * sc, f[8 * i + 5] * sc), pack2(f[8 * i + 6] * sc, f[8 * i + 7] * sc));
            }
            TS0(1, 25);
            bar_arrive(6, 224);
        }
        const uint32_t kv = sbase + OFF_X + (w * 2 + wg) * KV + lane * 16;
        uint32_t q[8][2], k0[7], k1[7], v0[7];
        {
            float acc[92];
#pragma unroll 1
            for (int kb = 0; kb < 7; kb++) {
                const bool held = kb == (wg ? 7 - HOLD : -1);
                if (held) { wg_wait<0>(); if (M.lead) mbar_arrive_remote(M.rel + B_QEMPTY + 8 * (6 - HOLD)); bar_sync(7, 256); }
                mbar_wait(bars + B_QFULL + 8 * kb, 0);
                TS0(1, 68 + wg * 7 + kb);
                const uint32_t dA = (xslot(kb) + wg) * 512, dB = wslot(kb) * 512 + (hp & 1);
                wg_fence();
#pragma unroll
                for (int k = 0; k < 4; k++) {
                    wgmma_n184<0, 1, HI_SW, HI_SW>(acc, dA + desc_lo(k * 32, 16), dB + desc_lo((k & 1) * 2048 + (k >> 1) * 12288, 4096), k > 0 || kb > 0);
                    if (k == 0) { wg_commit(); wg_wait<1>(); if (M.lead && kb > 0 && !held) mbar_arrive_remote(M.rel + B_QEMPTY + 8 * (kb - 1)); }
                }
                wg_commit();
            }
            if (wg == 0 && !LATEREL) bar_arrive(7, 256);
            bar_sync(8 + wg, 224);
            ep = __float_as_uint(lds1f(bars + 8 * NBAR));
            const uint32_t st = sbase + OFF_ST + (w * 32 + r * 2 + wg) * 8;
            const uint2 s0 = lds2(st), s1 = lds2(st + 128);
            const uint32_t a0 = t < 2 ? s0.y : 0, a1 = t < 2 ? s1.y : 0;
            wg_fence();
            wgmma_rs_n184<desc_hi(128, 0)>(acc, a0, a1, desc_lo(OFF_X, 0) + (hp & 1) * 8);
            wg_commit();
            if (wg == 0 && LATEREL) bar_arrive(7, 256);
            wg_wait<1>();
            M.release(4);
            wg_wait<0>();
            pin(acc);
            TS0(1, 4 + 7 * wg);
            uint32_t hi[14];
#pragma unroll
            for (int p = 2; p >= 0; p--) {
                const float f = p == 0 ? 0.1889822365046136f * 1.4426950408889634f : p, r0 = __uint_as_float(s0.x) * f, r1 = __uint_as_float(s1.x) * f;
#pragma unroll
                for (int g = 0; g < 7; g++) {
                    const int a = (p * 8 + g) * 4;
                    const uint32_t lo2 = pack2(acc[a] * r0, acc[a + 1] * r0), hi2 = pack2(acc[a + 2] * r1, acc[a + 3] * r1);
                    if (p == 0) { q[g][0] = lo2; q[g][1] = hi2; } else { hi[(p - 1) * 7 + g] = hi2; }
                    if (p == 1) { k0[g] = lo2; k1[g] = hi2; }
                    if (p == 2) v0[g] = lo2;
                }
                if (p == 1) {
#pragma unroll
                    for (int i = 0; i < 3; i++) stsm4(kv + 2 * KV + i * 512, hi[4 * i], hi[4 * i + 1], hi[4 * i + 2], hi[4 * i + 3]);
                    stsm2(kv + 2 * KV + 1536, hi[12], hi[13]);
                    if (w == 3) {
#pragma unroll
                        for (int i = 0; i < 14; i++) stg1(G->halo[c] + wg * KV + lane * 4 + i * 128, tag(hi[i], t == 0, ep));
                    }
                    bar_arrive(3, 288);
                }
            }
#pragma unroll
            for (int j = 0; j < 2; j++) { q[7][j] = t < 2 ? 0u : q[3][j]; q[3][j] = t < 2 ? q[3][j] : 0u; }
#pragma unroll
            for (int g = 0; g < 7; g++) v0[g] = transpose8(v0[g]);
        }
        TS0(1, 9 + 11 * wg);
        float a[56];
#pragma unroll
        for (int i = 0; i < 56; i++) asm volatile("" : "=f"(a[i]));
        if (__builtin_expect(!has_g1, 0)) {
            const int g = min(lane >> 1, 13), nt = rank * 2 + wg;
            const uint4* src = (const uint4*)(wo + (hp * 56 - (hp & 1) * 8 + w * 16 + (lane & 1)) * D_ + nt * 112) + g;
            uint4 v[8];
#pragma unroll
            for (int i = 0; i < 8; i++) v[i] = __ldg(src + i * (D_ / 4));
#pragma unroll
            for (int i = 0; i < 8; i++) ((uint4*)G->Wo[nt][hp])[w * (SLAB / 16) + g * 16 + (lane & 1) + 2 * i] = v[i];
            bar_arrive(5, 288);
        }
        M.run<true>(a, has_g1 ? PAUSE : 0, 1, 16, 0, 0, 32);
        {
            uint32_t kp[8], vv[14];
            TS0(2, 140 + wg);
            mbar_wait(bars + B_HALO, 0);
            TS0(2, 142 + wg);
            ldsm4(kp, kv); ldsm4(kp + 4, kv + (lane < 24 ? 512 : 0));
            const uint32_t va = kv + 896 + (lane & 8) * (2 * KV / 8 - 16) - (lane & 16) * 8;
            ldsm4t(vv, va); ldsm4t(vv + 4, va + 256); ldsm4t(vv + 8, va + 512); ldsm2t(vv + 12, va + 768);
            const bool e0 = 2 * t > r, e1 = 2 * t >= r;
            const uint32_t mk = (e0 ? 0xffffu : 0u) | (e1 ? 0xffff0000u : 0u);
            wg_wait<0>();
            pin(a);
            if (has_g1) M.release(M.prev);
            TS0(2, 144 + wg);
            bar_sync(2, 288);
            mbar_wait(bars + B_HALO, 0);
            TS0(2, 12 + 16 * wg);
            float sv[2][4];
#pragma unroll
            for (int h = 0; h < 2; h++) {
                const int ga = h * 4, gb = h * 4 + 1, gc = h * 4 + 2, gd = h * 4 + 3;
                float s[3][4] = {};
                mma16(s[0], q[ga][0], q[ga][1], q[gb][0], q[gb][1], kp[ga], kp[gb]);
                mma16(s[1], q[ga][0], q[ga][1], q[gb][0], q[gb][1], k0[ga], k0[gb]);
                mma16(s[2], q[ga][0], q[ga][1], q[gb][0], q[gb][1], k1[ga], k1[gb]);
                mma16(s[0], q[gc][0], q[gc][1], q[gd][0], q[gd][1], kp[gc], kp[gd]);
                mma16(s[1], q[gc][0], q[gc][1], q[gd][0], q[gd][1], k0[gc], k0[3]);
                mma16(s[2], q[gc][0], q[gc][1], q[gd][0], q[gd][1], k1[gc], k1[3]);
                if ((tb | w) == 0) s[0][0] = s[0][1] = -1e30f;
                sv[h][0] = e0 ? s[0][0] : s[1][0];
                sv[h][1] = e1 ? s[0][1] : s[1][1];
                sv[h][2] = e0 ? s[1][2] : s[2][2];
                sv[h][3] = e1 ? s[1][3] : s[2][3];
            }
            uint32_t pp[2][2];
#pragma unroll
            for (int i = 0; i < 4; i++) {
                float* v = &sv[i >> 1][(i & 1) * 2];
                const float m = quad_max(fmaxf(v[0], v[1]));
                const float p0 = ex2(v[0] - m), p1 = ex2(v[1] - m);
                const float inv = rcp(quad_sum(p0 + p1));
                pp[i >> 1][i & 1] = pack2(p0 * inv, p1 * inv);
            }
            uint32_t o[8][2];
#pragma unroll
            for (int i = 0; i < 8; i++) {
                const int h = i >> 2, g = i - h;
                float d[4] = {};
                mma16(d, pp[h][0] & mk, 0u, 0u, pp[h][1] & ~mk, vv[2 * g], vv[2 * g + 1]);
                mma8(d, pp[h][0] & ~mk, pp[h][1] & mk, v0[g]);
                o[i][0] = pack2(d[0], d[1]); o[i][1] = pack2(d[2], d[3]);
            }
            if (t >= 2) { o[3][0] = o[4][0]; o[3][1] = o[4][1]; }
            const int word = wg * 4 + t - (w & 1) * 4 - (r >> 2);
#pragma unroll
            for (int i = 0; i < 8; i++) { o[i][0] = tag(o[i][0], word == 0, ep); o[i][1] = tag(o[i][1], word == 2, ep); }
            const uint32_t dst = sbase + OFF_X + (w >> 1) * HALF + ((w & 1) * 32 + (lane & 15) * 2 + wg) * 16 + (lane >> 4) * 1024;
            stsm4(dst, o[0][0], o[0][1], o[1][0], o[1][1]);
            stsm4(dst + 2048, o[2][0], o[2][1], o[3][0], o[3][1]);
            stsm4(dst + 4096, o[5][0], o[5][1], o[6][0], o[6][1]);
            stsm2(dst + 6144, o[7][0], o[7][1]);
            if (ENDBAR) bar_sync(4, 288); else bar_arrive(4, 288);
            TS0(2, 10 + 19 * wg);
        }
        if (has_g1) {
            M.run<true>(a, 16 - PAUSE, 1, 16, LAG1, 1, 32 + PAUSE);
            mbar_wait(bars + B_FREE, 0);
            const uint32_t xb = sbase + OFF_X + wg * 8192 + (threadIdx.x & 127) * 16, xbar = bars + B_X + 16 * wg;
            const uint32_t rx = mapa(xb, rank ^ 1), rbar = mapa(xbar, rank ^ 1);
            wg_wait<0>();
            pin(a);
            M.release(M.prev);
            TS0(4, 5 + wg);
#pragma unroll
            for (int i = 0; i < 3; i++)
                st_async4(rx + i * 2048, rbar + 8 * (i >> 1), pack2(a[28 + 8 * i], a[29 + 8 * i]), pack2(a[30 + 8 * i], a[31 + 8 * i]), pack2(a[32 + 8 * i], a[33 + 8 * i]), pack2(a[34 + 8 * i], a[35 + 8 * i]));
            const uint32_t tail = 6144 - (threadIdx.x & 127) * 8;
            st_async2(rx + tail, rbar + 8, pack2(a[52], a[53]), pack2(a[54], a[55]));
            uint8_t* dst = G->U[nt1][((ft >= 7) + wg) * 7 + ft] + rank * HALF + w * 256 + lane * 4;
            uint32_t u[14];
#pragma unroll
            for (int i = 0; i < 14; i++) {
                if (i % 8 == 0) {
                    mbar_wait(xbar + i, 0);
                    if (i == 0) TS0(4, 1 + wg);
#pragma unroll
                    for (int k = i / 4; k < i / 4 + 2; k++) {
                        if (k < 3) { const uint4 v = lds4(xb + k * 2048); u[4 * k] = v.x; u[4 * k + 1] = v.y; u[4 * k + 2] = v.z; u[4 * k + 3] = v.w; }
                        else { const uint2 v = lds2(xb + tail); u[12] = v.x; u[13] = v.y; }
                    }
                } else if (i % SPLIT == 0) mbar_wait(xbar, 0);
                if (i == HINT && threadIdx.x == 0) hint(G->flag[8 + nt1 * 2] + ft + (ft >= 7) * 25);
                const float bias = bf_lo((i & 1) ? bias1 : bias0);
                stg1(dst + (i >> 1) * 1024 + (i & 1) * 128, tag(pack2(gelu2(a[2 * i] + bias + bf_lo(u[i])), gelu2(a[2 * i + 1] + bias + bf_hi(u[i]))), (lane & 7) == w * 2 + (i & 1), ep));
            }
            TS0(4, 30 + wg);
        }
        uint32_t c0 = ld_u16(b2 + mt * 128 + warp * 16 + r), c1 = ld_u16(b2 + mt * 128 + warp * 16 + r + 8);
        M.run_o(a);
        if (wg == 1) TS0(4, 13);
        c0 *= ks == 0 ? 0x10001u : 0u; c1 *= ks == 0 ? 0x10001u : 0u;
        M.run<false>(a, 14, 0, 15 - NSLOT, LAG2, 1, 52);
        mbar_wait(bars + B_FREE, 0);
        mbar_wait(bars + B_ROW, 1);
        const uint32_t stg = sbase + OFF_X + wg * (OFF_Y - OFF_X) + w * SLAB;
        const uint32_t sa = stg + (lane & 15) * 224 + (lane >> 4) * 16;
        wg_wait<0>();
        pin(a);
        TS0(8, 14 + wg);
#pragma unroll
        for (int i = 0; i < 7; i++)
            stsm4(sa + i * 32, half_plus(pack2(a[8 * i], a[8 * i + 1]), c0), half_plus(pack2(a[8 * i + 2], a[8 * i + 3]), c1),
                  half_plus(pack2(a[8 * i + 4], a[8 * i + 5]), c0), half_plus(pack2(a[8 * i + 6], a[8 * i + 7]), c1));
        fence_async_shared();
        __syncwarp();
        if (elect()) {
            asm volatile("cp.reduce.async.bulk.tensor.2d.global.shared::cta.add.tile.bulk_group [%0, {%2, %3}], [%1];\ncp.async.bulk.commit_group;" ::"l"(&P.tmOut), "r"(stg), "r"(nt2 * 112), "r"(mt * 128 + warp * 16) : "memory");
            if (w == 0) mbar_arrive(bars + B_END);
            asm volatile("cp.async.bulk.wait_group.read 0;" ::: "memory");
        }
        if (wg == 1) TS0(15, 19);
        TSDUMP();
    }
}

typedef CUresult (*EncodeFn)(CUtensorMap*, CUtensorMapDataType, cuuint32_t, void*, const cuuint64_t*, const cuuint64_t*, const cuuint32_t*, const cuuint32_t*,
                             CUtensorMapInterleave, CUtensorMapSwizzle, CUtensorMapL2promotion, CUtensorMapFloatOOBfill);

void make_map(EncodeFn enc, CUtensorMap* tm, const void* base, bool swizzle, int d0, int d1, int d2, int s1, int s2, int b0, int b1, int b2) {
    const cuuint64_t dims[3] = {(cuuint64_t)d0, (cuuint64_t)d1, (cuuint64_t)d2}, strides[2] = {(cuuint64_t)s1 * 2, (cuuint64_t)s2 * 2};
    const cuuint32_t box[3] = {(cuuint32_t)b0, (cuuint32_t)b1, (cuuint32_t)b2}, es[3] = {1, 1, 1};
    enc(tm, CU_TENSOR_MAP_DATA_TYPE_BFLOAT16, d2 ? 3 : 2, (void*)base, dims, strides, box, es, CU_TENSOR_MAP_INTERLEAVE_NONE,
        swizzle ? CU_TENSOR_MAP_SWIZZLE_128B : CU_TENSOR_MAP_SWIZZLE_NONE, CU_TENSOR_MAP_L2_PROMOTION_L2_128B, CU_TENSOR_MAP_FLOAT_OOB_FILL_NONE);
}

}

extern "C" void kernel_launch(void* const* d_in, const int* in_sizes, int n_in, void* d_out, int out_size) {
    static EncodeFn enc = nullptr;
    static Scratch* scratch = nullptr;
    if (!enc) {
        void* fn = nullptr;
        cudaDriverEntryPointQueryResult qr;
        cudaGetDriverEntryPoint("cuTensorMapEncodeTiled", &fn, cudaEnableDefault, &qr);
        enc = (EncodeFn)fn;
        cudaGetSymbolAddress((void**)&scratch, g_s);
        cudaFuncSetAttribute(fused_kernel, cudaFuncAttributeMaxDynamicSharedMemorySize, SMEM_BYTES);
    }
    Params P;
    const __nv_bfloat16* x = (const __nv_bfloat16*)d_in[0];
    make_map(enc, &P.tmX, x, true, D_, S_ / 2, 2, 2 * D_, D_, 64, 64, 2);
    make_map(enc, &P.tmWqkv, d_in[1], true, D_, D_, 3, 3 * D_, D_, 64, 32, 3);
    make_map(enc, &P.tmW1, d_in[4], true, 64, S_, F_ / 64, F_, 64, 64, 64, 2);
    make_map(enc, &P.tmW2, d_in[6], true, S_, F_, 0, S_, 0, 64, 64, 1);
    make_map(enc, &P.tmOut, d_out, false, D_, S_, 0, D_, 0, 112, 16, 1);
    fused_kernel<<<NCTA, NTHREADS, SMEM_BYTES, cudaStreamPerThread>>>(x, (const __nv_bfloat16*)d_in[5], (const __nv_bfloat16*)d_in[7], (const __nv_bfloat16*)d_in[2], (__nv_bfloat16*)d_out, scratch,
                                                                      (const __nv_bfloat16*)d_in[4], (const __nv_bfloat16*)d_in[6], P);
}
```

```cpp
#include <cuda_runtime.h>
#include <cuda_bf16.h>
#include <cuda.h>
#include <stdint.h>

#define HALO_NS 300
#define HINT 4
#define HOLD 2
#define ROT 4
#define LATEREL 0
#define PF 400
#define PF0 2
#define PF1 8
#define ENDBAR 1
#define PG0 3
#define PG1 5
#define STG1 4
#define STG0 4
#define STGS 1
#define UGAP 120
#define UGAPN 6
#define PACE 800
#define PAUSE 8
#define LAG1 4
#define LAG2 6

namespace {

constexpr int S_ = 2048, D_ = 448, F_ = 1792;
constexpr int NCTA = 128, NTHREADS = 384;
constexpr int NSLOT = 6, SLOT = 32768, QSLOT = 40960, TILEB = 14336, SLAB = 3584, HALF = 7168;
constexpr int KV = 1792;
constexpr int OFF_X = NSLOT * SLOT;
constexpr int OFF_Y = OFF_X + 10 * KV;
constexpr int OFF_ST = OFF_Y + TILEB;
constexpr int OFF_BAR = OFF_ST + 1024;
constexpr int SMEM_BYTES = OFF_BAR + 1280;
constexpr uint32_t SMEM0 = 1024;
constexpr int B_QFULL = 0, B_FULL = 56, B_ROW = 112, B_CS = 120, B_HALO = 128, B_X = 136, B_FREE = 176, B_END = 184, B_QEMPTY = 192, B_EMPTY = 208, NBAR = 33;
constexpr float LN_EPS = 1e-5f;
constexpr int SPIN_LIMIT = 1 << 22;

struct Scratch {
    uint8_t H[4][32][TILEB];
    uint8_t U[4][28][TILEB];
    uint8_t O[16][8][TILEB];
    uint8_t Wo[4][8][TILEB];
    uint8_t halo[NCTA][2 * KV];
    uint2 stat[S_];
    uint2 colsum[8][8][96];
    uint32_t flag[32][32];
    uint32_t epoch[NCTA];
};
__device__ __align__(1024) Scratch g_s;

#define TS(g, i)
#define TS0(g, i)
#define TSDUMP()

struct Params {
    CUtensorMap tmX, tmWqkv, tmW1, tmW2, tmOut;
};

__device__ __forceinline__ bool elect() {
    uint32_t p;
    asm volatile("{\n.reg .pred p;\nelect.sync _|p, 0xffffffff;\nselp.u32 %0, 1, 0, p;\n}" : "=r"(p));
    return p;
}
__device__ __forceinline__ void mbar_init(uint32_t b, uint32_t c) { asm volatile("mbarrier.init.shared::cta.b64 [%0], %1;" ::"r"(b), "r"(c) : "memory"); }
__device__ __forceinline__ void mbar_expect(uint32_t b, uint32_t tx) { asm volatile("mbarrier.arrive.expect_tx.shared::cta.b64 _, [%0], %1;" ::"r"(b), "r"(tx) : "memory"); }
__device__ __forceinline__ void mbar_arrive(uint32_t b) { asm volatile("mbarrier.arrive.shared::cta.b64 _, [%0];" ::"r"(b) : "memory"); }
__device__ __forceinline__ void mbar_arrive16(uint32_t b) { asm volatile("mbarrier.arrive.shared::cta.b64 _, [%0], 16;" ::"r"(b) : "memory"); }
__device__ __forceinline__ void mbar_arrive4_remote(uint32_t b) { asm volatile("mbarrier.arrive.shared::cluster.b64 _, [%0], 4;" ::"r"(b) : "memory"); }
__device__ __forceinline__ void mbar_arrive_remote(uint32_t b) { asm volatile("mbarrier.arrive.shared::cluster.b64 _, [%0];" ::"r"(b) : "memory"); }
#define MBAR_WAIT_ASM(SEM) \
    asm volatile("{\n.reg .pred p;\nWAIT:\nmbarrier.try_wait.parity" SEM ".shared::cta.b64 p, [%0], %1;\n@!p bra WAIT;\n}" ::"r"(b), "r"(parity) : "memory")
__device__ __forceinline__ void mbar_wait(uint32_t b, uint32_t parity) { MBAR_WAIT_ASM(""); }
__device__ __forceinline__ void mbar_wait_bounded(uint32_t b, uint32_t parity, uint32_t& n) {
    asm volatile("{\n.reg .pred p;\nWAIT:\nadd.u32 %0, %0, 1;\nsetp.gt.u32 p, %0, %3;\n@p st.global.u32 [%4], %0;\n"
                 "mbarrier.try_wait.parity.shared::cta.b64 p, [%1], %2;\n@!p bra WAIT;\n}" : "+r"(n) : "r"(b), "r"(parity), "n"(SPIN_LIMIT), "l"(0ull) : "memory");
}
__device__ __forceinline__ uint32_t mapa(uint32_t a, uint32_t rank) { uint32_t r; asm("mapa.shared::cluster.u32 %0, %1, %2;" : "=r"(r) : "r"(a), "r"(rank)); return r; }
__device__ __forceinline__ void tma3d(uint32_t dst, const CUtensorMap* tm, uint32_t bar, int c0, int c1, int c2) {
    asm volatile("cp.async.bulk.tensor.3d.shared::cluster.global.mbarrier::complete_tx::bytes [%0], [%1, {%3, %4, %5}], [%2];" ::"r"(dst), "l"(tm), "r"(bar), "r"(c0), "r"(c1), "r"(c2) : "memory");
}
__device__ __forceinline__ void tma2d_pair(uint32_t dst, const CUtensorMap* tm, uint32_t bar, int c0, int c1) {
    asm volatile("cp.async.bulk.tensor.2d.shared::cluster.global.mbarrier::complete_tx::bytes.multicast::cluster [%0], [%1, {%3, %4}], [%2], %5;" ::"r"(dst), "l"(tm), "r"(bar), "r"(c0), "r"(c1), "h"((uint16_t)3) : "memory");
}
__device__ __forceinline__ void tma3d_pair(uint32_t dst, const CUtensorMap* tm, uint32_t bar, int c0, int c1, int c2) {
    asm volatile("cp.async.bulk.tensor.3d.shared::cluster.global.mbarrier::complete_tx::bytes.multicast::cluster [%0], [%1, {%3, %4, %5}], [%2], %6;" ::"r"(dst), "l"(tm), "r"(bar), "r"(c0), "r"(c1), "r"(c2), "h"((uint16_t)3) : "memory");
}
__device__ __forceinline__ void bulk_load(uint32_t dst, const void* src, uint32_t bytes, uint32_t bar) {
    asm volatile("cp.async.bulk.shared::cluster.global.mbarrier::complete_tx::bytes [%0], [%1], %2, [%3];" ::"r"(dst), "l"(src), "r"(bytes), "r"(bar) : "memory");
}
__device__ __forceinline__ void bulk_load_pair(uint32_t dst, const void* src, uint32_t bytes, uint32_t bar) {
    asm volatile("cp.async.bulk.shared::cluster.global.mbarrier::complete_tx::bytes.multicast::cluster [%0], [%1], %2, [%3], %4;" ::"r"(dst), "l"(src), "r"(bytes), "r"(bar), "h"((uint16_t)3) : "memory");
}
__device__ __forceinline__ void bulk_store(void* dst, uint32_t src, uint32_t bytes) {
    asm volatile("cp.async.bulk.global.shared::cta.bulk_group [%0], [%1], %2;" ::"l"(dst), "r"(src), "r"(bytes) : "memory");
}
__device__ __forceinline__ uint32_t ld_u16(const void* p) { uint32_t v; asm volatile("ld.global.nc.u16 %0, [%1];" : "=r"(v) : "l"(p)); return v; }
__device__ __forceinline__ uint32_t ld_relaxed(const uint32_t* p) { uint32_t v; asm volatile("ld.relaxed.gpu.global.u32 %0, [%1];" : "=r"(v) : "l"(p) : "memory"); return v; }
__device__ __forceinline__ void bulk_flush() { asm volatile("cp.async.bulk.commit_group;\ncp.async.bulk.wait_group 0;" ::: "memory"); }
__device__ __forceinline__ void signal(uint32_t* flag) { asm volatile("fence.acq_rel.gpu;\nred.relaxed.gpu.global.add.u32 [%0], 1;" ::"l"(flag) : "memory"); }
__device__ __forceinline__ void hint(uint32_t* flag) { asm volatile("red.relaxed.gpu.global.add.u32 [%0], 1;" ::"l"(flag) : "memory"); }
__device__ __forceinline__ uint32_t tag(uint32_t v, uint32_t mask, uint32_t parity) { return (v & ~mask) | (parity & mask); }
__device__ __forceinline__ uint32_t or_diff(uint32_t acc, uint32_t v, uint32_t parity) { asm("lop3.b32 %0, %0, %1, %2, 0xf6;" : "+r"(acc) : "r"(v), "r"(parity)); return acc; }
__device__ __forceinline__ uint4 ld_relaxed4(const void* p) {
    uint4 v;
    asm volatile("ld.relaxed.gpu.global.v4.u32 {%0, %1, %2, %3}, [%4];" : "=r"(v.x), "=r"(v.y), "=r"(v.z), "=r"(v.w) : "l"(p) : "memory");
    return v;
}
__device__ __forceinline__ uint2 ld_relaxed2(const void* p) { uint2 v; asm volatile("ld.relaxed.gpu.global.v2.u32 {%0, %1}, [%2];" : "=r"(v.x), "=r"(v.y) : "l"(p) : "memory"); return v; }
__device__ __forceinline__ void sts4(uint32_t a, uint4 v) { asm volatile("st.shared.v4.b32 [%0], {%1, %2, %3, %4};" ::"r"(a), "r"(v.x), "r"(v.y), "r"(v.z), "r"(v.w) : "memory"); }
__device__ __forceinline__ void stg1(void* p, uint32_t v) { asm volatile("st.global.b32 [%0], %1;" ::"l"(p), "r"(v) : "memory"); }
__device__ __forceinline__ void fence_async_shared() { asm volatile("fence.proxy.async.shared::cta;" ::: "memory"); }
#define BOUND "add.u32 %0, %0, 16;\nsetp.gt.u32 p, %0, %1;\n@p st.global.u32 [%2], %0;\n"
__device__ __forceinline__ void wait_flag(const uint32_t* p, uint32_t target, uint32_t& n) {
    asm volatile("{\n.reg .pred p;\n.reg .u32 v;\nPOLL:\n" BOUND "ld.acquire.gpu.global.u32 v, [%3];\nsetp.ne.u32 p, v, %4;\n@p bra POLL;\nfence.proxy.async.global;\n}"
                 : "+r"(n) : "n"(SPIN_LIMIT), "l"(0ull), "l"(p), "r"(target) : "memory");
}
__device__ __forceinline__ void wait_flag2(const uint32_t* h, uint32_t th, const uint32_t* p, uint32_t target, uint32_t& n) {
    asm volatile("{\n.reg .pred p;\n.reg .u32 u, v;\nPOLL:\n" BOUND "ld.relaxed.gpu.global.u32 u, [%3];\nld.acquire.gpu.global.u32 v, [%5];\nsetp.ne.u32 p, u, %4;\nsetp.ne.or.u32 p, v, %6, p;\n@p bra POLL;\nfence.proxy.async.global;\n}"
                 : "+r"(n) : "n"(SPIN_LIMIT), "l"(0ull), "l"(h), "r"(th), "l"(p), "r"(target) : "memory");
}
__device__ __forceinline__ void bar_sync(int id, int n) { asm volatile("bar.sync %0, %1;" ::"r"(id), "r"(n) : "memory"); }
__device__ __forceinline__ void bar_arrive(int id, int n) { asm volatile("bar.arrive %0, %1;" ::"r"(id), "r"(n) : "memory"); }
__device__ __forceinline__ void wg_fence() { asm volatile("wgmma.fence.sync.aligned;" ::: "memory"); }
__device__ __forceinline__ void wg_commit() { asm volatile("wgmma.commit_group.sync.aligned;" ::: "memory"); }
template <int N> __device__ __forceinline__ void wg_wait() { asm volatile("wgmma.wait_group.sync.aligned %0;" ::"n"(N) : "memory"); }
template <int N> __device__ __forceinline__ void pin(float (&d)[N]) {
#pragma unroll
    for (int i = 0; i < N; i++) asm volatile("" : "+f"(d[i])::"memory");
}
__host__ __device__ constexpr uint32_t desc_hi(uint32_t sbo, uint32_t swz) { return (sbo >> 4) | (swz << 30); }
__host__ __device__ constexpr uint32_t desc_lo(uint32_t off, uint32_t lbo) { return ((SMEM0 + off) >> 4) | ((lbo >> 4) << 16); }
__device__ __forceinline__ uint32_t pack2(float lo, float hi) { uint32_t r; asm("cvt.rn.bf16x2.f32 %0, %1, %2;" : "=r"(r) : "f"(hi), "f"(lo)); return r; }
__device__ __forceinline__ float bf_lo(uint32_t v) { return __uint_as_float(v << 16); }
__device__ __forceinline__ float bf_hi(uint32_t v) { return __uint_as_float(v & 0xffff0000u); }
__device__ __forceinline__ uint32_t half_plus(uint32_t a, uint32_t b) { uint32_t r; asm("fma.rn.bf16x2 %0, %1, %2, %3;" : "=r"(r) : "r"(a), "r"(0x3f003f00u), "r"(b)); return r; }
__device__ __forceinline__ void stsm4(uint32_t a, uint32_t r0, uint32_t r1, uint32_t r2, uint32_t r3) {
    asm volatile("stmatrix.sync.aligned.m8n8.x4.shared.b16 [%0], {%1, %2, %3, %4};" ::"r"(a), "r"(r0), "r"(r1), "r"(r2), "r"(r3) : "memory");
}
__device__ __forceinline__ void stsm2(uint32_t a, uint32_t r0, uint32_t r1) {
    asm volatile("stmatrix.sync.aligned.m8n8.x2.shared.b16 [%0], {%1, %2};" ::"r"(a), "r"(r0), "r"(r1) : "memory");
}
__device__ __forceinline__ uint4 lds4(uint32_t a) { uint4 v; asm volatile("ld.shared.v4.b32 {%0, %1, %2, %3}, [%4];" : "=r"(v.x), "=r"(v.y), "=r"(v.z), "=r"(v.w) : "r"(a) : "memory"); return v; }
__device__ __forceinline__ uint2 lds2(uint32_t a) { uint2 v; asm volatile("ld.shared.v2.b32 {%0, %1}, [%2];" : "=r"(v.x), "=r"(v.y) : "r"(a) : "memory"); return v; }
__device__ __forceinline__ float lds1f(uint32_t a) { float v; asm volatile("ld.shared.f32 %0, [%1];" : "=f"(v) : "r"(a) : "memory"); return v; }
__device__ __forceinline__ void ldsm4(uint32_t* r, uint32_t a) {
    asm volatile("ldmatrix.sync.aligned.m8n8.x4.shared.b16 {%0, %1, %2, %3}, [%4];" : "=r"(r[0]), "=r"(r[1]), "=r"(r[2]), "=r"(r[3]) : "r"(a) : "memory");
}
__device__ __forceinline__ void ldsm4t(uint32_t* r, uint32_t a) {
    asm volatile("ldmatrix.sync.aligned.m8n8.x4.trans.shared.b16 {%0, %1, %2, %3}, [%4];" : "=r"(r[0]), "=r"(r[1]), "=r"(r[2]), "=r"(r[3]) : "r"(a) : "memory");
}
__device__ __forceinline__ void ldsm2t(uint32_t* r, uint32_t a) {
    asm volatile("ldmatrix.sync.aligned.m8n8.x2.trans.shared.b16 {%0, %1}, [%2];" : "=r"(r[0]), "=r"(r[1]) : "r"(a) : "memory");
}
__device__ __forceinline__ uint32_t transpose8(uint32_t v) { uint32_t r; asm volatile("movmatrix.sync.aligned.m8n8.trans.b16 %0, %1;" : "=r"(r) : "r"(v)); return r; }
__device__ __forceinline__ void mma16(float (&c)[4], uint32_t a0, uint32_t a1, uint32_t a2, uint32_t a3, uint32_t b0, uint32_t b1) {
    asm volatile("mma.sync.aligned.m16n8k16.row.col.f32.bf16.bf16.f32 {%0, %1, %2, %3}, {%4, %5, %6, %7}, {%8, %9}, {%0, %1, %2, %3};"
                 : "+f"(c[0]), "+f"(c[1]), "+f"(c[2]), "+f"(c[3]) : "r"(a0), "r"(a1), "r"(a2), "r"(a3), "r"(b0), "r"(b1));
}
__device__ __forceinline__ void mma8(float (&c)[4], uint32_t a0, uint32_t a1, uint32_t b0) {
    asm volatile("mma.sync.aligned.m16n8k8.row.col.f32.bf16.bf16.f32 {%0, %1, %2, %3}, {%4, %5}, {%6}, {%0, %1, %2, %3};"
                 : "+f"(c[0]), "+f"(c[1]), "+f"(c[2]), "+f"(c[3]) : "r"(a0), "r"(a1), "r"(b0));
}
__device__ __forceinline__ void st_async4(uint32_t a, uint32_t bar, uint32_t v0, uint32_t v1, uint32_t v2, uint32_t v3) {
    asm volatile("st.async.weak.shared::cluster.mbarrier::complete_tx::bytes.v4.b32 [%0], {%2, %3, %4, %5}, [%1];" ::"r"(a), "r"(bar), "r"(v0), "r"(v1), "r"(v2), "r"(v3) : "memory");
}
__device__ __forceinline__ void st_async2(uint32_t a, uint32_t bar, uint32_t v0, uint32_t v1) {
    asm volatile("st.async.weak.shared::cluster.mbarrier::complete_tx::bytes.v2.b32 [%0], {%2, %3}, [%1];" ::"r"(a), "r"(bar), "r"(v0), "r"(v1) : "memory");
}
__device__ __forceinline__ float quad_max(float v) { v = fmaxf(v, __shfl_xor_sync(~0u, v, 1)); return fmaxf(v, __shfl_xor_sync(~0u, v, 2)); }
__device__ __forceinline__ float quad_sum(float v) { v += __shfl_xor_sync(~0u, v, 1); return v + __shfl_xor_sync(~0u, v, 2); }
__device__ __forceinline__ float ex2(float v) { float r; asm("ex2.approx.ftz.f32 %0, %1;" : "=f"(r) : "f"(v)); return r; }
__device__ __forceinline__ float rcp(float v) { float r; asm("rcp.approx.ftz.f32 %0, %1;" : "=f"(r) : "f"(v)); return r; }
__device__ __forceinline__ float rsq(float v) { float r; asm("rsqrt.approx.ftz.f32 %0, %1;" : "=f"(r) : "f"(v)); return r; }
__device__ __forceinline__ float gelu2(float u) {
    float z = u * fmaf(u * u, 0.044715f * 0.7978845608028654f, 0.7978845608028654f), t;
    asm("tanh.approx.f32 %0, %1;" : "=f"(t) : "f"(z));
    return fmaf(u, t, u);
}
__device__ __forceinline__ float oct_sum(float v) {
    v += __shfl_xor_sync(~0u, v, 4); v += __shfl_xor_sync(~0u, v, 8); v += __shfl_xor_sync(~0u, v, 16);
    return v;
}

template <int TA, int TB, uint32_t HA, uint32_t HB>
__device__ __forceinline__ void wgmma_n112(float (&d)[56], uint32_t da, uint32_t db, int accumulate) {
    asm volatile("{\n.reg .pred p;\n.reg .b64 a, b;\nmov.b64 a, {%56, %61};\nmov.b64 b, {%57, %62};\nsetp.ne.b32 p, %58, 0;\n"
        "wgmma.mma_async.sync.aligned.m64n112k16.f32.bf16.bf16 {"
        "%0, %1, %2, %3, %4, %5, %6, %7, %8, %9, %10, %11, %12, %13, %14, %15, "
        "%16, %17, %18, %19, %20, %21, %22, %23, %24, %25, %26, %27, %28, %29, %30, %31, "
        "%32, %33, %34, %35, %36, %37, %38, %39, %40, %41, %42, %43, %44, %45, %46, %47, "
        "%48, %49, %50, %51, %52, %53, %54, %55"
        "}, a, b, p, 1, 1, %59, %60;\n}\n"
        : "+f"(d[0]), "+f"(d[1]), "+f"(d[2]), "+f"(d[3]), "+f"(d[4]), "+f"(d[5]), "+f"(d[6]), "+f"(d[7]),
          "+f"(d[8]), "+f"(d[9]), "+f"(d[10]), "+f"(d[11]), "+f"(d[12]), "+f"(d[13]), "+f"(d[14]), "+f"(d[15]),
          "+f"(d[16]), "+f"(d[17]), "+f"(d[18]), "+f"(d[19]), "+f"(d[20]), "+f"(d[21]), "+f"(d[22]), "+f"(d[23]),
          "+f"(d[24]), "+f"(d[25]), "+f"(d[26]), "+f"(d[27]), "+f"(d[28]), "+f"(d[29]), "+f"(d[30]), "+f"(d[31]),
          "+f"(d[32]), "+f"(d[33]), "+f"(d[34]), "+f"(d[35]), "+f"(d[36]), "+f"(d[37]), "+f"(d[38]), "+f"(d[39]),
          "+f"(d[40]), "+f"(d[41]), "+f"(d[42]), "+f"(d[43]), "+f"(d[44]), "+f"(d[45]), "+f"(d[46]), "+f"(d[47]),
          "+f"(d[48]), "+f"(d[49]), "+f"(d[50]), "+f"(d[51]), "+f"(d[52]), "+f"(d[53]), "+f"(d[54]), "+f"(d[55])
        : "r"(da), "r"(db), "r"(accumulate), "n"(TA), "n"(TB), "n"(HA), "n"(HB));
}

template <int TA, int TB, uint32_t HA, uint32_t HB>
__device__ __forceinline__ void wgmma_n184(float (&d)[92], uint32_t da, uint32_t db, int accumulate) {
    asm volatile("{\n.reg .pred p;\n.reg .b64 a, b;\nmov.b64 a, {%92, %97};\nmov.b64 b, {%93, %98};\nsetp.ne.b32 p, %94, 0;\n"
        "wgmma.mma_async.sync.aligned.m64n184k16.f32.bf16.bf16 {"
        "%0, %1, %2, %3, %4, %5, %6, %7, %8, %9, %10, %11, %12, %13, %14, %15, "
        "%16, %17, %18, %19, %20, %21, %22, %23, %24, %25, %26, %27, %28, %29, %30, %31, "
        "%32, %33, %34, %35, %36, %37, %38, %39, %40, %41, %42, %43, %44, %45, %46, %47, "
        "%48, %49, %50, %51, %52, %53, %54, %55, %56, %57, %58, %59, %60, %61, %62, %63, "
        "%64, %65, %66, %67, %68, %69, %70, %71, %72, %73, %74, %75, %76, %77, %78, %79, "
        "%80, %81, %82, %83, %84, %85, %86, %87, %88, %89, %90, %91"
        "}, a, b, p, 1, 1, %95, %96;\n}\n"
        : "+f"(d[0]), "+f"(d[1]), "+f"(d[2]), "+f"(d[3]), "+f"(d[4]), "+f"(d[5]), "+f"(d[6]), "+f"(d[7]),
          "+f"(d[8]), "+f"(d[9]), "+f"(d[10]), "+f"(d[11]), "+f"(d[12]), "+f"(d[13]), "+f"(d[14]), "+f"(d[15]),
          "+f"(d[16]), "+f"(d[17]), "+f"(d[18]), "+f"(d[19]), "+f"(d[20]), "+f"(d[21]), "+f"(d[22]), "+f"(d[23]),
          "+f"(d[24]), "+f"(d[25]), "+f"(d[26]), "+f"(d[27]), "+f"(d[28]), "+f"(d[29]), "+f"(d[30]), "+f"(d[31]),
          "+f"(d[32]), "+f"(d[33]), "+f"(d[34]), "+f"(d[35]), "+f"(d[36]), "+f"(d[37]), "+f"(d[38]), "+f"(d[39]),
          "+f"(d[40]), "+f"(d[41]), "+f"(d[42]), "+f"(d[43]), "+f"(d[44]), "+f"(d[45]), "+f"(d[46]), "+f"(d[47]),
          "+f"(d[48]), "+f"(d[49]), "+f"(d[50]), "+f"(d[51]), "+f"(d[52]), "+f"(d[53]), "+f"(d[54]), "+f"(d[55]),
          "+f"(d[56]), "+f"(d[57]), "+f"(d[58]), "+f"(d[59]), "+f"(d[60]), "+f"(d[61]), "+f"(d[62]), "+f"(d[63]),
          "+f"(d[64]), "+f"(d[65]), "+f"(d[66]), "+f"(d[67]), "+f"(d[68]), "+f"(d[69]), "+f"(d[70]), "+f"(d[71]),
          "+f"(d[72]), "+f"(d[73]), "+f"(d[74]), "+f"(d[75]), "+f"(d[76]), "+f"(d[77]), "+f"(d[78]), "+f"(d[79]),
          "+f"(d[80]), "+f"(d[81]), "+f"(d[82]), "+f"(d[83]), "+f"(d[84]), "+f"(d[85]), "+f"(d[86]), "+f"(d[87]),
          "+f"(d[88]), "+f"(d[89]), "+f"(d[90]), "+f"(d[91])
        : "r"(da), "r"(db), "r"(accumulate), "n"(TA), "n"(TB), "n"(HA), "n"(HB));
}

template <uint32_t HB>
__device__ __forceinline__ void wgmma_rs_n184(float (&d)[92], uint32_t a0, uint32_t a1, uint32_t db) {
    asm volatile("{\n.reg .b64 b;\nmov.b64 b, {%94, %96};\n"
        "wgmma.mma_async.sync.aligned.m64n184k16.f32.bf16.bf16 {"
        "%0, %1, %2, %3, %4, %5, %6, %7, %8, %9, %10, %11, %12, %13, %14, %15, "
        "%16, %17, %18, %19, %20, %21, %22, %23, %24, %25, %26, %27, %28, %29, %30, %31, "
        "%32, %33, %34, %35, %36, %37, %38, %39, %40, %41, %42, %43, %44, %45, %46, %47, "
        "%48, %49, %50, %51, %52, %53, %54, %55, %56, %57, %58, %59, %60, %61, %62, %63, "
        "%64, %65, %66, %67, %68, %69, %70, %71, %72, %73, %74, %75, %76, %77, %78, %79, "
        "%80, %81, %82, %83, %84, %85, %86, %87, %88, %89, %90, %91"
        "}, {%92, %93, %95, %95}, b, 1, 1, 1, 0;\n}\n"
        : "+f"(d[0]), "+f"(d[1]), "+f"(d[2]), "+f"(d[3]), "+f"(d[4]), "+f"(d[5]), "+f"(d[6]), "+f"(d[7]),
          "+f"(d[8]), "+f"(d[9]), "+f"(d[10]), "+f"(d[11]), "+f"(d[12]), "+f"(d[13]), "+f"(d[14]), "+f"(d[15]),
          "+f"(d[16]), "+f"(d[17]), "+f"(d[18]), "+f"(d[19]), "+f"(d[20]), "+f"(d[21]), "+f"(d[22]), "+f"(d[23]),
          "+f"(d[24]), "+f"(d[25]), "+f"(d[26]), "+f"(d[27]), "+f"(d[28]), "+f"(d[29]), "+f"(d[30]), "+f"(d[31]),
          "+f"(d[32]), "+f"(d[33]), "+f"(d[34]), "+f"(d[35]), "+f"(d[36]), "+f"(d[37]), "+f"(d[38]), "+f"(d[39]),
          "+f"(d[40]), "+f"(d[41]), "+f"(d[42]), "+f"(d[43]), "+f"(d[44]), "+f"(d[45]), "+f"(d[46]), "+f"(d[47]),
          "+f"(d[48]), "+f"(d[49]), "+f"(d[50]), "+f"(d[51]), "+f"(d[52]), "+f"(d[53]), "+f"(d[54]), "+f"(d[55]),
          "+f"(d[56]), "+f"(d[57]), "+f"(d[58]), "+f"(d[59]), "+f"(d[60]), "+f"(d[61]), "+f"(d[62]), "+f"(d[63]),
          "+f"(d[64]), "+f"(d[65]), "+f"(d[66]), "+f"(d[67]), "+f"(d[68]), "+f"(d[69]), "+f"(d[70]), "+f"(d[71]),
          "+f"(d[72]), "+f"(d[73]), "+f"(d[74]), "+f"(d[75]), "+f"(d[76]), "+f"(d[77]), "+f"(d[78]), "+f"(d[79]),
          "+f"(d[80]), "+f"(d[81]), "+f"(d[82]), "+f"(d[83]), "+f"(d[84]), "+f"(d[85]), "+f"(d[86]), "+f"(d[87]),
          "+f"(d[88]), "+f"(d[89]), "+f"(d[90]), "+f"(d[91])
        : "r"(a0), "r"(a1), "r"(db), "r"(0), "n"(HB));
}

struct Ring {
    uint32_t slot, ph;
    __device__ __forceinline__ void next() { if (++slot == NSLOT) { slot = 0; ph ^= 1; } }
    __device__ __forceinline__ void next2() { ph ^= slot == 5; slot = __byte_perm(0x06030201u, 0x00040005u, 0x7770 + slot); }
};
struct Slot {
    uint32_t dst, bar, ph;
    __device__ __forceinline__ void next(uint32_t bars) {
        dst += SLOT; bar += 8;
        if (bar == bars + 8 * NSLOT) { dst -= NSLOT * SLOT; bar = bars; ph ^= 1; }
    }
};
__device__ __forceinline__ uint32_t xslot(int i) { return __byte_perm(0x04130e0cu, 0x00130e0cu, 0x7770 + i); }
__device__ __forceinline__ uint32_t wslot(int i) { return __byte_perm(0x06001510u, 0x00151009u, 0x7770 + i); }

constexpr uint32_t HI_SW = desc_hi(1024, 1);

struct Mma {
    uint32_t bars, rel;
    bool lead;
    int wg, w;
    Ring r;
    uint32_t prev;
    __device__ __forceinline__ void release(uint32_t s) { if (lead) mbar_arrive4_remote(rel + B_EMPTY + 8 * s); }
    template <bool G1>
    __device__ __forceinline__ void run(float (&a)[56], int n, int first, int last, int lag, int accumulate, int ts) {
#pragma unroll 1
        for (int i = 0; i < n; i++) {
            if (lag && i == (wg ? n - lag : -1)) bar_sync(7, 256);
            const uint32_t s = r.slot;
            mbar_wait(bars + B_FULL + 8 * s, r.ph);
            if (G1) r.next(); else r.next2();
            TS0(G1 ? 2 : 8, ts + i + wg * 68);
            const uint32_t dB = s * (SLOT >> 4), dA = dB + wg * 512;
            wg_fence();
#pragma unroll
            for (int k = 0; k < 4; k++) {
                wgmma_n112<1, 1, HI_SW, desc_hi(G1 ? 256 : 1024, 0)>(a, dA + desc_lo(k * 2048, 8192), dB + desc_lo(16384 + k * (G1 ? SLAB : 256), 128), k > 0 || accumulate || i > 0);
                if (k == 1) {
                    wg_commit(); wg_wait<1>();
                    if ((uint32_t)(i - first) < (uint32_t)(last - first)) release(prev);
                    if (lag && i == (wg ? -1 : n - 1)) bar_arrive(7, 256);
                }
            }
            wg_commit();
            prev = s;
        }
    }
    __device__ __forceinline__ void run_o(float (&a)[56]) {
#pragma unroll 1
        for (int i = 0; i < 2; i++) {
            const uint32_t s = r.slot, dB = s * (SLOT >> 4), dA = dB + wg * 512;
            mbar_wait(bars + B_FULL + 8 * s, r.ph);
            TS0(8, 48 + 2 * i + wg * 68);
            wg_fence();
#pragma unroll
            for (int k = 0; k < 7; k++) {
                if (k == 3) { mbar_wait(bars + B_FULL + 8 * s + 8, r.ph); wg_fence(); }
                wgmma_n112<0, 1, desc_hi(128, 0), desc_hi(256, 0)>(a, dA + desc_lo(k * 2048 + (k > 3) * (SLOT - HALF), k == 3 ? SLOT - 6144 : 1024),
                                                                   dB + desc_lo(16384 + k * SLAB + (k > 2) * (SLOT - 3 * SLAB), 128), k > 0 || i > 0);
                if (k & 1) wg_commit();
                if (k == 1) { wg_wait<1>(); if (i) release(prev); }
                if (k == 5) { wg_wait<1>(); release(s); }
            }
            wg_commit();
            prev = s + 1;
            r.slot++; r.next2();
        }
    }
};

__global__ void __cluster_dims__(2, 1, 1) __launch_bounds__(NTHREADS, 1)
fused_kernel(const __nv_bfloat16* __restrict__ x, const __nv_bfloat16* __restrict__ b1, const __nv_bfloat16* __restrict__ b2, const __nv_bfloat16* __restrict__ wo, __nv_bfloat16* out, Scratch* G,
             const __nv_bfloat16* __restrict__ w1, const __nv_bfloat16* __restrict__ w2,
             const __grid_constant__ Params P) {
    extern __shared__ __align__(1024) uint8_t smem[];
    const uint32_t sbase = (uint32_t)__cvta_generic_to_shared(smem);
    const uint32_t bars = sbase + OFF_BAR;
    const int lane = threadIdx.x & 31;
    const int warp = __shfl_sync(~0u, threadIdx.x >> 5, 0), w = warp & 3;
    const uint32_t rank = blockIdx.x & 1, pr = blockIdx.x >> 1;
    const uint32_t pv = pr < 4 ? pr * 8 + 36 : pr < 40 ? pr - 4 : pr - 3 + (((pr - 40) * 37) >> 8);
    const uint32_t gp = (pv + 4) & 7, hp = pv >> 3;
    const uint32_t tb = gp * 2 + rank, c = hp * 16 + tb, row0 = (tb * 8 + hp) * 16;
    const bool has_g1 = gp > 0;
    const uint32_t nt1 = hp & 3, ft = max((int)gp - 1, 0) * 2 + (hp >> 2);
    const uint32_t nt2 = tb & 3, mt = (gp & 2) * 4 + hp, ks = gp >> 2;

    if (warp < NBAR / 3 && elect()) {
        if (warp == 0) TS(15, 0);
#pragma unroll
        for (int i = 0; i < 3; i++) mbar_init(bars + warp * 24 + 8 * i, warp * 24 + 8 * i < B_FREE ? 1 : warp * 24 + 8 * i < B_QEMPTY ? 2 : 16);
        asm volatile("fence.mbarrier_init.release.cluster;" ::: "memory");
        if (warp == B_ROW / 24) {
            mbar_expect(bars + B_ROW, TILEB);
            bulk_load(sbase + OFF_Y, x + row0 * D_, TILEB, bars + B_ROW);
            TS(1, 97);
        }
    }
    __syncwarp();
    asm volatile("barrier.cluster.arrive.relaxed.aligned;\nbarrier.cluster.wait.aligned;" ::: "memory");
    if (warp == 8) TS(1, 98);

    if (warp == 8) {
        if (elect()) {
            TS(1, 99);
            uint32_t spins = (sbase & 0xffffffu) == SMEM0 ? 0 : SPIN_LIMIT;
            uint32_t kw = gp % ROT * (512 / ROT), kx = kw;
            uint32_t due = (uint32_t)clock(), ep = 0;
#pragma unroll 1
            for (int i = 0; i < 8; i++) {
                if (i >= 5) mbar_wait_bounded(bars + B_QEMPTY + 8 * (i - 5), 0, spins);
                else { while ((int)((uint32_t)clock() - due) < 0) {} due += PACE; }
                if (kw == D_) kw = 0;
                if (i < 4) kx = kw;
                const int ix = i - (i > 4);
                if (i < 7) mbar_expect(bars + B_QFULL + 8 * i, QSLOT);
                if (i != 4) tma3d(sbase + xslot(ix) * 8192, &P.tmX, bars + B_QFULL + 8 * ix, kx, tb * 64, 0);
                if (i == 5) mbar_wait_bounded(bars + B_CS, 0, spins);
                if (i < 7) tma3d_pair(sbase + wslot(i) * 8192 + rank * 12288, &P.tmWqkv, bars + B_QFULL + 8 * i, (hp * 56) & ~15, kw + rank * 32, 0);
                kx = kw; kw += 64;
                if (i == 0) { TS(1, 23); ep = ld_relaxed(&G->epoch[c]); }
            }
            ep++;
            Slot r{sbase, bars, 0};
            if (has_g1) {
                const uint8_t* src = G->H[nt1][rank * 16];
                const int row = rank * 1024;
                mbar_arrive(bars + B_FULL + 48); mbar_arrive16(bars + B_EMPTY + 48);
                mbar_expect(bars + B_FULL, 16384 + TILEB);
                tma3d(sbase, &P.tmW1, bars + B_FULL, 0, row, ft * 2);
                wait_flag(G->flag[1] + rank * 2, 20 * ep, spins);
                TS(1, 16);
#pragma unroll 1
                for (int j = 64;; j += 64) {
                    bulk_load(r.dst + 16384, src, TILEB, r.bar + B_FULL);
                    src += TILEB;
                    r.next(bars);
                    if (j == 1024) break;
                    mbar_wait_bounded(r.bar + B_EMPTY, r.ph, spins);
                    if (j < 14 * 64) TS(2, 146 + j / 64);
                    mbar_expect(r.bar + B_FULL, 16384 + TILEB);
                    tma3d(r.dst, &P.tmW1, r.bar + B_FULL, 0, row + j, ft * 2);
                }
#pragma unroll
                for (int i = 0; i < 4; i++) mbar_expect(bars + B_X + 8 * i, (i & 1) ? 3072 : 4096);
            } else {
                due = (uint32_t)clock();
#pragma unroll 1
                for (int j = PF0; j < PF1; j++) {
                    asm volatile("cp.async.bulk.prefetch.L2.global [%0], %1;" ::"l"(w1 + (rank * 1024 + j * 64 + hp * 8) * F_), "n"(16 * F_) : "memory");
                    due += PF;
                    while ((int)((uint32_t)clock() - due) < 0) {}
                }
            }
            const uint8_t *so = G->O[mt][ks * 4] + rank * HALF, *sw = G->Wo[nt2][ks * 4];
            wait_flag2(G->flag[16 + mt], 8 * ep, G->flag[0], 16 * ep, spins);
            TS(4, 18);
#pragma unroll 1
            for (int j = 0; j < 4 * TILEB; j += TILEB) {
                mbar_wait_bounded(r.bar + B_EMPTY, r.ph, spins);
                mbar_expect(r.bar + B_QFULL, TILEB);
                bulk_load_pair(r.dst + rank * 8192, so + j, HALF, r.bar + B_QFULL);
                bulk_load(r.dst + 16384, sw + j, (r.bar & 8) ? TILEB : 3 * SLAB, r.bar + B_FULL);
                r.next(bars);
            }
            if (!has_g1) {
#pragma unroll 1
                for (int j = PG0; j < PG1; j++)
                    asm volatile("cp.async.bulk.prefetch.L2.global [%0], %1;" ::"l"(w2 + (rank * 896 + j * 128 + hp * 8) * S_), "n"(16 * S_) : "memory");
            }
            Ring q{has_g1 ? 2u : 6u, has_g1};
#pragma unroll 1
            for (int j = 0; j < 14 * 128; j += 128) {
                mbar_wait_bounded(bars + B_EMPTY + 8 * q.slot, q.ph, spins);
                TS(8, 176 + j / 128);
                tma2d_pair(sbase + q.slot * SLOT + rank * 8192, &P.tmW2, bars + B_FULL + 8 * q.slot, mt * 128 + rank * 64, ks * 896 + j - (j < 896 ? 0 : 832));
                q.next2();
            }
            mbar_wait_bounded(bars + B_END, 0, spins);
        }
    } else if (warp > 8) {
        const uint32_t ep = ld_relaxed(&G->epoch[c]) + 1;
        {
            const uint32_t src = (sbase + wslot(gp / ROT) * 8192 - 4096 + w * 4096 + rank * 64 + (lane & 15) * 4 + (lane >> 4) * 12288) ^ ((lane >> 4) * 576);
            float s0 = 0.f, s1 = 0.f, s2 = 0.f, s3 = 0.f;
            mbar_wait(bars + B_QFULL + 8 * (gp / ROT), 0);
            if (w == 1) TS(1, 66);
            uint32_t v[32];
#pragma unroll
            for (int k = 0; k < 32; k++) v[k] = __float_as_uint(lds1f((src ^ ((k & 7) * 144)) + (k >> 3) * 1024));
#pragma unroll
            for (int k = 0; k < 32; k += 2) { s0 += bf_lo(v[k]); s1 += bf_hi(v[k]); s2 += bf_lo(v[k + 1]); s3 += bf_hi(v[k + 1]); }
            s0 += s2; s1 += s3;
            s0 += __shfl_xor_sync(~0u, s0, 16); s1 += __shfl_xor_sync(~0u, s1, 16);
            uint2* cs = G->colsum[hp][0] + w * 32 - 32;
            if (lane < 16) cs[gp * 96 + rank * 16 + lane] = make_uint2(tag(__float_as_uint(s0), 1, ep), __float_as_uint(s1));
            if (w == 1) TS(1, 24);
            if (w == 2) {
                bar_sync(6, 224);
                TS(1, 8);
                if (elect()) { mbar_arrive(bars + B_CS); signal(G->flag[1] + (gp >> 2) * 2 + ((row0 & 1023) >= 320)); TS(1, 3); }
                __syncwarp();
            } else {
                bar_arrive(6, 224);
            }
            bar_sync(1, 96);
            const int i0 = threadIdx.x - 288;
            uint2 u[7];
            uint4 sv;
            uint32_t bad;
            do {
                sv = ld_relaxed4(G->stat + tb * 128 + (i0 & 63) * 2);
                bad = or_diff(sv.x ^ ep, sv.z, ep);
#pragma unroll
                for (int i = 0; i < 7; i++) { u[i] = ld_relaxed2(cs + i * 96 + lane); bad = or_diff(bad, u[i].x, ep); }
            } while (bad & 1);
            if (w < 3) sts4(sbase + OFF_ST + i0 * 16, sv);
#pragma unroll
            for (int e = 0; e < 2; e++) {
                float f = 0.f;
#pragma unroll
                for (int i = 0; i < 7; i++) f += __uint_as_float(e ? u[i].y : u[i].x);
                const uint32_t hi = pack2(f, f);
                sts4(sbase + OFF_X + i0 * 32 + e * 16, make_uint4(hi, pack2(f - bf_hi(hi), f - bf_hi(hi)), 0, 0));
            }
            asm volatile("st.shared.u32 [%0], %1;" ::"r"(bars + 8 * NBAR), "r"(ep) : "memory");
            fence_async_shared();
            __syncwarp();
            bar_arrive(8, 224); bar_arrive(9, 224);
            TS(1, 90 + w);
        }
        const uint8_t* src = G->U[nt2][ks * 14];
        uint32_t spins = 0;
        if (w < 3) {
            uint32_t bad;
            if (w == 1) {
                if (elect()) {
                    wait_flag(G->flag[1] + rank * 2 + 1, 44 * ep, spins);
                    mbar_arrive16(bars + B_EMPTY + 8 * 5);
                    TS(1, 96);
                }
                __syncwarp();
                if (!has_g1) { bar_sync(5, 288); if (elect()) signal(G->flag[0]); __syncwarp(); TS(2, 26); }
            } else {
                bar_sync(3, 288);
                __nanosleep(HALO_NS);
                uint4 v[7];
                do {
                    bad = 0;
#pragma unroll
                    for (int i = 0; i < 7; i++) { v[i] = ld_relaxed4(G->halo[c - (tb > 0)] + i * 512 + lane * 16); bad = or_diff(bad, v[i].x, ep); }
                } while (bad & 1);
#pragma unroll
                for (int i = 0; i < 7; i++) sts4(sbase + OFF_X + i * 512 + lane * 16, v[i]);
                __syncwarp();
                if (elect()) mbar_arrive(bars + B_HALO);
                TS(2, 21);
            }
            mbar_wait(bars + B_HALO, 0);
            uint32_t slot = (has_g1 ? 16 % NSLOT : 0) + w - 1, ph = ~0u;
#pragma unroll 1
            for (int i = w - 1; i < 18;) {
                const uint32_t d0 = sbase + slot * SLOT + (i < 4 ? 0 : 16384), d1 = d0 + (i < 4 ? 8192 : HALF), landed = bars + B_QFULL + 8 * slot;
                mbar_wait(landed, (ph >> slot) & 1);
                ph ^= 1 << slot;
                if (i < 8) TS(4, 82 + i);
                if (i >= 4) TS(8, 156 + i);
                bad = 0;
#pragma unroll
                for (int k = 0; k < 14; k++) bad = or_diff(bad, __float_as_uint(lds1f((k < 7 ? d0 : d1) + k % 7 * 1024 + lane * 32 + (lane >> 2) * 4)), ep);
                if (__any_sync(~0u, bad & 1)) {
                    if (elect()) {
                        const uint8_t* cur = (i < 4 ? G->O[mt][ks * 4] : src - 4 * TILEB) + i * TILEB;
                        fence_async_shared();
                        mbar_expect(landed, TILEB);
                        bulk_load(d0, cur, HALF, landed);
                        bulk_load(d1, cur + HALF, HALF, landed);
                    }
                    TS(4, i < 4 ? 94 : 95);
                } else {
                    if (elect()) mbar_expect(landed + (B_FULL - B_QFULL), i < 4 ? (2 + w) * SLAB : 16384);
                    i += __byte_perm(0x03020202u, 0x00010202u, 0x7770 + slot);
                    slot = __byte_perm(0x05060302u, 0x00040100u, 0x7770 + slot);
                }
            }
        } else {
            bar_sync(2, 288);
            if (elect()) bulk_store(out + row0 * D_, sbase + OFF_Y, TILEB);
            __syncwarp();
            bar_sync(4, 288);
            if (elect()) {
                fence_async_shared();
                bulk_store(G->O[tb][hp], sbase + OFF_X, TILEB);
                bulk_flush();
                TS(2, 7);
                mbar_arrive_remote(mapa(bars + B_FREE, rank ^ 1));
                mbar_arrive(bars + B_FREE);
                hint(G->flag[16 + tb]);
                signal(G->flag[16 + tb] + 1);
                TS(2, 22);
            }
            __syncwarp();
            uint32_t late = ~0u;
            const uint32_t* hints = G->flag[8 + nt2 * 2 + ks] + lane;
            mbar_wait(bars + (has_g1 ? B_X : B_FREE), 0);
            Ring r{has_g1 ? 2u : 6u, has_g1};
#pragma unroll 1
            for (int i = 0; i < 14; i++) {
                while ((late >> i) & 1) late = __ballot_sync(~0u, ld_relaxed(hints) != 2 * ep) & 127;
                if (i == 0) TS(4, 17);
                mbar_wait(bars + B_EMPTY + 8 * r.slot, r.ph);
                TS(8, 192 + i);
                if (elect()) {
                    mbar_expect(bars + B_QFULL + 8 * r.slot, TILEB);
                    bulk_load(sbase + r.slot * SLOT + 16384, src, TILEB, bars + B_QFULL + 8 * r.slot);
                }
                src += TILEB; r.next2();
                if (UGAP && i < UGAPN) { const uint32_t t0 = clock(); while ((uint32_t)clock() - t0 < UGAP) {} }
            }
            if (elect()) {
                wait_flag(G->flag[16 + mt] + 1, 8 * ep, spins);
                mbar_arrive(bars + B_ROW);
                TS(2, 27);
                G->epoch[c] = ep;
            }
        }
    } else {
        const int wg = warp >> 2;
        Mma M{bars, mapa(bars, rank ^ (lane & 1)), (threadIdx.x & 127) < 2, wg, w, Ring{0, 0}, 0};
        const int r = lane >> 2, t = lane & 3;
        uint32_t ep;
        const uint32_t bias0 = ld_u16(b1 + ft * 128 + warp * 16 + r), bias1 = ld_u16(b1 + ft * 128 + warp * 16 + r + 8);
        if (wg == 1) {
            ep = ld_relaxed(&G->epoch[c]);
            const int r16 = w * 4 + t, c8 = (r + 2 * t) & 7;
            const uint32_t row = sbase + OFF_Y + r16 * (2 * D_) + c8 * 16;
            mbar_wait(bars + B_ROW, 0);
            TS0(1, 67);
            float f[56];
#pragma unroll
            for (int i = 0; i < 7; i++) {
                const uint4 v = lds4(row + i * 128);
                f[8 * i] = bf_lo(v.x); f[8 * i + 1] = bf_hi(v.x); f[8 * i + 2] = bf_lo(v.y); f[8 * i + 3] = bf_hi(v.y);
                f[8 * i + 4] = bf_lo(v.z); f[8 * i + 5] = bf_hi(v.z); f[8 * i + 6] = bf_lo(v.w); f[8 * i + 7] = bf_hi(v.w);
            }
            float s0 = f[0], s1 = f[1], s2 = f[2], s3 = f[3];
#pragma unroll
            for (int i = 4; i < 56; i += 4) { s0 += f[i]; s1 += f[i + 1]; s2 += f[i + 2]; s3 += f[i + 3]; }
            const float nmean = oct_sum((s0 + s1) + (s2 + s3)) * (-1.f / D_);
            s0 = s1 = s2 = s3 = 0.f;
#pragma unroll
            for (int i = 0; i < 56; i += 4) {
                f[i] += nmean; f[i + 1] += nmean; f[i + 2] += nmean; f[i + 3] += nmean;
                s0 = fmaf(f[i], f[i], s0); s1 = fmaf(f[i + 1], f[i + 1], s1); s2 = fmaf(f[i + 2], f[i + 2], s2); s3 = fmaf(f[i + 3], f[i + 3], s3);
            }
            const float var = oct_sum((s0 + s1) + (s2 + s3)) * (1.f / D_);
            const float rstd = rsq(var + LN_EPS);
            const float sc = rstd * rsq(fmaf(var * rstd, rstd, LN_EPS));
            if (lane < 4) G->stat[row0 + r16] = make_uint2(tag(__float_as_uint(rstd), 1, ~ep), pack2(nmean, nmean - bf_hi(pack2(nmean, nmean))));
            uint8_t* hb = G->H[0][0] + row0 * (SLAB / 16) + r16 * 16 + c8 * 256;
            const int sw = tb < 8 ? 0 : 7 * 256;
#pragma unroll
            for (int i = 0; i < 7; i++) {
                const int lo = (8 * i) % 14, nt = (8 * i) / 14, next = 32 * TILEB - SLAB;
                const int off = lo < 7 ? (c8 < 7 - lo ? sw : -sw) : (c8 >= 14 - lo ? sw + next : -sw);
                *(uint4*)(hb + off + i * 2048 + nt * next) = make_uint4(pack2(f[8 * i] * sc, f[8 * i + 1] * sc), pack2(f[8 * i + 2] * sc, f[8 * i + 3] * sc),
                                                                        pack2(f[8 * i + 4] * sc, f[8 * i + 5] * sc), pack2(f[8 * i + 6] * sc, f[8 * i + 7] * sc));
            }
            TS0(1, 25);
            bar_arrive(6, 224);
        }
        const uint32_t kv = sbase + OFF_X + (w * 2 + wg) * KV + lane * 16;
        uint32_t q[8][2], k0[7], k1[7], v0[7];
        {
            float acc[92];
#pragma unroll 1
            for (int kb = 0; kb < 7; kb++) {
                const bool held = kb == (wg ? 7 - HOLD : -1);
                if (held) { wg_wait<0>(); M.release(4 - HOLD); bar_sync(7, 256); }
                mbar_wait(bars + B_QFULL + 8 * kb, 0);
                TS0(1, 68 + wg * 7 + kb);
                const uint32_t dA = (xslot(kb) + wg) * 512, dB = wslot(kb) * 512 + (hp & 1);
                wg_fence();
#pragma unroll
                for (int k = 0; k < 4; k++) {
                    wgmma_n184<0, 1, HI_SW, HI_SW>(acc, dA + desc_lo(k * 32, 16), dB + desc_lo((k & 1) * 2048 + (k >> 1) * 12288, 4096), k > 0 || kb > 0);
                    if (k == 0) { wg_commit(); wg_wait<1>(); if (kb > 0 && !held) M.release(kb - 3); }
                }
                wg_commit();
            }
            if (wg == 0 && !LATEREL) bar_arrive(7, 256);
            bar_sync(8 + wg, 224);
            ep = __float_as_uint(lds1f(bars + 8 * NBAR));
            const uint32_t st = sbase + OFF_ST + (w * 32 + r * 2 + wg) * 8;
            const uint2 s0 = lds2(st), s1 = lds2(st + 128);
            const uint32_t a0 = t < 2 ? s0.y : 0, a1 = t < 2 ? s1.y : 0;
            wg_fence();
            wgmma_rs_n184<desc_hi(128, 0)>(acc, a0, a1, desc_lo(OFF_X, 0) + (hp & 1) * 8);
            wg_commit();
            if (wg == 0 && LATEREL) bar_arrive(7, 256);
            wg_wait<1>();
            M.release(4);
            wg_wait<0>();
            pin(acc);
            TS0(1, 4 + 7 * wg);
            uint32_t hi[14];
#pragma unroll
            for (int p = 2; p >= 0; p--) {
                const float f = p == 0 ? 0.1889822365046136f * 1.4426950408889634f : p, r0 = __uint_as_float(s0.x) * f, r1 = __uint_as_float(s1.x) * f;
#pragma unroll
                for (int g = 0; g < 7; g++) {
                    const int a = (p * 8 + g) * 4;
                    const uint32_t lo2 = pack2(acc[a] * r0, acc[a + 1] * r0), hi2 = pack2(acc[a + 2] * r1, acc[a + 3] * r1);
                    if (p == 0) { q[g][0] = lo2; q[g][1] = hi2; } else { hi[(p - 1) * 7 + g] = hi2; }
                    if (p == 1) { k0[g] = lo2; k1[g] = hi2; }
                    if (p == 2) v0[g] = lo2;
                }
                if (p == 1) {
#pragma unroll
                    for (int i = 0; i < 3; i++) stsm4(kv + 2 * KV + i * 512, hi[4 * i], hi[4 * i + 1], hi[4 * i + 2], hi[4 * i + 3]);
                    stsm2(kv + 2 * KV + 1536, hi[12], hi[13]);
                    if (w == 3) {
#pragma unroll
                        for (int i = 0; i < 14; i++) stg1(G->halo[c] + wg * KV + lane * 4 + i * 128, tag(hi[i], t == 0, ep));
                    }
                    bar_arrive(3, 288);
                }
            }
#pragma unroll
            for (int j = 0; j < 2; j++) { q[7][j] = t < 2 ? 0u : q[3][j]; q[3][j] = t < 2 ? q[3][j] : 0u; }
#pragma unroll
            for (int g = 0; g < 7; g++) v0[g] = transpose8(v0[g]);
        }
        TS0(1, 9 + 11 * wg);
        float a[56];
#pragma unroll
        for (int i = 0; i < 56; i++) asm volatile("" : "=f"(a[i]));
        if (__builtin_expect(!has_g1, 0)) {
            const int g = min(lane >> 1, 13), nt = rank * 2 + wg;
            const uint4* src = (const uint4*)(wo + (hp * 56 - (hp & 1) * 8 + w * 16 + (lane & 1)) * D_ + nt * 112) + g;
            uint4 v[8];
#pragma unroll
            for (int i = 0; i < 8; i++) v[i] = __ldg(src + i * (D_ / 4));
#pragma unroll
            for (int i = 0; i < 8; i++) ((uint4*)G->Wo[nt][hp])[w * (SLAB / 16) + g * 16 + (lane & 1) + 2 * i] = v[i];
            bar_arrive(5, 288);
        }
        M.run<true>(a, has_g1 ? PAUSE : 0, 1, 16, 0, 0, 32);
        {
            uint32_t kp[8], vv[14];
            TS0(2, 140 + wg);
            mbar_wait(bars + B_HALO, 0);
            TS0(2, 142 + wg);
            ldsm4(kp, kv); ldsm4(kp + 4, kv + (lane < 24 ? 512 : 0));
            const uint32_t va = kv + 896 + (lane & 8) * (2 * KV / 8 - 16) - (lane & 16) * 8;
            ldsm4t(vv, va); ldsm4t(vv + 4, va + 256); ldsm4t(vv + 8, va + 512); ldsm2t(vv + 12, va + 768);
            const bool e0 = 2 * t > r, e1 = 2 * t >= r;
            const uint32_t mk = (e0 ? 0xffffu : 0u) | (e1 ? 0xffff0000u : 0u);
            wg_wait<0>();
            pin(a);
            if (has_g1) M.release(M.prev);
            TS0(2, 144 + wg);
            bar_sync(2, 288);
            mbar_wait(bars + B_HALO, 0);
            TS0(2, 12 + 16 * wg);
            float sv[2][4];
#pragma unroll
            for (int h = 0; h < 2; h++) {
                const int ga = h * 4, gb = h * 4 + 1, gc = h * 4 + 2, gd = h * 4 + 3;
                float s[3][4] = {};
                mma16(s[0], q[ga][0], q[ga][1], q[gb][0], q[gb][1], kp[ga], kp[gb]);
                mma16(s[1], q[ga][0], q[ga][1], q[gb][0], q[gb][1], k0[ga], k0[gb]);
                mma16(s[2], q[ga][0], q[ga][1], q[gb][0], q[gb][1], k1[ga], k1[gb]);
                mma16(s[0], q[gc][0], q[gc][1], q[gd][0], q[gd][1], kp[gc], kp[gd]);
                mma16(s[1], q[gc][0], q[gc][1], q[gd][0], q[gd][1], k0[gc], k0[3]);
                mma16(s[2], q[gc][0], q[gc][1], q[gd][0], q[gd][1], k1[gc], k1[3]);
                if ((tb | w) == 0) s[0][0] = s[0][1] = -1e30f;
                sv[h][0] = e0 ? s[0][0] : s[1][0];
                sv[h][1] = e1 ? s[0][1] : s[1][1];
                sv[h][2] = e0 ? s[1][2] : s[2][2];
                sv[h][3] = e1 ? s[1][3] : s[2][3];
            }
            uint32_t pp[2][2];
#pragma unroll
            for (int i = 0; i < 4; i++) {
                float* v = &sv[i >> 1][(i & 1) * 2];
                const float m = quad_max(fmaxf(v[0], v[1]));
                const float p0 = ex2(v[0] - m), p1 = ex2(v[1] - m);
                const float inv = rcp(quad_sum(p0 + p1));
                pp[i >> 1][i & 1] = pack2(p0 * inv, p1 * inv);
            }
            uint32_t o[8][2];
#pragma unroll
            for (int i = 0; i < 8; i++) {
                const int h = i >> 2, g = i - h;
                float d[4] = {};
                mma16(d, pp[h][0] & mk, 0u, 0u, pp[h][1] & ~mk, vv[2 * g], vv[2 * g + 1]);
                mma8(d, pp[h][0] & ~mk, pp[h][1] & mk, v0[g]);
                o[i][0] = pack2(d[0], d[1]); o[i][1] = pack2(d[2], d[3]);
            }
            if (t >= 2) { o[3][0] = o[4][0]; o[3][1] = o[4][1]; }
            const int word = wg * 4 + t - (w & 1) * 4 - (r >> 2);
#pragma unroll
            for (int i = 0; i < 8; i++) { o[i][0] = tag(o[i][0], word == 0, ep); o[i][1] = tag(o[i][1], word == 2, ep); }
            const uint32_t dst = sbase + OFF_X + (w >> 1) * HALF + ((w & 1) * 32 + (lane & 15) * 2 + wg) * 16 + (lane >> 4) * 1024;
            stsm4(dst, o[0][0], o[0][1], o[1][0], o[1][1]);
            stsm4(dst + 2048, o[2][0], o[2][1], o[3][0], o[3][1]);
            stsm4(dst + 4096, o[5][0], o[5][1], o[6][0], o[6][1]);
            stsm2(dst + 6144, o[7][0], o[7][1]);
            if (ENDBAR) bar_sync(4, 288); else bar_arrive(4, 288);
            TS0(2, 10 + 19 * wg);
        }
        if (has_g1) {
            M.run<true>(a, 16 - PAUSE, 1, 16, LAG1, 1, 32 + PAUSE);
            mbar_wait(bars + B_FREE, 0);
            const uint32_t xb = sbase + OFF_X + wg * 8192 + (threadIdx.x & 127) * 16, xbar = bars + B_X + 16 * wg;
            const uint32_t rx = mapa(xb, rank ^ 1), rbar = mapa(xbar, rank ^ 1);
            wg_wait<0>();
            pin(a);
            M.release(M.prev);
            TS0(4, 5 + wg);
#pragma unroll
            for (int i = 0; i < 3; i++)
                st_async4(rx + i * 2048, rbar + 8 * (i >> 1), pack2(a[28 + 8 * i], a[29 + 8 * i]), pack2(a[30 + 8 * i], a[31 + 8 * i]), pack2(a[32 + 8 * i], a[33 + 8 * i]), pack2(a[34 + 8 * i], a[35 + 8 * i]));
            const uint32_t tail = 6144 - (threadIdx.x & 127) * 8;
            st_async2(rx + tail, rbar + 8, pack2(a[52], a[53]), pack2(a[54], a[55]));
            uint8_t* dst = G->U[nt1][((ft >= 7) + wg) * 7 + ft] + rank * HALF + w * 256 + lane * 4;
            uint32_t u[14];
#pragma unroll
            for (int i = 0; i < 14; i++) {
                if (i % 8 == 0) {
                    mbar_wait(xbar + i, 0);
                    if (i == 0) TS0(4, 1 + wg);
#pragma unroll
                    for (int k = i / 4; k < i / 4 + 2; k++) {
                        if (k < 3) { const uint4 v = lds4(xb + k * 2048); u[4 * k] = v.x; u[4 * k + 1] = v.y; u[4 * k + 2] = v.z; u[4 * k + 3] = v.w; }
                        else { const uint2 v = lds2(xb + tail); u[12] = v.x; u[13] = v.y; }
                    }
                    if (i && lane < 2) mbar_arrive_remote(M.rel + B_EMPTY + 48);
                }
                if (i == HINT && threadIdx.x == 0) hint(G->flag[8 + nt1 * 2] + ft + (ft >= 7) * 25);
                const float bias = bf_lo((i & 1) ? bias1 : bias0);
                stg1(dst + (i >> 1) * 1024 + (i & 1) * 128, tag(pack2(gelu2(a[2 * i] + bias + bf_lo(u[i])), gelu2(a[2 * i + 1] + bias + bf_hi(u[i]))), (lane & 7) == w * 2 + (i & 1), ep));
            }
            TS0(4, 30 + wg);
        } else {
            mbar_wait(bars + B_FREE, 0);
            if (lane < 2) mbar_arrive_remote(M.rel + B_EMPTY + 48);
        }
        uint32_t c0 = ld_u16(b2 + mt * 128 + warp * 16 + r), c1 = ld_u16(b2 + mt * 128 + warp * 16 + r + 8);
        M.run_o(a);
        if (wg == 1) TS0(4, 13);
        c0 *= ks == 0 ? 0x10001u : 0u; c1 *= ks == 0 ? 0x10001u : 0u;
        M.run<false>(a, 14, 0, 14 - NSLOT, LAG2, 1, 52);
        mbar_wait(bars + B_ROW, 1);
        const uint32_t stg = sbase + ((has_g1 ? STG1 : STG0) + (w >> 1) * STGS) * SLOT + wg * 8192 + (w & 1) * SLAB;
        const uint32_t sa = stg + (lane & 15) * 224 + (lane >> 4) * 16;
        wg_wait<0>();
        pin(a);
        TS0(8, 14 + wg);
#pragma unroll
        for (int i = 0; i < 7; i++)
            stsm4(sa + i * 32, half_plus(pack2(a[8 * i], a[8 * i + 1]), c0), half_plus(pack2(a[8 * i + 2], a[8 * i + 3]), c1),
                  half_plus(pack2(a[8 * i + 4], a[8 * i + 5]), c0), half_plus(pack2(a[8 * i + 6], a[8 * i + 7]), c1));
        fence_async_shared();
        __syncwarp();
        if (elect()) {
            asm volatile("cp.reduce.async.bulk.tensor.2d.global.shared::cta.add.tile.bulk_group [%0, {%2, %3}], [%1];\ncp.async.bulk.commit_group;" ::"l"(&P.tmOut), "r"(stg), "r"(nt2 * 112), "r"(mt * 128 + warp * 16) : "memory");
            if (w == 0) mbar_arrive(bars + B_END);
            asm volatile("cp.async.bulk.wait_group.read 0;" ::: "memory");
        }
        if (wg == 1) TS0(15, 19);
        TSDUMP();
    }
}

typedef CUresult (*EncodeFn)(CUtensorMap*, CUtensorMapDataType, cuuint32_t, void*, const cuuint64_t*, const cuuint64_t*, const cuuint32_t*, const cuuint32_t*,
                             CUtensorMapInterleave, CUtensorMapSwizzle, CUtensorMapL2promotion, CUtensorMapFloatOOBfill);

void make_map(EncodeFn enc, CUtensorMap* tm, const void* base, bool swizzle, int d0, int d1, int d2, int s1, int s2, int b0, int b1, int b2) {
    const cuuint64_t dims[3] = {(cuuint64_t)d0, (cuuint64_t)d1, (cuuint64_t)d2}, strides[2] = {(cuuint64_t)s1 * 2, (cuuint64_t)s2 * 2};
    const cuuint32_t box[3] = {(cuuint32_t)b0, (cuuint32_t)b1, (cuuint32_t)b2}, es[3] = {1, 1, 1};
    enc(tm, CU_TENSOR_MAP_DATA_TYPE_BFLOAT16, d2 ? 3 : 2, (void*)base, dims, strides, box, es, CU_TENSOR_MAP_INTERLEAVE_NONE,
        swizzle ? CU_TENSOR_MAP_SWIZZLE_128B : CU_TENSOR_MAP_SWIZZLE_NONE, CU_TENSOR_MAP_L2_PROMOTION_L2_128B, CU_TENSOR_MAP_FLOAT_OOB_FILL_NONE);
}

}

extern "C" void kernel_launch(void* const* d_in, const int* in_sizes, int n_in, void* d_out, int out_size) {
    static EncodeFn enc = nullptr;
    static Scratch* scratch = nullptr;
    if (!enc) {
        void* fn = nullptr;
        cudaDriverEntryPointQueryResult qr;
        cudaGetDriverEntryPoint("cuTensorMapEncodeTiled", &fn, cudaEnableDefault, &qr);
        enc = (EncodeFn)fn;
        cudaGetSymbolAddress((void**)&scratch, g_s);
        cudaFuncSetAttribute(fused_kernel, cudaFuncAttributeMaxDynamicSharedMemorySize, SMEM_BYTES);
    }
    Params P;
    const __nv_bfloat16* x = (const __nv_bfloat16*)d_in[0];
    make_map(enc, &P.tmX, x, true, D_, S_ / 2, 2, 2 * D_, D_, 64, 64, 2);
    make_map(enc, &P.tmWqkv, d_in[1], true, D_, D_, 3, 3 * D_, D_, 64, 32, 3);
    make_map(enc, &P.tmW1, d_in[4], true, 64, S_, F_ / 64, F_, 64, 64, 64, 2);
    make_map(enc, &P.tmW2, d_in[6], true, S_, F_, 0, S_, 0, 64, 64, 1);
    make_map(enc, &P.tmOut, d_out, false, D_, S_, 0, D_, 0, 112, 16, 1);
    fused_kernel<<<NCTA, NTHREADS, SMEM_BYTES, cudaStreamPerThread>>>(x, (const __nv_bfloat16*)d_in[5], (const __nv_bfloat16*)d_in[7], (const __nv_bfloat16*)d_in[2], (__nv_bfloat16*)d_out, scratch,
                                                                      (const __nv_bfloat16*)d_in[4], (const __nv_bfloat16*)d_in[6], P);
}
```

```cpp
#include <cuda_runtime.h>
#include <cuda_bf16.h>
#include <cuda.h>
#include <stdint.h>

#define HALO_NS 300
#define HINT 4
#define HOLD 2
#define ROT 4
#define LATEREL 0
#define PF 400
#define PF0 2
#define PF1 8
#define ENDBAR 1
#define PG0 3
#define PG1 5
#define STG1 4
#define STG0 4
#define STGS 1
#define UGAP 120
#define UGAPN 6
#define PACE 800
#define PAUSE 8
#define LAG1 4
#define LAG2 6

namespace {

constexpr int S_ = 2048, D_ = 448, F_ = 1792;
constexpr int NCTA = 128, NTHREADS = 384;
constexpr int NSLOT = 6, SLOT = 32768, QSLOT = 40960, TILEB = 14336, SLAB = 3584, HALF = 7168;
constexpr int KV = 1792;
constexpr int OFF_X = NSLOT * SLOT;
constexpr int OFF_Y = OFF_X + 10 * KV;
constexpr int OFF_ST = OFF_Y + TILEB;
constexpr int OFF_BAR = OFF_ST + 1024;
constexpr int SMEM_BYTES = OFF_BAR + 1280;
constexpr uint32_t SMEM0 = 1024;
constexpr int B_QFULL = 0, B_FULL = 56, B_CS = 120, B_HALO = 128, B_X = 136, B_FREE = 192, B_END = 200, B_QEMPTY = 216, B_EMPTY = 232, B_ROW = 288, NBAR = 37;
constexpr float LN_EPS = 1e-5f;
constexpr int SPIN_LIMIT = 1 << 22;

struct Scratch {
    uint8_t H[4][32][TILEB];
    uint8_t U[4][28][TILEB];
    uint8_t O[16][8][TILEB];
    uint8_t Wo[4][8][TILEB];
    uint8_t halo[NCTA][2 * KV];
    uint2 stat[S_];
    uint2 colsum[8][8][96];
    uint32_t flag[32][32];
    uint32_t epoch[NCTA];
};
__device__ __align__(1024) Scratch g_s;

#define TS(g, i)
#define TS0(g, i)
#define TSDUMP()

struct Params {
    CUtensorMap tmX, tmWqkv, tmW1, tmW2, tmOut;
};

__device__ __forceinline__ bool elect() {
    uint32_t p;
    asm volatile("{\n.reg .pred p;\nelect.sync _|p, 0xffffffff;\nselp.u32 %0, 1, 0, p;\n}" : "=r"(p));
    return p;
}
__device__ __forceinline__ void mbar_init(uint32_t b, uint32_t c) { asm volatile("mbarrier.init.shared::cta.b64 [%0], %1;" ::"r"(b), "r"(c) : "memory"); }
__device__ __forceinline__ void mbar_expect(uint32_t b, uint32_t tx) { asm volatile("mbarrier.arrive.expect_tx.shared::cta.b64 _, [%0], %1;" ::"r"(b), "r"(tx) : "memory"); }
__device__ __forceinline__ void mbar_arrive(uint32_t b) { asm volatile("mbarrier.arrive.shared::cta.b64 _, [%0];" ::"r"(b) : "memory"); }
__device__ __forceinline__ void mbar_arrive16(uint32_t b) { asm volatile("mbarrier.arrive.shared::cta.b64 _, [%0], 16;" ::"r"(b) : "memory"); }
__device__ __forceinline__ void mbar_arrive4_remote(uint32_t b) { asm volatile("mbarrier.arrive.shared::cluster.b64 _, [%0], 4;" ::"r"(b) : "memory"); }
__device__ __forceinline__ void mbar_arrive_remote(uint32_t b) { asm volatile("mbarrier.arrive.shared::cluster.b64 _, [%0];" ::"r"(b) : "memory"); }
#define MBAR_WAIT_ASM(SEM) \
    asm volatile("{\n.reg .pred p;\nWAIT:\nmbarrier.try_wait.parity" SEM ".shared::cta.b64 p, [%0], %1;\n@!p bra WAIT;\n}" ::"r"(b), "r"(parity) : "memory")
__device__ __forceinline__ void mbar_wait(uint32_t b, uint32_t parity) { MBAR_WAIT_ASM(""); }
__device__ __forceinline__ void mbar_wait_bounded(uint32_t b, uint32_t parity, uint32_t& n) {
    asm volatile("{\n.reg .pred p;\nWAIT:\nadd.u32 %0, %0, 1;\nsetp.gt.u32 p, %0, %3;\n@p st.global.u32 [%4], %0;\n"
                 "mbarrier.try_wait.parity.shared::cta.b64 p, [%1], %2;\n@!p bra WAIT;\n}" : "+r"(n) : "r"(b), "r"(parity), "n"(SPIN_LIMIT), "l"(0ull) : "memory");
}
__device__ __forceinline__ uint32_t mapa(uint32_t a, uint32_t rank) { uint32_t r; asm("mapa.shared::cluster.u32 %0, %1, %2;" : "=r"(r) : "r"(a), "r"(rank)); return r; }
__device__ __forceinline__ void tma3d(uint32_t dst, const CUtensorMap* tm, uint32_t bar, int c0, int c1, int c2) {
    asm volatile("cp.async.bulk.tensor.3d.shared::cluster.global.mbarrier::complete_tx::bytes [%0], [%1, {%3, %4, %5}], [%2];" ::"r"(dst), "l"(tm), "r"(bar), "r"(c0), "r"(c1), "r"(c2) : "memory");
}
__device__ __forceinline__ void tma2d_pair(uint32_t dst, const CUtensorMap* tm, uint32_t bar, int c0, int c1) {
    asm volatile("cp.async.bulk.tensor.2d.shared::cluster.global.mbarrier::complete_tx::bytes.multicast::cluster [%0], [%1, {%3, %4}], [%2], %5;" ::"r"(dst), "l"(tm), "r"(bar), "r"(c0), "r"(c1), "h"((uint16_t)3) : "memory");
}
__device__ __forceinline__ void tma3d_pair(uint32_t dst, const CUtensorMap* tm, uint32_t bar, int c0, int c1, int c2) {
    asm volatile("cp.async.bulk.tensor.3d.shared::cluster.global.mbarrier::complete_tx::bytes.multicast::cluster [%0], [%1, {%3, %4, %5}], [%2], %6;" ::"r"(dst), "l"(tm), "r"(bar), "r"(c0), "r"(c1), "r"(c2), "h"((uint16_t)3) : "memory");
}
__device__ __forceinline__ void bulk_load(uint32_t dst, const void* src, uint32_t bytes, uint32_t bar) {
    asm volatile("cp.async.bulk.shared::cluster.global.mbarrier::complete_tx::bytes [%0], [%1], %2, [%3];" ::"r"(dst), "l"(src), "r"(bytes), "r"(bar) : "memory");
}
__device__ __forceinline__ void bulk_load_pair(uint32_t dst, const void* src, uint32_t bytes, uint32_t bar) {
    asm volatile("cp.async.bulk.shared::cluster.global.mbarrier::complete_tx::bytes.multicast::cluster [%0], [%1], %2, [%3], %4;" ::"r"(dst), "l"(src), "r"(bytes), "r"(bar), "h"((uint16_t)3) : "memory");
}
__device__ __forceinline__ void bulk_store(void* dst, uint32_t src, uint32_t bytes) {
    asm volatile("cp.async.bulk.global.shared::cta.bulk_group [%0], [%1], %2;" ::"l"(dst), "r"(src), "r"(bytes) : "memory");
}
__device__ __forceinline__ uint32_t ld_u16(const void* p) { uint32_t v; asm volatile("ld.global.nc.u16 %0, [%1];" : "=r"(v) : "l"(p)); return v; }
__device__ __forceinline__ uint32_t ld_relaxed(const uint32_t* p) { uint32_t v; asm volatile("ld.relaxed.gpu.global.u32 %0, [%1];" : "=r"(v) : "l"(p) : "memory"); return v; }
__device__ __forceinline__ void bulk_flush() { asm volatile("cp.async.bulk.commit_group;\ncp.async.bulk.wait_group 0;" ::: "memory"); }
__device__ __forceinline__ void signal(uint32_t* flag) { asm volatile("fence.acq_rel.gpu;\nred.relaxed.gpu.global.add.u32 [%0], 1;" ::"l"(flag) : "memory"); }
__device__ __forceinline__ void hint(uint32_t* flag) { asm volatile("red.relaxed.gpu.global.add.u32 [%0], 1;" ::"l"(flag) : "memory"); }
__device__ __forceinline__ uint32_t tag(uint32_t v, uint32_t mask, uint32_t parity) { return (v & ~mask) | (parity & mask); }
__device__ __forceinline__ uint32_t or_diff(uint32_t acc, uint32_t v, uint32_t parity) { asm("lop3.b32 %0, %0, %1, %2, 0xf6;" : "+r"(acc) : "r"(v), "r"(parity)); return acc; }
__device__ __forceinline__ uint4 ld_relaxed4(const void* p) {
    uint4 v;
    asm volatile("ld.relaxed.gpu.global.v4.u32 {%0, %1, %2, %3}, [%4];" : "=r"(v.x), "=r"(v.y), "=r"(v.z), "=r"(v.w) : "l"(p) : "memory");
    return v;
}
__device__ __forceinline__ uint2 ld_relaxed2(const void* p) { uint2 v; asm volatile("ld.relaxed.gpu.global.v2.u32 {%0, %1}, [%2];" : "=r"(v.x), "=r"(v.y) : "l"(p) : "memory"); return v; }
__device__ __forceinline__ void sts4(uint32_t a, uint4 v) { asm volatile("st.shared.v4.b32 [%0], {%1, %2, %3, %4};" ::"r"(a), "r"(v.x), "r"(v.y), "r"(v.z), "r"(v.w) : "memory"); }
__device__ __forceinline__ void stg1(void* p, uint32_t v) { asm volatile("st.global.b32 [%0], %1;" ::"l"(p), "r"(v) : "memory"); }
__device__ __forceinline__ void fence_async_shared() { asm volatile("fence.proxy.async.shared::cta;" ::: "memory"); }
#define BOUND "add.u32 %0, %0, 16;\nsetp.gt.u32 p, %0, %1;\n@p st.global.u32 [%2], %0;\n"
__device__ __forceinline__ void wait_flag(const uint32_t* p, uint32_t target, uint32_t& n) {
    asm volatile("{\n.reg .pred p;\n.reg .u32 v;\nPOLL:\n" BOUND "ld.acquire.gpu.global.u32 v, [%3];\nsetp.ne.u32 p, v, %4;\n@p bra POLL;\nfence.proxy.async.global;\n}"
                 : "+r"(n) : "n"(SPIN_LIMIT), "l"(0ull), "l"(p), "r"(target) : "memory");
}
__device__ __forceinline__ void wait_flag2(const uint32_t* h, uint32_t th, const uint32_t* p, uint32_t target, uint32_t& n) {
    asm volatile("{\n.reg .pred p;\n.reg .u32 u, v;\nPOLL:\n" BOUND "ld.relaxed.gpu.global.u32 u, [%3];\nld.acquire.gpu.global.u32 v, [%5];\nsetp.ne.u32 p, u, %4;\nsetp.ne.or.u32 p, v, %6, p;\n@p bra POLL;\nfence.proxy.async.global;\n}"
                 : "+r"(n) : "n"(SPIN_LIMIT), "l"(0ull), "l"(h), "r"(th), "l"(p), "r"(target) : "memory");
}
__device__ __forceinline__ void bar_sync(int id, int n) { asm volatile("bar.sync %0, %1;" ::"r"(id), "r"(n) : "memory"); }
__device__ __forceinline__ void bar_arrive(int id, int n) { asm volatile("bar.arrive %0, %1;" ::"r"(id), "r"(n) : "memory"); }
__device__ __forceinline__ void wg_fence() { asm volatile("wgmma.fence.sync.aligned;" ::: "memory"); }
__device__ __forceinline__ void wg_commit() { asm volatile("wgmma.commit_group.sync.aligned;" ::: "memory"); }
template <int N> __device__ __forceinline__ void wg_wait() { asm volatile("wgmma.wait_group.sync.aligned %0;" ::"n"(N) : "memory"); }
template <int N> __device__ __forceinline__ void pin(float (&d)[N]) {
#pragma unroll
    for (int i = 0; i < N; i++) asm volatile("" : "+f"(d[i])::"memory");
}
__host__ __device__ constexpr uint32_t desc_hi(uint32_t sbo, uint32_t swz) { return (sbo >> 4) | (swz << 30); }
__host__ __device__ constexpr uint32_t desc_lo(uint32_t off, uint32_t lbo) { return ((SMEM0 + off) >> 4) | ((lbo >> 4) << 16); }
__device__ __forceinline__ uint32_t pack2(float lo, float hi) { uint32_t r; asm("cvt.rn.bf16x2.f32 %0, %1, %2;" : "=r"(r) : "f"(hi), "f"(lo)); return r; }
__device__ __forceinline__ float bf_lo(uint32_t v) { return __uint_as_float(v << 16); }
__device__ __forceinline__ float bf_hi(uint32_t v) { return __uint_as_float(v & 0xffff0000u); }
__device__ __forceinline__ uint32_t half_plus(uint32_t a, uint32_t b) { uint32_t r; asm("fma.rn.bf16x2 %0, %1, %2, %3;" : "=r"(r) : "r"(a), "r"(0x3f003f00u), "r"(b)); return r; }
__device__ __forceinline__ void stsm4(uint32_t a, uint32_t r0, uint32_t r1, uint32_t r2, uint32_t r3) {
    asm volatile("stmatrix.sync.aligned.m8n8.x4.shared.b16 [%0], {%1, %2, %3, %4};" ::"r"(a), "r"(r0), "r"(r1), "r"(r2), "r"(r3) : "memory");
}
__device__ __forceinline__ void stsm2(uint32_t a, uint32_t r0, uint32_t r1) {
    asm volatile("stmatrix.sync.aligned.m8n8.x2.shared.b16 [%0], {%1, %2};" ::"r"(a), "r"(r0), "r"(r1) : "memory");
}
__device__ __forceinline__ uint4 lds4(uint32_t a) { uint4 v; asm volatile("ld.shared.v4.b32 {%0, %1, %2, %3}, [%4];" : "=r"(v.x), "=r"(v.y), "=r"(v.z), "=r"(v.w) : "r"(a) : "memory"); return v; }
__device__ __forceinline__ uint2 lds2(uint32_t a) { uint2 v; asm volatile("ld.shared.v2.b32 {%0, %1}, [%2];" : "=r"(v.x), "=r"(v.y) : "r"(a) : "memory"); return v; }
__device__ __forceinline__ float lds1f(uint32_t a) { float v; asm volatile("ld.shared.f32 %0, [%1];" : "=f"(v) : "r"(a) : "memory"); return v; }
__device__ __forceinline__ void ldsm4(uint32_t* r, uint32_t a) {
    asm volatile("ldmatrix.sync.aligned.m8n8.x4.shared.b16 {%0, %1, %2, %3}, [%4];" : "=r"(r[0]), "=r"(r[1]), "=r"(r[2]), "=r"(r[3]) : "r"(a) : "memory");
}
__device__ __forceinline__ void ldsm4t(uint32_t* r, uint32_t a) {
    asm volatile("ldmatrix.sync.aligned.m8n8.x4.trans.shared.b16 {%0, %1, %2, %3}, [%4];" : "=r"(r[0]), "=r"(r[1]), "=r"(r[2]), "=r"(r[3]) : "r"(a) : "memory");
}
__device__ __forceinline__ void ldsm2t(uint32_t* r, uint32_t a) {
    asm volatile("ldmatrix.sync.aligned.m8n8.x2.trans.shared.b16 {%0, %1}, [%2];" : "=r"(r[0]), "=r"(r[1]) : "r"(a) : "memory");
}
__device__ __forceinline__ uint32_t transpose8(uint32_t v) { uint32_t r; asm volatile("movmatrix.sync.aligned.m8n8.trans.b16 %0, %1;" : "=r"(r) : "r"(v)); return r; }
__device__ __forceinline__ void mma16(float (&c)[4], uint32_t a0, uint32_t a1, uint32_t a2, uint32_t a3, uint32_t b0, uint32_t b1) {
    asm volatile("mma.sync.aligned.m16n8k16.row.col.f32.bf16.bf16.f32 {%0, %1, %2, %3}, {%4, %5, %6, %7}, {%8, %9}, {%0, %1, %2, %3};"
                 : "+f"(c[0]), "+f"(c[1]), "+f"(c[2]), "+f"(c[3]) : "r"(a0), "r"(a1), "r"(a2), "r"(a3), "r"(b0), "r"(b1));
}
__device__ __forceinline__ void mma8(float (&c)[4], uint32_t a0, uint32_t a1, uint32_t b0) {
    asm volatile("mma.sync.aligned.m16n8k8.row.col.f32.bf16.bf16.f32 {%0, %1, %2, %3}, {%4, %5}, {%6}, {%0, %1, %2, %3};"
                 : "+f"(c[0]), "+f"(c[1]), "+f"(c[2]), "+f"(c[3]) : "r"(a0), "r"(a1), "r"(b0));
}
__device__ __forceinline__ void st_async4(uint32_t a, uint32_t bar, uint32_t v0, uint32_t v1, uint32_t v2, uint32_t v3) {
    asm volatile("st.async.weak.shared::cluster.mbarrier::complete_tx::bytes.v4.b32 [%0], {%2, %3, %4, %5}, [%1];" ::"r"(a), "r"(bar), "r"(v0), "r"(v1), "r"(v2), "r"(v3) : "memory");
}
__device__ __forceinline__ void st_async2(uint32_t a, uint32_t bar, uint32_t v0, uint32_t v1) {
    asm volatile("st.async.weak.shared::cluster.mbarrier::complete_tx::bytes.v2.b32 [%0], {%2, %3}, [%1];" ::"r"(a), "r"(bar), "r"(v0), "r"(v1) : "memory");
}
__device__ __forceinline__ float quad_max(float v) { v = fmaxf(v, __shfl_xor_sync(~0u, v, 1)); return fmaxf(v, __shfl_xor_sync(~0u, v, 2)); }
__device__ __forceinline__ float quad_sum(float v) { v += __shfl_xor_sync(~0u, v, 1); return v + __shfl_xor_sync(~0u, v, 2); }
__device__ __forceinline__ float ex2(float v) { float r; asm("ex2.approx.ftz.f32 %0, %1;" : "=f"(r) : "f"(v)); return r; }
__device__ __forceinline__ float rcp(float v) { float r; asm("rcp.approx.ftz.f32 %0, %1;" : "=f"(r) : "f"(v)); return r; }
__device__ __forceinline__ float rsq(float v) { float r; asm("rsqrt.approx.ftz.f32 %0, %1;" : "=f"(r) : "f"(v)); return r; }
__device__ __forceinline__ float gelu2(float u) {
    float z = u * fmaf(u * u, 0.044715f * 0.7978845608028654f, 0.7978845608028654f), t;
    asm("tanh.approx.f32 %0, %1;" : "=f"(t) : "f"(z));
    return fmaf(u, t, u);
}
__device__ __forceinline__ float oct_sum(float v) {
    v += __shfl_xor_sync(~0u, v, 4); v += __shfl_xor_sync(~0u, v, 8); v += __shfl_xor_sync(~0u, v, 16);
    return v;
}

template <int TA, int TB, uint32_t HA, uint32_t HB>
__device__ __forceinline__ void wgmma_n112(float (&d)[56], uint32_t da, uint32_t db, int accumulate) {
    asm volatile("{\n.reg .pred p;\n.reg .b64 a, b;\nmov.b64 a, {%56, %61};\nmov.b64 b, {%57, %62};\nsetp.ne.b32 p, %58, 0;\n"
        "wgmma.mma_async.sync.aligned.m64n112k16.f32.bf16.bf16 {"
        "%0, %1, %2, %3, %4, %5, %6, %7, %8, %9, %10, %11, %12, %13, %14, %15, "
        "%16, %17, %18, %19, %20, %21, %22, %23, %24, %25, %26, %27, %28, %29, %30, %31, "
        "%32, %33, %34, %35, %36, %37, %38, %39, %40, %41, %42, %43, %44, %45, %46, %47, "
        "%48, %49, %50, %51, %52, %53, %54, %55"
        "}, a, b, p, 1, 1, %59, %60;\n}\n"
        : "+f"(d[0]), "+f"(d[1]), "+f"(d[2]), "+f"(d[3]), "+f"(d[4]), "+f"(d[5]), "+f"(d[6]), "+f"(d[7]),
          "+f"(d[8]), "+f"(d[9]), "+f"(d[10]), "+f"(d[11]), "+f"(d[12]), "+f"(d[13]), "+f"(d[14]), "+f"(d[15]),
          "+f"(d[16]), "+f"(d[17]), "+f"(d[18]), "+f"(d[19]), "+f"(d[20]), "+f"(d[21]), "+f"(d[22]), "+f"(d[23]),
          "+f"(d[24]), "+f"(d[25]), "+f"(d[26]), "+f"(d[27]), "+f"(d[28]), "+f"(d[29]), "+f"(d[30]), "+f"(d[31]),
          "+f"(d[32]), "+f"(d[33]), "+f"(d[34]), "+f"(d[35]), "+f"(d[36]), "+f"(d[37]), "+f"(d[38]), "+f"(d[39]),
          "+f"(d[40]), "+f"(d[41]), "+f"(d[42]), "+f"(d[43]), "+f"(d[44]), "+f"(d[45]), "+f"(d[46]), "+f"(d[47]),
          "+f"(d[48]), "+f"(d[49]), "+f"(d[50]), "+f"(d[51]), "+f"(d[52]), "+f"(d[53]), "+f"(d[54]), "+f"(d[55])
        : "r"(da), "r"(db), "r"(accumulate), "n"(TA), "n"(TB), "n"(HA), "n"(HB));
}

template <int TA, int TB, uint32_t HA, uint32_t HB>
__device__ __forceinline__ void wgmma_n184(float (&d)[92], uint32_t da, uint32_t db, int accumulate) {
    asm volatile("{\n.reg .pred p;\n.reg .b64 a, b;\nmov.b64 a, {%92, %97};\nmov.b64 b, {%93, %98};\nsetp.ne.b32 p, %94, 0;\n"
        "wgmma.mma_async.sync.aligned.m64n184k16.f32.bf16.bf16 {"
        "%0, %1, %2, %3, %4, %5, %6, %7, %8, %9, %10, %11, %12, %13, %14, %15, "
        "%16, %17, %18, %19, %20, %21, %22, %23, %24, %25, %26, %27, %28, %29, %30, %31, "
        "%32, %33, %34, %35, %36, %37, %38, %39, %40, %41, %42, %43, %44, %45, %46, %47, "
        "%48, %49, %50, %51, %52, %53, %54, %55, %56, %57, %58, %59, %60, %61, %62, %63, "
        "%64, %65, %66, %67, %68, %69, %70, %71, %72, %73, %74, %75, %76, %77, %78, %79, "
        "%80, %81, %82, %83, %84, %85, %86, %87, %88, %89, %90, %91"
        "}, a, b, p, 1, 1, %95, %96;\n}\n"
        : "+f"(d[0]), "+f"(d[1]), "+f"(d[2]), "+f"(d[3]), "+f"(d[4]), "+f"(d[5]), "+f"(d[6]), "+f"(d[7]),
          "+f"(d[8]), "+f"(d[9]), "+f"(d[10]), "+f"(d[11]), "+f"(d[12]), "+f"(d[13]), "+f"(d[14]), "+f"(d[15]),
          "+f"(d[16]), "+f"(d[17]), "+f"(d[18]), "+f"(d[19]), "+f"(d[20]), "+f"(d[21]), "+f"(d[22]), "+f"(d[23]),
          "+f"(d[24]), "+f"(d[25]), "+f"(d[26]), "+f"(d[27]), "+f"(d[28]), "+f"(d[29]), "+f"(d[30]), "+f"(d[31]),
          "+f"(d[32]), "+f"(d[33]), "+f"(d[34]), "+f"(d[35]), "+f"(d[36]), "+f"(d[37]), "+f"(d[38]), "+f"(d[39]),
          "+f"(d[40]), "+f"(d[41]), "+f"(d[42]), "+f"(d[43]), "+f"(d[44]), "+f"(d[45]), "+f"(d[46]), "+f"(d[47]),
          "+f"(d[48]), "+f"(d[49]), "+f"(d[50]), "+f"(d[51]), "+f"(d[52]), "+f"(d[53]), "+f"(d[54]), "+f"(d[55]),
          "+f"(d[56]), "+f"(d[57]), "+f"(d[58]), "+f"(d[59]), "+f"(d[60]), "+f"(d[61]), "+f"(d[62]), "+f"(d[63]),
          "+f"(d[64]), "+f"(d[65]), "+f"(d[66]), "+f"(d[67]), "+f"(d[68]), "+f"(d[69]), "+f"(d[70]), "+f"(d[71]),
          "+f"(d[72]), "+f"(d[73]), "+f"(d[74]), "+f"(d[75]), "+f"(d[76]), "+f"(d[77]), "+f"(d[78]), "+f"(d[79]),
          "+f"(d[80]), "+f"(d[81]), "+f"(d[82]), "+f"(d[83]), "+f"(d[84]), "+f"(d[85]), "+f"(d[86]), "+f"(d[87]),
          "+f"(d[88]), "+f"(d[89]), "+f"(d[90]), "+f"(d[91])
        : "r"(da), "r"(db), "r"(accumulate), "n"(TA), "n"(TB), "n"(HA), "n"(HB));
}

template <uint32_t HB>
__device__ __forceinline__ void wgmma_rs_n184(float (&d)[92], uint32_t a0, uint32_t a1, uint32_t db) {
    asm volatile("{\n.reg .b64 b;\nmov.b64 b, {%94, %96};\n"
        "wgmma.mma_async.sync.aligned.m64n184k16.f32.bf16.bf16 {"
        "%0, %1, %2, %3, %4, %5, %6, %7, %8, %9, %10, %11, %12, %13, %14, %15, "
        "%16, %17, %18, %19, %20, %21, %22, %23, %24, %25, %26, %27, %28, %29, %30, %31, "
        "%32, %33, %34, %35, %36, %37, %38, %39, %40, %41, %42, %43, %44, %45, %46, %47, "
        "%48, %49, %50, %51, %52, %53, %54, %55, %56, %57, %58, %59, %60, %61, %62, %63, "
        "%64, %65, %66, %67, %68, %69, %70, %71, %72, %73, %74, %75, %76, %77, %78, %79, "
        "%80, %81, %82, %83, %84, %85, %86, %87, %88, %89, %90, %91"
        "}, {%92, %93, %95, %95}, b, 1, 1, 1, 0;\n}\n"
        : "+f"(d[0]), "+f"(d[1]), "+f"(d[2]), "+f"(d[3]), "+f"(d[4]), "+f"(d[5]), "+f"(d[6]), "+f"(d[7]),
          "+f"(d[8]), "+f"(d[9]), "+f"(d[10]), "+f"(d[11]), "+f"(d[12]), "+f"(d[13]), "+f"(d[14]), "+f"(d[15]),
          "+f"(d[16]), "+f"(d[17]), "+f"(d[18]), "+f"(d[19]), "+f"(d[20]), "+f"(d[21]), "+f"(d[22]), "+f"(d[23]),
          "+f"(d[24]), "+f"(d[25]), "+f"(d[26]), "+f"(d[27]), "+f"(d[28]), "+f"(d[29]), "+f"(d[30]), "+f"(d[31]),
          "+f"(d[32]), "+f"(d[33]), "+f"(d[34]), "+f"(d[35]), "+f"(d[36]), "+f"(d[37]), "+f"(d[38]), "+f"(d[39]),
          "+f"(d[40]), "+f"(d[41]), "+f"(d[42]), "+f"(d[43]), "+f"(d[44]), "+f"(d[45]), "+f"(d[46]), "+f"(d[47]),
          "+f"(d[48]), "+f"(d[49]), "+f"(d[50]), "+f"(d[51]), "+f"(d[52]), "+f"(d[53]), "+f"(d[54]), "+f"(d[55]),
          "+f"(d[56]), "+f"(d[57]), "+f"(d[58]), "+f"(d[59]), "+f"(d[60]), "+f"(d[61]), "+f"(d[62]), "+f"(d[63]),
          "+f"(d[64]), "+f"(d[65]), "+f"(d[66]), "+f"(d[67]), "+f"(d[68]), "+f"(d[69]), "+f"(d[70]), "+f"(d[71]),
          "+f"(d[72]), "+f"(d[73]), "+f"(d[74]), "+f"(d[75]), "+f"(d[76]), "+f"(d[77]), "+f"(d[78]), "+f"(d[79]),
          "+f"(d[80]), "+f"(d[81]), "+f"(d[82]), "+f"(d[83]), "+f"(d[84]), "+f"(d[85]), "+f"(d[86]), "+f"(d[87]),
          "+f"(d[88]), "+f"(d[89]), "+f"(d[90]), "+f"(d[91])
        : "r"(a0), "r"(a1), "r"(db), "r"(0), "n"(HB));
}

struct Ring {
    uint32_t slot, ph;
    __device__ __forceinline__ void next() { if (++slot == NSLOT) { slot = 0; ph ^= 1; } }
    __device__ __forceinline__ void next2() { ph ^= slot == 5; slot = __byte_perm(0x06030201u, 0x00040005u, 0x7770 + slot); }
};
struct Slot {
    uint32_t dst, bar, ph;
    __device__ __forceinline__ void next(uint32_t bars) {
        dst += SLOT; bar += 8;
        if (bar == bars + 8 * NSLOT) { dst -= NSLOT * SLOT; bar = bars; ph ^= 1; }
    }
};
__device__ __forceinline__ uint32_t xslot(int i) { return __byte_perm(0x04130e0cu, 0x00130e0cu, 0x7770 + i); }
__device__ __forceinline__ uint32_t wslot(int i) { return __byte_perm(0x06001510u, 0x00151009u, 0x7770 + i); }

constexpr uint32_t HI_SW = desc_hi(1024, 1);

struct Mma {
    uint32_t bars, rel;
    bool lead;
    int wg, w;
    Ring r;
    uint32_t prev;
    __device__ __forceinline__ void release(uint32_t s) { if (lead) mbar_arrive4_remote(rel + B_EMPTY + 8 * s); }
    template <bool G1>
    __device__ __forceinline__ void run(float (&a)[56], int n, int first, int last, int lag, int accumulate, int ts) {
#pragma unroll 1
        for (int i = 0; i < n; i++) {
            if (lag && i == (wg ? n - lag : -1)) bar_sync(7, 256);
            const uint32_t s = r.slot;
            mbar_wait(bars + B_FULL + 8 * s, r.ph);
            if (G1) r.next(); else r.next2();
            TS0(G1 ? 2 : 8, ts + i + wg * 68);
            const uint32_t dB = s * (SLOT >> 4), dA = dB + wg * 512;
            wg_fence();
#pragma unroll
            for (int k = 0; k < 4; k++) {
                wgmma_n112<1, 1, HI_SW, desc_hi(G1 ? 256 : 1024, 0)>(a, dA + desc_lo(k * 2048, 8192), dB + desc_lo(16384 + k * (G1 ? SLAB : 256), 128), k > 0 || accumulate || i > 0);
                if (k == 1) {
                    wg_commit(); wg_wait<1>();
                    if ((uint32_t)(i - first) < (uint32_t)(last - first)) release(prev);
                    if (lag && i == (wg ? -1 : n - 1)) bar_arrive(7, 256);
                }
            }
            wg_commit();
            prev = s;
        }
    }
    __device__ __forceinline__ void run_o(float (&a)[56]) {
#pragma unroll 1
        for (int i = 0; i < 2; i++) {
            const uint32_t s = r.slot, dB = s * (SLOT >> 4), dA = dB + wg * 512;
            mbar_wait(bars + B_FULL + 8 * s, r.ph);
            TS0(8, 48 + 2 * i + wg * 68);
            wg_fence();
#pragma unroll
            for (int k = 0; k < 7; k++) {
                if (k == 3) { mbar_wait(bars + B_FULL + 8 * s + 8, r.ph); wg_fence(); }
                wgmma_n112<0, 1, desc_hi(128, 0), desc_hi(256, 0)>(a, dA + desc_lo(k * 2048 + (k > 3) * (SLOT - HALF), k == 3 ? SLOT - 6144 : 1024),
                                                                   dB + desc_lo(16384 + k * SLAB + (k > 2) * (SLOT - 3 * SLAB), 128), k > 0 || i > 0);
                if (k & 1) wg_commit();
                if (k == 1) { wg_wait<1>(); if (i) release(prev); }
                if (k == 5) { wg_wait<1>(); release(s); }
            }
            wg_commit();
            prev = s + 1;
            r.slot++; r.next2();
        }
    }
};

__global__ void __cluster_dims__(2, 1, 1) __launch_bounds__(NTHREADS, 1)
fused_kernel(const __nv_bfloat16* __restrict__ x, const __nv_bfloat16* __restrict__ b1, const __nv_bfloat16* __restrict__ b2, const __nv_bfloat16* __restrict__ wo, __nv_bfloat16* out, Scratch* G,
             const __nv_bfloat16* __restrict__ w1, const __nv_bfloat16* __restrict__ w2,
             const __grid_constant__ Params P) {
    extern __shared__ __align__(1024) uint8_t smem[];
    const uint32_t sbase = (uint32_t)__cvta_generic_to_shared(smem);
    const uint32_t bars = sbase + OFF_BAR;
    const uint32_t rank = blockIdx.x & 1, pr = blockIdx.x >> 1;
    const uint32_t row0 = blockIdx.x * 16;
    if (threadIdx.x == 0) {
        TS(15, 0);
        mbar_init(bars + B_ROW, 1);
        asm volatile("fence.mbarrier_init.release.cluster;" ::: "memory");
        bulk_load(sbase + OFF_Y, x + row0 * D_, TILEB, bars + B_ROW);
        mbar_expect(bars + B_ROW, TILEB);
        TS(1, 97);
    }
    const int lane = threadIdx.x & 31;
    const int warp = __shfl_sync(~0u, threadIdx.x >> 5, 0), w = warp & 3;
    if (elect()) {
        const uint32_t first = bars + warp * 24, count = warp < 8 ? 1 : warp == 8 ? 2 : 16;
#pragma unroll
        for (int i = 0; i < 3; i++) mbar_init(first + 8 * i, count);
        asm volatile("fence.mbarrier_init.release.cluster;" ::: "memory");
    }
    __syncwarp();
    asm volatile("barrier.cluster.arrive.relaxed.aligned;" ::: "memory");
    const uint32_t pv = pr < 4 ? pr * 8 + 36 : pr - 4 + (max((int)pr - 33, 0) * 37 >> 8);
    const uint32_t gp = (pv + 4) & 7, hp = pv >> 3;
    const uint32_t tb = gp * 2 + rank, c = hp * 16 + tb;
    const bool has_g1 = gp > 0;
    const uint32_t nt1 = hp & 3, ft = max((int)gp - 1, 0) * 2 + (hp >> 2);
    const uint32_t nt2 = tb & 3, mt = (gp & 2) * 4 + hp, ks = gp >> 2;
    asm volatile("barrier.cluster.wait.aligned;" ::: "memory");

    if (warp == 8) {
        uint32_t kw = gp % ROT * (512 / ROT), kx;
        if (elect()) {
            mbar_expect(bars + B_QFULL, QSLOT);
            tma3d(sbase + xslot(0) * 8192, &P.tmX, bars + B_QFULL, kw, tb * 64, 0);
            tma3d_pair(sbase + wslot(0) * 8192 + rank * 12288, &P.tmWqkv, bars + B_QFULL, (hp * 56) & ~15, kw + rank * 32, 0);
            TS(1, 23);
            uint32_t due = (uint32_t)clock() + PACE, ep = ld_relaxed(&G->epoch[c]);
            uint32_t spins = sbase == (rank << 24 | SMEM0) ? 0 : SPIN_LIMIT;
#pragma unroll 1
            for (int i = 1; i < 8; i++) {
                kx = kw; kw += 64;
                if (i >= 5) mbar_wait_bounded(bars + B_QEMPTY + 8 * (i - 5), 0, spins);
                else { while ((int)((uint32_t)clock() - due) < 0) {} due += PACE; }
                if (kw == D_) kw = 0;
                if (i < 4) kx = kw;
                const int ix = i - (i > 4);
                if (i < 7) mbar_expect(bars + B_QFULL + 8 * i, QSLOT);
                if (i != 4) tma3d(sbase + xslot(ix) * 8192, &P.tmX, bars + B_QFULL + 8 * ix, kx, tb * 64, 0);
                if (i == 5) mbar_wait_bounded(bars + B_CS, 0, spins);
                if (i < 7) tma3d_pair(sbase + wslot(i) * 8192 + rank * 12288, &P.tmWqkv, bars + B_QFULL + 8 * i, (hp * 56) & ~15, kw + rank * 32, 0);
            }
            ep++;
            Slot r{sbase, bars, 0};
            if (has_g1) {
                const uint8_t* src = G->H[nt1][rank * 16];
                const int row = rank * 1024;
                mbar_arrive(bars + B_FULL + 48); mbar_arrive16(bars + B_EMPTY + 48);
                mbar_expect(bars + B_FULL, 16384 + TILEB);
                tma3d(sbase, &P.tmW1, bars + B_FULL, 0, row, ft * 2);
                wait_flag(G->flag[1] + rank * 2, 20 * ep, spins);
                TS(1, 16);
#pragma unroll 1
                for (int j = 64;; j += 64) {
                    bulk_load(r.dst + 16384, src, TILEB, r.bar + B_FULL);
                    src += TILEB;
                    r.next(bars);
                    if (j == 1024) break;
                    mbar_wait_bounded(r.bar + B_EMPTY, r.ph, spins);
                    if (j < 14 * 64) TS(2, 146 + j / 64);
                    mbar_expect(r.bar + B_FULL, 16384 + TILEB);
                    tma3d(r.dst, &P.tmW1, r.bar + B_FULL, 0, row + j, ft * 2);
                }
#pragma unroll
                for (int i = 0; i < 4; i++) mbar_expect(bars + B_X + 8 * i, (i & 1) ? 3072 : 4096);
            } else {
                due = (uint32_t)clock();
#pragma unroll 1
                for (int j = PF0; j < PF1; j++) {
                    asm volatile("cp.async.bulk.prefetch.L2.global [%0], %1;" ::"l"(w1 + (rank * 1024 + j * 64 + hp * 8) * F_), "n"(16 * F_) : "memory");
                    due += PF;
                    while ((int)((uint32_t)clock() - due) < 0) {}
                }
            }
            const uint8_t *so = G->O[mt][ks * 4] + rank * HALF, *sw = G->Wo[nt2][ks * 4];
            wait_flag2(G->flag[16 + mt], 8 * ep, G->flag[0], 16 * ep, spins);
            TS(4, 18);
#pragma unroll 1
            for (int j = 0; j < 4 * TILEB; j += TILEB) {
                mbar_wait_bounded(r.bar + B_EMPTY, r.ph, spins);
                mbar_expect(r.bar + B_QFULL, TILEB);
                bulk_load_pair(r.dst + rank * 8192, so + j, HALF, r.bar + B_QFULL);
                bulk_load(r.dst + 16384, sw + j, (r.bar & 8) ? TILEB : 3 * SLAB, r.bar + B_FULL);
                r.next(bars);
            }
            if (!has_g1) {
#pragma unroll 1
                for (int j = PG0; j < PG1; j++)
                    asm volatile("cp.async.bulk.prefetch.L2.global [%0], %1;" ::"l"(w2 + (rank * 896 + j * 128 + hp * 8) * S_), "n"(16 * S_) : "memory");
            }
            Ring q{has_g1 ? 2u : 6u, has_g1};
#pragma unroll 1
            for (int j = 0; j < 14 * 128; j += 128) {
                mbar_wait_bounded(bars + B_EMPTY + 8 * q.slot, q.ph, spins);
                TS(8, 176 + j / 128);
                tma2d_pair(sbase + q.slot * SLOT + rank * 8192, &P.tmW2, bars + B_FULL + 8 * q.slot, mt * 128 + rank * 64, ks * 896 + j - (j < 896 ? 0 : 832));
                q.next2();
            }
            mbar_wait_bounded(bars + B_END, 0, spins);
        }
    } else if (warp > 8) {
        const uint32_t ep = ld_relaxed(&G->epoch[c]) + 1;
        {
            const uint32_t src = (sbase + wslot(gp / ROT) * 8192 - 4096 + w * 4096 + rank * 64 + (lane & 15) * 4 + (lane >> 4) * 12288) ^ ((lane >> 4) * 576);
            float s0 = 0.f, s1 = 0.f, s2 = 0.f, s3 = 0.f;
            mbar_wait(bars + B_QFULL + 8 * (gp / ROT), 0);
            if (w == 1) TS(1, 66);
            uint32_t v[32];
#pragma unroll
            for (int k = 0; k < 32; k++) v[k] = __float_as_uint(lds1f((src ^ ((k & 7) * 144)) + (k >> 3) * 1024));
#pragma unroll
            for (int k = 0; k < 32; k += 2) { s0 += bf_lo(v[k]); s1 += bf_hi(v[k]); s2 += bf_lo(v[k + 1]); s3 += bf_hi(v[k + 1]); }
            s0 += s2; s1 += s3;
            s0 += __shfl_xor_sync(~0u, s0, 16); s1 += __shfl_xor_sync(~0u, s1, 16);
            uint2* cs = G->colsum[hp][0] + w * 32 - 32;
            if (lane < 16) cs[gp * 96 + rank * 16 + lane] = make_uint2(tag(__float_as_uint(s0), 1, ep), __float_as_uint(s1));
            if (w == 1) TS(1, 24);
            if (w == 2) {
                bar_sync(6, 224);
                TS(1, 8);
                if (elect()) { mbar_arrive(bars + B_CS); signal(G->flag[1] + (row0 >> 10) * 2 + ((row0 & 1023) >= 320)); TS(1, 3); }
                __syncwarp();
            } else {
                bar_arrive(6, 224);
            }
            bar_sync(1, 96);
            const int i0 = threadIdx.x - 288;
            uint2 u[7];
            uint4 sv;
            uint32_t bad;
            do {
                sv = ld_relaxed4(G->stat + tb * 128 + (i0 & 63) * 2);
                bad = or_diff(sv.x ^ ep, sv.z, ep);
#pragma unroll
                for (int i = 0; i < 7; i++) { u[i] = ld_relaxed2(cs + i * 96 + lane); bad = or_diff(bad, u[i].x, ep); }
            } while (bad & 1);
            if (w < 3) sts4(sbase + OFF_ST + i0 * 16, sv);
#pragma unroll
            for (int e = 0; e < 2; e++) {
                float f = 0.f;
#pragma unroll
                for (int i = 0; i < 7; i++) f += __uint_as_float(e ? u[i].y : u[i].x);
                const uint32_t hi = pack2(f, f);
                sts4(sbase + OFF_X + i0 * 32 + e * 16, make_uint4(hi, pack2(f - bf_hi(hi), f - bf_hi(hi)), 0, 0));
            }
            asm volatile("st.shared.u32 [%0], %1;" ::"r"(bars + 8 * NBAR), "r"(ep) : "memory");
            fence_async_shared();
            __syncwarp();
            bar_arrive(8, 224); bar_arrive(9, 224);
            TS(1, 90 + w);
        }
        const uint8_t* src = G->U[nt2][ks * 14];
        uint32_t spins = 0;
        if (w < 3) {
            uint32_t bad;
            if (w == 1) {
                if (elect()) {
                    wait_flag(G->flag[1] + rank * 2 + 1, 44 * ep, spins);
                    mbar_arrive16(bars + B_EMPTY + 8 * 5);
                    TS(1, 96);
                }
                __syncwarp();
                if (!has_g1) { bar_sync(5, 288); if (elect()) signal(G->flag[0]); __syncwarp(); TS(2, 26); }
            } else {
                bar_sync(3, 288);
                __nanosleep(HALO_NS);
                uint4 v[7];
                do {
                    bad = 0;
#pragma unroll
                    for (int i = 0; i < 7; i++) { v[i] = ld_relaxed4(G->halo[c - (tb > 0)] + i * 512 + lane * 16); bad = or_diff(bad, v[i].x, ep); }
                } while (bad & 1);
#pragma unroll
                for (int i = 0; i < 7; i++) sts4(sbase + OFF_X + i * 512 + lane * 16, v[i]);
                __syncwarp();
                if (elect()) mbar_arrive(bars + B_HALO);
                TS(2, 21);
            }
            mbar_wait(bars + B_HALO, 0);
            uint32_t slot = (has_g1 ? 16 % NSLOT : 0) + w - 1, ph = ~0u;
#pragma unroll 1
            for (int i = w - 1; i < 18;) {
                const uint32_t d0 = sbase + slot * SLOT + (i < 4 ? 0 : 16384), d1 = d0 + (i < 4 ? 8192 : HALF), landed = bars + B_QFULL + 8 * slot;
                mbar_wait(landed, (ph >> slot) & 1);
                ph ^= 1 << slot;
                if (i < 8) TS(4, 82 + i);
                if (i >= 4) TS(8, 156 + i);
                bad = 0;
#pragma unroll
                for (int k = 0; k < 14; k++) bad = or_diff(bad, __float_as_uint(lds1f((k < 7 ? d0 : d1) + k % 7 * 1024 + lane * 32 + (lane >> 2) * 4)), ep);
                if (__any_sync(~0u, bad & 1)) {
                    if (elect()) {
                        const uint8_t* cur = (i < 4 ? G->O[mt][ks * 4] : src - 4 * TILEB) + i * TILEB;
                        fence_async_shared();
                        mbar_expect(landed, TILEB);
                        bulk_load(d0, cur, HALF, landed);
                        bulk_load(d1, cur + HALF, HALF, landed);
                    }
                    TS(4, i < 4 ? 94 : 95);
                } else {
                    if (elect()) mbar_expect(landed + (B_FULL - B_QFULL), i < 4 ? (2 + w) * SLAB : 16384);
                    i += __byte_perm(0x03020202u, 0x00010202u, 0x7770 + slot);
                    slot = __byte_perm(0x05060302u, 0x00040100u, 0x7770 + slot);
                }
            }
        } else {
            bar_sync(2, 288);
            if (elect()) bulk_store(out + row0 * D_, sbase + OFF_Y, TILEB);
            __syncwarp();
            bar_sync(4, 288);
            if (elect()) {
                fence_async_shared();
                bulk_store(G->O[tb][hp], sbase + OFF_X, TILEB);
                bulk_flush();
                TS(2, 7);
                mbar_arrive_remote(mapa(bars + B_FREE, rank ^ 1));
                mbar_arrive(bars + B_FREE);
                hint(G->flag[16 + tb]);
                signal(G->flag[16 + (row0 >> 7)] + 1);
                TS(2, 22);
            }
            __syncwarp();
            uint32_t late = ~0u;
            const uint32_t* hints = G->flag[8 + nt2 * 2 + ks] + lane;
            mbar_wait(bars + (has_g1 ? B_X : B_FREE), 0);
            Ring r{has_g1 ? 2u : 6u, has_g1};
#pragma unroll 1
            for (int i = 0; i < 14; i++) {
                while ((late >> i) & 1) late = __ballot_sync(~0u, ld_relaxed(hints) != 2 * ep) & 127;
                if (i == 0) TS(4, 17);
                mbar_wait(bars + B_EMPTY + 8 * r.slot, r.ph);
                TS(8, 192 + i);
                if (elect()) {
                    mbar_expect(bars + B_QFULL + 8 * r.slot, TILEB);
                    bulk_load(sbase + r.slot * SLOT + 16384, src, TILEB, bars + B_QFULL + 8 * r.slot);
                }
                src += TILEB; r.next2();
                if (UGAP && i < UGAPN) { const uint32_t t0 = clock(); while ((uint32_t)clock() - t0 < UGAP) {} }
            }
            if (elect()) {
                wait_flag(G->flag[16 + mt] + 1, 8 * ep, spins);
                mbar_arrive(bars + B_ROW);
                TS(2, 27);
                G->epoch[c] = ep;
            }
        }
    } else {
        const int wg = warp >> 2;
        Mma M{bars, mapa(bars, rank ^ (lane & 1)), (threadIdx.x & 127) < 2, wg, w, Ring{0, 0}, 0};
        const int r = lane >> 2, t = lane & 3;
        uint32_t ep;
        const uint32_t bias0 = ld_u16(b1 + ft * 128 + warp * 16 + r), bias1 = ld_u16(b1 + ft * 128 + warp * 16 + r + 8);
        if (wg == 1) {
            ep = ld_relaxed(&G->epoch[c]);
            const int r16 = w * 4 + t, c8 = (r + 2 * t) & 7;
            const uint32_t row = sbase + OFF_Y + r16 * (2 * D_) + c8 * 16;
            mbar_wait(bars + B_ROW, 0);
            TS0(1, 67);
            float f[56];
#pragma unroll
            for (int i = 0; i < 7; i++) {
                const uint4 v = lds4(row + i * 128);
                f[8 * i] = bf_lo(v.x); f[8 * i + 1] = bf_hi(v.x); f[8 * i + 2] = bf_lo(v.y); f[8 * i + 3] = bf_hi(v.y);
                f[8 * i + 4] = bf_lo(v.z); f[8 * i + 5] = bf_hi(v.z); f[8 * i + 6] = bf_lo(v.w); f[8 * i + 7] = bf_hi(v.w);
            }
            float s0 = f[0], s1 = f[1], s2 = f[2], s3 = f[3];
#pragma unroll
            for (int i = 4; i < 56; i += 4) { s0 += f[i]; s1 += f[i + 1]; s2 += f[i + 2]; s3 += f[i + 3]; }
            const float nmean = oct_sum((s0 + s1) + (s2 + s3)) * (-1.f / D_);
            s0 = s1 = s2 = s3 = 0.f;
#pragma unroll
            for (int i = 0; i < 56; i += 4) {
                f[i] += nmean; f[i + 1] += nmean; f[i + 2] += nmean; f[i + 3] += nmean;
                s0 = fmaf(f[i], f[i], s0); s1 = fmaf(f[i + 1], f[i + 1], s1); s2 = fmaf(f[i + 2], f[i + 2], s2); s3 = fmaf(f[i + 3], f[i + 3], s3);
            }
            const float var = oct_sum((s0 + s1) + (s2 + s3)) * (1.f / D_);
            const float rstd = rsq(var + LN_EPS);
            const float sc = rstd * rsq(fmaf(var * rstd, rstd, LN_EPS));
            if (lane < 4) G->stat[row0 + r16] = make_uint2(tag(__float_as_uint(rstd), 1, ~ep), pack2(nmean, nmean - bf_hi(pack2(nmean, nmean))));
            uint8_t* hb = G->H[0][0] + row0 * (SLAB / 16) + r16 * 16 + c8 * 256;
            const int sw = row0 < 1024 ? 0 : 7 * 256;
#pragma unroll
            for (int i = 0; i < 7; i++) {
                const int lo = (8 * i) % 14, nt = (8 * i) / 14, next = 32 * TILEB - SLAB;
                const int off = lo < 7 ? (c8 < 7 - lo ? sw : -sw) : (c8 >= 14 - lo ? sw + next : -sw);
                *(uint4*)(hb + off + i * 2048 + nt * next) = make_uint4(pack2(f[8 * i] * sc, f[8 * i + 1] * sc), pack2(f[8 * i + 2] * sc, f[8 * i + 3] * sc),
                                                                        pack2(f[8 * i + 4] * sc, f[8 * i + 5] * sc), pack2(f[8 * i + 6] * sc, f[8 * i + 7] * sc));
            }
            TS0(1, 25);
            bar_arrive(6, 224);
        }
        const uint32_t kv = sbase + OFF_X + (w * 2 + wg) * KV + lane * 16;
        uint32_t q[8][2], k0[7], k1[7], v0[7];
        {
            float acc[92];
#pragma unroll 1
            for (int kb = 0; kb < 7; kb++) {
                const bool held = kb == (wg ? 7 - HOLD : -1);
                if (held) { wg_wait<0>(); M.release(4 - HOLD); bar_sync(7, 256); }
                mbar_wait(bars + B_QFULL + 8 * kb, 0);
                TS0(1, 68 + wg * 7 + kb);
                const uint32_t dA = (xslot(kb) + wg) * 512, dB = wslot(kb) * 512 + (hp & 1);
                wg_fence();
#pragma unroll
                for (int k = 0; k < 4; k++) {
                    wgmma_n184<0, 1, HI_SW, HI_SW>(acc, dA + desc_lo(k * 32, 16), dB + desc_lo((k & 1) * 2048 + (k >> 1) * 12288, 4096), k > 0 || kb > 0);
                    if (k == 0) { wg_commit(); wg_wait<1>(); if (kb > 0 && !held) M.release(kb - 3); }
                }
                wg_commit();
            }
            if (wg == 0 && !LATEREL) bar_arrive(7, 256);
            bar_sync(8 + wg, 224);
            ep = __float_as_uint(lds1f(bars + 8 * NBAR));
            const uint32_t st = sbase + OFF_ST + (w * 32 + r * 2 + wg) * 8;
            const uint2 s0 = lds2(st), s1 = lds2(st + 128);
            const uint32_t a0 = t < 2 ? s0.y : 0, a1 = t < 2 ? s1.y : 0;
            wg_fence();
            wgmma_rs_n184<desc_hi(128, 0)>(acc, a0, a1, desc_lo(OFF_X, 0) + (hp & 1) * 8);
            wg_commit();
            if (wg == 0 && LATEREL) bar_arrive(7, 256);
            wg_wait<1>();
            M.release(4);
            wg_wait<0>();
            pin(acc);
            TS0(1, 4 + 7 * wg);
            uint32_t hi[14];
#pragma unroll
            for (int p = 2; p >= 0; p--) {
                const float f = p == 0 ? 0.1889822365046136f * 1.4426950408889634f : p, r0 = __uint_as_float(s0.x) * f, r1 = __uint_as_float(s1.x) * f;
#pragma unroll
                for (int g = 0; g < 7; g++) {
                    const int a = (p * 8 + g) * 4;
                    const uint32_t lo2 = pack2(acc[a] * r0, acc[a + 1] * r0), hi2 = pack2(acc[a + 2] * r1, acc[a + 3] * r1);
                    if (p == 0) { q[g][0] = lo2; q[g][1] = hi2; } else { hi[(p - 1) * 7 + g] = hi2; }
                    if (p == 1) { k0[g] = lo2; k1[g] = hi2; }
                    if (p == 2) v0[g] = lo2;
                }
                if (p == 1) {
#pragma unroll
                    for (int i = 0; i < 3; i++) stsm4(kv + 2 * KV + i * 512, hi[4 * i], hi[4 * i + 1], hi[4 * i + 2], hi[4 * i + 3]);
                    stsm2(kv + 2 * KV + 1536, hi[12], hi[13]);
                    if (w == 3) {
#pragma unroll
                        for (int i = 0; i < 14; i++) stg1(G->halo[c] + wg * KV + lane * 4 + i * 128, tag(hi[i], t == 0, ep));
                    }
                    bar_arrive(3, 288);
                }
            }
#pragma unroll
            for (int j = 0; j < 2; j++) { q[7][j] = t < 2 ? 0u : q[3][j]; q[3][j] = t < 2 ? q[3][j] : 0u; }
#pragma unroll
            for (int g = 0; g < 7; g++) v0[g] = transpose8(v0[g]);
        }
        TS0(1, 9 + 11 * wg);
        float a[56];
#pragma unroll
        for (int i = 0; i < 56; i++) asm volatile("" : "=f"(a[i]));
        if (__builtin_expect(!has_g1, 0)) {
            const int g = min(lane >> 1, 13), nt = rank * 2 + wg;
            const uint4* src = (const uint4*)(wo + (hp * 56 - (hp & 1) * 8 + w * 16 + (lane & 1)) * D_ + nt * 112) + g;
            uint4 v[8];
#pragma unroll
            for (int i = 0; i < 8; i++) v[i] = __ldg(src + i * (D_ / 4));
#pragma unroll
            for (int i = 0; i < 8; i++) ((uint4*)G->Wo[nt][hp])[w * (SLAB / 16) + g * 16 + (lane & 1) + 2 * i] = v[i];
            bar_arrive(5, 288);
        }
        M.run<true>(a, has_g1 ? PAUSE : 0, 1, 16, 0, 0, 32);
        {
            uint32_t kp[8], vv[14];
            TS0(2, 140 + wg);
            mbar_wait(bars + B_HALO, 0);
            TS0(2, 142 + wg);
            ldsm4(kp, kv); ldsm4(kp + 4, kv + (lane < 24 ? 512 : 0));
            const uint32_t va = kv + 896 + (lane & 8) * (2 * KV / 8 - 16) - (lane & 16) * 8;
            ldsm4t(vv, va); ldsm4t(vv + 4, va + 256); ldsm4t(vv + 8, va + 512); ldsm2t(vv + 12, va + 768);
            const bool e0 = 2 * t > r, e1 = 2 * t >= r;
            const uint32_t mk = (e0 ? 0xffffu : 0u) | (e1 ? 0xffff0000u : 0u);
            wg_wait<0>();
            pin(a);
            if (has_g1) M.release(M.prev);
            TS0(2, 144 + wg);
            bar_sync(2, 288);
            mbar_wait(bars + B_HALO, 0);
            TS0(2, 12 + 16 * wg);
            float sv[2][4];
#pragma unroll
            for (int h = 0; h < 2; h++) {
                const int ga = h * 4, gb = h * 4 + 1, gc = h * 4 + 2, gd = h * 4 + 3;
                float s[3][4] = {};
                mma16(s[0], q[ga][0], q[ga][1], q[gb][0], q[gb][1], kp[ga], kp[gb]);
                mma16(s[1], q[ga][0], q[ga][1], q[gb][0], q[gb][1], k0[ga], k0[gb]);
                mma16(s[2], q[ga][0], q[ga][1], q[gb][0], q[gb][1], k1[ga], k1[gb]);
                mma16(s[0], q[gc][0], q[gc][1], q[gd][0], q[gd][1], kp[gc], kp[gd]);
                mma16(s[1], q[gc][0], q[gc][1], q[gd][0], q[gd][1], k0[gc], k0[3]);
                mma16(s[2], q[gc][0], q[gc][1], q[gd][0], q[gd][1], k1[gc], k1[3]);
                if ((tb | w) == 0) s[0][0] = s[0][1] = -1e30f;
                sv[h][0] = e0 ? s[0][0] : s[1][0];
                sv[h][1] = e1 ? s[0][1] : s[1][1];
                sv[h][2] = e0 ? s[1][2] : s[2][2];
                sv[h][3] = e1 ? s[1][3] : s[2][3];
            }
            uint32_t pp[2][2];
#pragma unroll
            for (int i = 0; i < 4; i++) {
                float* v = &sv[i >> 1][(i & 1) * 2];
                const float m = quad_max(fmaxf(v[0], v[1]));
                const float p0 = ex2(v[0] - m), p1 = ex2(v[1] - m);
                const float inv = rcp(quad_sum(p0 + p1));
                pp[i >> 1][i & 1] = pack2(p0 * inv, p1 * inv);
            }
            uint32_t o[8][2];
#pragma unroll
            for (int i = 0; i < 8; i++) {
                const int h = i >> 2, g = i - h;
                float d[4] = {};
                mma16(d, pp[h][0] & mk, 0u, 0u, pp[h][1] & ~mk, vv[2 * g], vv[2 * g + 1]);
                mma8(d, pp[h][0] & ~mk, pp[h][1] & mk, v0[g]);
                o[i][0] = pack2(d[0], d[1]); o[i][1] = pack2(d[2], d[3]);
            }
            if (t >= 2) { o[3][0] = o[4][0]; o[3][1] = o[4][1]; }
            const int word = wg * 4 + t - (w & 1) * 4 - (r >> 2);
#pragma unroll
            for (int i = 0; i < 8; i++) { o[i][0] = tag(o[i][0], word == 0, ep); o[i][1] = tag(o[i][1], word == 2, ep); }
            const uint32_t dst = sbase + OFF_X + (w >> 1) * HALF + ((w & 1) * 32 + (lane & 15) * 2 + wg) * 16 + (lane >> 4) * 1024;
            stsm4(dst, o[0][0], o[0][1], o[1][0], o[1][1]);
            stsm4(dst + 2048, o[2][0], o[2][1], o[3][0], o[3][1]);
            stsm4(dst + 4096, o[5][0], o[5][1], o[6][0], o[6][1]);
            stsm2(dst + 6144, o[7][0], o[7][1]);
            if (ENDBAR) bar_sync(4, 288); else bar_arrive(4, 288);
            TS0(2, 10 + 19 * wg);
        }
        if (has_g1) {
            M.run<true>(a, 16 - PAUSE, 1, 16, LAG1, 1, 32 + PAUSE);
            mbar_wait(bars + B_FREE, 0);
            const uint32_t xb = sbase + OFF_X + wg * 8192 + (threadIdx.x & 127) * 16, xbar = bars + B_X + 16 * wg;
            const uint32_t rx = mapa(xb, rank ^ 1), rbar = mapa(xbar, rank ^ 1);
            wg_wait<0>();
            pin(a);
            M.release(M.prev);
            TS0(4, 5 + wg);
#pragma unroll
            for (int i = 0; i < 3; i++)
                st_async4(rx + i * 2048, rbar + 8 * (i >> 1), pack2(a[28 + 8 * i], a[29 + 8 * i]), pack2(a[30 + 8 * i], a[31 + 8 * i]), pack2(a[32 + 8 * i], a[33 + 8 * i]), pack2(a[34 + 8 * i], a[35 + 8 * i]));
            const uint32_t tail = 6144 - (threadIdx.x & 127) * 8;
            st_async2(rx + tail, rbar + 8, pack2(a[52], a[53]), pack2(a[54], a[55]));
            uint8_t* dst = G->U[nt1][((ft >= 7) + wg) * 7 + ft] + rank * HALF + w * 256 + lane * 4;
            uint32_t u[14];
#pragma unroll
            for (int i = 0; i < 14; i++) {
                if (i % 8 == 0) {
                    mbar_wait(xbar + i, 0);
                    if (i == 0) TS0(4, 1 + wg);
#pragma unroll
                    for (int k = i / 4; k < i / 4 + 2; k++) {
                        if (k < 3) { const uint4 v = lds4(xb + k * 2048); u[4 * k] = v.x; u[4 * k + 1] = v.y; u[4 * k + 2] = v.z; u[4 * k + 3] = v.w; }
                        else { const uint2 v = lds2(xb + tail); u[12] = v.x; u[13] = v.y; }
                    }
                    if (i && lane < 2) mbar_arrive_remote(M.rel + B_EMPTY + 48);
                }
                if (i == HINT && threadIdx.x == 0) hint(G->flag[8 + nt1 * 2] + ft + (ft >= 7) * 25);
                const float bias = bf_lo((i & 1) ? bias1 : bias0);
                stg1(dst + (i >> 1) * 1024 + (i & 1) * 128, tag(pack2(gelu2(a[2 * i] + bias + bf_lo(u[i])), gelu2(a[2 * i + 1] + bias + bf_hi(u[i]))), (lane & 7) == w * 2 + (i & 1), ep));
            }
            TS0(4, 30 + wg);
        } else {
            mbar_wait(bars + B_FREE, 0);
            if (lane < 2) mbar_arrive_remote(M.rel + B_EMPTY + 48);
        }
        uint32_t c0 = ld_u16(b2 + mt * 128 + warp * 16 + r), c1 = ld_u16(b2 + mt * 128 + warp * 16 + r + 8);
        M.run_o(a);
        if (wg == 1) TS0(4, 13);
        c0 *= ks == 0 ? 0x10001u : 0u; c1 *= ks == 0 ? 0x10001u : 0u;
        M.run<false>(a, 14, 0, 14 - NSLOT, LAG2, 1, 52);
        mbar_wait(bars + B_ROW, 1);
        const uint32_t stg = sbase + ((has_g1 ? STG1 : STG0) + (w >> 1) * STGS) * SLOT + wg * 8192 + (w & 1) * SLAB;
        const uint32_t sa = stg + (lane & 15) * 224 + (lane >> 4) * 16;
        wg_wait<0>();
        pin(a);
        TS0(8, 14 + wg);
#pragma unroll
        for (int i = 0; i < 7; i++)
            stsm4(sa + i * 32, half_plus(pack2(a[8 * i], a[8 * i + 1]), c0), half_plus(pack2(a[8 * i + 2], a[8 * i + 3]), c1),
                  half_plus(pack2(a[8 * i + 4], a[8 * i + 5]), c0), half_plus(pack2(a[8 * i + 6], a[8 * i + 7]), c1));
        fence_async_shared();
        __syncwarp();
        if (elect()) {
            asm volatile("cp.reduce.async.bulk.tensor.2d.global.shared::cta.add.tile.bulk_group [%0, {%2, %3}], [%1];\ncp.async.bulk.commit_group;" ::"l"(&P.tmOut), "r"(stg), "r"(nt2 * 112), "r"(mt * 128 + warp * 16) : "memory");
            if (w == 0) mbar_arrive(bars + B_END);
            asm volatile("cp.async.bulk.wait_group.read 0;" ::: "memory");
        }
        if (wg == 1) TS0(15, 19);
        TSDUMP();
    }
}

typedef CUresult (*EncodeFn)(CUtensorMap*, CUtensorMapDataType, cuuint32_t, void*, const cuuint64_t*, const cuuint64_t*, const cuuint32_t*, const cuuint32_t*,
                             CUtensorMapInterleave, CUtensorMapSwizzle, CUtensorMapL2promotion, CUtensorMapFloatOOBfill);

void make_map(EncodeFn enc, CUtensorMap* tm, const void* base, bool swizzle, int d0, int d1, int d2, int s1, int s2, int b0, int b1, int b2) {
    const cuuint64_t dims[3] = {(cuuint64_t)d0, (cuuint64_t)d1, (cuuint64_t)d2}, strides[2] = {(cuuint64_t)s1 * 2, (cuuint64_t)s2 * 2};
    const cuuint32_t box[3] = {(cuuint32_t)b0, (cuuint32_t)b1, (cuuint32_t)b2}, es[3] = {1, 1, 1};
    enc(tm, CU_TENSOR_MAP_DATA_TYPE_BFLOAT16, d2 ? 3 : 2, (void*)base, dims, strides, box, es, CU_TENSOR_MAP_INTERLEAVE_NONE,
        swizzle ? CU_TENSOR_MAP_SWIZZLE_128B : CU_TENSOR_MAP_SWIZZLE_NONE, CU_TENSOR_MAP_L2_PROMOTION_L2_128B, CU_TENSOR_MAP_FLOAT_OOB_FILL_NONE);
}

}

extern "C" void kernel_launch(void* const* d_in, const int* in_sizes, int n_in, void* d_out, int out_size) {
    static EncodeFn enc = nullptr;
    static Scratch* scratch = nullptr;
    if (!enc) {
        void* fn = nullptr;
        cudaDriverEntryPointQueryResult qr;
        cudaGetDriverEntryPoint("cuTensorMapEncodeTiled", &fn, cudaEnableDefault, &qr);
        enc = (EncodeFn)fn;
        cudaGetSymbolAddress((void**)&scratch, g_s);
        cudaFuncSetAttribute(fused_kernel, cudaFuncAttributeMaxDynamicSharedMemorySize, SMEM_BYTES);
    }
    Params P;
    const __nv_bfloat16* x = (const __nv_bfloat16*)d_in[0];
    make_map(enc, &P.tmX, x, true, D_, S_ / 2, 2, 2 * D_, D_, 64, 64, 2);
    make_map(enc, &P.tmWqkv, d_in[1], true, D_, D_, 3, 3 * D_, D_, 64, 32, 3);
    make_map(enc, &P.tmW1, d_in[4], true, 64, S_, F_ / 64, F_, 64, 64, 64, 2);
    make_map(enc, &P.tmW2, d_in[6], true, S_, F_, 0, S_, 0, 64, 64, 1);
    make_map(enc, &P.tmOut, d_out, false, D_, S_, 0, D_, 0, 112, 16, 1);
    fused_kernel<<<NCTA, NTHREADS, SMEM_BYTES, cudaStreamPerThread>>>(x, (const __nv_bfloat16*)d_in[5], (const __nv_bfloat16*)d_in[7], (const __nv_bfloat16*)d_in[2], (__nv_bfloat16*)d_out, scratch,
                                                                      (const __nv_bfloat16*)d_in[4], (const __nv_bfloat16*)d_in[6], P);
}
```

```cpp
#include <cuda_runtime.h>
#include <cuda_bf16.h>
#include <cuda.h>
#include <stdint.h>

#define HALO_NS 300
#define HINT 4
#define HOLD 2
#define ROT 4
#define LATEREL 0
#define PF 400
#define PF0 2
#define PF1 8
#define ENDBAR 1
#define PG0 3
#define PG1 5
#define STG1 4
#define STG0 4
#define STGS 1
#define UGAP 120
#define UGAPN 6
#define PACE 600
#define PAUSE 8
#define LAG1 4
#define LAG2 6

namespace {

constexpr int S_ = 2048, D_ = 448, F_ = 1792;
constexpr int NCTA = 128, NTHREADS = 384;
constexpr int NSLOT = 6, SLOT = 32768, QSLOT = 40960, TILEB = 14336, SLAB = 3584, HALF = 7168;
constexpr int KV = 1792;
constexpr int OFF_X = NSLOT * SLOT;
constexpr int OFF_Y = OFF_X + 10 * KV;
constexpr int OFF_ST = OFF_Y + TILEB;
constexpr int OFF_BAR = OFF_ST + 1024;
constexpr int SMEM_BYTES = OFF_BAR + 1280;
constexpr uint32_t SMEM0 = 1024;
constexpr int B_QFULL = 0, B_FULL = 56, B_CS = 120, B_HALO = 128, B_X = 136, B_FREE = 192, B_END = 200, B_QEMPTY = 216, B_EMPTY = 232, B_ROW = 288, NBAR = 37;
constexpr float LN_EPS = 1e-5f;
constexpr int SPIN_LIMIT = 1 << 22;

struct Scratch {
    uint8_t H[4][32][TILEB];
    uint8_t U[4][28][TILEB];
    uint8_t O[16][8][TILEB];
    uint8_t Wo[4][8][TILEB];
    uint8_t halo[NCTA][2 * KV];
    uint2 stat[S_];
    uint2 colsum[8][8][96];
    uint32_t flag[32][32];
    uint32_t epoch[NCTA];
};
__device__ __align__(1024) Scratch g_s;

#define TS(g, i)
#define TS0(g, i)
#define TSDUMP()

struct Params {
    CUtensorMap tmX, tmWqkv, tmW1, tmW2, tmOut;
};

__device__ __forceinline__ bool elect() {
    uint32_t p;
    asm volatile("{\n.reg .pred p;\nelect.sync _|p, 0xffffffff;\nselp.u32 %0, 1, 0, p;\n}" : "=r"(p));
    return p;
}
__device__ __forceinline__ void mbar_init(uint32_t b, uint32_t c) { asm volatile("mbarrier.init.shared::cta.b64 [%0], %1;" ::"r"(b), "r"(c) : "memory"); }
__device__ __forceinline__ void mbar_expect(uint32_t b, uint32_t tx) { asm volatile("mbarrier.arrive.expect_tx.shared::cta.b64 _, [%0], %1;" ::"r"(b), "r"(tx) : "memory"); }
__device__ __forceinline__ void mbar_arrive(uint32_t b) { asm volatile("mbarrier.arrive.shared::cta.b64 _, [%0];" ::"r"(b) : "memory"); }
__device__ __forceinline__ void mbar_arrive16(uint32_t b) { asm volatile("mbarrier.arrive.shared::cta.b64 _, [%0], 16;" ::"r"(b) : "memory"); }
__device__ __forceinline__ void mbar_arrive4_remote(uint32_t b) { asm volatile("mbarrier.arrive.shared::cluster.b64 _, [%0], 4;" ::"r"(b) : "memory"); }
__device__ __forceinline__ void mbar_arrive_remote(uint32_t b) { asm volatile("mbarrier.arrive.shared::cluster.b64 _, [%0];" ::"r"(b) : "memory"); }
#define MBAR_WAIT_ASM(SEM) \
    asm volatile("{\n.reg .pred p;\nWAIT:\nmbarrier.try_wait.parity" SEM ".shared::cta.b64 p, [%0], %1;\n@!p bra WAIT;\n}" ::"r"(b), "r"(parity) : "memory")
__device__ __forceinline__ void mbar_wait(uint32_t b, uint32_t parity) { MBAR_WAIT_ASM(""); }
__device__ __forceinline__ void mbar_wait_bounded(uint32_t b, uint32_t parity, uint32_t& n) {
    asm volatile("{\n.reg .pred p;\nWAIT:\nadd.u32 %0, %0, 1;\nsetp.gt.u32 p, %0, %3;\n@p st.global.u32 [%4], %0;\n"
                 "mbarrier.try_wait.parity.shared::cta.b64 p, [%1], %2;\n@!p bra WAIT;\n}" : "+r"(n) : "r"(b), "r"(parity), "n"(SPIN_LIMIT), "l"(0ull) : "memory");
}
__device__ __forceinline__ uint32_t mapa(uint32_t a, uint32_t rank) { uint32_t r; asm("mapa.shared::cluster.u32 %0, %1, %2;" : "=r"(r) : "r"(a), "r"(rank)); return r; }
__device__ __forceinline__ void tma3d(uint32_t dst, const CUtensorMap* tm, uint32_t bar, int c0, int c1, int c2) {
    asm volatile("cp.async.bulk.tensor.3d.shared::cluster.global.mbarrier::complete_tx::bytes [%0], [%1, {%3, %4, %5}], [%2];" ::"r"(dst), "l"(tm), "r"(bar), "r"(c0), "r"(c1), "r"(c2) : "memory");
}
__device__ __forceinline__ void tma2d_pair(uint32_t dst, const CUtensorMap* tm, uint32_t bar, int c0, int c1) {
    asm volatile("cp.async.bulk.tensor.2d.shared::cluster.global.mbarrier::complete_tx::bytes.multicast::cluster [%0], [%1, {%3, %4}], [%2], %5;" ::"r"(dst), "l"(tm), "r"(bar), "r"(c0), "r"(c1), "h"((uint16_t)3) : "memory");
}
__device__ __forceinline__ void tma3d_pair(uint32_t dst, const CUtensorMap* tm, uint32_t bar, int c0, int c1, int c2) {
    asm volatile("cp.async.bulk.tensor.3d.shared::cluster.global.mbarrier::complete_tx::bytes.multicast::cluster [%0], [%1, {%3, %4, %5}], [%2], %6;" ::"r"(dst), "l"(tm), "r"(bar), "r"(c0), "r"(c1), "r"(c2), "h"((uint16_t)3) : "memory");
}
__device__ __forceinline__ void bulk_load(uint32_t dst, const void* src, uint32_t bytes, uint32_t bar) {
    asm volatile("cp.async.bulk.shared::cluster.global.mbarrier::complete_tx::bytes [%0], [%1], %2, [%3];" ::"r"(dst), "l"(src), "r"(bytes), "r"(bar) : "memory");
}
__device__ __forceinline__ void bulk_load_pair(uint32_t dst, const void* src, uint32_t bytes, uint32_t bar) {
    asm volatile("cp.async.bulk.shared::cluster.global.mbarrier::complete_tx::bytes.multicast::cluster [%0], [%1], %2, [%3], %4;" ::"r"(dst), "l"(src), "r"(bytes), "r"(bar), "h"((uint16_t)3) : "memory");
}
__device__ __forceinline__ void bulk_store(void* dst, uint32_t src, uint32_t bytes) {
    asm volatile("cp.async.bulk.global.shared::cta.bulk_group [%0], [%1], %2;" ::"l"(dst), "r"(src), "r"(bytes) : "memory");
}
__device__ __forceinline__ uint32_t ld_u16(const void* p) { uint32_t v; asm volatile("ld.global.nc.u16 %0, [%1];" : "=r"(v) : "l"(p)); return v; }
__device__ __forceinline__ uint32_t ld_relaxed(const uint32_t* p) { uint32_t v; asm volatile("ld.relaxed.gpu.global.u32 %0, [%1];" : "=r"(v) : "l"(p) : "memory"); return v; }
__device__ __forceinline__ void bulk_flush() { asm volatile("cp.async.bulk.commit_group;\ncp.async.bulk.wait_group 0;" ::: "memory"); }
__device__ __forceinline__ void signal(uint32_t* flag) { asm volatile("fence.acq_rel.gpu;\nred.relaxed.gpu.global.add.u32 [%0], 1;" ::"l"(flag) : "memory"); }
__device__ __forceinline__ void hint(uint32_t* flag) { asm volatile("red.relaxed.gpu.global.add.u32 [%0], 1;" ::"l"(flag) : "memory"); }
__device__ __forceinline__ uint32_t tag(uint32_t v, uint32_t mask, uint32_t parity) { return (v & ~mask) | (parity & mask); }
__device__ __forceinline__ uint32_t or_diff(uint32_t acc, uint32_t v, uint32_t parity) { asm("lop3.b32 %0, %0, %1, %2, 0xf6;" : "+r"(acc) : "r"(v), "r"(parity)); return acc; }
__device__ __forceinline__ uint4 ld_relaxed4(const void* p) {
    uint4 v;
    asm volatile("ld.relaxed.gpu.global.v4.u32 {%0, %1, %2, %3}, [%4];" : "=r"(v.x), "=r"(v.y), "=r"(v.z), "=r"(v.w) : "l"(p) : "memory");
    return v;
}
__device__ __forceinline__ uint2 ld_relaxed2(const void* p) { uint2 v; asm volatile("ld.relaxed.gpu.global.v2.u32 {%0, %1}, [%2];" : "=r"(v.x), "=r"(v.y) : "l"(p) : "memory"); return v; }
__device__ __forceinline__ void sts4(uint32_t a, uint4 v) { asm volatile("st.shared.v4.b32 [%0], {%1, %2, %3, %4};" ::"r"(a), "r"(v.x), "r"(v.y), "r"(v.z), "r"(v.w) : "memory"); }
__device__ __forceinline__ void stg1(void* p, uint32_t v) { asm volatile("st.global.b32 [%0], %1;" ::"l"(p), "r"(v) : "memory"); }
__device__ __forceinline__ void fence_async_shared() { asm volatile("fence.proxy.async.shared::cta;" ::: "memory"); }
#define BOUND "add.u32 %0, %0, 16;\nsetp.gt.u32 p, %0, %1;\n@p st.global.u32 [%2], %0;\n"
__device__ __forceinline__ void wait_flag(const uint32_t* p, uint32_t target, uint32_t& n) {
    asm volatile("{\n.reg .pred p;\n.reg .u32 v;\nPOLL:\n" BOUND "ld.acquire.gpu.global.u32 v, [%3];\nsetp.ne.u32 p, v, %4;\n@p bra POLL;\nfence.proxy.async.global;\n}"
                 : "+r"(n) : "n"(SPIN_LIMIT), "l"(0ull), "l"(p), "r"(target) : "memory");
}
__device__ __forceinline__ void wait_flag2(const uint32_t* h, uint32_t th, const uint32_t* p, uint32_t target, uint32_t& n) {
    asm volatile("{\n.reg .pred p;\n.reg .u32 u, v;\nPOLL:\n" BOUND "ld.relaxed.gpu.global.u32 u, [%3];\nld.acquire.gpu.global.u32 v, [%5];\nsetp.ne.u32 p, u, %4;\nsetp.ne.or.u32 p, v, %6, p;\n@p bra POLL;\nfence.proxy.async.global;\n}"
                 : "+r"(n) : "n"(SPIN_LIMIT), "l"(0ull), "l"(h), "r"(th), "l"(p), "r"(target) : "memory");
}
__device__ __forceinline__ void bar_sync(int id, int n) { asm volatile("bar.sync %0, %1;" ::"r"(id), "r"(n) : "memory"); }
__device__ __forceinline__ void bar_arrive(int id, int n) { asm volatile("bar.arrive %0, %1;" ::"r"(id), "r"(n) : "memory"); }
__device__ __forceinline__ void wg_fence() { asm volatile("wgmma.fence.sync.aligned;" ::: "memory"); }
__device__ __forceinline__ void wg_commit() { asm volatile("wgmma.commit_group.sync.aligned;" ::: "memory"); }
template <int N> __device__ __forceinline__ void wg_wait() { asm volatile("wgmma.wait_group.sync.aligned %0;" ::"n"(N) : "memory"); }
template <int N> __device__ __forceinline__ void pin(float (&d)[N]) {
#pragma unroll
    for (int i = 0; i < N; i++) asm volatile("" : "+f"(d[i])::"memory");
}
__host__ __device__ constexpr uint32_t desc_hi(uint32_t sbo, uint32_t swz) { return (sbo >> 4) | (swz << 30); }
__host__ __device__ constexpr uint32_t desc_lo(uint32_t off, uint32_t lbo) { return ((SMEM0 + off) >> 4) | ((lbo >> 4) << 16); }
__device__ __forceinline__ uint32_t pack2(float lo, float hi) { uint32_t r; asm("cvt.rn.bf16x2.f32 %0, %1, %2;" : "=r"(r) : "f"(hi), "f"(lo)); return r; }
__device__ __forceinline__ float bf_lo(uint32_t v) { return __uint_as_float(v << 16); }
__device__ __forceinline__ float bf_hi(uint32_t v) { return __uint_as_float(v & 0xffff0000u); }
__device__ __forceinline__ uint32_t half_plus(uint32_t a, uint32_t b) { uint32_t r; asm("fma.rn.bf16x2 %0, %1, %2, %3;" : "=r"(r) : "r"(a), "r"(0x3f003f00u), "r"(b)); return r; }
__device__ __forceinline__ void stsm4(uint32_t a, uint32_t r0, uint32_t r1, uint32_t r2, uint32_t r3) {
    asm volatile("stmatrix.sync.aligned.m8n8.x4.shared.b16 [%0], {%1, %2, %3, %4};" ::"r"(a), "r"(r0), "r"(r1), "r"(r2), "r"(r3) : "memory");
}
__device__ __forceinline__ void stsm2(uint32_t a, uint32_t r0, uint32_t r1) {
    asm volatile("stmatrix.sync.aligned.m8n8.x2.shared.b16 [%0], {%1, %2};" ::"r"(a), "r"(r0), "r"(r1) : "memory");
}
__device__ __forceinline__ uint4 lds4(uint32_t a) { uint4 v; asm volatile("ld.shared.v4.b32 {%0, %1, %2, %3}, [%4];" : "=r"(v.x), "=r"(v.y), "=r"(v.z), "=r"(v.w) : "r"(a) : "memory"); return v; }
__device__ __forceinline__ uint2 lds2(uint32_t a) { uint2 v; asm volatile("ld.shared.v2.b32 {%0, %1}, [%2];" : "=r"(v.x), "=r"(v.y) : "r"(a) : "memory"); return v; }
__device__ __forceinline__ float lds1f(uint32_t a) { float v; asm volatile("ld.shared.f32 %0, [%1];" : "=f"(v) : "r"(a) : "memory"); return v; }
__device__ __forceinline__ void ldsm4(uint32_t* r, uint32_t a) {
    asm volatile("ldmatrix.sync.aligned.m8n8.x4.shared.b16 {%0, %1, %2, %3}, [%4];" : "=r"(r[0]), "=r"(r[1]), "=r"(r[2]), "=r"(r[3]) : "r"(a) : "memory");
}
__device__ __forceinline__ void ldsm4t(uint32_t* r, uint32_t a) {
    asm volatile("ldmatrix.sync.aligned.m8n8.x4.trans.shared.b16 {%0, %1, %2, %3}, [%4];" : "=r"(r[0]), "=r"(r[1]), "=r"(r[2]), "=r"(r[3]) : "r"(a) : "memory");
}
__device__ __forceinline__ void ldsm2t(uint32_t* r, uint32_t a) {
    asm volatile("ldmatrix.sync.aligned.m8n8.x2.trans.shared.b16 {%0, %1}, [%2];" : "=r"(r[0]), "=r"(r[1]) : "r"(a) : "memory");
}
__device__ __forceinline__ uint32_t transpose8(uint32_t v) { uint32_t r; asm volatile("movmatrix.sync.aligned.m8n8.trans.b16 %0, %1;" : "=r"(r) : "r"(v)); return r; }
__device__ __forceinline__ void mma16(float (&c)[4], uint32_t a0, uint32_t a1, uint32_t a2, uint32_t a3, uint32_t b0, uint32_t b1) {
    asm volatile("mma.sync.aligned.m16n8k16.row.col.f32.bf16.bf16.f32 {%0, %1, %2, %3}, {%4, %5, %6, %7}, {%8, %9}, {%0, %1, %2, %3};"
                 : "+f"(c[0]), "+f"(c[1]), "+f"(c[2]), "+f"(c[3]) : "r"(a0), "r"(a1), "r"(a2), "r"(a3), "r"(b0), "r"(b1));
}
__device__ __forceinline__ void mma8(float (&c)[4], uint32_t a0, uint32_t a1, uint32_t b0) {
    asm volatile("mma.sync.aligned.m16n8k8.row.col.f32.bf16.bf16.f32 {%0, %1, %2, %3}, {%4, %5}, {%6}, {%0, %1, %2, %3};"
                 : "+f"(c[0]), "+f"(c[1]), "+f"(c[2]), "+f"(c[3]) : "r"(a0), "r"(a1), "r"(b0));
}
__device__ __forceinline__ void st_async4(uint32_t a, uint32_t bar, uint32_t v0, uint32_t v1, uint32_t v2, uint32_t v3) {
    asm volatile("st.async.weak.shared::cluster.mbarrier::complete_tx::bytes.v4.b32 [%0], {%2, %3, %4, %5}, [%1];" ::"r"(a), "r"(bar), "r"(v0), "r"(v1), "r"(v2), "r"(v3) : "memory");
}
__device__ __forceinline__ void st_async2(uint32_t a, uint32_t bar, uint32_t v0, uint32_t v1) {
    asm volatile("st.async.weak.shared::cluster.mbarrier::complete_tx::bytes.v2.b32 [%0], {%2, %3}, [%1];" ::"r"(a), "r"(bar), "r"(v0), "r"(v1) : "memory");
}
__device__ __forceinline__ float quad_max(float v) { v = fmaxf(v, __shfl_xor_sync(~0u, v, 1)); return fmaxf(v, __shfl_xor_sync(~0u, v, 2)); }
__device__ __forceinline__ float quad_sum(float v) { v += __shfl_xor_sync(~0u, v, 1); return v + __shfl_xor_sync(~0u, v, 2); }
__device__ __forceinline__ float ex2(float v) { float r; asm("ex2.approx.ftz.f32 %0, %1;" : "=f"(r) : "f"(v)); return r; }
__device__ __forceinline__ float rcp(float v) { float r; asm("rcp.approx.ftz.f32 %0, %1;" : "=f"(r) : "f"(v)); return r; }
__device__ __forceinline__ float rsq(float v) { float r; asm("rsqrt.approx.ftz.f32 %0, %1;" : "=f"(r) : "f"(v)); return r; }
__device__ __forceinline__ float gelu2(float u) {
    float z = u * fmaf(u * u, 0.044715f * 0.7978845608028654f, 0.7978845608028654f), t;
    asm("tanh.approx.f32 %0, %1;" : "=f"(t) : "f"(z));
    return fmaf(u, t, u);
}
__device__ __forceinline__ float oct_sum(float v) {
    v += __shfl_xor_sync(~0u, v, 4); v += __shfl_xor_sync(~0u, v, 8); v += __shfl_xor_sync(~0u, v, 16);
    return v;
}

template <int TA, int TB, uint32_t HA, uint32_t HB>
__device__ __forceinline__ void wgmma_n112(float (&d)[56], uint32_t da, uint32_t db, int accumulate) {
    asm volatile("{\n.reg .pred p;\n.reg .b64 a, b;\nmov.b64 a, {%56, %61};\nmov.b64 b, {%57, %62};\nsetp.ne.b32 p, %58, 0;\n"
        "wgmma.mma_async.sync.aligned.m64n112k16.f32.bf16.bf16 {"
        "%0, %1, %2, %3, %4, %5, %6, %7, %8, %9, %10, %11, %12, %13, %14, %15, "
        "%16, %17, %18, %19, %20, %21, %22, %23, %24, %25, %26, %27, %28, %29, %30, %31, "
        "%32, %33, %34, %35, %36, %37, %38, %39, %40, %41, %42, %43, %44, %45, %46, %47, "
        "%48, %49, %50, %51, %52, %53, %54, %55"
        "}, a, b, p, 1, 1, %59, %60;\n}\n"
        : "+f"(d[0]), "+f"(d[1]), "+f"(d[2]), "+f"(d[3]), "+f"(d[4]), "+f"(d[5]), "+f"(d[6]), "+f"(d[7]),
          "+f"(d[8]), "+f"(d[9]), "+f"(d[10]), "+f"(d[11]), "+f"(d[12]), "+f"(d[13]), "+f"(d[14]), "+f"(d[15]),
          "+f"(d[16]), "+f"(d[17]), "+f"(d[18]), "+f"(d[19]), "+f"(d[20]), "+f"(d[21]), "+f"(d[22]), "+f"(d[23]),
          "+f"(d[24]), "+f"(d[25]), "+f"(d[26]), "+f"(d[27]), "+f"(d[28]), "+f"(d[29]), "+f"(d[30]), "+f"(d[31]),
          "+f"(d[32]), "+f"(d[33]), "+f"(d[34]), "+f"(d[35]), "+f"(d[36]), "+f"(d[37]), "+f"(d[38]), "+f"(d[39]),
          "+f"(d[40]), "+f"(d[41]), "+f"(d[42]), "+f"(d[43]), "+f"(d[44]), "+f"(d[45]), "+f"(d[46]), "+f"(d[47]),
          "+f"(d[48]), "+f"(d[49]), "+f"(d[50]), "+f"(d[51]), "+f"(d[52]), "+f"(d[53]), "+f"(d[54]), "+f"(d[55])
        : "r"(da), "r"(db), "r"(accumulate), "n"(TA), "n"(TB), "n"(HA), "n"(HB));
}

template <int TA, int TB, uint32_t HA, uint32_t HB>
__device__ __forceinline__ void wgmma_n184(float (&d)[92], uint32_t da, uint32_t db, int accumulate) {
    asm volatile("{\n.reg .pred p;\n.reg .b64 a, b;\nmov.b64 a, {%92, %97};\nmov.b64 b, {%93, %98};\nsetp.ne.b32 p, %94, 0;\n"
        "wgmma.mma_async.sync.aligned.m64n184k16.f32.bf16.bf16 {"
        "%0, %1, %2, %3, %4, %5, %6, %7, %8, %9, %10, %11, %12, %13, %14, %15, "
        "%16, %17, %18, %19, %20, %21, %22, %23, %24, %25, %26, %27, %28, %29, %30, %31, "
        "%32, %33, %34, %35, %36, %37, %38, %39, %40, %41, %42, %43, %44, %45, %46, %47, "
        "%48, %49, %50, %51, %52, %53, %54, %55, %56, %57, %58, %59, %60, %61, %62, %63, "
        "%64, %65, %66, %67, %68, %69, %70, %71, %72, %73, %74, %75, %76, %77, %78, %79, "
        "%80, %81, %82, %83, %84, %85, %86, %87, %88, %89, %90, %91"
        "}, a, b, p, 1, 1, %95, %96;\n}\n"
        : "+f"(d[0]), "+f"(d[1]), "+f"(d[2]), "+f"(d[3]), "+f"(d[4]), "+f"(d[5]), "+f"(d[6]), "+f"(d[7]),
          "+f"(d[8]), "+f"(d[9]), "+f"(d[10]), "+f"(d[11]), "+f"(d[12]), "+f"(d[13]), "+f"(d[14]), "+f"(d[15]),
          "+f"(d[16]), "+f"(d[17]), "+f"(d[18]), "+f"(d[19]), "+f"(d[20]), "+f"(d[21]), "+f"(d[22]), "+f"(d[23]),
          "+f"(d[24]), "+f"(d[25]), "+f"(d[26]), "+f"(d[27]), "+f"(d[28]), "+f"(d[29]), "+f"(d[30]), "+f"(d[31]),
          "+f"(d[32]), "+f"(d[33]), "+f"(d[34]), "+f"(d[35]), "+f"(d[36]), "+f"(d[37]), "+f"(d[38]), "+f"(d[39]),
          "+f"(d[40]), "+f"(d[41]), "+f"(d[42]), "+f"(d[43]), "+f"(d[44]), "+f"(d[45]), "+f"(d[46]), "+f"(d[47]),
          "+f"(d[48]), "+f"(d[49]), "+f"(d[50]), "+f"(d[51]), "+f"(d[52]), "+f"(d[53]), "+f"(d[54]), "+f"(d[55]),
          "+f"(d[56]), "+f"(d[57]), "+f"(d[58]), "+f"(d[59]), "+f"(d[60]), "+f"(d[61]), "+f"(d[62]), "+f"(d[63]),
          "+f"(d[64]), "+f"(d[65]), "+f"(d[66]), "+f"(d[67]), "+f"(d[68]), "+f"(d[69]), "+f"(d[70]), "+f"(d[71]),
          "+f"(d[72]), "+f"(d[73]), "+f"(d[74]), "+f"(d[75]), "+f"(d[76]), "+f"(d[77]), "+f"(d[78]), "+f"(d[79]),
          "+f"(d[80]), "+f"(d[81]), "+f"(d[82]), "+f"(d[83]), "+f"(d[84]), "+f"(d[85]), "+f"(d[86]), "+f"(d[87]),
          "+f"(d[88]), "+f"(d[89]), "+f"(d[90]), "+f"(d[91])
        : "r"(da), "r"(db), "r"(accumulate), "n"(TA), "n"(TB), "n"(HA), "n"(HB));
}

template <uint32_t HB>
__device__ __forceinline__ void wgmma_rs_n184(float (&d)[92], uint32_t a0, uint32_t a1, uint32_t db) {
    asm volatile("{\n.reg .b64 b;\nmov.b64 b, {%94, %96};\n"
        "wgmma.mma_async.sync.aligned.m64n184k16.f32.bf16.bf16 {"
        "%0, %1, %2, %3, %4, %5, %6, %7, %8, %9, %10, %11, %12, %13, %14, %15, "
        "%16, %17, %18, %19, %20, %21, %22, %23, %24, %25, %26, %27, %28, %29, %30, %31, "
        "%32, %33, %34, %35, %36, %37, %38, %39, %40, %41, %42, %43, %44, %45, %46, %47, "
        "%48, %49, %50, %51, %52, %53, %54, %55, %56, %57, %58, %59, %60, %61, %62, %63, "
        "%64, %65, %66, %67, %68, %69, %70, %71, %72, %73, %74, %75, %76, %77, %78, %79, "
        "%80, %81, %82, %83, %84, %85, %86, %87, %88, %89, %90, %91"
        "}, {%92, %93, %95, %95}, b, 1, 1, 1, 0;\n}\n"
        : "+f"(d[0]), "+f"(d[1]), "+f"(d[2]), "+f"(d[3]), "+f"(d[4]), "+f"(d[5]), "+f"(d[6]), "+f"(d[7]),
          "+f"(d[8]), "+f"(d[9]), "+f"(d[10]), "+f"(d[11]), "+f"(d[12]), "+f"(d[13]), "+f"(d[14]), "+f"(d[15]),
          "+f"(d[16]), "+f"(d[17]), "+f"(d[18]), "+f"(d[19]), "+f"(d[20]), "+f"(d[21]), "+f"(d[22]), "+f"(d[23]),
          "+f"(d[24]), "+f"(d[25]), "+f"(d[26]), "+f"(d[27]), "+f"(d[28]), "+f"(d[29]), "+f"(d[30]), "+f"(d[31]),
          "+f"(d[32]), "+f"(d[33]), "+f"(d[34]), "+f"(d[35]), "+f"(d[36]), "+f"(d[37]), "+f"(d[38]), "+f"(d[39]),
          "+f"(d[40]), "+f"(d[41]), "+f"(d[42]), "+f"(d[43]), "+f"(d[44]), "+f"(d[45]), "+f"(d[46]), "+f"(d[47]),
          "+f"(d[48]), "+f"(d[49]), "+f"(d[50]), "+f"(d[51]), "+f"(d[52]), "+f"(d[53]), "+f"(d[54]), "+f"(d[55]),
          "+f"(d[56]), "+f"(d[57]), "+f"(d[58]), "+f"(d[59]), "+f"(d[60]), "+f"(d[61]), "+f"(d[62]), "+f"(d[63]),
          "+f"(d[64]), "+f"(d[65]), "+f"(d[66]), "+f"(d[67]), "+f"(d[68]), "+f"(d[69]), "+f"(d[70]), "+f"(d[71]),
          "+f"(d[72]), "+f"(d[73]), "+f"(d[74]), "+f"(d[75]), "+f"(d[76]), "+f"(d[77]), "+f"(d[78]), "+f"(d[79]),
          "+f"(d[80]), "+f"(d[81]), "+f"(d[82]), "+f"(d[83]), "+f"(d[84]), "+f"(d[85]), "+f"(d[86]), "+f"(d[87]),
          "+f"(d[88]), "+f"(d[89]), "+f"(d[90]), "+f"(d[91])
        : "r"(a0), "r"(a1), "r"(db), "r"(0), "n"(HB));
}

struct Ring {
    uint32_t slot, ph;
    __device__ __forceinline__ void next() { if (++slot == NSLOT) { slot = 0; ph ^= 1; } }
    __device__ __forceinline__ void next2() { ph ^= slot == 5; slot = __byte_perm(0x06030201u, 0x00040005u, 0x7770 + slot); }
};
struct Slot {
    uint32_t dst, bar, ph;
    __device__ __forceinline__ void next(uint32_t bars) {
        dst += SLOT; bar += 8;
        if (bar == bars + 8 * NSLOT) { dst -= NSLOT * SLOT; bar = bars; ph ^= 1; }
    }
};
__device__ __forceinline__ uint32_t xslot(int i) { return __byte_perm(0x04130e0cu, 0x00130e0cu, 0x7770 + i); }
__device__ __forceinline__ uint32_t wslot(int i) { return __byte_perm(0x06001510u, 0x00151009u, 0x7770 + i); }

constexpr uint32_t HI_SW = desc_hi(1024, 1);

struct Mma {
    uint32_t bars, rel;
    bool lead;
    int wg, w;
    Ring r;
    uint32_t prev;
    __device__ __forceinline__ void release(uint32_t s) { if (lead) mbar_arrive4_remote(rel + B_EMPTY + 8 * s); }
    template <bool G1>
    __device__ __forceinline__ void run(float (&a)[56], int n, int first, int last, int lag, int accumulate, int ts) {
#pragma unroll 1
        for (int i = 0; i < n; i++) {
            if (lag && i == (wg ? n - lag : -1)) bar_sync(7, 256);
            const uint32_t s = r.slot;
            mbar_wait(bars + B_FULL + 8 * s, r.ph);
            if (G1) r.next(); else r.next2();
            TS0(G1 ? 2 : 8, ts + i + wg * 68);
            const uint32_t dB = s * (SLOT >> 4), dA = dB + wg * 512;
            wg_fence();
#pragma unroll
            for (int k = 0; k < 4; k++) {
                wgmma_n112<1, 1, HI_SW, desc_hi(G1 ? 256 : 1024, 0)>(a, dA + desc_lo(k * 2048, 8192), dB + desc_lo(16384 + k * (G1 ? SLAB : 256), 128), k > 0 || accumulate || i > 0);
                if (k == 1) {
                    wg_commit(); wg_wait<1>();
                    if ((uint32_t)(i - first) < (uint32_t)(last - first)) release(prev);
                    if (lag && i == (wg ? -1 : n - 1)) bar_arrive(7, 256);
                }
            }
            wg_commit();
            prev = s;
        }
    }
    __device__ __forceinline__ void run_o(float (&a)[56]) {
#pragma unroll 1
        for (int i = 0; i < 2; i++) {
            const uint32_t s = r.slot, dB = s * (SLOT >> 4), dA = dB + wg * 512;
            mbar_wait(bars + B_FULL + 8 * s, r.ph);
            TS0(8, 48 + 2 * i + wg * 68);
            wg_fence();
#pragma unroll
            for (int k = 0; k < 7; k++) {
                if (k == 3) { mbar_wait(bars + B_FULL + 8 * s + 8, r.ph); wg_fence(); }
                wgmma_n112<0, 1, desc_hi(128, 0), desc_hi(256, 0)>(a, dA + desc_lo(k * 2048 + (k > 3) * (SLOT - HALF), k == 3 ? SLOT - 6144 : 1024),
                                                                   dB + desc_lo(16384 + k * SLAB + (k > 2) * (SLOT - 3 * SLAB), 128), k > 0 || i > 0);
                if (k & 1) wg_commit();
                if (k == 1) { wg_wait<1>(); if (i) release(prev); }
                if (k == 5) { wg_wait<1>(); release(s); }
            }
            wg_commit();
            prev = s + 1;
            r.slot++; r.next2();
        }
    }
};

__global__ void __cluster_dims__(2, 1, 1) __launch_bounds__(NTHREADS, 1)
fused_kernel(const __nv_bfloat16* __restrict__ x, const __nv_bfloat16* __restrict__ b1, const __nv_bfloat16* __restrict__ b2, const __nv_bfloat16* __restrict__ wo, __nv_bfloat16* out, Scratch* G,
             const __nv_bfloat16* __restrict__ w1, const __nv_bfloat16* __restrict__ w2,
             const __grid_constant__ Params P) {
    extern __shared__ __align__(1024) uint8_t smem[];
    const uint32_t sbase = (uint32_t)__cvta_generic_to_shared(smem);
    const uint32_t bars = sbase + OFF_BAR;
    const uint32_t rank = blockIdx.x & 1, pr = blockIdx.x >> 1;
    const uint32_t row0 = blockIdx.x * 16;
    if (threadIdx.x == 0) {
        TS(15, 0);
        mbar_init(bars + B_ROW, 1);
        asm volatile("fence.mbarrier_init.release.cluster;" ::: "memory");
        bulk_load(sbase + OFF_Y, x + row0 * D_, TILEB, bars + B_ROW);
        mbar_expect(bars + B_ROW, TILEB);
        TS(1, 97);
    }
    const int lane = threadIdx.x & 31;
    const int warp = __shfl_sync(~0u, threadIdx.x >> 5, 0), w = warp & 3;
    if (elect()) {
        const uint32_t first = bars + warp * 24, count = warp < 8 ? 1 : warp == 8 ? 2 : 16;
#pragma unroll
        for (int i = 0; i < 3; i++) mbar_init(first + 8 * i, count);
        asm volatile("fence.mbarrier_init.release.cluster;" ::: "memory");
    }
    __syncwarp();
    asm volatile("barrier.cluster.arrive.relaxed.aligned;" ::: "memory");
    const uint32_t pv = pr < 4 ? pr * 8 + 36 : pr - 4 + (max((int)pr - 33, 0) * 37 >> 8);
    const uint32_t gp = (pv + 4) & 7, hp = pv >> 3;
    const uint32_t tb = gp * 2 + rank, c = hp * 16 + tb;
    const bool has_g1 = gp > 0;
    const uint32_t nt1 = hp & 3, ft = max((int)gp - 1, 0) * 2 + (hp >> 2);
    const uint32_t nt2 = tb & 3, mt = (gp & 2) * 4 + hp, ks = gp >> 2;
    asm volatile("barrier.cluster.wait.aligned;" ::: "memory");

    if (warp == 8) {
        uint32_t kw = gp % ROT * (512 / ROT), kx;
        if (elect()) {
            mbar_expect(bars + B_QFULL, QSLOT);
            tma3d(sbase + xslot(0) * 8192, &P.tmX, bars + B_QFULL, kw, tb * 64, 0);
            tma3d_pair(sbase + wslot(0) * 8192 + rank * 12288, &P.tmWqkv, bars + B_QFULL, (hp * 56) & ~15, kw + rank * 32, 0);
            TS(1, 23);
            uint32_t due = (uint32_t)clock() + PACE, ep = ld_relaxed(&G->epoch[c]);
            uint32_t spins = sbase == (rank << 24 | SMEM0) ? 0 : SPIN_LIMIT;
#pragma unroll 1
            for (int i = 1; i < 8; i++) {
                kx = kw; kw += 64;
                if (i >= 5) mbar_wait_bounded(bars + B_QEMPTY + 8 * (i - 5), 0, spins);
                else { while ((int)((uint32_t)clock() - due) < 0) {} due += PACE; }
                if (kw == D_) kw = 0;
                if (i < 4) kx = kw;
                const int ix = i - (i > 4);
                if (i < 7) mbar_expect(bars + B_QFULL + 8 * i, QSLOT);
                if (i != 4) tma3d(sbase + xslot(ix) * 8192, &P.tmX, bars + B_QFULL + 8 * ix, kx, tb * 64, 0);
                if (i == 5) mbar_wait_bounded(bars + B_CS, 0, spins);
                if (i < 7) tma3d_pair(sbase + wslot(i) * 8192 + rank * 12288, &P.tmWqkv, bars + B_QFULL + 8 * i, (hp * 56) & ~15, kw + rank * 32, 0);
            }
            ep++;
            Slot r{sbase, bars, 0};
            if (has_g1) {
                const uint8_t* src = G->H[nt1][rank * 16];
                const int row = rank * 1024;
                mbar_arrive(bars + B_FULL + 48); mbar_arrive16(bars + B_EMPTY + 48);
                mbar_expect(bars + B_FULL, 16384 + TILEB);
                tma3d(sbase, &P.tmW1, bars + B_FULL, 0, row, ft * 2);
                wait_flag(G->flag[1] + rank * 2, 20 * ep, spins);
                TS(1, 16);
#pragma unroll 1
                for (int j = 64;; j += 64) {
                    bulk_load(r.dst + 16384, src, TILEB, r.bar + B_FULL);
                    src += TILEB;
                    r.next(bars);
                    if (j == 1024) break;
                    mbar_wait_bounded(r.bar + B_EMPTY, r.ph, spins);
                    if (j < 14 * 64) TS(2, 146 + j / 64);
                    mbar_expect(r.bar + B_FULL, 16384 + TILEB);
                    tma3d(r.dst, &P.tmW1, r.bar + B_FULL, 0, row + j, ft * 2);
                }
#pragma unroll
                for (int i = 0; i < 4; i++) mbar_expect(bars + B_X + 8 * i, (i & 1) ? 3072 : 4096);
            } else {
                due = (uint32_t)clock();
#pragma unroll 1
                for (int j = PF0; j < PF1; j++) {
                    asm volatile("cp.async.bulk.prefetch.L2.global [%0], %1;" ::"l"(w1 + (rank * 1024 + j * 64 + hp * 8) * F_), "n"(16 * F_) : "memory");
                    due += PF;
                    while ((int)((uint32_t)clock() - due) < 0) {}
                }
            }
            const uint8_t *so = G->O[mt][ks * 4] + rank * HALF, *sw = G->Wo[nt2][ks * 4];
            wait_flag2(G->flag[16 + mt], 8 * ep, G->flag[0], 16 * ep, spins);
            TS(4, 18);
#pragma unroll 1
            for (int j = 0; j < 4 * TILEB; j += TILEB) {
                mbar_wait_bounded(r.bar + B_EMPTY, r.ph, spins);
                mbar_expect(r.bar + B_QFULL, TILEB);
                bulk_load_pair(r.dst + rank * 8192, so + j, HALF, r.bar + B_QFULL);
                bulk_load(r.dst + 16384, sw + j, (r.bar & 8) ? TILEB : 3 * SLAB, r.bar + B_FULL);
                r.next(bars);
            }
            if (!has_g1) {
#pragma unroll 1
                for (int j = PG0; j < PG1; j++)
                    asm volatile("cp.async.bulk.prefetch.L2.global [%0], %1;" ::"l"(w2 + (rank * 896 + j * 128 + hp * 8) * S_), "n"(16 * S_) : "memory");
            }
            Ring q{has_g1 ? 2u : 6u, has_g1};
#pragma unroll 1
            for (int j = 0; j < 14 * 128; j += 128) {
                mbar_wait_bounded(bars + B_EMPTY + 8 * q.slot, q.ph, spins);
                TS(8, 176 + j / 128);
                tma2d_pair(sbase + q.slot * SLOT + rank * 8192, &P.tmW2, bars + B_FULL + 8 * q.slot, mt * 128 + rank * 64, ks * 896 + j - (j < 896 ? 0 : 832));
                q.next2();
            }
            mbar_wait_bounded(bars + B_END, 0, spins);
        }
    } else if (warp > 8) {
        const uint32_t ep = ld_relaxed(&G->epoch[c]) + 1;
        {
            const uint32_t src = (sbase + wslot(gp / ROT) * 8192 - 4096 + w * 4096 + rank * 64 + (lane & 15) * 4 + (lane >> 4) * 12288) ^ ((lane >> 4) * 576);
            float s0 = 0.f, s1 = 0.f, s2 = 0.f, s3 = 0.f;
            if (w == 2) {
                bar_sync(6, 160);
                if (elect()) {
                    fence_async_shared();
#pragma unroll
                    for (int i = 0; i < 4; i++) bulk_store(G->H[i][0] + row0 * (SLAB / 16), sbase + OFF_X + i * (SLAB + 64), SLAB);
                }
                __syncwarp();
            }
            mbar_wait(bars + B_QFULL + 8 * (gp / ROT), 0);
            if (w == 1) TS(1, 66);
            uint32_t v[32];
#pragma unroll
            for (int k = 0; k < 32; k++) v[k] = __float_as_uint(lds1f((src ^ ((k & 7) * 144)) + (k >> 3) * 1024));
#pragma unroll
            for (int k = 0; k < 32; k += 2) { s0 += bf_lo(v[k]); s1 += bf_hi(v[k]); s2 += bf_lo(v[k + 1]); s3 += bf_hi(v[k + 1]); }
            s0 += s2; s1 += s3;
            s0 += __shfl_xor_sync(~0u, s0, 16); s1 += __shfl_xor_sync(~0u, s1, 16);
            uint2* cs = G->colsum[hp][0] + w * 32 - 32;
            if (lane < 16) cs[gp * 96 + rank * 16 + lane] = make_uint2(tag(__float_as_uint(s0), 1, ep), __float_as_uint(s1));
            if (w == 1) TS(1, 24);
            if (w == 2) {
                bar_sync(10, 96);
                TS(1, 8);
                if (elect()) { mbar_arrive(bars + B_CS); bulk_flush(); signal(G->flag[1] + (row0 >> 10) * 2 + ((row0 & 1023) >= 320)); TS(1, 3); }
                __syncwarp();
            } else {
                bar_arrive(10, 96);
            }
            bar_sync(1, 96);
            const int i0 = threadIdx.x - 288;
            uint2 u[7];
            uint4 sv;
            uint32_t bad;
            do {
                sv = ld_relaxed4(G->stat + tb * 128 + (i0 & 63) * 2);
                bad = or_diff(sv.x ^ ep, sv.z, ep);
#pragma unroll
                for (int i = 0; i < 7; i++) { u[i] = ld_relaxed2(cs + i * 96 + lane); bad = or_diff(bad, u[i].x, ep); }
            } while (bad & 1);
            if (w < 3) sts4(sbase + OFF_ST + i0 * 16, sv);
#pragma unroll
            for (int e = 0; e < 2; e++) {
                float f = 0.f;
#pragma unroll
                for (int i = 0; i < 7; i++) f += __uint_as_float(e ? u[i].y : u[i].x);
                const uint32_t hi = pack2(f, f);
                sts4(sbase + OFF_X + i0 * 32 + e * 16, make_uint4(hi, pack2(f - bf_hi(hi), f - bf_hi(hi)), 0, 0));
            }
            asm volatile("st.shared.u32 [%0], %1;" ::"r"(bars + 8 * NBAR), "r"(ep) : "memory");
            fence_async_shared();
            __syncwarp();
            bar_arrive(8, 224); bar_arrive(9, 224);
            TS(1, 90 + w);
        }
        const uint8_t* src = G->U[nt2][ks * 14];
        uint32_t spins = 0;
        if (w < 3) {
            uint32_t bad;
            if (w == 1) {
                if (elect()) {
                    wait_flag(G->flag[1] + rank * 2 + 1, 44 * ep, spins);
                    mbar_arrive16(bars + B_EMPTY + 8 * 5);
                    TS(1, 96);
                }
                __syncwarp();
                if (!has_g1) { bar_sync(5, 288); if (elect()) signal(G->flag[0]); __syncwarp(); TS(2, 26); }
            } else {
                bar_sync(3, 288);
                __nanosleep(HALO_NS);
                uint4 v[7];
                do {
                    bad = 0;
#pragma unroll
                    for (int i = 0; i < 7; i++) { v[i] = ld_relaxed4(G->halo[c - (tb > 0)] + i * 512 + lane * 16); bad = or_diff(bad, v[i].x, ep); }
                } while (bad & 1);
#pragma unroll
                for (int i = 0; i < 7; i++) sts4(sbase + OFF_X + i * 512 + lane * 16, v[i]);
                __syncwarp();
                if (elect()) mbar_arrive(bars + B_HALO);
                TS(2, 21);
            }
            mbar_wait(bars + B_HALO, 0);
            uint32_t slot = (has_g1 ? 16 % NSLOT : 0) + w - 1, ph = ~0u;
#pragma unroll 1
            for (int i = w - 1; i < 18;) {
                const uint32_t d0 = sbase + slot * SLOT + (i < 4 ? 0 : 16384), d1 = d0 + (i < 4 ? 8192 : HALF), landed = bars + B_QFULL + 8 * slot;
                mbar_wait(landed, (ph >> slot) & 1);
                ph ^= 1 << slot;
                if (i < 8) TS(4, 82 + i);
                if (i >= 4) TS(8, 156 + i);
                bad = 0;
#pragma unroll
                for (int k = 0; k < 14; k++) bad = or_diff(bad, __float_as_uint(lds1f((k < 7 ? d0 : d1) + k % 7 * 1024 + lane * 32 + (lane >> 2) * 4)), ep);
                if (__any_sync(~0u, bad & 1)) {
                    if (elect()) {
                        const uint8_t* cur = (i < 4 ? G->O[mt][ks * 4] : src - 4 * TILEB) + i * TILEB;
                        fence_async_shared();
                        mbar_expect(landed, TILEB);
                        bulk_load(d0, cur, HALF, landed);
                        bulk_load(d1, cur + HALF, HALF, landed);
                    }
                    TS(4, i < 4 ? 94 : 95);
                } else {
                    if (elect()) mbar_expect(landed + (B_FULL - B_QFULL), i < 4 ? (2 + w) * SLAB : 16384);
                    i += __byte_perm(0x03020202u, 0x00010202u, 0x7770 + slot);
                    slot = __byte_perm(0x05060302u, 0x00040100u, 0x7770 + slot);
                }
            }
        } else {
            bar_sync(2, 288);
            if (elect()) bulk_store(out + row0 * D_, sbase + OFF_Y, TILEB);
            __syncwarp();
            bar_sync(4, 288);
            if (elect()) {
                fence_async_shared();
                bulk_store(G->O[tb][hp], sbase + OFF_X, TILEB);
                bulk_flush();
                TS(2, 7);
                mbar_arrive_remote(mapa(bars + B_FREE, rank ^ 1));
                mbar_arrive(bars + B_FREE);
                hint(G->flag[16 + tb]);
                signal(G->flag[16 + (row0 >> 7)] + 1);
                TS(2, 22);
            }
            __syncwarp();
            uint32_t late = ~0u;
            const uint32_t* hints = G->flag[8 + nt2 * 2 + ks] + lane;
            mbar_wait(bars + (has_g1 ? B_X : B_FREE), 0);
            Ring r{has_g1 ? 2u : 6u, has_g1};
#pragma unroll 1
            for (int i = 0; i < 14; i++) {
                while ((late >> i) & 1) late = __ballot_sync(~0u, ld_relaxed(hints) != 2 * ep) & 127;
                if (i == 0) TS(4, 17);
                mbar_wait(bars + B_EMPTY + 8 * r.slot, r.ph);
                TS(8, 192 + i);
                if (elect()) {
                    mbar_expect(bars + B_QFULL + 8 * r.slot, TILEB);
                    bulk_load(sbase + r.slot * SLOT + 16384, src, TILEB, bars + B_QFULL + 8 * r.slot);
                }
                src += TILEB; r.next2();
                if (UGAP && i < UGAPN) { const uint32_t t0 = clock(); while ((uint32_t)clock() - t0 < UGAP) {} }
            }
            if (elect()) {
                wait_flag(G->flag[16 + mt] + 1, 8 * ep, spins);
                mbar_arrive(bars + B_ROW);
                TS(2, 27);
                G->epoch[c] = ep;
            }
        }
    } else {
        const int wg = warp >> 2;
        Mma M{bars, mapa(bars, rank ^ (lane & 1)), (threadIdx.x & 127) < 2, wg, w, Ring{0, 0}, 0};
        const int r = lane >> 2, t = lane & 3;
        uint32_t ep;
        const uint32_t bias0 = ld_u16(b1 + ft * 128 + warp * 16 + r), bias1 = ld_u16(b1 + ft * 128 + warp * 16 + r + 8);
        if (wg == 1) {
            ep = ld_relaxed(&G->epoch[c]);
            const int r16 = w * 4 + t, nt = (r + 2 * t) & 3, half = ((r + 2 * t) >> 2) & 1;
            const uint32_t row = sbase + OFF_Y + r16 * (2 * D_), part = row + nt * 224 + half * 112;
            const uint32_t hb = sbase + OFF_X + nt * (SLAB + 64) + r16 * 16 + (half ^ (row0 >> 10)) * (7 * 256);
            mbar_wait(bars + B_ROW, 0);
            TS0(1, 67);
            const float x0 = bf_lo(__float_as_uint(lds1f(row)));
            float d[56], s0 = 0.f, s1 = 0.f, q0 = 0.f, q1 = 0.f;
#pragma unroll
            for (int i = 0; i < 7; i++) {
                const uint4 v = lds4(part + i * 16);
                const uint32_t u[4] = {v.x, v.y, v.z, v.w};
#pragma unroll
                for (int k = 0; k < 4; k++) {
                    const float d0 = d[8 * i + 2 * k] = bf_lo(u[k]) - x0, d1 = d[8 * i + 2 * k + 1] = bf_hi(u[k]) - x0;
                    s0 += d0; s1 += d1; q0 = fmaf(d0, d0, q0); q1 = fmaf(d1, d1, q1);
                }
            }
            const float md = oct_sum(s0 + s1) * (1.f / D_), var = fmaf(-md, md, oct_sum(q0 + q1) * (1.f / D_)), nmean = -(x0 + md);
            const float rstd = rsq(var + LN_EPS);
            const float sc = rstd * rsq(fmaf(var * rstd, rstd, LN_EPS)), nb = -md * sc;
            if (lane < 4) G->stat[row0 + r16] = make_uint2(tag(__float_as_uint(rstd), 1, ~ep), pack2(nmean, nmean - bf_hi(pack2(nmean, nmean))));
#pragma unroll
            for (int i = 0; i < 7; i++) {
                uint32_t u[4];
#pragma unroll
                for (int k = 0; k < 4; k++) u[k] = pack2(fmaf(d[8 * i + 2 * k], sc, nb), fmaf(d[8 * i + 2 * k + 1], sc, nb));
                sts4(hb + i * 256, make_uint4(u[0], u[1], u[2], u[3]));
            }
            TS0(1, 25);
            bar_arrive(6, 160);
        }
        const uint32_t kv = sbase + OFF_X + (w * 2 + wg) * KV + lane * 16;
        uint32_t q[8][2], k0[7], k1[7], v0[7];
        {
            float acc[92];
#pragma unroll 1
            for (int kb = 0; kb < 7; kb++) {
                const bool held = kb == (wg ? 7 - HOLD : -1);
                if (held) { wg_wait<0>(); M.release(4 - HOLD); bar_sync(7, 256); }
                mbar_wait(bars + B_QFULL + 8 * kb, 0);
                TS0(1, 68 + wg * 7 + kb);
                const uint32_t dA = (xslot(kb) + wg) * 512, dB = wslot(kb) * 512 + (hp & 1);
                wg_fence();
#pragma unroll
                for (int k = 0; k < 4; k++) {
                    wgmma_n184<0, 1, HI_SW, HI_SW>(acc, dA + desc_lo(k * 32, 16), dB + desc_lo((k & 1) * 2048 + (k >> 1) * 12288, 4096), k > 0 || kb > 0);
                    if (k == 0) { wg_commit(); wg_wait<1>(); if (kb > 0 && !held) M.release(kb - 3); }
                }
                wg_commit();
            }
            if (wg == 0 && !LATEREL) bar_arrive(7, 256);
            bar_sync(8 + wg, 224);
            ep = __float_as_uint(lds1f(bars + 8 * NBAR));
            const uint32_t st = sbase + OFF_ST + (w * 32 + r * 2 + wg) * 8;
            const uint2 s0 = lds2(st), s1 = lds2(st + 128);
            const uint32_t a0 = t < 2 ? s0.y : 0, a1 = t < 2 ? s1.y : 0;
            wg_fence();
            wgmma_rs_n184<desc_hi(128, 0)>(acc, a0, a1, desc_lo(OFF_X, 0) + (hp & 1) * 8);
            wg_commit();
            if (wg == 0 && LATEREL) bar_arrive(7, 256);
            wg_wait<1>();
            M.release(4);
            wg_wait<0>();
            pin(acc);
            TS0(1, 4 + 7 * wg);
            uint32_t hi[14];
#pragma unroll
            for (int p = 2; p >= 0; p--) {
                const float f = p == 0 ? 0.1889822365046136f * 1.4426950408889634f : p, r0 = __uint_as_float(s0.x) * f, r1 = __uint_as_float(s1.x) * f;
#pragma unroll
                for (int g = 0; g < 7; g++) {
                    const int a = (p * 8 + g) * 4;
                    const uint32_t lo2 = pack2(acc[a] * r0, acc[a + 1] * r0), hi2 = pack2(acc[a + 2] * r1, acc[a + 3] * r1);
                    if (p == 0) { q[g][0] = lo2; q[g][1] = hi2; } else { hi[(p - 1) * 7 + g] = hi2; }
                    if (p == 1) { k0[g] = lo2; k1[g] = hi2; }
                    if (p == 2) v0[g] = lo2;
                }
                if (p == 1) {
#pragma unroll
                    for (int i = 0; i < 3; i++) stsm4(kv + 2 * KV + i * 512, hi[4 * i], hi[4 * i + 1], hi[4 * i + 2], hi[4 * i + 3]);
                    stsm2(kv + 2 * KV + 1536, hi[12], hi[13]);
                    if (w == 3) {
#pragma unroll
                        for (int i = 0; i < 14; i++) stg1(G->halo[c] + wg * KV + lane * 4 + i * 128, tag(hi[i], t == 0, ep));
                    }
                    bar_arrive(3, 288);
                }
            }
#pragma unroll
            for (int j = 0; j < 2; j++) { q[7][j] = t < 2 ? 0u : q[3][j]; q[3][j] = t < 2 ? q[3][j] : 0u; }
#pragma unroll
            for (int g = 0; g < 7; g++) v0[g] = transpose8(v0[g]);
        }
        TS0(1, 9 + 11 * wg);
        float a[56];
#pragma unroll
        for (int i = 0; i < 56; i++) asm volatile("" : "=f"(a[i]));
        if (__builtin_expect(!has_g1, 0)) {
            const int g = min(lane >> 1, 13), nt = rank * 2 + wg;
            const uint4* src = (const uint4*)(wo + (hp * 56 - (hp & 1) * 8 + w * 16 + (lane & 1)) * D_ + nt * 112) + g;
            uint4 v[8];
#pragma unroll
            for (int i = 0; i < 8; i++) v[i] = __ldg(src + i * (D_ / 4));
#pragma unroll
            for (int i = 0; i < 8; i++) ((uint4*)G->Wo[nt][hp])[w * (SLAB / 16) + g * 16 + (lane & 1) + 2 * i] = v[i];
            bar_arrive(5, 288);
        }
        M.run<true>(a, has_g1 ? PAUSE : 0, 1, 16, 0, 0, 32);
        {
            uint32_t kp[8], vv[14];
            TS0(2, 140 + wg);
            mbar_wait(bars + B_HALO, 0);
            TS0(2, 142 + wg);
            ldsm4(kp, kv); ldsm4(kp + 4, kv + (lane < 24 ? 512 : 0));
            const uint32_t va = kv + 896 + (lane & 8) * (2 * KV / 8 - 16) - (lane & 16) * 8;
            ldsm4t(vv, va); ldsm4t(vv + 4, va + 256); ldsm4t(vv + 8, va + 512); ldsm2t(vv + 12, va + 768);
            const bool e0 = 2 * t > r, e1 = 2 * t >= r;
            const uint32_t mk = (e0 ? 0xffffu : 0u) | (e1 ? 0xffff0000u : 0u);
            wg_wait<0>();
            pin(a);
            if (has_g1) M.release(M.prev);
            TS0(2, 144 + wg);
            bar_sync(2, 288);
            mbar_wait(bars + B_HALO, 0);
            TS0(2, 12 + 16 * wg);
            float sv[2][4];
#pragma unroll
            for (int h = 0; h < 2; h++) {
                const int ga = h * 4, gb = h * 4 + 1, gc = h * 4 + 2, gd = h * 4 + 3;
                float s[3][4] = {};
                mma16(s[0], q[ga][0], q[ga][1], q[gb][0], q[gb][1], kp[ga], kp[gb]);
                mma16(s[1], q[ga][0], q[ga][1], q[gb][0], q[gb][1], k0[ga], k0[gb]);
                mma16(s[2], q[ga][0], q[ga][1], q[gb][0], q[gb][1], k1[ga], k1[gb]);
                mma16(s[0], q[gc][0], q[gc][1], q[gd][0], q[gd][1], kp[gc], kp[gd]);
                mma16(s[1], q[gc][0], q[gc][1], q[gd][0], q[gd][1], k0[gc], k0[3]);
                mma16(s[2], q[gc][0], q[gc][1], q[gd][0], q[gd][1], k1[gc], k1[3]);
                if ((tb | w) == 0) s[0][0] = s[0][1] = -1e30f;
                sv[h][0] = e0 ? s[0][0] : s[1][0];
                sv[h][1] = e1 ? s[0][1] : s[1][1];
                sv[h][2] = e0 ? s[1][2] : s[2][2];
                sv[h][3] = e1 ? s[1][3] : s[2][3];
            }
            uint32_t pp[2][2];
#pragma unroll
            for (int i = 0; i < 4; i++) {
                float* v = &sv[i >> 1][(i & 1) * 2];
                const float m = quad_max(fmaxf(v[0], v[1]));
                const float p0 = ex2(v[0] - m), p1 = ex2(v[1] - m);
                const float inv = rcp(quad_sum(p0 + p1));
                pp[i >> 1][i & 1] = pack2(p0 * inv, p1 * inv);
            }
            uint32_t o[8][2];
#pragma unroll
            for (int i = 0; i < 8; i++) {
                const int h = i >> 2, g = i - h;
                float d[4] = {};
                mma16(d, pp[h][0] & mk, 0u, 0u, pp[h][1] & ~mk, vv[2 * g], vv[2 * g + 1]);
                mma8(d, pp[h][0] & ~mk, pp[h][1] & mk, v0[g]);
                o[i][0] = pack2(d[0], d[1]); o[i][1] = pack2(d[2], d[3]);
            }
            if (t >= 2) { o[3][0] = o[4][0]; o[3][1] = o[4][1]; }
            const int word = wg * 4 + t - (w & 1) * 4 - (r >> 2);
#pragma unroll
            for (int i = 0; i < 8; i++) { o[i][0] = tag(o[i][0], word == 0, ep); o[i][1] = tag(o[i][1], word == 2, ep); }
            const uint32_t dst = sbase + OFF_X + (w >> 1) * HALF + ((w & 1) * 32 + (lane & 15) * 2 + wg) * 16 + (lane >> 4) * 1024;
            stsm4(dst, o[0][0], o[0][1], o[1][0], o[1][1]);
            stsm4(dst + 2048, o[2][0], o[2][1], o[3][0], o[3][1]);
            stsm4(dst + 4096, o[5][0], o[5][1], o[6][0], o[6][1]);
            stsm2(dst + 6144, o[7][0], o[7][1]);
            if (ENDBAR) bar_sync(4, 288); else bar_arrive(4, 288);
            TS0(2, 10 + 19 * wg);
        }
        if (has_g1) {
            M.run<true>(a, 16 - PAUSE, 1, 16, LAG1, 1, 32 + PAUSE);
            mbar_wait(bars + B_FREE, 0);
            const uint32_t xb = sbase + OFF_X + wg * 8192 + (threadIdx.x & 127) * 16, xbar = bars + B_X + 16 * wg;
            const uint32_t rx = mapa(xb, rank ^ 1), rbar = mapa(xbar, rank ^ 1);
            wg_wait<0>();
            pin(a);
            M.release(M.prev);
            TS0(4, 5 + wg);
#pragma unroll
            for (int i = 0; i < 3; i++)
                st_async4(rx + i * 2048, rbar + 8 * (i >> 1), pack2(a[28 + 8 * i], a[29 + 8 * i]), pack2(a[30 + 8 * i], a[31 + 8 * i]), pack2(a[32 + 8 * i], a[33 + 8 * i]), pack2(a[34 + 8 * i], a[35 + 8 * i]));
            const uint32_t tail = 6144 - (threadIdx.x & 127) * 8;
            st_async2(rx + tail, rbar + 8, pack2(a[52], a[53]), pack2(a[54], a[55]));
            uint8_t* dst = G->U[nt1][((ft >= 7) + wg) * 7 + ft] + rank * HALF + w * 256 + lane * 4;
            uint32_t u[14];
#pragma unroll
            for (int i = 0; i < 14; i++) {
                if (i % 8 == 0) {
                    mbar_wait(xbar + i, 0);
                    if (i == 0) TS0(4, 1 + wg);
#pragma unroll
                    for (int k = i / 4; k < i / 4 + 2; k++) {
                        if (k < 3) { const uint4 v = lds4(xb + k * 2048); u[4 * k] = v.x; u[4 * k + 1] = v.y; u[4 * k + 2] = v.z; u[4 * k + 3] = v.w; }
                        else { const uint2 v = lds2(xb + tail); u[12] = v.x; u[13] = v.y; }
                    }
                    if (i && lane < 2) mbar_arrive_remote(M.rel + B_EMPTY + 48);
                }
                if (i == HINT && threadIdx.x == 0) hint(G->flag[8 + nt1 * 2] + ft + (ft >= 7) * 25);
                const float bias = bf_lo((i & 1) ? bias1 : bias0);
                stg1(dst + (i >> 1) * 1024 + (i & 1) * 128, tag(pack2(gelu2(a[2 * i] + bias + bf_lo(u[i])), gelu2(a[2 * i + 1] + bias + bf_hi(u[i]))), (lane & 7) == w * 2 + (i & 1), ep));
            }
            TS0(4, 30 + wg);
        } else {
            mbar_wait(bars + B_FREE, 0);
            if (lane < 2) mbar_arrive_remote(M.rel + B_EMPTY + 48);
        }
        uint32_t c0 = ld_u16(b2 + mt * 128 + warp * 16 + r), c1 = ld_u16(b2 + mt * 128 + warp * 16 + r + 8);
        M.run_o(a);
        if (wg == 1) TS0(4, 13);
        c0 *= ks == 0 ? 0x10001u : 0u; c1 *= ks == 0 ? 0x10001u : 0u;
        M.run<false>(a, 14, 0, 14 - NSLOT, LAG2, 1, 52);
        mbar_wait(bars + B_ROW, 1);
        const uint32_t stg = sbase + ((has_g1 ? STG1 : STG0) + (w >> 1) * STGS) * SLOT + wg * 8192 + (w & 1) * SLAB;
        const uint32_t sa = stg + (lane & 15) * 224 + (lane >> 4) * 16;
        wg_wait<0>();
        pin(a);
        TS0(8, 14 + wg);
#pragma unroll
        for (int i = 0; i < 7; i++)
            stsm4(sa + i * 32, half_plus(pack2(a[8 * i], a[8 * i + 1]), c0), half_plus(pack2(a[8 * i + 2], a[8 * i + 3]), c1),
                  half_plus(pack2(a[8 * i + 4], a[8 * i + 5]), c0), half_plus(pack2(a[8 * i + 6], a[8 * i + 7]), c1));
        fence_async_shared();
        __syncwarp();
        if (elect()) {
            asm volatile("cp.reduce.async.bulk.tensor.2d.global.shared::cta.add.tile.bulk_group [%0, {%2, %3}], [%1];\ncp.async.bulk.commit_group;" ::"l"(&P.tmOut), "r"(stg), "r"(nt2 * 112), "r"(mt * 128 + warp * 16) : "memory");
            if (w == 0) mbar_arrive(bars + B_END);
            asm volatile("cp.async.bulk.wait_group.read 0;" ::: "memory");
        }
        if (wg == 1) TS0(15, 19);
        TSDUMP();
    }
}

typedef CUresult (*EncodeFn)(CUtensorMap*, CUtensorMapDataType, cuuint32_t, void*, const cuuint64_t*, const cuuint64_t*, const cuuint32_t*, const cuuint32_t*,
                             CUtensorMapInterleave, CUtensorMapSwizzle, CUtensorMapL2promotion, CUtensorMapFloatOOBfill);

void make_map(EncodeFn enc, CUtensorMap* tm, const void* base, bool swizzle, int d0, int d1, int d2, int s1, int s2, int b0, int b1, int b2) {
    const cuuint64_t dims[3] = {(cuuint64_t)d0, (cuuint64_t)d1, (cuuint64_t)d2}, strides[2] = {(cuuint64_t)s1 * 2, (cuuint64_t)s2 * 2};
    const cuuint32_t box[3] = {(cuuint32_t)b0, (cuuint32_t)b1, (cuuint32_t)b2}, es[3] = {1, 1, 1};
    enc(tm, CU_TENSOR_MAP_DATA_TYPE_BFLOAT16, d2 ? 3 : 2, (void*)base, dims, strides, box, es, CU_TENSOR_MAP_INTERLEAVE_NONE,
        swizzle ? CU_TENSOR_MAP_SWIZZLE_128B : CU_TENSOR_MAP_SWIZZLE_NONE, CU_TENSOR_MAP_L2_PROMOTION_L2_128B, CU_TENSOR_MAP_FLOAT_OOB_FILL_NONE);
}

}

extern "C" void kernel_launch(void* const* d_in, const int* in_sizes, int n_in, void* d_out, int out_size) {
    static EncodeFn enc = nullptr;
    static Scratch* scratch = nullptr;
    if (!enc) {
        void* fn = nullptr;
        cudaDriverEntryPointQueryResult qr;
        cudaGetDriverEntryPoint("cuTensorMapEncodeTiled", &fn, cudaEnableDefault, &qr);
        enc = (EncodeFn)fn;
        cudaGetSymbolAddress((void**)&scratch, g_s);
        cudaFuncSetAttribute(fused_kernel, cudaFuncAttributeMaxDynamicSharedMemorySize, SMEM_BYTES);
    }
    Params P;
    const __nv_bfloat16* x = (const __nv_bfloat16*)d_in[0];
    make_map(enc, &P.tmX, x, true, D_, S_ / 2, 2, 2 * D_, D_, 64, 64, 2);
    make_map(enc, &P.tmWqkv, d_in[1], true, D_, D_, 3, 3 * D_, D_, 64, 32, 3);
    make_map(enc, &P.tmW1, d_in[4], true, 64, S_, F_ / 64, F_, 64, 64, 64, 2);
    make_map(enc, &P.tmW2, d_in[6], true, S_, F_, 0, S_, 0, 64, 64, 1);
    make_map(enc, &P.tmOut, d_out, false, D_, S_, 0, D_, 0, 112, 16, 1);
    fused_kernel<<<NCTA, NTHREADS, SMEM_BYTES, cudaStreamPerThread>>>(x, (const __nv_bfloat16*)d_in[5], (const __nv_bfloat16*)d_in[7], (const __nv_bfloat16*)d_in[2], (__nv_bfloat16*)d_out, scratch,
                                                                      (const __nv_bfloat16*)d_in[4], (const __nv_bfloat16*)d_in[6], P);
}
```

```cpp
#include <cuda_runtime.h>
#include <cuda_bf16.h>
#include <cuda.h>
#include <stdint.h>

#define HALO_NS 300
#define HINT 4
#define HOLD 2
#define ROT 2
#define LATEREL 1
#define PF 400
#define PF0 2
#define PF1 8
#define ENDBAR 1
#define PG0 3
#define PG1 5
#define STG1 4
#define STG0 4
#define STGS 1
#define UGAP 120
#define UGAPN 6
#define CSU 1
#define REC_NS 0
#define PACE 600
#define PAUSE 8
#define LAG1 4
#define LAG2 6

namespace {

constexpr int S_ = 2048, D_ = 448, F_ = 1792;
constexpr int NCTA = 128, NTHREADS = 384;
constexpr int NSLOT = 6, SLOT = 32768, QSLOT = 40960, TILEB = 14336, SLAB = 3584, HALF = 7168;
constexpr int KV = 1792, kCsu = CSU;
constexpr int OFF_X = NSLOT * SLOT;
constexpr int OFF_Y = OFF_X + 10 * KV;
constexpr int OFF_ST = OFF_Y + TILEB;
constexpr int OFF_BAR = OFF_ST + 1024;
constexpr int SMEM_BYTES = OFF_BAR + 1280;
constexpr uint32_t SMEM0 = 1024;
constexpr int B_QFULL = 0, B_FULL = 56, B_HALO = 128, B_X = 136, B_FREE = 192, B_END = 200, B_CS = 208, B_QEMPTY = 216, B_EMPTY = 232, B_ROW = 288, NBAR = 37;
constexpr float LN_EPS = 1e-5f;
constexpr int SPIN_LIMIT = 1 << 22;

struct Scratch {
    uint8_t H[4][32][TILEB];
    uint8_t U[4][28][TILEB];
    uint8_t O[16][8][TILEB];
    uint8_t Wo[4][8][TILEB];
    uint8_t halo[NCTA][2 * KV];
    uint2 stat[S_];
    uint2 colsum[8][8][96];
    uint32_t flag[32][32];
    uint32_t epoch[NCTA];
};
__device__ __align__(1024) Scratch g_s;

#define TS(g, i)
#define TS0(g, i)
#define TSDUMP()

struct Params {
    CUtensorMap tmX, tmWqkv, tmW1, tmW2, tmOut;
};

__device__ __forceinline__ bool elect() {
    uint32_t p;
    asm volatile("{\n.reg .pred p;\nelect.sync _|p, 0xffffffff;\nselp.u32 %0, 1, 0, p;\n}" : "=r"(p));
    return p;
}
__device__ __forceinline__ void mbar_init(uint32_t b, uint32_t c) { asm volatile("mbarrier.init.shared::cta.b64 [%0], %1;" ::"r"(b), "r"(c) : "memory"); }
__device__ __forceinline__ void mbar_expect(uint32_t b, uint32_t tx) { asm volatile("mbarrier.arrive.expect_tx.shared::cta.b64 _, [%0], %1;" ::"r"(b), "r"(tx) : "memory"); }
__device__ __forceinline__ void mbar_arrive(uint32_t b) { asm volatile("mbarrier.arrive.shared::cta.b64 _, [%0];" ::"r"(b) : "memory"); }
__device__ __forceinline__ void mbar_arrive16(uint32_t b) { asm volatile("mbarrier.arrive.shared::cta.b64 _, [%0], 16;" ::"r"(b) : "memory"); }
__device__ __forceinline__ void mbar_arrive4_remote(uint32_t b) { asm volatile("mbarrier.arrive.shared::cluster.b64 _, [%0], 4;" ::"r"(b) : "memory"); }
__device__ __forceinline__ void mbar_arrive_remote(uint32_t b) { asm volatile("mbarrier.arrive.shared::cluster.b64 _, [%0];" ::"r"(b) : "memory"); }
#define MBAR_WAIT_ASM(SEM) \
    asm volatile("{\n.reg .pred p;\nWAIT:\nmbarrier.try_wait.parity" SEM ".shared::cta.b64 p, [%0], %1;\n@!p bra WAIT;\n}" ::"r"(b), "r"(parity) : "memory")
__device__ __forceinline__ void mbar_wait(uint32_t b, uint32_t parity) { MBAR_WAIT_ASM(""); }
__device__ __forceinline__ void mbar_wait_bounded(uint32_t b, uint32_t parity, uint32_t& n) {
    asm volatile("{\n.reg .pred p;\nWAIT:\nadd.u32 %0, %0, 1;\nsetp.gt.u32 p, %0, %3;\n@p st.global.u32 [%4], %0;\n"
                 "mbarrier.try_wait.parity.shared::cta.b64 p, [%1], %2;\n@!p bra WAIT;\n}" : "+r"(n) : "r"(b), "r"(parity), "n"(SPIN_LIMIT), "l"(0ull) : "memory");
}
__device__ __forceinline__ uint32_t mapa(uint32_t a, uint32_t rank) { uint32_t r; asm("mapa.shared::cluster.u32 %0, %1, %2;" : "=r"(r) : "r"(a), "r"(rank)); return r; }
__device__ __forceinline__ void tma3d(uint32_t dst, const CUtensorMap* tm, uint32_t bar, int c0, int c1, int c2) {
    asm volatile("cp.async.bulk.tensor.3d.shared::cluster.global.mbarrier::complete_tx::bytes [%0], [%1, {%3, %4, %5}], [%2];" ::"r"(dst), "l"(tm), "r"(bar), "r"(c0), "r"(c1), "r"(c2) : "memory");
}
__device__ __forceinline__ void tma2d_pair(uint32_t dst, const CUtensorMap* tm, uint32_t bar, int c0, int c1) {
    asm volatile("cp.async.bulk.tensor.2d.shared::cluster.global.mbarrier::complete_tx::bytes.multicast::cluster [%0], [%1, {%3, %4}], [%2], %5;" ::"r"(dst), "l"(tm), "r"(bar), "r"(c0), "r"(c1), "h"((uint16_t)3) : "memory");
}
__device__ __forceinline__ void tma3d_pair(uint32_t dst, const CUtensorMap* tm, uint32_t bar, int c0, int c1, int c2) {
    asm volatile("cp.async.bulk.tensor.3d.shared::cluster.global.mbarrier::complete_tx::bytes.multicast::cluster [%0], [%1, {%3, %4, %5}], [%2], %6;" ::"r"(dst), "l"(tm), "r"(bar), "r"(c0), "r"(c1), "r"(c2), "h"((uint16_t)3) : "memory");
}
__device__ __forceinline__ void bulk_load(uint32_t dst, const void* src, uint32_t bytes, uint32_t bar) {
    asm volatile("cp.async.bulk.shared::cluster.global.mbarrier::complete_tx::bytes [%0], [%1], %2, [%3];" ::"r"(dst), "l"(src), "r"(bytes), "r"(bar) : "memory");
}
__device__ __forceinline__ void bulk_load_pair(uint32_t dst, const void* src, uint32_t bytes, uint32_t bar) {
    asm volatile("cp.async.bulk.shared::cluster.global.mbarrier::complete_tx::bytes.multicast::cluster [%0], [%1], %2, [%3], %4;" ::"r"(dst), "l"(src), "r"(bytes), "r"(bar), "h"((uint16_t)3) : "memory");
}
__device__ __forceinline__ void bulk_store(void* dst, uint32_t src, uint32_t bytes) {
    asm volatile("cp.async.bulk.global.shared::cta.bulk_group [%0], [%1], %2;" ::"l"(dst), "r"(src), "r"(bytes) : "memory");
}
__device__ __forceinline__ uint32_t ld_u16(const void* p) { uint32_t v; asm volatile("ld.global.nc.u16 %0, [%1];" : "=r"(v) : "l"(p)); return v; }
__device__ __forceinline__ uint32_t ld_relaxed(const uint32_t* p) { uint32_t v; asm volatile("ld.relaxed.gpu.global.u32 %0, [%1];" : "=r"(v) : "l"(p) : "memory"); return v; }
__device__ __forceinline__ void bulk_flush() { asm volatile("cp.async.bulk.commit_group;\ncp.async.bulk.wait_group 0;" ::: "memory"); }
__device__ __forceinline__ void signal(uint32_t* flag) { asm volatile("fence.acq_rel.gpu;\nred.relaxed.gpu.global.add.u32 [%0], 1;" ::"l"(flag) : "memory"); }
__device__ __forceinline__ void hint(uint32_t* flag) { asm volatile("red.relaxed.gpu.global.add.u32 [%0], 1;" ::"l"(flag) : "memory"); }
__device__ __forceinline__ uint32_t tag(uint32_t v, uint32_t mask, uint32_t parity) { return (v & ~mask) | (parity & mask); }
__device__ __forceinline__ uint32_t or_diff(uint32_t acc, uint32_t v, uint32_t parity) { asm("lop3.b32 %0, %0, %1, %2, 0xf6;" : "+r"(acc) : "r"(v), "r"(parity)); return acc; }
__device__ __forceinline__ uint4 ld_relaxed4(const void* p) {
    uint4 v;
    asm volatile("ld.relaxed.gpu.global.v4.u32 {%0, %1, %2, %3}, [%4];" : "=r"(v.x), "=r"(v.y), "=r"(v.z), "=r"(v.w) : "l"(p) : "memory");
    return v;
}
__device__ __forceinline__ uint2 ld_relaxed2(const void* p) { uint2 v; asm volatile("ld.relaxed.gpu.global.v2.u32 {%0, %1}, [%2];" : "=r"(v.x), "=r"(v.y) : "l"(p) : "memory"); return v; }
__device__ __forceinline__ void sts4(uint32_t a, uint4 v) { asm volatile("st.shared.v4.b32 [%0], {%1, %2, %3, %4};" ::"r"(a), "r"(v.x), "r"(v.y), "r"(v.z), "r"(v.w) : "memory"); }
__device__ __forceinline__ void stg1(void* p, uint32_t v) { asm volatile("st.global.b32 [%0], %1;" ::"l"(p), "r"(v) : "memory"); }
__device__ __forceinline__ void fence_async_shared() { asm volatile("fence.proxy.async.shared::cta;" ::: "memory"); }
#define BOUND "add.u32 %0, %0, 16;\nsetp.gt.u32 p, %0, %1;\n@p st.global.u32 [%2], %0;\n"
__device__ __forceinline__ void wait_flag(const uint32_t* p, uint32_t target, uint32_t& n) {
    asm volatile("{\n.reg .pred p;\n.reg .u32 v;\nPOLL:\n" BOUND "ld.acquire.gpu.global.u32 v, [%3];\nsetp.ne.u32 p, v, %4;\n@p bra POLL;\nfence.proxy.async.global;\n}"
                 : "+r"(n) : "n"(SPIN_LIMIT), "l"(0ull), "l"(p), "r"(target) : "memory");
}
__device__ __forceinline__ void wait_flag2(const uint32_t* h, uint32_t th, const uint32_t* p, uint32_t target, uint32_t& n) {
    asm volatile("{\n.reg .pred p;\n.reg .u32 u, v;\nPOLL:\n" BOUND "ld.relaxed.gpu.global.u32 u, [%3];\nld.acquire.gpu.global.u32 v, [%5];\nsetp.ne.u32 p, u, %4;\nsetp.ne.or.u32 p, v, %6, p;\n@p bra POLL;\nfence.proxy.async.global;\n}"
                 : "+r"(n) : "n"(SPIN_LIMIT), "l"(0ull), "l"(h), "r"(th), "l"(p), "r"(target) : "memory");
}
__device__ __forceinline__ void bar_sync(int id, int n) { asm volatile("bar.sync %0, %1;" ::"r"(id), "r"(n) : "memory"); }
__device__ __forceinline__ void bar_arrive(int id, int n) { asm volatile("bar.arrive %0, %1;" ::"r"(id), "r"(n) : "memory"); }
__device__ __forceinline__ void wg_fence() { asm volatile("wgmma.fence.sync.aligned;" ::: "memory"); }
__device__ __forceinline__ void wg_commit() { asm volatile("wgmma.commit_group.sync.aligned;" ::: "memory"); }
template <int N> __device__ __forceinline__ void wg_wait() { asm volatile("wgmma.wait_group.sync.aligned %0;" ::"n"(N) : "memory"); }
template <int N> __device__ __forceinline__ void pin(float (&d)[N]) {
#pragma unroll
    for (int i = 0; i < N; i++) asm volatile("" : "+f"(d[i])::"memory");
}
__host__ __device__ constexpr uint32_t desc_hi(uint32_t sbo, uint32_t swz) { return (sbo >> 4) | (swz << 30); }
__host__ __device__ constexpr uint32_t desc_lo(uint32_t off, uint32_t lbo) { return ((SMEM0 + off) >> 4) | ((lbo >> 4) << 16); }
__device__ __forceinline__ uint32_t pack2(float lo, float hi) { uint32_t r; asm("cvt.rn.bf16x2.f32 %0, %1, %2;" : "=r"(r) : "f"(hi), "f"(lo)); return r; }
__device__ __forceinline__ float bf_lo(uint32_t v) { return __uint_as_float(v << 16); }
__device__ __forceinline__ float bf_hi(uint32_t v) { return __uint_as_float(v & 0xffff0000u); }
__device__ __forceinline__ uint32_t half_plus(uint32_t a, uint32_t b) { uint32_t r; asm("fma.rn.bf16x2 %0, %1, %2, %3;" : "=r"(r) : "r"(a), "r"(0x3f003f00u), "r"(b)); return r; }
__device__ __forceinline__ void stsm4(uint32_t a, uint32_t r0, uint32_t r1, uint32_t r2, uint32_t r3) {
    asm volatile("stmatrix.sync.aligned.m8n8.x4.shared.b16 [%0], {%1, %2, %3, %4};" ::"r"(a), "r"(r0), "r"(r1), "r"(r2), "r"(r3) : "memory");
}
__device__ __forceinline__ void stsm2(uint32_t a, uint32_t r0, uint32_t r1) {
    asm volatile("stmatrix.sync.aligned.m8n8.x2.shared.b16 [%0], {%1, %2};" ::"r"(a), "r"(r0), "r"(r1) : "memory");
}
__device__ __forceinline__ uint4 lds4(uint32_t a) { uint4 v; asm volatile("ld.shared.v4.b32 {%0, %1, %2, %3}, [%4];" : "=r"(v.x), "=r"(v.y), "=r"(v.z), "=r"(v.w) : "r"(a) : "memory"); return v; }
__device__ __forceinline__ uint2 lds2(uint32_t a) { uint2 v; asm volatile("ld.shared.v2.b32 {%0, %1}, [%2];" : "=r"(v.x), "=r"(v.y) : "r"(a) : "memory"); return v; }
__device__ __forceinline__ float lds1f(uint32_t a) { float v; asm volatile("ld.shared.f32 %0, [%1];" : "=f"(v) : "r"(a) : "memory"); return v; }
__device__ __forceinline__ void ldsm4(uint32_t* r, uint32_t a) {
    asm volatile("ldmatrix.sync.aligned.m8n8.x4.shared.b16 {%0, %1, %2, %3}, [%4];" : "=r"(r[0]), "=r"(r[1]), "=r"(r[2]), "=r"(r[3]) : "r"(a) : "memory");
}
__device__ __forceinline__ void ldsm4t(uint32_t* r, uint32_t a) {
    asm volatile("ldmatrix.sync.aligned.m8n8.x4.trans.shared.b16 {%0, %1, %2, %3}, [%4];" : "=r"(r[0]), "=r"(r[1]), "=r"(r[2]), "=r"(r[3]) : "r"(a) : "memory");
}
__device__ __forceinline__ void ldsm2t(uint32_t* r, uint32_t a) {
    asm volatile("ldmatrix.sync.aligned.m8n8.x2.trans.shared.b16 {%0, %1}, [%2];" : "=r"(r[0]), "=r"(r[1]) : "r"(a) : "memory");
}
__device__ __forceinline__ uint32_t transpose8(uint32_t v) { uint32_t r; asm volatile("movmatrix.sync.aligned.m8n8.trans.b16 %0, %1;" : "=r"(r) : "r"(v)); return r; }
__device__ __forceinline__ void mma16(float (&c)[4], uint32_t a0, uint32_t a1, uint32_t a2, uint32_t a3, uint32_t b0, uint32_t b1) {
    asm volatile("mma.sync.aligned.m16n8k16.row.col.f32.bf16.bf16.f32 {%0, %1, %2, %3}, {%4, %5, %6, %7}, {%8, %9}, {%0, %1, %2, %3};"
                 : "+f"(c[0]), "+f"(c[1]), "+f"(c[2]), "+f"(c[3]) : "r"(a0), "r"(a1), "r"(a2), "r"(a3), "r"(b0), "r"(b1));
}
__device__ __forceinline__ void mma8(float (&c)[4], uint32_t a0, uint32_t a1, uint32_t b0) {
    asm volatile("mma.sync.aligned.m16n8k8.row.col.f32.bf16.bf16.f32 {%0, %1, %2, %3}, {%4, %5}, {%6}, {%0, %1, %2, %3};"
                 : "+f"(c[0]), "+f"(c[1]), "+f"(c[2]), "+f"(c[3]) : "r"(a0), "r"(a1), "r"(b0));
}
__device__ __forceinline__ void st_async4(uint32_t a, uint32_t bar, uint32_t v0, uint32_t v1, uint32_t v2, uint32_t v3) {
    asm volatile("st.async.weak.shared::cluster.mbarrier::complete_tx::bytes.v4.b32 [%0], {%2, %3, %4, %5}, [%1];" ::"r"(a), "r"(bar), "r"(v0), "r"(v1), "r"(v2), "r"(v3) : "memory");
}
__device__ __forceinline__ void st_async2(uint32_t a, uint32_t bar, uint32_t v0, uint32_t v1) {
    asm volatile("st.async.weak.shared::cluster.mbarrier::complete_tx::bytes.v2.b32 [%0], {%2, %3}, [%1];" ::"r"(a), "r"(bar), "r"(v0), "r"(v1) : "memory");
}
__device__ __forceinline__ float quad_max(float v) { v = fmaxf(v, __shfl_xor_sync(~0u, v, 1)); return fmaxf(v, __shfl_xor_sync(~0u, v, 2)); }
__device__ __forceinline__ float quad_sum(float v) { v += __shfl_xor_sync(~0u, v, 1); return v + __shfl_xor_sync(~0u, v, 2); }
__device__ __forceinline__ float ex2(float v) { float r; asm("ex2.approx.ftz.f32 %0, %1;" : "=f"(r) : "f"(v)); return r; }
__device__ __forceinline__ float rcp(float v) { float r; asm("rcp.approx.ftz.f32 %0, %1;" : "=f"(r) : "f"(v)); return r; }
__device__ __forceinline__ float rsq(float v) { float r; asm("rsqrt.approx.ftz.f32 %0, %1;" : "=f"(r) : "f"(v)); return r; }
__device__ __forceinline__ float gelu2(float u) {
    float z = u * fmaf(u * u, 0.044715f * 0.7978845608028654f, 0.7978845608028654f), t;
    asm("tanh.approx.f32 %0, %1;" : "=f"(t) : "f"(z));
    return fmaf(u, t, u);
}
__device__ __forceinline__ float oct_sum(float v) {
    v += __shfl_xor_sync(~0u, v, 4); v += __shfl_xor_sync(~0u, v, 8); v += __shfl_xor_sync(~0u, v, 16);
    return v;
}

template <int TA, int TB, uint32_t HA, uint32_t HB>
__device__ __forceinline__ void wgmma_n112(float (&d)[56], uint32_t da, uint32_t db, int accumulate) {
    asm volatile("{\n.reg .pred p;\n.reg .b64 a, b;\nmov.b64 a, {%56, %61};\nmov.b64 b, {%57, %62};\nsetp.ne.b32 p, %58, 0;\n"
        "wgmma.mma_async.sync.aligned.m64n112k16.f32.bf16.bf16 {"
        "%0, %1, %2, %3, %4, %5, %6, %7, %8, %9, %10, %11, %12, %13, %14, %15, "
        "%16, %17, %18, %19, %20, %21, %22, %23, %24, %25, %26, %27, %28, %29, %30, %31, "
        "%32, %33, %34, %35, %36, %37, %38, %39, %40, %41, %42, %43, %44, %45, %46, %47, "
        "%48, %49, %50, %51, %52, %53, %54, %55"
        "}, a, b, p, 1, 1, %59, %60;\n}\n"
        : "+f"(d[0]), "+f"(d[1]), "+f"(d[2]), "+f"(d[3]), "+f"(d[4]), "+f"(d[5]), "+f"(d[6]), "+f"(d[7]),
          "+f"(d[8]), "+f"(d[9]), "+f"(d[10]), "+f"(d[11]), "+f"(d[12]), "+f"(d[13]), "+f"(d[14]), "+f"(d[15]),
          "+f"(d[16]), "+f"(d[17]), "+f"(d[18]), "+f"(d[19]), "+f"(d[20]), "+f"(d[21]), "+f"(d[22]), "+f"(d[23]),
          "+f"(d[24]), "+f"(d[25]), "+f"(d[26]), "+f"(d[27]), "+f"(d[28]), "+f"(d[29]), "+f"(d[30]), "+f"(d[31]),
          "+f"(d[32]), "+f"(d[33]), "+f"(d[34]), "+f"(d[35]), "+f"(d[36]), "+f"(d[37]), "+f"(d[38]), "+f"(d[39]),
          "+f"(d[40]), "+f"(d[41]), "+f"(d[42]), "+f"(d[43]), "+f"(d[44]), "+f"(d[45]), "+f"(d[46]), "+f"(d[47]),
          "+f"(d[48]), "+f"(d[49]), "+f"(d[50]), "+f"(d[51]), "+f"(d[52]), "+f"(d[53]), "+f"(d[54]), "+f"(d[55])
        : "r"(da), "r"(db), "r"(accumulate), "n"(TA), "n"(TB), "n"(HA), "n"(HB));
}

template <int TA, int TB, uint32_t HA, uint32_t HB>
__device__ __forceinline__ void wgmma_n184(float (&d)[92], uint32_t da, uint32_t db, int accumulate) {
    asm volatile("{\n.reg .pred p;\n.reg .b64 a, b;\nmov.b64 a, {%92, %97};\nmov.b64 b, {%93, %98};\nsetp.ne.b32 p, %94, 0;\n"
        "wgmma.mma_async.sync.aligned.m64n184k16.f32.bf16.bf16 {"
        "%0, %1, %2, %3, %4, %5, %6, %7, %8, %9, %10, %11, %12, %13, %14, %15, "
        "%16, %17, %18, %19, %20, %21, %22, %23, %24, %25, %26, %27, %28, %29, %30, %31, "
        "%32, %33, %34, %35, %36, %37, %38, %39, %40, %41, %42, %43, %44, %45, %46, %47, "
        "%48, %49, %50, %51, %52, %53, %54, %55, %56, %57, %58, %59, %60, %61, %62, %63, "
        "%64, %65, %66, %67, %68, %69, %70, %71, %72, %73, %74, %75, %76, %77, %78, %79, "
        "%80, %81, %82, %83, %84, %85, %86, %87, %88, %89, %90, %91"
        "}, a, b, p, 1, 1, %95, %96;\n}\n"
        : "+f"(d[0]), "+f"(d[1]), "+f"(d[2]), "+f"(d[3]), "+f"(d[4]), "+f"(d[5]), "+f"(d[6]), "+f"(d[7]),
          "+f"(d[8]), "+f"(d[9]), "+f"(d[10]), "+f"(d[11]), "+f"(d[12]), "+f"(d[13]), "+f"(d[14]), "+f"(d[15]),
          "+f"(d[16]), "+f"(d[17]), "+f"(d[18]), "+f"(d[19]), "+f"(d[20]), "+f"(d[21]), "+f"(d[22]), "+f"(d[23]),
          "+f"(d[24]), "+f"(d[25]), "+f"(d[26]), "+f"(d[27]), "+f"(d[28]), "+f"(d[29]), "+f"(d[30]), "+f"(d[31]),
          "+f"(d[32]), "+f"(d[33]), "+f"(d[34]), "+f"(d[35]), "+f"(d[36]), "+f"(d[37]), "+f"(d[38]), "+f"(d[39]),
          "+f"(d[40]), "+f"(d[41]), "+f"(d[42]), "+f"(d[43]), "+f"(d[44]), "+f"(d[45]), "+f"(d[46]), "+f"(d[47]),
          "+f"(d[48]), "+f"(d[49]), "+f"(d[50]), "+f"(d[51]), "+f"(d[52]), "+f"(d[53]), "+f"(d[54]), "+f"(d[55]),
          "+f"(d[56]), "+f"(d[57]), "+f"(d[58]), "+f"(d[59]), "+f"(d[60]), "+f"(d[61]), "+f"(d[62]), "+f"(d[63]),
          "+f"(d[64]), "+f"(d[65]), "+f"(d[66]), "+f"(d[67]), "+f"(d[68]), "+f"(d[69]), "+f"(d[70]), "+f"(d[71]),
          "+f"(d[72]), "+f"(d[73]), "+f"(d[74]), "+f"(d[75]), "+f"(d[76]), "+f"(d[77]), "+f"(d[78]), "+f"(d[79]),
          "+f"(d[80]), "+f"(d[81]), "+f"(d[82]), "+f"(d[83]), "+f"(d[84]), "+f"(d[85]), "+f"(d[86]), "+f"(d[87]),
          "+f"(d[88]), "+f"(d[89]), "+f"(d[90]), "+f"(d[91])
        : "r"(da), "r"(db), "r"(accumulate), "n"(TA), "n"(TB), "n"(HA), "n"(HB));
}

template <uint32_t HB>
__device__ __forceinline__ void wgmma_rs_n184(float (&d)[92], uint32_t a0, uint32_t a1, uint32_t db) {
    asm volatile("{\n.reg .b64 b;\nmov.b64 b, {%94, %96};\n"
        "wgmma.mma_async.sync.aligned.m64n184k16.f32.bf16.bf16 {"
        "%0, %1, %2, %3, %4, %5, %6, %7, %8, %9, %10, %11, %12, %13, %14, %15, "
        "%16, %17, %18, %19, %20, %21, %22, %23, %24, %25, %26, %27, %28, %29, %30, %31, "
        "%32, %33, %34, %35, %36, %37, %38, %39, %40, %41, %42, %43, %44, %45, %46, %47, "
        "%48, %49, %50, %51, %52, %53, %54, %55, %56, %57, %58, %59, %60, %61, %62, %63, "
        "%64, %65, %66, %67, %68, %69, %70, %71, %72, %73, %74, %75, %76, %77, %78, %79, "
        "%80, %81, %82, %83, %84, %85, %86, %87, %88, %89, %90, %91"
        "}, {%92, %93, %95, %95}, b, 1, 1, 1, 0;\n}\n"
        : "+f"(d[0]), "+f"(d[1]), "+f"(d[2]), "+f"(d[3]), "+f"(d[4]), "+f"(d[5]), "+f"(d[6]), "+f"(d[7]),
          "+f"(d[8]), "+f"(d[9]), "+f"(d[10]), "+f"(d[11]), "+f"(d[12]), "+f"(d[13]), "+f"(d[14]), "+f"(d[15]),
          "+f"(d[16]), "+f"(d[17]), "+f"(d[18]), "+f"(d[19]), "+f"(d[20]), "+f"(d[21]), "+f"(d[22]), "+f"(d[23]),
          "+f"(d[24]), "+f"(d[25]), "+f"(d[26]), "+f"(d[27]), "+f"(d[28]), "+f"(d[29]), "+f"(d[30]), "+f"(d[31]),
          "+f"(d[32]), "+f"(d[33]), "+f"(d[34]), "+f"(d[35]), "+f"(d[36]), "+f"(d[37]), "+f"(d[38]), "+f"(d[39]),
          "+f"(d[40]), "+f"(d[41]), "+f"(d[42]), "+f"(d[43]), "+f"(d[44]), "+f"(d[45]), "+f"(d[46]), "+f"(d[47]),
          "+f"(d[48]), "+f"(d[49]), "+f"(d[50]), "+f"(d[51]), "+f"(d[52]), "+f"(d[53]), "+f"(d[54]), "+f"(d[55]),
          "+f"(d[56]), "+f"(d[57]), "+f"(d[58]), "+f"(d[59]), "+f"(d[60]), "+f"(d[61]), "+f"(d[62]), "+f"(d[63]),
          "+f"(d[64]), "+f"(d[65]), "+f"(d[66]), "+f"(d[67]), "+f"(d[68]), "+f"(d[69]), "+f"(d[70]), "+f"(d[71]),
          "+f"(d[72]), "+f"(d[73]), "+f"(d[74]), "+f"(d[75]), "+f"(d[76]), "+f"(d[77]), "+f"(d[78]), "+f"(d[79]),
          "+f"(d[80]), "+f"(d[81]), "+f"(d[82]), "+f"(d[83]), "+f"(d[84]), "+f"(d[85]), "+f"(d[86]), "+f"(d[87]),
          "+f"(d[88]), "+f"(d[89]), "+f"(d[90]), "+f"(d[91])
        : "r"(a0), "r"(a1), "r"(db), "r"(0), "n"(HB));
}

struct Ring {
    uint32_t slot, ph;
    __device__ __forceinline__ void next() { if (++slot == NSLOT) { slot = 0; ph ^= 1; } }
    __device__ __forceinline__ void next2() { ph ^= slot == 5; slot = __byte_perm(0x06030201u, 0x00040005u, 0x7770 + slot); }
};
struct Slot {
    uint32_t dst, bar, ph;
    __device__ __forceinline__ void next(uint32_t bars) {
        dst += SLOT; bar += 8;
        if (bar == bars + 8 * NSLOT) { dst -= NSLOT * SLOT; bar = bars; ph ^= 1; }
    }
};
__device__ __forceinline__ uint32_t xslot(int i) { return __byte_perm(0x04130e0cu, 0x00130e0cu, 0x7770 + i); }
__device__ __forceinline__ uint32_t wslot(int i) { return __byte_perm(0x06001510u, 0x00151009u, 0x7770 + i); }

constexpr uint32_t HI_SW = desc_hi(1024, 1);

struct Mma {
    uint32_t bars, rel;
    bool lead;
    int wg, w;
    Ring r;
    uint32_t prev;
    __device__ __forceinline__ void release(uint32_t s) { if (lead) mbar_arrive4_remote(rel + B_EMPTY + 8 * s); }
    template <bool G1>
    __device__ __forceinline__ void run(float (&a)[56], int n, int first, int last, int lag, int accumulate, int ts) {
#pragma unroll 1
        for (int i = 0; i < n; i++) {
            if (lag && i == (wg ? n - lag : -1)) bar_sync(7, 256);
            const uint32_t s = r.slot;
            mbar_wait(bars + B_FULL + 8 * s, r.ph);
            if (G1) r.next(); else r.next2();
            TS0(G1 ? 2 : 8, ts + i + wg * 68);
            const uint32_t dB = s * (SLOT >> 4), dA = dB + wg * 512;
            wg_fence();
#pragma unroll
            for (int k = 0; k < 4; k++) {
                wgmma_n112<1, 1, HI_SW, desc_hi(G1 ? 256 : 1024, 0)>(a, dA + desc_lo(k * 2048, 8192), dB + desc_lo(16384 + k * (G1 ? SLAB : 256), 128), k > 0 || accumulate || i > 0);
                if (k == 1) {
                    wg_commit(); wg_wait<1>();
                    if ((uint32_t)(i - first) < (uint32_t)(last - first)) release(prev);
                    if (lag && i == (wg ? -1 : n - 1)) bar_arrive(7, 256);
                }
            }
            wg_commit();
            prev = s;
        }
    }
    __device__ __forceinline__ void run_o(float (&a)[56]) {
#pragma unroll 1
        for (int i = 0; i < 2; i++) {
            const uint32_t s = r.slot, dB = s * (SLOT >> 4), dA = dB + wg * 512;
            mbar_wait(bars + B_FULL + 8 * s, r.ph);
            TS0(8, 48 + 2 * i + wg * 68);
            wg_fence();
#pragma unroll
            for (int k = 0; k < 7; k++) {
                if (k == 3) { mbar_wait(bars + B_FULL + 8 * s + 8, r.ph); wg_fence(); }
                wgmma_n112<0, 1, desc_hi(128, 0), desc_hi(256, 0)>(a, dA + desc_lo(k * 2048 + (k > 3) * (SLOT - HALF), k == 3 ? SLOT - 6144 : 1024),
                                                                   dB + desc_lo(16384 + k * SLAB + (k > 2) * (SLOT - 3 * SLAB), 128), k > 0 || i > 0);
                if (k & 1) wg_commit();
                if (k == 1) { wg_wait<1>(); if (i) release(prev); }
                if (k == 5) { wg_wait<1>(); release(s); }
            }
            wg_commit();
            prev = s + 1;
            r.slot++; r.next2();
        }
    }
};

__global__ void __cluster_dims__(2, 1, 1) __launch_bounds__(NTHREADS, 1)
fused_kernel(const __nv_bfloat16* __restrict__ x, const __nv_bfloat16* __restrict__ b1, const __nv_bfloat16* __restrict__ b2, const __nv_bfloat16* __restrict__ wo, __nv_bfloat16* out, Scratch* G,
             const __nv_bfloat16* __restrict__ w1, const __nv_bfloat16* __restrict__ w2,
             const __grid_constant__ Params P) {
    extern __shared__ __align__(1024) uint8_t smem[];
    const uint32_t sbase = (uint32_t)__cvta_generic_to_shared(smem);
    const uint32_t bars = sbase + OFF_BAR;
    const uint32_t rank = blockIdx.x & 1, pr = blockIdx.x >> 1;
    const uint32_t row0 = blockIdx.x * 16;
    if (threadIdx.x == 0) {
        TS(15, 0);
        mbar_init(bars + B_ROW, 1);
        asm volatile("fence.mbarrier_init.release.cluster;" ::: "memory");
        bulk_load(sbase + OFF_Y, x + row0 * D_, TILEB, bars + B_ROW);
        mbar_expect(bars + B_ROW, TILEB);
        TS(1, 97);
    }
    const int lane = threadIdx.x & 31;
    const int warp = __shfl_sync(~0u, threadIdx.x >> 5, 0), w = warp & 3;
    if (elect()) {
        const uint32_t first = bars + warp * 24, count = warp < 8 ? 1 : warp == 8 ? 2 : 16;
#pragma unroll
        for (int i = 0; i < 3; i++) mbar_init(first + 8 * i, count);
        asm volatile("fence.mbarrier_init.release.cluster;" ::: "memory");
    }
    __syncwarp();
    asm volatile("barrier.cluster.arrive.relaxed.aligned;" ::: "memory");
    const uint32_t pv = pr < 4 ? pr * 8 + 36 : pr - 4 + (max((int)pr - 33, 0) * 37 >> 8);
    const uint32_t gp = (pv + 4) & 7, hp = pv >> 3;
    const uint32_t tb = gp * 2 + rank, c = hp * 16 + tb;
    const bool has_g1 = gp > 0;
    const uint32_t nt1 = hp & 3, ft = max((int)gp - 1, 0) * 2 + (hp >> 2);
    const uint32_t nt2 = tb & 3, mt = (gp & 2) * 4 + hp, ks = gp >> 2;
    asm volatile("barrier.cluster.wait.aligned;" ::: "memory");

    if (warp == 8) {
        uint32_t kw = gp % ROT * (512 / ROT), kx;
        if (elect()) {
            mbar_expect(bars + B_QFULL, QSLOT);
            tma3d(sbase + xslot(0) * 8192, &P.tmX, bars + B_QFULL, kw, tb * 64, 0);
            tma3d_pair(sbase + wslot(0) * 8192 + rank * 12288, &P.tmWqkv, bars + B_QFULL, (hp * 56) & ~15, kw + rank * 32, 0);
            TS(1, 23);
            uint32_t due = (uint32_t)clock() + PACE, ep = ld_relaxed(&G->epoch[c]);
            uint32_t spins = sbase == (rank << 24 | SMEM0) ? 0 : SPIN_LIMIT;
#pragma unroll 1
            for (int i = 1; i < 8; i++) {
                kx = kw; kw += 64;
                if (i >= 5) mbar_wait_bounded(bars + B_QEMPTY + 8 * (i - 5), 0, spins);
                else { while ((int)((uint32_t)clock() - due) < 0) {} due += PACE; }
                if (kw == D_) kw = 0;
                if (i < 4) kx = kw;
                const int ix = i - (i > 4);
                if (i < 7) mbar_expect(bars + B_QFULL + 8 * i, QSLOT);
                if (i != 4) tma3d(sbase + xslot(ix) * 8192, &P.tmX, bars + B_QFULL + 8 * ix, kx, tb * 64, 0);
                if (i == min(5 + gp / ROT, 7)) mbar_wait_bounded(bars + B_CS, 0, spins);
                if (i < 7) tma3d_pair(sbase + wslot(i) * 8192 + rank * 12288, &P.tmWqkv, bars + B_QFULL + 8 * i, (hp * 56) & ~15, kw + rank * 32, 0);
            }
            ep++;
            Slot r{sbase, bars, 0};
            if (has_g1) {
                const uint8_t* src = G->H[nt1][rank * 16];
                const int row = rank * 1024;
                mbar_arrive(bars + B_FULL + 48); mbar_arrive16(bars + B_EMPTY + 48);
                mbar_expect(bars + B_FULL, 16384 + TILEB);
                tma3d(sbase, &P.tmW1, bars + B_FULL, 0, row, ft * 2);
                wait_flag(G->flag[1] + rank * 2, 20 * ep, spins);
                TS(1, 16);
#pragma unroll 1
                for (int j = 64;; j += 64) {
                    bulk_load(r.dst + 16384, src, TILEB, r.bar + B_FULL);
                    src += TILEB;
                    r.next(bars);
                    if (j == 1024) break;
                    mbar_wait_bounded(r.bar + B_EMPTY, r.ph, spins);
                    if (j < 14 * 64) TS(2, 146 + j / 64);
                    mbar_expect(r.bar + B_FULL, 16384 + TILEB);
                    tma3d(r.dst, &P.tmW1, r.bar + B_FULL, 0, row + j, ft * 2);
                }
#pragma unroll
                for (int i = 0; i < 4; i++) mbar_expect(bars + B_X + 8 * i, (i & 1) ? 3072 : 4096);
            } else {
                due = (uint32_t)clock();
#pragma unroll 1
                for (int j = PF0; j < PF1; j++) {
                    asm volatile("cp.async.bulk.prefetch.L2.global [%0], %1;" ::"l"(w1 + (rank * 1024 + j * 64 + hp * 8) * F_), "n"(16 * F_) : "memory");
                    due += PF;
                    while ((int)((uint32_t)clock() - due) < 0) {}
                }
            }
            const uint8_t *so = G->O[mt][ks * 4] + rank * HALF, *sw = G->Wo[nt2][ks * 4];
            wait_flag2(G->flag[16 + mt], 8 * ep, G->flag[0], 16 * ep, spins);
            TS(4, 18);
#pragma unroll 1
            for (int j = 0; j < 4 * TILEB; j += TILEB) {
                mbar_wait_bounded(r.bar + B_EMPTY, r.ph, spins);
                mbar_expect(r.bar + B_QFULL, TILEB);
                bulk_load_pair(r.dst + rank * 8192, so + j, HALF, r.bar + B_QFULL);
                bulk_load(r.dst + 16384, sw + j, (r.bar & 8) ? TILEB : 3 * SLAB, r.bar + B_FULL);
                r.next(bars);
            }
            if (!has_g1) {
#pragma unroll 1
                for (int j = PG0; j < PG1; j++)
                    asm volatile("cp.async.bulk.prefetch.L2.global [%0], %1;" ::"l"(w2 + (rank * 896 + j * 128 + hp * 8) * S_), "n"(16 * S_) : "memory");
            }
            Ring q{has_g1 ? 2u : 6u, has_g1};
#pragma unroll 1
            for (int j = 0; j < 14 * 128; j += 128) {
                mbar_wait_bounded(bars + B_EMPTY + 8 * q.slot, q.ph, spins);
                TS(8, 176 + j / 128);
                tma2d_pair(sbase + q.slot * SLOT + rank * 8192, &P.tmW2, bars + B_FULL + 8 * q.slot, mt * 128 + rank * 64, ks * 896 + j - (j < 896 ? 0 : 832));
                q.next2();
            }
            mbar_wait_bounded(bars + B_END, 0, spins);
        }
    } else if (warp > 8) {
        const uint32_t ep = ld_relaxed(&G->epoch[c]) + 1;
        {
            uint2* cs = G->colsum[hp][0];
            if (w == 2) {
                bar_sync(6, 160);
                TS(1, 8);
                if (elect()) {
                    fence_async_shared();
#pragma unroll
                    for (int i = 0; i < 4; i++) bulk_store(G->H[i][0] + row0 * (SLAB / 16), sbase + OFF_X + i * (SLAB + 64), SLAB);
                    bulk_flush();
                    TS(1, 99);
                    signal(G->flag[1] + (row0 >> 10) * 2 + ((row0 & 1023) >= 320));
                    TS(1, 3);
                }
                __syncwarp();
            } else {
                const uint32_t q4 = lane >> 3, word = rank * 16 + (w & 2) * 4 + (lane & 7);
                uint32_t src = (sbase + wslot(gp / ROT) * 8192 + word * 4 + (q4 >> 1) * 12288 + (q4 & 1) * 2048) ^ (q4 * 288);
                mbar_wait(bars + B_QFULL + 8 * (gp / ROT), 0);
                if (w == 1) TS(1, 66);
#pragma unroll kCsu
                for (int i = 0; i < 96; i += 32) {
                    uint32_t v[16];
#pragma unroll
                    for (int k = 0; k < 16; k++) v[k] = __float_as_uint(lds1f((src ^ ((k & 7) * 144)) + (k >> 3) * 1024));
                    float s0 = bf_lo(v[0]), s1 = bf_hi(v[0]), s2 = bf_lo(v[1]), s3 = bf_hi(v[1]);
#pragma unroll
                    for (int k = 2; k < 16; k += 2) { s0 += bf_lo(v[k]); s1 += bf_hi(v[k]); s2 += bf_lo(v[k + 1]); s3 += bf_hi(v[k + 1]); }
                    s0 += s2; s1 += s3;
                    s0 += __shfl_xor_sync(~0u, s0, 8); s1 += __shfl_xor_sync(~0u, s1, 8);
                    s0 += __shfl_xor_sync(~0u, s0, 16); s1 += __shfl_xor_sync(~0u, s1, 16);
                    if (lane < 8) cs[gp * 96 + i + word] = make_uint2(tag(__float_as_uint(s0), 1, ep), __float_as_uint(s1));
                    src += 4096;
                }
                if (elect()) mbar_arrive(bars + B_CS);
                if (w == 1) TS(1, 24);
            }
            bar_sync(1, 96);
            if (REC_NS) __nanosleep(REC_NS);
            const int i0 = threadIdx.x - 288;
            uint2 u[7];
            uint4 sv;
            uint32_t bad;
            do {
                sv = ld_relaxed4(G->stat + tb * 128 + (i0 & 63) * 2);
                bad = or_diff(sv.x ^ ep, sv.z, ep);
#pragma unroll
                for (int i = 0; i < 7; i++) { u[i] = ld_relaxed2(cs + i * 96 + i0); bad = or_diff(bad, u[i].x, ep); }
            } while (bad & 1);
            if (w < 3) sts4(sbase + OFF_ST + i0 * 16, sv);
#pragma unroll
            for (int e = 0; e < 2; e++) {
                float f = 0.f;
#pragma unroll
                for (int i = 0; i < 7; i++) f += __uint_as_float(e ? u[i].y : u[i].x);
                const uint32_t hi = pack2(f, f);
                sts4(sbase + OFF_X + i0 * 32 + e * 16, make_uint4(hi, pack2(f - bf_hi(hi), f - bf_hi(hi)), 0, 0));
            }
            asm volatile("st.shared.u32 [%0], %1;" ::"r"(bars + 8 * NBAR), "r"(ep) : "memory");
            fence_async_shared();
            __syncwarp();
            bar_arrive(8, 224); bar_arrive(9, 224);
            TS(1, 90 + w);
        }
        const uint8_t* src = G->U[nt2][ks * 14];
        uint32_t spins = 0;
        if (w < 3) {
            uint32_t bad;
            if (w == 1) {
                if (elect()) {
                    wait_flag(G->flag[1] + rank * 2 + 1, 44 * ep, spins);
                    mbar_arrive16(bars + B_EMPTY + 8 * 5);
                    TS(1, 96);
                }
                __syncwarp();
                if (!has_g1) { bar_sync(5, 288); if (elect()) signal(G->flag[0]); __syncwarp(); TS(2, 26); }
            } else {
                bar_sync(3, 288);
                __nanosleep(HALO_NS);
                uint4 v[7];
                do {
                    bad = 0;
#pragma unroll
                    for (int i = 0; i < 7; i++) { v[i] = ld_relaxed4(G->halo[c - (tb > 0)] + i * 512 + lane * 16); bad = or_diff(bad, v[i].x, ep); }
                } while (bad & 1);
#pragma unroll
                for (int i = 0; i < 7; i++) sts4(sbase + OFF_X + i * 512 + lane * 16, v[i]);
                __syncwarp();
                if (elect()) mbar_arrive(bars + B_HALO);
                TS(2, 21);
            }
            mbar_wait(bars + B_HALO, 0);
            uint32_t slot = (has_g1 ? 16 % NSLOT : 0) + w - 1, ph = ~0u;
#pragma unroll 1
            for (int i = w - 1; i < 18;) {
                const uint32_t d0 = sbase + slot * SLOT + (i < 4 ? 0 : 16384), d1 = d0 + (i < 4 ? 8192 : HALF), landed = bars + B_QFULL + 8 * slot;
                mbar_wait(landed, (ph >> slot) & 1);
                ph ^= 1 << slot;
                if (i < 8) TS(4, 82 + i);
                if (i >= 4) TS(8, 156 + i);
                bad = 0;
#pragma unroll
                for (int k = 0; k < 14; k++) bad = or_diff(bad, __float_as_uint(lds1f((k < 7 ? d0 : d1) + k % 7 * 1024 + lane * 32 + (lane >> 2) * 4)), ep);
                if (__any_sync(~0u, bad & 1)) {
                    if (elect()) {
                        const uint8_t* cur = (i < 4 ? G->O[mt][ks * 4] : src - 4 * TILEB) + i * TILEB;
                        fence_async_shared();
                        mbar_expect(landed, TILEB);
                        bulk_load(d0, cur, HALF, landed);
                        bulk_load(d1, cur + HALF, HALF, landed);
                    }
                    TS(4, i < 4 ? 94 : 95);
                } else {
                    if (elect()) mbar_expect(landed + (B_FULL - B_QFULL), i < 4 ? (2 + w) * SLAB : 16384);
                    i += __byte_perm(0x03020202u, 0x00010202u, 0x7770 + slot);
                    slot = __byte_perm(0x05060302u, 0x00040100u, 0x7770 + slot);
                }
            }
        } else {
            bar_sync(2, 288);
            if (elect()) bulk_store(out + row0 * D_, sbase + OFF_Y, TILEB);
            __syncwarp();
            bar_sync(4, 288);
            if (elect()) {
                fence_async_shared();
                bulk_store(G->O[tb][hp], sbase + OFF_X, TILEB);
                bulk_flush();
                TS(2, 7);
                mbar_arrive_remote(mapa(bars + B_FREE, rank ^ 1));
                mbar_arrive(bars + B_FREE);
                hint(G->flag[16 + tb]);
                signal(G->flag[16 + (row0 >> 7)] + 1);
                TS(2, 22);
            }
            __syncwarp();
            uint32_t late = ~0u;
            const uint32_t* hints = G->flag[8 + nt2 * 2 + ks] + lane;
            mbar_wait(bars + (has_g1 ? B_X : B_FREE), 0);
            Ring r{has_g1 ? 2u : 6u, has_g1};
#pragma unroll 1
            for (int i = 0; i < 14; i++) {
                while ((late >> i) & 1) late = __ballot_sync(~0u, ld_relaxed(hints) != 2 * ep) & 127;
                if (i == 0) TS(4, 17);
                mbar_wait(bars + B_EMPTY + 8 * r.slot, r.ph);
                TS(8, 192 + i);
                if (elect()) {
                    mbar_expect(bars + B_QFULL + 8 * r.slot, TILEB);
                    bulk_load(sbase + r.slot * SLOT + 16384, src, TILEB, bars + B_QFULL + 8 * r.slot);
                }
                src += TILEB; r.next2();
                if (UGAP && i < UGAPN) { const uint32_t t0 = clock(); while ((uint32_t)clock() - t0 < UGAP) {} }
            }
            if (elect()) {
                wait_flag(G->flag[16 + mt] + 1, 8 * ep, spins);
                mbar_arrive(bars + B_ROW);
                TS(2, 27);
                G->epoch[c] = ep;
            }
        }
    } else {
        const int wg = warp >> 2;
        Mma M{bars, mapa(bars, rank ^ (lane & 1)), (threadIdx.x & 127) < 2, wg, w, Ring{0, 0}, 0};
        const int r = lane >> 2, t = lane & 3;
        uint32_t ep;
        const uint32_t bias0 = ld_u16(b1 + ft * 128 + warp * 16 + r), bias1 = ld_u16(b1 + ft * 128 + warp * 16 + r + 8);
        if (wg == 1) {
            ep = ld_relaxed(&G->epoch[c]);
            const int r16 = w * 4 + t, nt = (r + 2 * t) & 3, half = ((r + 2 * t) >> 2) & 1;
            const uint32_t row = sbase + OFF_Y + r16 * (2 * D_), part = row + nt * 224 + half * 112;
            const uint32_t hb = sbase + OFF_X + nt * (SLAB + 64) + r16 * 16 + (half ^ (row0 >> 10)) * (7 * 256);
            mbar_wait(bars + B_ROW, 0);
            TS0(1, 67);
            const float x0 = bf_lo(__float_as_uint(lds1f(row)));
            float d[56], s0 = 0.f, s1 = 0.f, q0 = 0.f, q1 = 0.f;
#pragma unroll
            for (int i = 0; i < 7; i++) {
                const uint4 v = lds4(part + i * 16);
                const uint32_t u[4] = {v.x, v.y, v.z, v.w};
#pragma unroll
                for (int k = 0; k < 4; k++) {
                    const float d0 = d[8 * i + 2 * k] = bf_lo(u[k]) - x0, d1 = d[8 * i + 2 * k + 1] = bf_hi(u[k]) - x0;
                    s0 += d0; s1 += d1; q0 = fmaf(d0, d0, q0); q1 = fmaf(d1, d1, q1);
                }
            }
            const float md = oct_sum(s0 + s1) * (1.f / D_), var = fmaf(-md, md, oct_sum(q0 + q1) * (1.f / D_)), nmean = -(x0 + md);
            const float rstd = rsq(var + LN_EPS);
            const float sc = rstd * rsq(fmaf(var * rstd, rstd, LN_EPS)), nb = -md * sc;
            if (lane < 4) G->stat[row0 + r16] = make_uint2(tag(__float_as_uint(rstd), 1, ~ep), pack2(nmean, nmean - bf_hi(pack2(nmean, nmean))));
#pragma unroll
            for (int i = 0; i < 7; i++) {
                uint32_t u[4];
#pragma unroll
                for (int k = 0; k < 4; k++) u[k] = pack2(fmaf(d[8 * i + 2 * k], sc, nb), fmaf(d[8 * i + 2 * k + 1], sc, nb));
                sts4(hb + i * 256, make_uint4(u[0], u[1], u[2], u[3]));
            }
            TS0(1, 25);
            bar_arrive(6, 160);
        }
        const uint32_t kv = sbase + OFF_X + (w * 2 + wg) * KV + lane * 16;
        uint32_t q[8][2], k0[7], k1[7], v0[7];
        {
            float acc[92];
#pragma unroll 1
            for (int kb = 0; kb < 7; kb++) {
                const bool held = kb == (wg ? 7 - HOLD : -1);
                if (held) { wg_wait<0>(); M.release(4 - HOLD); bar_sync(7, 256); }
                mbar_wait(bars + B_QFULL + 8 * kb, 0);
                TS0(1, 68 + wg * 7 + kb);
                const uint32_t dA = (xslot(kb) + wg) * 512, dB = wslot(kb) * 512 + (hp & 1);
                wg_fence();
#pragma unroll
                for (int k = 0; k < 4; k++) {
                    wgmma_n184<0, 1, HI_SW, HI_SW>(acc, dA + desc_lo(k * 32, 16), dB + desc_lo((k & 1) * 2048 + (k >> 1) * 12288, 4096), k > 0 || kb > 0);
                    if (k == 0) { wg_commit(); wg_wait<1>(); if (kb > 0 && !held) M.release(kb - 3); }
                }
                wg_commit();
            }
            if (wg == 0 && !LATEREL) bar_arrive(7, 256);
            bar_sync(8 + wg, 224);
            ep = __float_as_uint(lds1f(bars + 8 * NBAR));
            const uint32_t st = sbase + OFF_ST + (w * 32 + r * 2 + wg) * 8;
            const uint2 s0 = lds2(st), s1 = lds2(st + 128);
            const uint32_t a0 = t < 2 ? s0.y : 0, a1 = t < 2 ? s1.y : 0;
            wg_fence();
            wgmma_rs_n184<desc_hi(128, 0)>(acc, a0, a1, desc_lo(OFF_X, 0) + (hp & 1) * 8);
            wg_commit();
            if (wg == 0 && LATEREL) bar_arrive(7, 256);
            wg_wait<1>();
            M.release(4);
            wg_wait<0>();
            pin(acc);
            TS0(1, 4 + 7 * wg);
            uint32_t hi[14];
#pragma unroll
            for (int p = 2; p >= 0; p--) {
                const float f = p == 0 ? 0.1889822365046136f * 1.4426950408889634f : p, r0 = __uint_as_float(s0.x) * f, r1 = __uint_as_float(s1.x) * f;
#pragma unroll
                for (int g = 0; g < 7; g++) {
                    const int a = (p * 8 + g) * 4;
                    const uint32_t lo2 = pack2(acc[a] * r0, acc[a + 1] * r0), hi2 = pack2(acc[a + 2] * r1, acc[a + 3] * r1);
                    if (p == 0) { q[g][0] = lo2; q[g][1] = hi2; } else { hi[(p - 1) * 7 + g] = hi2; }
                    if (p == 1) { k0[g] = lo2; k1[g] = hi2; }
                    if (p == 2) v0[g] = lo2;
                }
                if (p == 1) {
#pragma unroll
                    for (int i = 0; i < 3; i++) stsm4(kv + 2 * KV + i * 512, hi[4 * i], hi[4 * i + 1], hi[4 * i + 2], hi[4 * i + 3]);
                    stsm2(kv + 2 * KV + 1536, hi[12], hi[13]);
                    if (w == 3) {
#pragma unroll
                        for (int i = 0; i < 14; i++) stg1(G->halo[c] + wg * KV + lane * 4 + i * 128, tag(hi[i], t == 0, ep));
                    }
                    bar_arrive(3, 288);
                }
            }
#pragma unroll
            for (int j = 0; j < 2; j++) { q[7][j] = t < 2 ? 0u : q[3][j]; q[3][j] = t < 2 ? q[3][j] : 0u; }
#pragma unroll
            for (int g = 0; g < 7; g++) v0[g] = transpose8(v0[g]);
        }
        TS0(1, 9 + 11 * wg);
        float a[56];
#pragma unroll
        for (int i = 0; i < 56; i++) asm volatile("" : "=f"(a[i]));
        if (__builtin_expect(!has_g1, 0)) {
            const int g = min(lane >> 1, 13), nt = rank * 2 + wg;
            const uint4* src = (const uint4*)(wo + (hp * 56 - (hp & 1) * 8 + w * 16 + (lane & 1)) * D_ + nt * 112) + g;
            uint4 v[8];
#pragma unroll
            for (int i = 0; i < 8; i++) v[i] = __ldg(src + i * (D_ / 4));
#pragma unroll
            for (int i = 0; i < 8; i++) ((uint4*)G->Wo[nt][hp])[w * (SLAB / 16) + g * 16 + (lane & 1) + 2 * i] = v[i];
            bar_arrive(5, 288);
        }
        M.run<true>(a, has_g1 ? PAUSE : 0, 1, 16, 0, 0, 32);
        {
            uint32_t kp[8], vv[14];
            TS0(2, 140 + wg);
            mbar_wait(bars + B_HALO, 0);
            TS0(2, 142 + wg);
            ldsm4(kp, kv); ldsm4(kp + 4, kv + (lane < 24 ? 512 : 0));
            const uint32_t va = kv + 896 + (lane & 8) * (2 * KV / 8 - 16) - (lane & 16) * 8;
            ldsm4t(vv, va); ldsm4t(vv + 4, va + 256); ldsm4t(vv + 8, va + 512); ldsm2t(vv + 12, va + 768);
            const bool e0 = 2 * t > r, e1 = 2 * t >= r;
            const uint32_t mk = (e0 ? 0xffffu : 0u) | (e1 ? 0xffff0000u : 0u);
            wg_wait<0>();
            pin(a);
            if (has_g1) M.release(M.prev);
            TS0(2, 144 + wg);
            bar_sync(2, 288);
            mbar_wait(bars + B_HALO, 0);
            TS0(2, 12 + 16 * wg);
            float sv[2][4];
#pragma unroll
            for (int h = 0; h < 2; h++) {
                const int ga = h * 4, gb = h * 4 + 1, gc = h * 4 + 2, gd = h * 4 + 3;
                float s[3][4] = {};
                mma16(s[0], q[ga][0], q[ga][1], q[gb][0], q[gb][1], kp[ga], kp[gb]);
                mma16(s[1], q[ga][0], q[ga][1], q[gb][0], q[gb][1], k0[ga], k0[gb]);
                mma16(s[2], q[ga][0], q[ga][1], q[gb][0], q[gb][1], k1[ga], k1[gb]);
                mma16(s[0], q[gc][0], q[gc][1], q[gd][0], q[gd][1], kp[gc], kp[gd]);
                mma16(s[1], q[gc][0], q[gc][1], q[gd][0], q[gd][1], k0[gc], k0[3]);
                mma16(s[2], q[gc][0], q[gc][1], q[gd][0], q[gd][1], k1[gc], k1[3]);
                if ((tb | w) == 0) s[0][0] = s[0][1] = -1e30f;
                sv[h][0] = e0 ? s[0][0] : s[1][0];
                sv[h][1] = e1 ? s[0][1] : s[1][1];
                sv[h][2] = e0 ? s[1][2] : s[2][2];
                sv[h][3] = e1 ? s[1][3] : s[2][3];
            }
            uint32_t pp[2][2];
#pragma unroll
            for (int i = 0; i < 4; i++) {
                float* v = &sv[i >> 1][(i & 1) * 2];
                const float m = quad_max(fmaxf(v[0], v[1]));
                const float p0 = ex2(v[0] - m), p1 = ex2(v[1] - m);
                const float inv = rcp(quad_sum(p0 + p1));
                pp[i >> 1][i & 1] = pack2(p0 * inv, p1 * inv);
            }
            uint32_t o[8][2];
#pragma unroll
            for (int i = 0; i < 8; i++) {
                const int h = i >> 2, g = i - h;
                float d[4] = {};
                mma16(d, pp[h][0] & mk, 0u, 0u, pp[h][1] & ~mk, vv[2 * g], vv[2 * g + 1]);
                mma8(d, pp[h][0] & ~mk, pp[h][1] & mk, v0[g]);
                o[i][0] = pack2(d[0], d[1]); o[i][1] = pack2(d[2], d[3]);
            }
            if (t >= 2) { o[3][0] = o[4][0]; o[3][1] = o[4][1]; }
            const int word = wg * 4 + t - (w & 1) * 4 - (r >> 2);
#pragma unroll
            for (int i = 0; i < 8; i++) { o[i][0] = tag(o[i][0], word == 0, ep); o[i][1] = tag(o[i][1], word == 2, ep); }
            const uint32_t dst = sbase + OFF_X + (w >> 1) * HALF + ((w & 1) * 32 + (lane & 15) * 2 + wg) * 16 + (lane >> 4) * 1024;
            stsm4(dst, o[0][0], o[0][1], o[1][0], o[1][1]);
            stsm4(dst + 2048, o[2][0], o[2][1], o[3][0], o[3][1]);
            stsm4(dst + 4096, o[5][0], o[5][1], o[6][0], o[6][1]);
            stsm2(dst + 6144, o[7][0], o[7][1]);
            if (ENDBAR) bar_sync(4, 288); else bar_arrive(4, 288);
            TS0(2, 10 + 19 * wg);
        }
        if (has_g1) {
            M.run<true>(a, 16 - PAUSE, 1, 16, LAG1, 1, 32 + PAUSE);
            mbar_wait(bars + B_FREE, 0);
            const uint32_t xb = sbase + OFF_X + wg * 8192 + (threadIdx.x & 127) * 16, xbar = bars + B_X + 16 * wg;
            const uint32_t rx = mapa(xb, rank ^ 1), rbar = mapa(xbar, rank ^ 1);
            wg_wait<0>();
            pin(a);
            M.release(M.prev);
            TS0(4, 5 + wg);
#pragma unroll
            for (int i = 0; i < 3; i++)
                st_async4(rx + i * 2048, rbar + 8 * (i >> 1), pack2(a[28 + 8 * i], a[29 + 8 * i]), pack2(a[30 + 8 * i], a[31 + 8 * i]), pack2(a[32 + 8 * i], a[33 + 8 * i]), pack2(a[34 + 8 * i], a[35 + 8 * i]));
            const uint32_t tail = 6144 - (threadIdx.x & 127) * 8;
            st_async2(rx + tail, rbar + 8, pack2(a[52], a[53]), pack2(a[54], a[55]));
            uint8_t* dst = G->U[nt1][((ft >= 7) + wg) * 7 + ft] + rank * HALF + w * 256 + lane * 4;
            uint32_t u[14];
#pragma unroll
            for (int i = 0; i < 14; i++) {
                if (i % 8 == 0) {
                    mbar_wait(xbar + i, 0);
                    if (i == 0) TS0(4, 1 + wg);
#pragma unroll
                    for (int k = i / 4; k < i / 4 + 2; k++) {
                        if (k < 3) { const uint4 v = lds4(xb + k * 2048); u[4 * k] = v.x; u[4 * k + 1] = v.y; u[4 * k + 2] = v.z; u[4 * k + 3] = v.w; }
                        else { const uint2 v = lds2(xb + tail); u[12] = v.x; u[13] = v.y; }
                    }
                    if (i && lane < 2) mbar_arrive_remote(M.rel + B_EMPTY + 48);
                }
                if (i == HINT && threadIdx.x == 0) hint(G->flag[8 + nt1 * 2] + ft + (ft >= 7) * 25);
                const float bias = bf_lo((i & 1) ? bias1 : bias0);
                stg1(dst + (i >> 1) * 1024 + (i & 1) * 128, tag(pack2(gelu2(a[2 * i] + bias + bf_lo(u[i])), gelu2(a[2 * i + 1] + bias + bf_hi(u[i]))), (lane & 7) == w * 2 + (i & 1), ep));
            }
            TS0(4, 30 + wg);
        } else {
            mbar_wait(bars + B_FREE, 0);
            if (lane < 2) mbar_arrive_remote(M.rel + B_EMPTY + 48);
        }
        uint32_t c0 = ld_u16(b2 + mt * 128 + warp * 16 + r), c1 = ld_u16(b2 + mt * 128 + warp * 16 + r + 8);
        M.run_o(a);
        if (wg == 1) TS0(4, 13);
        c0 *= ks == 0 ? 0x10001u : 0u; c1 *= ks == 0 ? 0x10001u : 0u;
        M.run<false>(a, 14, 0, 14 - NSLOT, LAG2, 1, 52);
        mbar_wait(bars + B_ROW, 1);
        const uint32_t stg = sbase + ((has_g1 ? STG1 : STG0) + (w >> 1) * STGS) * SLOT + wg * 8192 + (w & 1) * SLAB;
        const uint32_t sa = stg + (lane & 15) * 224 + (lane >> 4) * 16;
        wg_wait<0>();
        pin(a);
        TS0(8, 14 + wg);
#pragma unroll
        for (int i = 0; i < 7; i++)
            stsm4(sa + i * 32, half_plus(pack2(a[8 * i], a[8 * i + 1]), c0), half_plus(pack2(a[8 * i + 2], a[8 * i + 3]), c1),
                  half_plus(pack2(a[8 * i + 4], a[8 * i + 5]), c0), half_plus(pack2(a[8 * i + 6], a[8 * i + 7]), c1));
        fence_async_shared();
        __syncwarp();
        if (elect()) {
            asm volatile("cp.reduce.async.bulk.tensor.2d.global.shared::cta.add.tile.bulk_group [%0, {%2, %3}], [%1];\ncp.async.bulk.commit_group;" ::"l"(&P.tmOut), "r"(stg), "r"(nt2 * 112), "r"(mt * 128 + warp * 16) : "memory");
            if (w == 0) mbar_arrive(bars + B_END);
            asm volatile("cp.async.bulk.wait_group.read 0;" ::: "memory");
        }
        if (wg == 1) TS0(15, 19);
        TSDUMP();
    }
}

typedef CUresult (*EncodeFn)(CUtensorMap*, CUtensorMapDataType, cuuint32_t, void*, const cuuint64_t*, const cuuint64_t*, const cuuint32_t*, const cuuint32_t*,
                             CUtensorMapInterleave, CUtensorMapSwizzle, CUtensorMapL2promotion, CUtensorMapFloatOOBfill);

void make_map(EncodeFn enc, CUtensorMap* tm, const void* base, bool swizzle, int d0, int d1, int d2, int s1, int s2, int b0, int b1, int b2) {
    const cuuint64_t dims[3] = {(cuuint64_t)d0, (cuuint64_t)d1, (cuuint64_t)d2}, strides[2] = {(cuuint64_t)s1 * 2, (cuuint64_t)s2 * 2};
    const cuuint32_t box[3] = {(cuuint32_t)b0, (cuuint32_t)b1, (cuuint32_t)b2}, es[3] = {1, 1, 1};
    enc(tm, CU_TENSOR_MAP_DATA_TYPE_BFLOAT16, d2 ? 3 : 2, (void*)base, dims, strides, box, es, CU_TENSOR_MAP_INTERLEAVE_NONE,
        swizzle ? CU_TENSOR_MAP_SWIZZLE_128B : CU_TENSOR_MAP_SWIZZLE_NONE, CU_TENSOR_MAP_L2_PROMOTION_L2_128B, CU_TENSOR_MAP_FLOAT_OOB_FILL_NONE);
}

}

extern "C" void kernel_launch(void* const* d_in, const int* in_sizes, int n_in, void* d_out, int out_size) {
    static EncodeFn enc = nullptr;
    static Scratch* scratch = nullptr;
    if (!enc) {
        void* fn = nullptr;
        cudaDriverEntryPointQueryResult qr;
        cudaGetDriverEntryPoint("cuTensorMapEncodeTiled", &fn, cudaEnableDefault, &qr);
        enc = (EncodeFn)fn;
        cudaGetSymbolAddress((void**)&scratch, g_s);
        cudaFuncSetAttribute(fused_kernel, cudaFuncAttributeMaxDynamicSharedMemorySize, SMEM_BYTES);
    }
    Params P;
    const __nv_bfloat16* x = (const __nv_bfloat16*)d_in[0];
    make_map(enc, &P.tmX, x, true, D_, S_ / 2, 2, 2 * D_, D_, 64, 64, 2);
    make_map(enc, &P.tmWqkv, d_in[1], true, D_, D_, 3, 3 * D_, D_, 64, 32, 3);
    make_map(enc, &P.tmW1, d_in[4], true, 64, S_, F_ / 64, F_, 64, 64, 64, 2);
    make_map(enc, &P.tmW2, d_in[6], true, S_, F_, 0, S_, 0, 64, 64, 1);
    make_map(enc, &P.tmOut, d_out, false, D_, S_, 0, D_, 0, 112, 16, 1);
    fused_kernel<<<NCTA, NTHREADS, SMEM_BYTES, cudaStreamPerThread>>>(x, (const __nv_bfloat16*)d_in[5], (const __nv_bfloat16*)d_in[7], (const __nv_bfloat16*)d_in[2], (__nv_bfloat16*)d_out, scratch,
                                                                      (const __nv_bfloat16*)d_in[4], (const __nv_bfloat16*)d_in[6], P);
}
```

```cpp
#include <cuda_runtime.h>
#include <cuda_bf16.h>
#include <cuda.h>
#include <stdint.h>

#define HALO_NS 300
#define HINT 4
#define HOLD 2
#define ROT 2
#define LATEREL 1
#define PF 400
#define PF0 2
#define PF1 8
#define ENDBAR 1
#define PG0 3
#define PG1 5
#define STG1 4
#define STG0 4
#define STGS 1
#define CSU 1
#define REC_NS 0
#define LEADW 4
#define LEADN 7
#define PACE 600
#define PAUSE 8
#define LAG1 4
#define LAG2 6

namespace {

constexpr int S_ = 2048, D_ = 448, F_ = 1792;
constexpr int NCTA = 128, NTHREADS = 384;
constexpr int NSLOT = 6, SLOT = 32768, QSLOT = 40960, TILEB = 14336, SLAB = 3584, HALF = 7168;
constexpr int KV = 1792, kCsu = CSU;
constexpr int OFF_X = NSLOT * SLOT;
constexpr int OFF_Y = OFF_X + 10 * KV;
constexpr int OFF_ST = OFF_Y + TILEB;
constexpr int OFF_BAR = OFF_ST + 1024;
constexpr int SMEM_BYTES = OFF_BAR + 1280;
constexpr uint32_t SMEM0 = 1024;
constexpr int B_QFULL = 0, B_FULL = 56, B_HALO = 128, B_X = 136, B_FREE = 192, B_END = 200, B_CS = 208, B_QEMPTY = 216, B_EMPTY = 232, B_ROW = 288, NBAR = 37;
constexpr float LN_EPS = 1e-5f;
constexpr int SPIN_LIMIT = 1 << 22;

struct Scratch {
    uint8_t H[4][32][TILEB];
    uint8_t U[4][28][TILEB];
    uint8_t O[16][8][TILEB];
    uint8_t Wo[4][8][TILEB];
    uint8_t halo[NCTA][2 * KV];
    uint2 stat[S_];
    uint2 colsum[8][8][96];
    uint32_t flag[32][32];
    uint32_t epoch[NCTA];
};
__device__ __align__(1024) Scratch g_s;

#define TS(g, i)
#define TS0(g, i)
#define TSDUMP()

struct Params {
    CUtensorMap tmX, tmWqkv, tmW1, tmW2, tmOut;
};

__device__ __forceinline__ bool elect() {
    uint32_t p;
    asm volatile("{\n.reg .pred p;\nelect.sync _|p, 0xffffffff;\nselp.u32 %0, 1, 0, p;\n}" : "=r"(p));
    return p;
}
__device__ __forceinline__ void mbar_init(uint32_t b, uint32_t c) { asm volatile("mbarrier.init.shared::cta.b64 [%0], %1;" ::"r"(b), "r"(c) : "memory"); }
__device__ __forceinline__ void mbar_expect(uint32_t b, uint32_t tx) { asm volatile("mbarrier.arrive.expect_tx.shared::cta.b64 _, [%0], %1;" ::"r"(b), "r"(tx) : "memory"); }
__device__ __forceinline__ void mbar_arrive(uint32_t b) { asm volatile("mbarrier.arrive.shared::cta.b64 _, [%0];" ::"r"(b) : "memory"); }
__device__ __forceinline__ void mbar_arrive16(uint32_t b) { asm volatile("mbarrier.arrive.shared::cta.b64 _, [%0], 16;" ::"r"(b) : "memory"); }
__device__ __forceinline__ void mbar_arrive4_remote(uint32_t b) { asm volatile("mbarrier.arrive.shared::cluster.b64 _, [%0], 4;" ::"r"(b) : "memory"); }
__device__ __forceinline__ void mbar_arrive_remote(uint32_t b) { asm volatile("mbarrier.arrive.shared::cluster.b64 _, [%0];" ::"r"(b) : "memory"); }
#define MBAR_WAIT_ASM(SEM) \
    asm volatile("{\n.reg .pred p;\nWAIT:\nmbarrier.try_wait.parity" SEM ".shared::cta.b64 p, [%0], %1;\n@!p bra WAIT;\n}" ::"r"(b), "r"(parity) : "memory")
__device__ __forceinline__ void mbar_wait(uint32_t b, uint32_t parity) { MBAR_WAIT_ASM(""); }
__device__ __forceinline__ void mbar_wait_bounded(uint32_t b, uint32_t parity, uint32_t& n) {
    asm volatile("{\n.reg .pred p;\nWAIT:\nadd.u32 %0, %0, 1;\nsetp.gt.u32 p, %0, %3;\n@p st.global.u32 [%4], %0;\n"
                 "mbarrier.try_wait.parity.shared::cta.b64 p, [%1], %2;\n@!p bra WAIT;\n}" : "+r"(n) : "r"(b), "r"(parity), "n"(SPIN_LIMIT), "l"(0ull) : "memory");
}
__device__ __forceinline__ uint32_t mapa(uint32_t a, uint32_t rank) { uint32_t r; asm("mapa.shared::cluster.u32 %0, %1, %2;" : "=r"(r) : "r"(a), "r"(rank)); return r; }
__device__ __forceinline__ void tma3d(uint32_t dst, const CUtensorMap* tm, uint32_t bar, int c0, int c1, int c2) {
    asm volatile("cp.async.bulk.tensor.3d.shared::cluster.global.mbarrier::complete_tx::bytes [%0], [%1, {%3, %4, %5}], [%2];" ::"r"(dst), "l"(tm), "r"(bar), "r"(c0), "r"(c1), "r"(c2) : "memory");
}
__device__ __forceinline__ void tma2d_pair(uint32_t dst, const CUtensorMap* tm, uint32_t bar, int c0, int c1) {
    asm volatile("cp.async.bulk.tensor.2d.shared::cluster.global.mbarrier::complete_tx::bytes.multicast::cluster [%0], [%1, {%3, %4}], [%2], %5;" ::"r"(dst), "l"(tm), "r"(bar), "r"(c0), "r"(c1), "h"((uint16_t)3) : "memory");
}
__device__ __forceinline__ void tma3d_pair(uint32_t dst, const CUtensorMap* tm, uint32_t bar, int c0, int c1, int c2) {
    asm volatile("cp.async.bulk.tensor.3d.shared::cluster.global.mbarrier::complete_tx::bytes.multicast::cluster [%0], [%1, {%3, %4, %5}], [%2], %6;" ::"r"(dst), "l"(tm), "r"(bar), "r"(c0), "r"(c1), "r"(c2), "h"((uint16_t)3) : "memory");
}
__device__ __forceinline__ void bulk_load(uint32_t dst, const void* src, uint32_t bytes, uint32_t bar) {
    asm volatile("cp.async.bulk.shared::cluster.global.mbarrier::complete_tx::bytes [%0], [%1], %2, [%3];" ::"r"(dst), "l"(src), "r"(bytes), "r"(bar) : "memory");
}
__device__ __forceinline__ void bulk_load_pair(uint32_t dst, const void* src, uint32_t bytes, uint32_t bar) {
    asm volatile("cp.async.bulk.shared::cluster.global.mbarrier::complete_tx::bytes.multicast::cluster [%0], [%1], %2, [%3], %4;" ::"r"(dst), "l"(src), "r"(bytes), "r"(bar), "h"((uint16_t)3) : "memory");
}
__device__ __forceinline__ void bulk_store(void* dst, uint32_t src, uint32_t bytes) {
    asm volatile("cp.async.bulk.global.shared::cta.bulk_group [%0], [%1], %2;" ::"l"(dst), "r"(src), "r"(bytes) : "memory");
}
__device__ __forceinline__ uint32_t ld_u16(const void* p) { uint32_t v; asm volatile("ld.global.nc.u16 %0, [%1];" : "=r"(v) : "l"(p)); return v; }
__device__ __forceinline__ uint32_t ld_relaxed(const uint32_t* p) { uint32_t v; asm volatile("ld.relaxed.gpu.global.u32 %0, [%1];" : "=r"(v) : "l"(p) : "memory"); return v; }
__device__ __forceinline__ void bulk_flush() { asm volatile("cp.async.bulk.commit_group;\ncp.async.bulk.wait_group 0;" ::: "memory"); }
__device__ __forceinline__ void signal(uint32_t* flag) { asm volatile("fence.acq_rel.gpu;\nred.relaxed.gpu.global.add.u32 [%0], 1;" ::"l"(flag) : "memory"); }
__device__ __forceinline__ void hint(uint32_t* flag) { asm volatile("red.relaxed.gpu.global.add.u32 [%0], 1;" ::"l"(flag) : "memory"); }
__device__ __forceinline__ uint32_t tag(uint32_t v, uint32_t mask, uint32_t parity) { return (v & ~mask) | (parity & mask); }
__device__ __forceinline__ uint32_t or_diff(uint32_t acc, uint32_t v, uint32_t parity) { asm("lop3.b32 %0, %0, %1, %2, 0xf6;" : "+r"(acc) : "r"(v), "r"(parity)); return acc; }
__device__ __forceinline__ uint4 ld_relaxed4(const void* p) {
    uint4 v;
    asm volatile("ld.relaxed.gpu.global.v4.u32 {%0, %1, %2, %3}, [%4];" : "=r"(v.x), "=r"(v.y), "=r"(v.z), "=r"(v.w) : "l"(p) : "memory");
    return v;
}
__device__ __forceinline__ uint2 ld_relaxed2(const void* p) { uint2 v; asm volatile("ld.relaxed.gpu.global.v2.u32 {%0, %1}, [%2];" : "=r"(v.x), "=r"(v.y) : "l"(p) : "memory"); return v; }
__device__ __forceinline__ void sts4(uint32_t a, uint4 v) { asm volatile("st.shared.v4.b32 [%0], {%1, %2, %3, %4};" ::"r"(a), "r"(v.x), "r"(v.y), "r"(v.z), "r"(v.w) : "memory"); }
__device__ __forceinline__ void stg1(void* p, uint32_t v) { asm volatile("st.global.b32 [%0], %1;" ::"l"(p), "r"(v) : "memory"); }
__device__ __forceinline__ void fence_async_shared() { asm volatile("fence.proxy.async.shared::cta;" ::: "memory"); }
#define BOUND "add.u32 %0, %0, 16;\nsetp.gt.u32 p, %0, %1;\n@p st.global.u32 [%2], %0;\n"
__device__ __forceinline__ void wait_flag(const uint32_t* p, uint32_t target, uint32_t& n) {
    asm volatile("{\n.reg .pred p;\n.reg .u32 v;\nPOLL:\n" BOUND "ld.acquire.gpu.global.u32 v, [%3];\nsetp.ne.u32 p, v, %4;\n@p bra POLL;\nfence.proxy.async.global;\n}"
                 : "+r"(n) : "n"(SPIN_LIMIT), "l"(0ull), "l"(p), "r"(target) : "memory");
}
__device__ __forceinline__ void wait_flag2(const uint32_t* h, uint32_t th, const uint32_t* p, uint32_t target, uint32_t& n) {
    asm volatile("{\n.reg .pred p;\n.reg .u32 u, v;\nPOLL:\n" BOUND "ld.relaxed.gpu.global.u32 u, [%3];\nld.acquire.gpu.global.u32 v, [%5];\nsetp.ne.u32 p, u, %4;\nsetp.ne.or.u32 p, v, %6, p;\n@p bra POLL;\nfence.proxy.async.global;\n}"
                 : "+r"(n) : "n"(SPIN_LIMIT), "l"(0ull), "l"(h), "r"(th), "l"(p), "r"(target) : "memory");
}
__device__ __forceinline__ void bar_sync(int id, int n) { asm volatile("bar.sync %0, %1;" ::"r"(id), "r"(n) : "memory"); }
__device__ __forceinline__ void bar_arrive(int id, int n) { asm volatile("bar.arrive %0, %1;" ::"r"(id), "r"(n) : "memory"); }
__device__ __forceinline__ void wg_fence() { asm volatile("wgmma.fence.sync.aligned;" ::: "memory"); }
__device__ __forceinline__ void wg_commit() { asm volatile("wgmma.commit_group.sync.aligned;" ::: "memory"); }
template <int N> __device__ __forceinline__ void wg_wait() { asm volatile("wgmma.wait_group.sync.aligned %0;" ::"n"(N) : "memory"); }
template <int N> __device__ __forceinline__ void pin(float (&d)[N]) {
#pragma unroll
    for (int i = 0; i < N; i++) asm volatile("" : "+f"(d[i])::"memory");
}
__host__ __device__ constexpr uint32_t desc_hi(uint32_t sbo, uint32_t swz) { return (sbo >> 4) | (swz << 30); }
__host__ __device__ constexpr uint32_t desc_lo(uint32_t off, uint32_t lbo) { return ((SMEM0 + off) >> 4) | ((lbo >> 4) << 16); }
__device__ __forceinline__ uint32_t pack2(float lo, float hi) { uint32_t r; asm("cvt.rn.bf16x2.f32 %0, %1, %2;" : "=r"(r) : "f"(hi), "f"(lo)); return r; }
__device__ __forceinline__ float bf_lo(uint32_t v) { return __uint_as_float(v << 16); }
__device__ __forceinline__ float bf_hi(uint32_t v) { return __uint_as_float(v & 0xffff0000u); }
__device__ __forceinline__ uint32_t half_plus(uint32_t a, uint32_t b) { uint32_t r; asm("fma.rn.bf16x2 %0, %1, %2, %3;" : "=r"(r) : "r"(a), "r"(0x3f003f00u), "r"(b)); return r; }
__device__ __forceinline__ void stsm4(uint32_t a, uint32_t r0, uint32_t r1, uint32_t r2, uint32_t r3) {
    asm volatile("stmatrix.sync.aligned.m8n8.x4.shared.b16 [%0], {%1, %2, %3, %4};" ::"r"(a), "r"(r0), "r"(r1), "r"(r2), "r"(r3) : "memory");
}
__device__ __forceinline__ void stsm2(uint32_t a, uint32_t r0, uint32_t r1) {
    asm volatile("stmatrix.sync.aligned.m8n8.x2.shared.b16 [%0], {%1, %2};" ::"r"(a), "r"(r0), "r"(r1) : "memory");
}
__device__ __forceinline__ uint4 lds4(uint32_t a) { uint4 v; asm volatile("ld.shared.v4.b32 {%0, %1, %2, %3}, [%4];" : "=r"(v.x), "=r"(v.y), "=r"(v.z), "=r"(v.w) : "r"(a) : "memory"); return v; }
__device__ __forceinline__ uint2 lds2(uint32_t a) { uint2 v; asm volatile("ld.shared.v2.b32 {%0, %1}, [%2];" : "=r"(v.x), "=r"(v.y) : "r"(a) : "memory"); return v; }
__device__ __forceinline__ float lds1f(uint32_t a) { float v; asm volatile("ld.shared.f32 %0, [%1];" : "=f"(v) : "r"(a) : "memory"); return v; }
__device__ __forceinline__ void ldsm4(uint32_t* r, uint32_t a) {
    asm volatile("ldmatrix.sync.aligned.m8n8.x4.shared.b16 {%0, %1, %2, %3}, [%4];" : "=r"(r[0]), "=r"(r[1]), "=r"(r[2]), "=r"(r[3]) : "r"(a) : "memory");
}
__device__ __forceinline__ void ldsm4t(uint32_t* r, uint32_t a) {
    asm volatile("ldmatrix.sync.aligned.m8n8.x4.trans.shared.b16 {%0, %1, %2, %3}, [%4];" : "=r"(r[0]), "=r"(r[1]), "=r"(r[2]), "=r"(r[3]) : "r"(a) : "memory");
}
__device__ __forceinline__ void ldsm2t(uint32_t* r, uint32_t a) {
    asm volatile("ldmatrix.sync.aligned.m8n8.x2.trans.shared.b16 {%0, %1}, [%2];" : "=r"(r[0]), "=r"(r[1]) : "r"(a) : "memory");
}
__device__ __forceinline__ uint32_t transpose8(uint32_t v) { uint32_t r; asm volatile("movmatrix.sync.aligned.m8n8.trans.b16 %0, %1;" : "=r"(r) : "r"(v)); return r; }
__device__ __forceinline__ void mma16(float (&c)[4], uint32_t a0, uint32_t a1, uint32_t a2, uint32_t a3, uint32_t b0, uint32_t b1) {
    asm volatile("mma.sync.aligned.m16n8k16.row.col.f32.bf16.bf16.f32 {%0, %1, %2, %3}, {%4, %5, %6, %7}, {%8, %9}, {%0, %1, %2, %3};"
                 : "+f"(c[0]), "+f"(c[1]), "+f"(c[2]), "+f"(c[3]) : "r"(a0), "r"(a1), "r"(a2), "r"(a3), "r"(b0), "r"(b1));
}
__device__ __forceinline__ void mma8(float (&c)[4], uint32_t a0, uint32_t a1, uint32_t b0) {
    asm volatile("mma.sync.aligned.m16n8k8.row.col.f32.bf16.bf16.f32 {%0, %1, %2, %3}, {%4, %5}, {%6}, {%0, %1, %2, %3};"
                 : "+f"(c[0]), "+f"(c[1]), "+f"(c[2]), "+f"(c[3]) : "r"(a0), "r"(a1), "r"(b0));
}
__device__ __forceinline__ void st_async4(uint32_t a, uint32_t bar, uint32_t v0, uint32_t v1, uint32_t v2, uint32_t v3) {
    asm volatile("st.async.weak.shared::cluster.mbarrier::complete_tx::bytes.v4.b32 [%0], {%2, %3, %4, %5}, [%1];" ::"r"(a), "r"(bar), "r"(v0), "r"(v1), "r"(v2), "r"(v3) : "memory");
}
__device__ __forceinline__ void st_async2(uint32_t a, uint32_t bar, uint32_t v0, uint32_t v1) {
    asm volatile("st.async.weak.shared::cluster.mbarrier::complete_tx::bytes.v2.b32 [%0], {%2, %3}, [%1];" ::"r"(a), "r"(bar), "r"(v0), "r"(v1) : "memory");
}
__device__ __forceinline__ float quad_max(float v) { v = fmaxf(v, __shfl_xor_sync(~0u, v, 1)); return fmaxf(v, __shfl_xor_sync(~0u, v, 2)); }
__device__ __forceinline__ float quad_sum(float v) { v += __shfl_xor_sync(~0u, v, 1); return v + __shfl_xor_sync(~0u, v, 2); }
__device__ __forceinline__ float ex2(float v) { float r; asm("ex2.approx.ftz.f32 %0, %1;" : "=f"(r) : "f"(v)); return r; }
__device__ __forceinline__ float rcp(float v) { float r; asm("rcp.approx.ftz.f32 %0, %1;" : "=f"(r) : "f"(v)); return r; }
__device__ __forceinline__ float rsq(float v) { float r; asm("rsqrt.approx.ftz.f32 %0, %1;" : "=f"(r) : "f"(v)); return r; }
__device__ __forceinline__ float gelu2(float u) {
    float z = u * fmaf(u * u, 0.044715f * 0.7978845608028654f, 0.7978845608028654f), t;
    asm("tanh.approx.f32 %0, %1;" : "=f"(t) : "f"(z));
    return fmaf(u, t, u);
}
__device__ __forceinline__ float oct_sum(float v) {
    v += __shfl_xor_sync(~0u, v, 4); v += __shfl_xor_sync(~0u, v, 8); v += __shfl_xor_sync(~0u, v, 16);
    return v;
}

template <int TA, int TB, uint32_t HA, uint32_t HB>
__device__ __forceinline__ void wgmma_n112(float (&d)[56], uint32_t da, uint32_t db, int accumulate) {
    asm volatile("{\n.reg .pred p;\n.reg .b64 a, b;\nmov.b64 a, {%56, %61};\nmov.b64 b, {%57, %62};\nsetp.ne.b32 p, %58, 0;\n"
        "wgmma.mma_async.sync.aligned.m64n112k16.f32.bf16.bf16 {"
        "%0, %1, %2, %3, %4, %5, %6, %7, %8, %9, %10, %11, %12, %13, %14, %15, "
        "%16, %17, %18, %19, %20, %21, %22, %23, %24, %25, %26, %27, %28, %29, %30, %31, "
        "%32, %33, %34, %35, %36, %37, %38, %39, %40, %41, %42, %43, %44, %45, %46, %47, "
        "%48, %49, %50, %51, %52, %53, %54, %55"
        "}, a, b, p, 1, 1, %59, %60;\n}\n"
        : "+f"(d[0]), "+f"(d[1]), "+f"(d[2]), "+f"(d[3]), "+f"(d[4]), "+f"(d[5]), "+f"(d[6]), "+f"(d[7]),
          "+f"(d[8]), "+f"(d[9]), "+f"(d[10]), "+f"(d[11]), "+f"(d[12]), "+f"(d[13]), "+f"(d[14]), "+f"(d[15]),
          "+f"(d[16]), "+f"(d[17]), "+f"(d[18]), "+f"(d[19]), "+f"(d[20]), "+f"(d[21]), "+f"(d[22]), "+f"(d[23]),
          "+f"(d[24]), "+f"(d[25]), "+f"(d[26]), "+f"(d[27]), "+f"(d[28]), "+f"(d[29]), "+f"(d[30]), "+f"(d[31]),
          "+f"(d[32]), "+f"(d[33]), "+f"(d[34]), "+f"(d[35]), "+f"(d[36]), "+f"(d[37]), "+f"(d[38]), "+f"(d[39]),
          "+f"(d[40]), "+f"(d[41]), "+f"(d[42]), "+f"(d[43]), "+f"(d[44]), "+f"(d[45]), "+f"(d[46]), "+f"(d[47]),
          "+f"(d[48]), "+f"(d[49]), "+f"(d[50]), "+f"(d[51]), "+f"(d[52]), "+f"(d[53]), "+f"(d[54]), "+f"(d[55])
        : "r"(da), "r"(db), "r"(accumulate), "n"(TA), "n"(TB), "n"(HA), "n"(HB));
}

template <int TA, int TB, uint32_t HA, uint32_t HB>
__device__ __forceinline__ void wgmma_n184(float (&d)[92], uint32_t da, uint32_t db, int accumulate) {
    asm volatile("{\n.reg .pred p;\n.reg .b64 a, b;\nmov.b64 a, {%92, %97};\nmov.b64 b, {%93, %98};\nsetp.ne.b32 p, %94, 0;\n"
        "wgmma.mma_async.sync.aligned.m64n184k16.f32.bf16.bf16 {"
        "%0, %1, %2, %3, %4, %5, %6, %7, %8, %9, %10, %11, %12, %13, %14, %15, "
        "%16, %17, %18, %19, %20, %21, %22, %23, %24, %25, %26, %27, %28, %29, %30, %31, "
        "%32, %33, %34, %35, %36, %37, %38, %39, %40, %41, %42, %43, %44, %45, %46, %47, "
        "%48, %49, %50, %51, %52, %53, %54, %55, %56, %57, %58, %59, %60, %61, %62, %63, "
        "%64, %65, %66, %67, %68, %69, %70, %71, %72, %73, %74, %75, %76, %77, %78, %79, "
        "%80, %81, %82, %83, %84, %85, %86, %87, %88, %89, %90, %91"
        "}, a, b, p, 1, 1, %95, %96;\n}\n"
        : "+f"(d[0]), "+f"(d[1]), "+f"(d[2]), "+f"(d[3]), "+f"(d[4]), "+f"(d[5]), "+f"(d[6]), "+f"(d[7]),
          "+f"(d[8]), "+f"(d[9]), "+f"(d[10]), "+f"(d[11]), "+f"(d[12]), "+f"(d[13]), "+f"(d[14]), "+f"(d[15]),
          "+f"(d[16]), "+f"(d[17]), "+f"(d[18]), "+f"(d[19]), "+f"(d[20]), "+f"(d[21]), "+f"(d[22]), "+f"(d[23]),
          "+f"(d[24]), "+f"(d[25]), "+f"(d[26]), "+f"(d[27]), "+f"(d[28]), "+f"(d[29]), "+f"(d[30]), "+f"(d[31]),
          "+f"(d[32]), "+f"(d[33]), "+f"(d[34]), "+f"(d[35]), "+f"(d[36]), "+f"(d[37]), "+f"(d[38]), "+f"(d[39]),
          "+f"(d[40]), "+f"(d[41]), "+f"(d[42]), "+f"(d[43]), "+f"(d[44]), "+f"(d[45]), "+f"(d[46]), "+f"(d[47]),
          "+f"(d[48]), "+f"(d[49]), "+f"(d[50]), "+f"(d[51]), "+f"(d[52]), "+f"(d[53]), "+f"(d[54]), "+f"(d[55]),
          "+f"(d[56]), "+f"(d[57]), "+f"(d[58]), "+f"(d[59]), "+f"(d[60]), "+f"(d[61]), "+f"(d[62]), "+f"(d[63]),
          "+f"(d[64]), "+f"(d[65]), "+f"(d[66]), "+f"(d[67]), "+f"(d[68]), "+f"(d[69]), "+f"(d[70]), "+f"(d[71]),
          "+f"(d[72]), "+f"(d[73]), "+f"(d[74]), "+f"(d[75]), "+f"(d[76]), "+f"(d[77]), "+f"(d[78]), "+f"(d[79]),
          "+f"(d[80]), "+f"(d[81]), "+f"(d[82]), "+f"(d[83]), "+f"(d[84]), "+f"(d[85]), "+f"(d[86]), "+f"(d[87]),
          "+f"(d[88]), "+f"(d[89]), "+f"(d[90]), "+f"(d[91])
        : "r"(da), "r"(db), "r"(accumulate), "n"(TA), "n"(TB), "n"(HA), "n"(HB));
}

template <uint32_t HB>
__device__ __forceinline__ void wgmma_rs_n184(float (&d)[92], uint32_t a0, uint32_t a1, uint32_t db) {
    asm volatile("{\n.reg .b64 b;\nmov.b64 b, {%94, %96};\n"
        "wgmma.mma_async.sync.aligned.m64n184k16.f32.bf16.bf16 {"
        "%0, %1, %2, %3, %4, %5, %6, %7, %8, %9, %10, %11, %12, %13, %14, %15, "
        "%16, %17, %18, %19, %20, %21, %22, %23, %24, %25, %26, %27, %28, %29, %30, %31, "
        "%32, %33, %34, %35, %36, %37, %38, %39, %40, %41, %42, %43, %44, %45, %46, %47, "
        "%48, %49, %50, %51, %52, %53, %54, %55, %56, %57, %58, %59, %60, %61, %62, %63, "
        "%64, %65, %66, %67, %68, %69, %70, %71, %72, %73, %74, %75, %76, %77, %78, %79, "
        "%80, %81, %82, %83, %84, %85, %86, %87, %88, %89, %90, %91"
        "}, {%92, %93, %95, %95}, b, 1, 1, 1, 0;\n}\n"
        : "+f"(d[0]), "+f"(d[1]), "+f"(d[2]), "+f"(d[3]), "+f"(d[4]), "+f"(d[5]), "+f"(d[6]), "+f"(d[7]),
          "+f"(d[8]), "+f"(d[9]), "+f"(d[10]), "+f"(d[11]), "+f"(d[12]), "+f"(d[13]), "+f"(d[14]), "+f"(d[15]),
          "+f"(d[16]), "+f"(d[17]), "+f"(d[18]), "+f"(d[19]), "+f"(d[20]), "+f"(d[21]), "+f"(d[22]), "+f"(d[23]),
          "+f"(d[24]), "+f"(d[25]), "+f"(d[26]), "+f"(d[27]), "+f"(d[28]), "+f"(d[29]), "+f"(d[30]), "+f"(d[31]),
          "+f"(d[32]), "+f"(d[33]), "+f"(d[34]), "+f"(d[35]), "+f"(d[36]), "+f"(d[37]), "+f"(d[38]), "+f"(d[39]),
          "+f"(d[40]), "+f"(d[41]), "+f"(d[42]), "+f"(d[43]), "+f"(d[44]), "+f"(d[45]), "+f"(d[46]), "+f"(d[47]),
          "+f"(d[48]), "+f"(d[49]), "+f"(d[50]), "+f"(d[51]), "+f"(d[52]), "+f"(d[53]), "+f"(d[54]), "+f"(d[55]),
          "+f"(d[56]), "+f"(d[57]), "+f"(d[58]), "+f"(d[59]), "+f"(d[60]), "+f"(d[61]), "+f"(d[62]), "+f"(d[63]),
          "+f"(d[64]), "+f"(d[65]), "+f"(d[66]), "+f"(d[67]), "+f"(d[68]), "+f"(d[69]), "+f"(d[70]), "+f"(d[71]),
          "+f"(d[72]), "+f"(d[73]), "+f"(d[74]), "+f"(d[75]), "+f"(d[76]), "+f"(d[77]), "+f"(d[78]), "+f"(d[79]),
          "+f"(d[80]), "+f"(d[81]), "+f"(d[82]), "+f"(d[83]), "+f"(d[84]), "+f"(d[85]), "+f"(d[86]), "+f"(d[87]),
          "+f"(d[88]), "+f"(d[89]), "+f"(d[90]), "+f"(d[91])
        : "r"(a0), "r"(a1), "r"(db), "r"(0), "n"(HB));
}

struct Ring {
    uint32_t slot, ph;
    __device__ __forceinline__ void next() { if (++slot == NSLOT) { slot = 0; ph ^= 1; } }
    __device__ __forceinline__ void next2() { ph ^= slot == 5; slot = __byte_perm(0x06030201u, 0x00040005u, 0x7770 + slot); }
};
struct Slot {
    uint32_t dst, bar, ph;
    __device__ __forceinline__ void next(uint32_t bars) {
        dst += SLOT; bar += 8;
        if (bar == bars + 8 * NSLOT) { dst -= NSLOT * SLOT; bar = bars; ph ^= 1; }
    }
};
__device__ __forceinline__ uint32_t xslot(int i) { return __byte_perm(0x04130e0cu, 0x00130e0cu, 0x7770 + i); }
__device__ __forceinline__ uint32_t wslot(int i) { return __byte_perm(0x06001510u, 0x00151009u, 0x7770 + i); }

constexpr uint32_t HI_SW = desc_hi(1024, 1);

struct Mma {
    uint32_t bars, rel;
    bool lead;
    int wg, w;
    Ring r;
    uint32_t prev;
    __device__ __forceinline__ void release(uint32_t s) { if (lead) mbar_arrive4_remote(rel + B_EMPTY + 8 * s); }
    template <bool G1>
    __device__ __forceinline__ void run(float (&a)[56], int n, int first, int last, int lag, int accumulate, int ts) {
#pragma unroll 1
        for (int i = 0; i < n; i++) {
            if (lag && i == (wg ? n - lag : -1)) bar_sync(7, 256);
            const uint32_t s = r.slot;
            mbar_wait(bars + B_FULL + 8 * s, r.ph);
            if (G1) r.next(); else r.next2();
            TS0(G1 ? 2 : 8, ts + i + wg * 68);
            const uint32_t dB = s * (SLOT >> 4), dA = dB + wg * 512;
            wg_fence();
#pragma unroll
            for (int k = 0; k < 4; k++) {
                wgmma_n112<1, 1, HI_SW, desc_hi(G1 ? 256 : 1024, 0)>(a, dA + desc_lo(k * 2048, 8192), dB + desc_lo(16384 + k * (G1 ? SLAB : 256), 128), k > 0 || accumulate || i > 0);
                if (k == 1) {
                    wg_commit(); wg_wait<1>();
                    if ((uint32_t)(i - first) < (uint32_t)(last - first)) release(prev);
                    if (lag && i == (wg ? -1 : n - 1)) bar_arrive(7, 256);
                }
            }
            wg_commit();
            prev = s;
        }
    }
    __device__ __forceinline__ void run_o(float (&a)[56]) {
#pragma unroll 1
        for (int i = 0; i < 2; i++) {
            const uint32_t s = r.slot, dB = s * (SLOT >> 4), dA = dB + wg * 512;
            mbar_wait(bars + B_FULL + 8 * s, r.ph);
            TS0(8, 48 + 2 * i + wg * 68);
            wg_fence();
#pragma unroll
            for (int k = 0; k < 7; k++) {
                if (k == 3) { mbar_wait(bars + B_FULL + 8 * s + 8, r.ph); wg_fence(); }
                wgmma_n112<0, 1, desc_hi(128, 0), desc_hi(256, 0)>(a, dA + desc_lo(k * 2048 + (k > 3) * (SLOT - HALF), k == 3 ? SLOT - 6144 : 1024),
                                                                   dB + desc_lo(16384 + k * SLAB + (k > 2) * (SLOT - 3 * SLAB), 128), k > 0 || i > 0);
                if (k & 1) wg_commit();
                if (k == 1) { wg_wait<1>(); if (i) release(prev); }
                if (k == 5) { wg_wait<1>(); release(s); }
            }
            wg_commit();
            prev = s + 1;
            r.slot++; r.next2();
        }
    }
};

__global__ void __cluster_dims__(2, 1, 1) __launch_bounds__(NTHREADS, 1)
fused_kernel(const __nv_bfloat16* __restrict__ x, const __nv_bfloat16* __restrict__ b1, const __nv_bfloat16* __restrict__ b2, const __nv_bfloat16* __restrict__ wo, __nv_bfloat16* out, Scratch* G,
             const __nv_bfloat16* __restrict__ w1, const __nv_bfloat16* __restrict__ w2,
             const __grid_constant__ Params P) {
    extern __shared__ __align__(1024) uint8_t smem[];
    const uint32_t sbase = (uint32_t)__cvta_generic_to_shared(smem);
    const uint32_t bars = sbase + OFF_BAR;
    const uint32_t rank = blockIdx.x & 1, pr = blockIdx.x >> 1;
    const uint32_t row0 = blockIdx.x * 16;
    if (threadIdx.x == 0) {
        TS(15, 0);
        mbar_init(bars + B_ROW, 1);
        asm volatile("fence.mbarrier_init.release.cluster;" ::: "memory");
        bulk_load(sbase + OFF_Y, x + row0 * D_, TILEB, bars + B_ROW);
        mbar_expect(bars + B_ROW, TILEB);
        TS(1, 97);
    }
    const int lane = threadIdx.x & 31;
    const int warp = __shfl_sync(~0u, threadIdx.x >> 5, 0), w = warp & 3;
    if (elect()) {
        const uint32_t first = bars + warp * 24, count = warp < 8 ? 1 : warp == 8 ? 2 : 16;
#pragma unroll
        for (int i = 0; i < 3; i++) mbar_init(first + 8 * i, count);
        asm volatile("fence.mbarrier_init.release.cluster;" ::: "memory");
    }
    __syncwarp();
    asm volatile("barrier.cluster.arrive.relaxed.aligned;" ::: "memory");
    const uint32_t pv = pr < 4 ? pr * 8 + 36 : pr - 4 + (max((int)pr - 33, 0) * 37 >> 8);
    const uint32_t gp = (pv + 4) & 7, hp = pv >> 3;
    const uint32_t tb = gp * 2 + rank, c = hp * 16 + tb;
    const bool has_g1 = gp > 0;
    const uint32_t nt1 = hp & 3, ft = max((int)gp - 1, 0) * 2 + (hp >> 2);
    const uint32_t nt2 = tb & 3, mt = (gp & 2) * 4 + hp, ks = gp >> 2;
    asm volatile("barrier.cluster.wait.aligned;" ::: "memory");

    if (warp == 8) {
        uint32_t kw = gp % ROT * (512 / ROT), kx;
        if (elect()) {
            mbar_expect(bars + B_QFULL, QSLOT);
            tma3d(sbase + xslot(0) * 8192, &P.tmX, bars + B_QFULL, kw, tb * 64, 0);
            tma3d_pair(sbase + wslot(0) * 8192 + rank * 12288, &P.tmWqkv, bars + B_QFULL, (hp * 56) & ~15, kw + rank * 32, 0);
            TS(1, 23);
            uint32_t due = (uint32_t)clock() + PACE, ep = ld_relaxed(&G->epoch[c]);
            uint32_t spins = sbase == (rank << 24 | SMEM0) ? 0 : SPIN_LIMIT;
#pragma unroll 1
            for (int i = 1; i < 8; i++) {
                kx = kw; kw += 64;
                if (i >= 5) mbar_wait_bounded(bars + B_QEMPTY + 8 * (i - 5), 0, spins);
                else { while ((int)((uint32_t)clock() - due) < 0) {} due += PACE; }
                if (kw == D_) kw = 0;
                if (i < 4) kx = kw;
                const int ix = i - (i > 4);
                if (i < 7) mbar_expect(bars + B_QFULL + 8 * i, QSLOT);
                if (i != 4) tma3d(sbase + xslot(ix) * 8192, &P.tmX, bars + B_QFULL + 8 * ix, kx, tb * 64, 0);
                if (i == min(5 + gp / ROT, 7)) mbar_wait_bounded(bars + B_CS, 0, spins);
                if (i < 7) tma3d_pair(sbase + wslot(i) * 8192 + rank * 12288, &P.tmWqkv, bars + B_QFULL + 8 * i, (hp * 56) & ~15, kw + rank * 32, 0);
            }
            ep++;
            Slot r{sbase, bars, 0};
            if (has_g1) {
                const uint8_t* src = G->H[nt1][rank * 16];
                const int row = rank * 1024;
                mbar_arrive(bars + B_FULL + 48); mbar_arrive16(bars + B_EMPTY + 48);
                mbar_expect(bars + B_FULL, 16384 + TILEB);
                tma3d(sbase, &P.tmW1, bars + B_FULL, 0, row, ft * 2);
                wait_flag(G->flag[1] + rank * 2, 20 * ep, spins);
                TS(1, 16);
#pragma unroll 1
                for (int j = 64;; j += 64) {
                    bulk_load(r.dst + 16384, src, TILEB, r.bar + B_FULL);
                    src += TILEB;
                    r.next(bars);
                    if (j == 1024) break;
                    mbar_wait_bounded(r.bar + B_EMPTY, r.ph, spins);
                    if (j < 14 * 64) TS(2, 146 + j / 64);
                    mbar_expect(r.bar + B_FULL, 16384 + TILEB);
                    tma3d(r.dst, &P.tmW1, r.bar + B_FULL, 0, row + j, ft * 2);
                }
#pragma unroll
                for (int i = 0; i < 4; i++) mbar_expect(bars + B_X + 8 * i, (i & 1) ? 3072 : 4096);
            } else {
                due = (uint32_t)clock();
#pragma unroll 1
                for (int j = PF0; j < PF1; j++) {
                    asm volatile("cp.async.bulk.prefetch.L2.global [%0], %1;" ::"l"(w1 + (rank * 1024 + j * 64 + hp * 8) * F_), "n"(16 * F_) : "memory");
                    due += PF;
                    while ((int)((uint32_t)clock() - due) < 0) {}
                }
            }
            const uint8_t *so = G->O[mt][ks * 4] + rank * HALF, *sw = G->Wo[nt2][ks * 4];
            wait_flag2(G->flag[16 + mt], 8 * ep, G->flag[0], 16 * ep, spins);
            TS(4, 18);
#pragma unroll 1
            for (int j = 0; j < 4 * TILEB; j += TILEB) {
                mbar_wait_bounded(r.bar + B_EMPTY, r.ph, spins);
                mbar_expect(r.bar + B_QFULL, TILEB);
                bulk_load_pair(r.dst + rank * 8192, so + j, HALF, r.bar + B_QFULL);
                bulk_load(r.dst + 16384, sw + j, (r.bar & 8) ? TILEB : 3 * SLAB, r.bar + B_FULL);
                r.next(bars);
            }
            if (!has_g1) {
#pragma unroll
                for (int j = PG0; j < PG1; j++)
                    asm volatile("cp.async.bulk.prefetch.L2.global [%0], %1;" ::"l"(w2 + (rank * 896 + j * 128 + hp * 8) * S_), "n"(16 * S_) : "memory");
            }
            Ring q{has_g1 ? 2u : 6u, has_g1}, p = q;
#pragma unroll 1
            for (int j = 0; j < 14 * 128; j += 128) {
                mbar_wait_bounded(bars + B_EMPTY + 8 * q.slot, q.ph, spins);
                if (LEADW && j >= LEADW * 128 && j < LEADN * 128) { mbar_wait_bounded(bars + B_FULL + 8 * p.slot, p.ph, spins); p.next2(); }
                TS(8, 176 + j / 128);
                tma2d_pair(sbase + q.slot * SLOT + rank * 8192, &P.tmW2, bars + B_FULL + 8 * q.slot, mt * 128 + rank * 64, ks * 896 + j - (j < 896 ? 0 : 832));
                q.next2();
            }
            mbar_wait_bounded(bars + B_END, 0, spins);
        }
    } else if (warp > 8) {
        const uint32_t ep = ld_relaxed(&G->epoch[c]) + 1;
        {
            uint2* cs = G->colsum[hp][0];
            if (w == 2) {
                bar_sync(6, 160);
                TS(1, 8);
                if (elect()) {
                    fence_async_shared();
#pragma unroll
                    for (int i = 0; i < 4; i++) bulk_store(G->H[i][0] + row0 * (SLAB / 16), sbase + OFF_X + i * (SLAB + 64), SLAB);
                    bulk_flush();
                    TS(1, 99);
                    signal(G->flag[1] + (row0 >> 10) * 2 + ((row0 & 1023) >= 320));
                    TS(1, 3);
                }
                __syncwarp();
            } else {
                const uint32_t q4 = lane >> 3, word = rank * 16 + (w & 2) * 4 + (lane & 7);
                uint32_t src = (sbase + wslot(gp / ROT) * 8192 + word * 4 + (q4 >> 1) * 12288 + (q4 & 1) * 2048) ^ (q4 * 288);
                mbar_wait(bars + B_QFULL + 8 * (gp / ROT), 0);
                if (w == 1) TS(1, 66);
#pragma unroll kCsu
                for (int i = 0; i < 96; i += 32) {
                    uint32_t v[16];
#pragma unroll
                    for (int k = 0; k < 16; k++) v[k] = __float_as_uint(lds1f((src ^ ((k & 7) * 144)) + (k >> 3) * 1024));
                    float s0 = bf_lo(v[0]), s1 = bf_hi(v[0]), s2 = bf_lo(v[1]), s3 = bf_hi(v[1]);
#pragma unroll
                    for (int k = 2; k < 16; k += 2) { s0 += bf_lo(v[k]); s1 += bf_hi(v[k]); s2 += bf_lo(v[k + 1]); s3 += bf_hi(v[k + 1]); }
                    s0 += s2; s1 += s3;
                    s0 += __shfl_xor_sync(~0u, s0, 8); s1 += __shfl_xor_sync(~0u, s1, 8);
                    s0 += __shfl_xor_sync(~0u, s0, 16); s1 += __shfl_xor_sync(~0u, s1, 16);
                    if (lane < 8) cs[gp * 96 + i + word] = make_uint2(tag(__float_as_uint(s0), 1, ep), __float_as_uint(s1));
                    src += 4096;
                }
                if (elect()) mbar_arrive(bars + B_CS);
                if (w == 1) TS(1, 24);
            }
            bar_sync(1, 96);
            if (REC_NS) __nanosleep(REC_NS);
            const int i0 = threadIdx.x - 288;
            uint2 u[7];
            uint4 sv;
            uint32_t bad;
            do {
                sv = ld_relaxed4(G->stat + tb * 128 + (i0 & 63) * 2);
                bad = or_diff(sv.x ^ ep, sv.z, ep);
#pragma unroll
                for (int i = 0; i < 7; i++) { u[i] = ld_relaxed2(cs + i * 96 + i0); bad = or_diff(bad, u[i].x, ep); }
            } while (bad & 1);
            if (w < 3) sts4(sbase + OFF_ST + i0 * 16, sv);
#pragma unroll
            for (int e = 0; e < 2; e++) {
                float f = 0.f;
#pragma unroll
                for (int i = 0; i < 7; i++) f += __uint_as_float(e ? u[i].y : u[i].x);
                const uint32_t hi = pack2(f, f);
                sts4(sbase + OFF_X + i0 * 32 + e * 16, make_uint4(hi, pack2(f - bf_hi(hi), f - bf_hi(hi)), 0, 0));
            }
            asm volatile("st.shared.u32 [%0], %1;" ::"r"(bars + 8 * NBAR), "r"(ep) : "memory");
            fence_async_shared();
            __syncwarp();
            bar_arrive(8, 224); bar_arrive(9, 224);
            TS(1, 90 + w);
        }
        const uint8_t* src = G->U[nt2][ks * 14];
        uint32_t spins = 0;
        if (w < 3) {
            uint32_t bad;
            if (w == 1) {
                if (elect()) {
                    wait_flag(G->flag[1] + rank * 2 + 1, 44 * ep, spins);
                    mbar_arrive16(bars + B_EMPTY + 8 * 5);
                    TS(1, 96);
                }
                __syncwarp();
                if (!has_g1) { bar_sync(5, 288); if (elect()) signal(G->flag[0]); __syncwarp(); TS(2, 26); }
            } else {
                bar_sync(3, 288);
                __nanosleep(HALO_NS);
                uint4 v[7];
                do {
                    bad = 0;
#pragma unroll
                    for (int i = 0; i < 7; i++) { v[i] = ld_relaxed4(G->halo[c - (tb > 0)] + i * 512 + lane * 16); bad = or_diff(bad, v[i].x, ep); }
                } while (bad & 1);
#pragma unroll
                for (int i = 0; i < 7; i++) sts4(sbase + OFF_X + i * 512 + lane * 16, v[i]);
                __syncwarp();
                if (elect()) mbar_arrive(bars + B_HALO);
                TS(2, 21);
            }
            mbar_wait(bars + B_HALO, 0);
            uint32_t slot = (has_g1 ? 16 % NSLOT : 0) + w - 1, ph = ~0u;
#pragma unroll 1
            for (int i = w - 1; i < 18;) {
                const uint32_t d0 = sbase + slot * SLOT + (i < 4 ? 0 : 16384), d1 = d0 + (i < 4 ? 8192 : HALF), landed = bars + B_QFULL + 8 * slot;
                mbar_wait(landed, (ph >> slot) & 1);
                ph ^= 1 << slot;
                if (i < 8) TS(4, 82 + i);
                if (i >= 4) TS(8, 156 + i);
                bad = 0;
#pragma unroll
                for (int k = 0; k < 14; k++) bad = or_diff(bad, __float_as_uint(lds1f((k < 7 ? d0 : d1) + k % 7 * 1024 + lane * 32 + (lane >> 2) * 4)), ep);
                if (__any_sync(~0u, bad & 1)) {
                    if (elect()) {
                        const uint8_t* cur = (i < 4 ? G->O[mt][ks * 4] : src - 4 * TILEB) + i * TILEB;
                        fence_async_shared();
                        mbar_expect(landed, TILEB);
                        bulk_load(d0, cur, HALF, landed);
                        bulk_load(d1, cur + HALF, HALF, landed);
                    }
                    TS(4, i < 4 ? 94 : 95);
                } else {
                    if (elect()) mbar_expect(landed + (B_FULL - B_QFULL), i < 4 ? (2 + w) * SLAB : 16384);
                    i += __byte_perm(0x03020202u, 0x00010202u, 0x7770 + slot);
                    slot = __byte_perm(0x05060302u, 0x00040100u, 0x7770 + slot);
                }
            }
        } else {
            bar_sync(2, 288);
            if (elect()) bulk_store(out + row0 * D_, sbase + OFF_Y, TILEB);
            __syncwarp();
            bar_sync(4, 288);
            if (elect()) {
                fence_async_shared();
                bulk_store(G->O[tb][hp], sbase + OFF_X, TILEB);
                bulk_flush();
                TS(2, 7);
                mbar_arrive_remote(mapa(bars + B_FREE, rank ^ 1));
                mbar_arrive(bars + B_FREE);
                hint(G->flag[16 + tb]);
                signal(G->flag[16 + (row0 >> 7)] + 1);
                TS(2, 22);
            }
            __syncwarp();
            uint32_t late = ~0u;
            const uint32_t* hints = G->flag[8 + nt2 * 2 + ks] + lane;
            mbar_wait(bars + (has_g1 ? B_X : B_FREE), 0);
            Ring r{has_g1 ? 2u : 6u, has_g1};
#pragma unroll 1
            for (int i = 0; i < 14; i++) {
                while ((late >> i) & 1) late = __ballot_sync(~0u, ld_relaxed(hints) != 2 * ep) & 127;
                if (i == 0) TS(4, 17);
                mbar_wait(bars + B_EMPTY + 8 * r.slot, r.ph);
                TS(8, 192 + i);
                if (elect()) {
                    mbar_expect(bars + B_QFULL + 8 * r.slot, TILEB);
                    bulk_load(sbase + r.slot * SLOT + 16384, src, TILEB, bars + B_QFULL + 8 * r.slot);
                }
                src += TILEB; r.next2();
            }
            if (elect()) {
                wait_flag(G->flag[16 + mt] + 1, 8 * ep, spins);
                mbar_arrive(bars + B_ROW);
                TS(2, 27);
                G->epoch[c] = ep;
            }
        }
    } else {
        const int wg = warp >> 2;
        Mma M{bars, mapa(bars, rank ^ (lane & 1)), (threadIdx.x & 127) < 2, wg, w, Ring{0, 0}, 0};
        const int r = lane >> 2, t = lane & 3;
        uint32_t ep;
        const uint32_t bias0 = ld_u16(b1 + ft * 128 + warp * 16 + r), bias1 = ld_u16(b1 + ft * 128 + warp * 16 + r + 8);
        if (wg == 1) {
            ep = ld_relaxed(&G->epoch[c]);
            const int r16 = w * 4 + t, nt = (r + 2 * t) & 3, half = ((r + 2 * t) >> 2) & 1;
            const uint32_t row = sbase + OFF_Y + r16 * (2 * D_), part = row + nt * 224 + half * 112;
            const uint32_t hb = sbase + OFF_X + nt * (SLAB + 64) + r16 * 16 + (half ^ (row0 >> 10)) * (7 * 256);
            mbar_wait(bars + B_ROW, 0);
            TS0(1, 67);
            const float x0 = bf_lo(__float_as_uint(lds1f(row)));
            float d[56], s0 = 0.f, s1 = 0.f, q0 = 0.f, q1 = 0.f;
#pragma unroll
            for (int i = 0; i < 7; i++) {
                const uint4 v = lds4(part + i * 16);
                const uint32_t u[4] = {v.x, v.y, v.z, v.w};
#pragma unroll
                for (int k = 0; k < 4; k++) {
                    const float d0 = d[8 * i + 2 * k] = bf_lo(u[k]) - x0, d1 = d[8 * i + 2 * k + 1] = bf_hi(u[k]) - x0;
                    s0 += d0; s1 += d1; q0 = fmaf(d0, d0, q0); q1 = fmaf(d1, d1, q1);
                }
            }
            const float md = oct_sum(s0 + s1) * (1.f / D_), var = fmaf(-md, md, oct_sum(q0 + q1) * (1.f / D_)), nmean = -(x0 + md);
            const float rstd = rsq(var + LN_EPS);
            const float sc = rstd * rsq(fmaf(var * rstd, rstd, LN_EPS)), nb = -md * sc;
            if (lane < 4) G->stat[row0 + r16] = make_uint2(tag(__float_as_uint(rstd), 1, ~ep), pack2(nmean, nmean - bf_hi(pack2(nmean, nmean))));
#pragma unroll
            for (int i = 0; i < 7; i++) {
                uint32_t u[4];
#pragma unroll
                for (int k = 0; k < 4; k++) u[k] = pack2(fmaf(d[8 * i + 2 * k], sc, nb), fmaf(d[8 * i + 2 * k + 1], sc, nb));
                sts4(hb + i * 256, make_uint4(u[0], u[1], u[2], u[3]));
            }
            TS0(1, 25);
            bar_arrive(6, 160);
        }
        const uint32_t kv = sbase + OFF_X + (w * 2 + wg) * KV + lane * 16;
        uint32_t q[8][2], k0[7], k1[7], v0[7];
        {
            float acc[92];
#pragma unroll 1
            for (int kb = 0; kb < 7; kb++) {
                const bool held = kb == (wg ? 7 - HOLD : -1);
                if (held) { wg_wait<0>(); M.release(4 - HOLD); bar_sync(7, 256); }
                mbar_wait(bars + B_QFULL + 8 * kb, 0);
                TS0(1, 68 + wg * 7 + kb);
                const uint32_t dA = (xslot(kb) + wg) * 512, dB = wslot(kb) * 512 + (hp & 1);
                wg_fence();
#pragma unroll
                for (int k = 0; k < 4; k++) {
                    wgmma_n184<0, 1, HI_SW, HI_SW>(acc, dA + desc_lo(k * 32, 16), dB + desc_lo((k & 1) * 2048 + (k >> 1) * 12288, 4096), k > 0 || kb > 0);
                    if (k == 0) { wg_commit(); wg_wait<1>(); if (kb > 0 && !held) M.release(kb - 3); }
                }
                wg_commit();
            }
            if (wg == 0 && !LATEREL) bar_arrive(7, 256);
            bar_sync(8 + wg, 224);
            ep = __float_as_uint(lds1f(bars + 8 * NBAR));
            const uint32_t st = sbase + OFF_ST + (w * 32 + r * 2 + wg) * 8;
            const uint2 s0 = lds2(st), s1 = lds2(st + 128);
            const uint32_t a0 = t < 2 ? s0.y : 0, a1 = t < 2 ? s1.y : 0;
            wg_fence();
            wgmma_rs_n184<desc_hi(128, 0)>(acc, a0, a1, desc_lo(OFF_X, 0) + (hp & 1) * 8);
            wg_commit();
            if (wg == 0 && LATEREL) bar_arrive(7, 256);
            wg_wait<1>();
            M.release(4);
            wg_wait<0>();
            pin(acc);
            TS0(1, 4 + 7 * wg);
            uint32_t hi[14];
#pragma unroll
            for (int p = 2; p >= 0; p--) {
                const float f = p == 0 ? 0.1889822365046136f * 1.4426950408889634f : p, r0 = __uint_as_float(s0.x) * f, r1 = __uint_as_float(s1.x) * f;
#pragma unroll
                for (int g = 0; g < 7; g++) {
                    const int a = (p * 8 + g) * 4;
                    const uint32_t lo2 = pack2(acc[a] * r0, acc[a + 1] * r0), hi2 = pack2(acc[a + 2] * r1, acc[a + 3] * r1);
                    if (p == 0) { q[g][0] = lo2; q[g][1] = hi2; } else { hi[(p - 1) * 7 + g] = hi2; }
                    if (p == 1) { k0[g] = lo2; k1[g] = hi2; }
                    if (p == 2) v0[g] = lo2;
                }
                if (p == 1) {
#pragma unroll
                    for (int i = 0; i < 3; i++) stsm4(kv + 2 * KV + i * 512, hi[4 * i], hi[4 * i + 1], hi[4 * i + 2], hi[4 * i + 3]);
                    stsm2(kv + 2 * KV + 1536, hi[12], hi[13]);
                    if (w == 3) {
#pragma unroll
                        for (int i = 0; i < 14; i++) stg1(G->halo[c] + wg * KV + lane * 4 + i * 128, tag(hi[i], t == 0, ep));
                    }
                    bar_arrive(3, 288);
                }
            }
#pragma unroll
            for (int j = 0; j < 2; j++) { q[7][j] = t < 2 ? 0u : q[3][j]; q[3][j] = t < 2 ? q[3][j] : 0u; }
#pragma unroll
            for (int g = 0; g < 7; g++) v0[g] = transpose8(v0[g]);
        }
        TS0(1, 9 + 11 * wg);
        float a[56];
#pragma unroll
        for (int i = 0; i < 56; i++) asm volatile("" : "=f"(a[i]));
        if (__builtin_expect(!has_g1, 0)) {
            const int g = min(lane >> 1, 13), nt = rank * 2 + wg;
            const uint4* src = (const uint4*)(wo + (hp * 56 - (hp & 1) * 8 + w * 16 + (lane & 1)) * D_ + nt * 112) + g;
            uint4 v[8];
#pragma unroll
            for (int i = 0; i < 8; i++) v[i] = __ldg(src + i * (D_ / 4));
#pragma unroll
            for (int i = 0; i < 8; i++) ((uint4*)G->Wo[nt][hp])[w * (SLAB / 16) + g * 16 + (lane & 1) + 2 * i] = v[i];
            bar_arrive(5, 288);
        }
        M.run<true>(a, has_g1 ? PAUSE : 0, 1, 16, 0, 0, 32);
        {
            uint32_t kp[8], vv[14];
            TS0(2, 140 + wg);
            mbar_wait(bars + B_HALO, 0);
            TS0(2, 142 + wg);
            ldsm4(kp, kv); ldsm4(kp + 4, kv + (lane < 24 ? 512 : 0));
            const uint32_t va = kv + 896 + (lane & 8) * (2 * KV / 8 - 16) - (lane & 16) * 8;
            ldsm4t(vv, va); ldsm4t(vv + 4, va + 256); ldsm4t(vv + 8, va + 512); ldsm2t(vv + 12, va + 768);
            const bool e0 = 2 * t > r, e1 = 2 * t >= r;
            const uint32_t mk = (e0 ? 0xffffu : 0u) | (e1 ? 0xffff0000u : 0u);
            wg_wait<0>();
            pin(a);
            if (has_g1) M.release(M.prev);
            TS0(2, 144 + wg);
            bar_sync(2, 288);
            mbar_wait(bars + B_HALO, 0);
            TS0(2, 12 + 16 * wg);
            float sv[2][4];
#pragma unroll
            for (int h = 0; h < 2; h++) {
                const int ga = h * 4, gb = h * 4 + 1, gc = h * 4 + 2, gd = h * 4 + 3;
                float s[3][4] = {};
                mma16(s[0], q[ga][0], q[ga][1], q[gb][0], q[gb][1], kp[ga], kp[gb]);
                mma16(s[1], q[ga][0], q[ga][1], q[gb][0], q[gb][1], k0[ga], k0[gb]);
                mma16(s[2], q[ga][0], q[ga][1], q[gb][0], q[gb][1], k1[ga], k1[gb]);
                mma16(s[0], q[gc][0], q[gc][1], q[gd][0], q[gd][1], kp[gc], kp[gd]);
                mma16(s[1], q[gc][0], q[gc][1], q[gd][0], q[gd][1], k0[gc], k0[3]);
                mma16(s[2], q[gc][0], q[gc][1], q[gd][0], q[gd][1], k1[gc], k1[3]);
                if ((tb | w) == 0) s[0][0] = s[0][1] = -1e30f;
                sv[h][0] = e0 ? s[0][0] : s[1][0];
                sv[h][1] = e1 ? s[0][1] : s[1][1];
                sv[h][2] = e0 ? s[1][2] : s[2][2];
                sv[h][3] = e1 ? s[1][3] : s[2][3];
            }
            uint32_t pp[2][2];
#pragma unroll
            for (int i = 0; i < 4; i++) {
                float* v = &sv[i >> 1][(i & 1) * 2];
                const float m = quad_max(fmaxf(v[0], v[1]));
                const float p0 = ex2(v[0] - m), p1 = ex2(v[1] - m);
                const float inv = rcp(quad_sum(p0 + p1));
                pp[i >> 1][i & 1] = pack2(p0 * inv, p1 * inv);
            }
            uint32_t o[8][2];
#pragma unroll
            for (int i = 0; i < 8; i++) {
                const int h = i >> 2, g = i - h;
                float d[4] = {};
                mma16(d, pp[h][0] & mk, 0u, 0u, pp[h][1] & ~mk, vv[2 * g], vv[2 * g + 1]);
                mma8(d, pp[h][0] & ~mk, pp[h][1] & mk, v0[g]);
                o[i][0] = pack2(d[0], d[1]); o[i][1] = pack2(d[2], d[3]);
            }
            if (t >= 2) { o[3][0] = o[4][0]; o[3][1] = o[4][1]; }
            const int word = wg * 4 + t - (w & 1) * 4 - (r >> 2);
#pragma unroll
            for (int i = 0; i < 8; i++) { o[i][0] = tag(o[i][0], word == 0, ep); o[i][1] = tag(o[i][1], word == 2, ep); }
            const uint32_t dst = sbase + OFF_X + (w >> 1) * HALF + ((w & 1) * 32 + (lane & 15) * 2 + wg) * 16 + (lane >> 4) * 1024;
            stsm4(dst, o[0][0], o[0][1], o[1][0], o[1][1]);
            stsm4(dst + 2048, o[2][0], o[2][1], o[3][0], o[3][1]);
            stsm4(dst + 4096, o[5][0], o[5][1], o[6][0], o[6][1]);
            stsm2(dst + 6144, o[7][0], o[7][1]);
            if (ENDBAR) bar_sync(4, 288); else bar_arrive(4, 288);
            TS0(2, 10 + 19 * wg);
        }
        if (has_g1) {
            M.run<true>(a, 16 - PAUSE, 1, 16, LAG1, 1, 32 + PAUSE);
            mbar_wait(bars + B_FREE, 0);
            const uint32_t xb = sbase + OFF_X + wg * 8192 + (threadIdx.x & 127) * 16, xbar = bars + B_X + 16 * wg;
            const uint32_t rx = mapa(xb, rank ^ 1), rbar = mapa(xbar, rank ^ 1);
            wg_wait<0>();
            pin(a);
            M.release(M.prev);
            TS0(4, 5 + wg);
#pragma unroll
            for (int i = 0; i < 3; i++)
                st_async4(rx + i * 2048, rbar + 8 * (i >> 1), pack2(a[28 + 8 * i], a[29 + 8 * i]), pack2(a[30 + 8 * i], a[31 + 8 * i]), pack2(a[32 + 8 * i], a[33 + 8 * i]), pack2(a[34 + 8 * i], a[35 + 8 * i]));
            const uint32_t tail = 6144 - (threadIdx.x & 127) * 8;
            st_async2(rx + tail, rbar + 8, pack2(a[52], a[53]), pack2(a[54], a[55]));
            uint8_t* dst = G->U[nt1][((ft >= 7) + wg) * 7 + ft] + rank * HALF + w * 256 + lane * 4;
            uint32_t u[14];
#pragma unroll
            for (int i = 0; i < 28; i++) a[i] += bf_lo((i & 2) ? bias1 : bias0);
#pragma unroll
            for (int i = 0; i < 14; i++) {
                if (i % 8 == 0) {
                    if (i) TS0(4, 134 + wg);
                    mbar_wait(xbar + i, 0);
                    TS0(4, (i ? 136 : 1) + wg);
#pragma unroll
                    for (int k = i / 4; k < i / 4 + 2; k++) {
                        if (k < 3) { const uint4 v = lds4(xb + k * 2048); u[4 * k] = v.x; u[4 * k + 1] = v.y; u[4 * k + 2] = v.z; u[4 * k + 3] = v.w; }
                        else { const uint2 v = lds2(xb + tail); u[12] = v.x; u[13] = v.y; }
                    }
                    if (i && lane < 2) mbar_arrive_remote(M.rel + B_EMPTY + 48);
                }
                if (i == HINT && threadIdx.x == 0) hint(G->flag[8 + nt1 * 2] + ft + (ft >= 7) * 25);
                stg1(dst + (i >> 1) * 1024 + (i & 1) * 128, tag(pack2(gelu2(a[2 * i] + bf_lo(u[i])), gelu2(a[2 * i + 1] + bf_hi(u[i]))), (lane & 7) == w * 2 + (i & 1), ep));
            }
            TS0(4, 30 + wg);
        } else {
            mbar_wait(bars + B_FREE, 0);
            if (lane < 2) mbar_arrive_remote(M.rel + B_EMPTY + 48);
        }
        uint32_t c0 = ld_u16(b2 + mt * 128 + warp * 16 + r), c1 = ld_u16(b2 + mt * 128 + warp * 16 + r + 8);
        M.run_o(a);
        if (wg == 1) TS0(4, 13);
        c0 *= ks == 0 ? 0x10001u : 0u; c1 *= ks == 0 ? 0x10001u : 0u;
        M.run<false>(a, 14, 0, 14 - NSLOT, LAG2, 1, 52);
        mbar_wait(bars + B_ROW, 1);
        const uint32_t stg = sbase + ((has_g1 ? STG1 : STG0) + (w >> 1) * STGS) * SLOT + wg * 8192 + (w & 1) * SLAB;
        const uint32_t sa = stg + (lane & 15) * 224 + (lane >> 4) * 16;
        wg_wait<0>();
        pin(a);
        TS0(8, 14 + wg);
#pragma unroll
        for (int i = 0; i < 7; i++)
            stsm4(sa + i * 32, half_plus(pack2(a[8 * i], a[8 * i + 1]), c0), half_plus(pack2(a[8 * i + 2], a[8 * i + 3]), c1),
                  half_plus(pack2(a[8 * i + 4], a[8 * i + 5]), c0), half_plus(pack2(a[8 * i + 6], a[8 * i + 7]), c1));
        fence_async_shared();
        __syncwarp();
        if (elect()) {
            asm volatile("cp.reduce.async.bulk.tensor.2d.global.shared::cta.add.tile.bulk_group [%0, {%2, %3}], [%1];\ncp.async.bulk.commit_group;" ::"l"(&P.tmOut), "r"(stg), "r"(nt2 * 112), "r"(mt * 128 + warp * 16) : "memory");
            if (w == 0) mbar_arrive(bars + B_END);
            asm volatile("cp.async.bulk.wait_group.read 0;" ::: "memory");
        }
        if (wg == 1) TS0(15, 19);
        TSDUMP();
    }
}

typedef CUresult (*EncodeFn)(CUtensorMap*, CUtensorMapDataType, cuuint32_t, void*, const cuuint64_t*, const cuuint64_t*, const cuuint32_t*, const cuuint32_t*,
                             CUtensorMapInterleave, CUtensorMapSwizzle, CUtensorMapL2promotion, CUtensorMapFloatOOBfill);

void make_map(EncodeFn enc, CUtensorMap* tm, const void* base, bool swizzle, int d0, int d1, int d2, int s1, int s2, int b0, int b1, int b2) {
    const cuuint64_t dims[3] = {(cuuint64_t)d0, (cuuint64_t)d1, (cuuint64_t)d2}, strides[2] = {(cuuint64_t)s1 * 2, (cuuint64_t)s2 * 2};
    const cuuint32_t box[3] = {(cuuint32_t)b0, (cuuint32_t)b1, (cuuint32_t)b2}, es[3] = {1, 1, 1};
    enc(tm, CU_TENSOR_MAP_DATA_TYPE_BFLOAT16, d2 ? 3 : 2, (void*)base, dims, strides, box, es, CU_TENSOR_MAP_INTERLEAVE_NONE,
        swizzle ? CU_TENSOR_MAP_SWIZZLE_128B : CU_TENSOR_MAP_SWIZZLE_NONE, CU_TENSOR_MAP_L2_PROMOTION_L2_128B, CU_TENSOR_MAP_FLOAT_OOB_FILL_NONE);
}

}

extern "C" void kernel_launch(void* const* d_in, const int* in_sizes, int n_in, void* d_out, int out_size) {
    static EncodeFn enc = nullptr;
    static Scratch* scratch = nullptr;
    if (!enc) {
        void* fn = nullptr;
        cudaDriverEntryPointQueryResult qr;
        cudaGetDriverEntryPoint("cuTensorMapEncodeTiled", &fn, cudaEnableDefault, &qr);
        enc = (EncodeFn)fn;
        cudaGetSymbolAddress((void**)&scratch, g_s);
        cudaFuncSetAttribute(fused_kernel, cudaFuncAttributeMaxDynamicSharedMemorySize, SMEM_BYTES);
    }
    Params P;
    const __nv_bfloat16* x = (const __nv_bfloat16*)d_in[0];
    make_map(enc, &P.tmX, x, true, D_, S_ / 2, 2, 2 * D_, D_, 64, 64, 2);
    make_map(enc, &P.tmWqkv, d_in[1], true, D_, D_, 3, 3 * D_, D_, 64, 32, 3);
    make_map(enc, &P.tmW1, d_in[4], true, 64, S_, F_ / 64, F_, 64, 64, 64, 2);
    make_map(enc, &P.tmW2, d_in[6], true, S_, F_, 0, S_, 0, 64, 64, 1);
    make_map(enc, &P.tmOut, d_out, false, D_, S_, 0, D_, 0, 112, 16, 1);
    fused_kernel<<<NCTA, NTHREADS, SMEM_BYTES, cudaStreamPerThread>>>(x, (const __nv_bfloat16*)d_in[5], (const __nv_bfloat16*)d_in[7], (const __nv_bfloat16*)d_in[2], (__nv_bfloat16*)d_out, scratch,
                                                                      (const __nv_bfloat16*)d_in[4], (const __nv_bfloat16*)d_in[6], P);
}
```

```cpp
#include <cuda_runtime.h>
#include <cuda_bf16.h>
#include <cuda.h>
#include <stdint.h>

#define HALO_NS 300
#define HINT 4
#define HOLD 2
#define ROT 2
#define LATEREL 1
#define PF 400
#define PF0 2
#define PF1 8
#define ENDBAR 1
#define PG0 3
#define PG1 5
#define STG1 4
#define STG0 4
#define STGS 1
#define CSU 1
#define REC_NS 0
#define LEADW 4
#define LEADN 7
#define LOCREL 1
#define SWAP2 0
#define PACE 600
#define PAUSE 8
#define LAG1 4
#define LAG2 6

namespace {

constexpr int S_ = 2048, D_ = 448, F_ = 1792;
constexpr int NCTA = 128, NTHREADS = 384;
constexpr int NSLOT = 6, SLOT = 32768, QSLOT = 40960, TILEB = 14336, SLAB = 3584, HALF = 7168;
constexpr int KV = 1792, kCsu = CSU;
constexpr int OFF_X = NSLOT * SLOT;
constexpr int OFF_Y = OFF_X + 10 * KV;
constexpr int OFF_ST = OFF_Y + TILEB;
constexpr int OFF_BAR = OFF_ST + 1024;
constexpr int SMEM_BYTES = OFF_BAR + 1280;
constexpr uint32_t SMEM0 = 1024;
constexpr int B_QFULL = 0, B_FULL = 56, B_HALO = 128, B_X = 136, B_FREE = 192, B_END = 200, B_CS = 208, B_QEMPTY = 216, B_EMPTY = 232, B_ROW = 288, NBAR = 37;
constexpr float LN_EPS = 1e-5f;
constexpr int SPIN_LIMIT = 1 << 22;

struct Scratch {
    uint8_t H[4][32][TILEB];
    uint8_t U[4][28][TILEB];
    uint8_t O[16][8][TILEB];
    uint8_t Wo[4][8][TILEB];
    uint8_t halo[NCTA][2 * KV];
    uint2 stat[S_];
    uint2 colsum[8][8][96];
    uint32_t flag[32][32];
    uint32_t epoch[NCTA];
};
__device__ __align__(1024) Scratch g_s;

#define TS(g, i)
#define TS0(g, i)
#define TSDUMP()

struct Params {
    CUtensorMap tmX, tmWqkv, tmW1, tmW2, tmOut;
};

__device__ __forceinline__ bool elect() {
    uint32_t p;
    asm volatile("{\n.reg .pred p;\nelect.sync _|p, 0xffffffff;\nselp.u32 %0, 1, 0, p;\n}" : "=r"(p));
    return p;
}
__device__ __forceinline__ void mbar_init(uint32_t b, uint32_t c) { asm volatile("mbarrier.init.shared::cta.b64 [%0], %1;" ::"r"(b), "r"(c) : "memory"); }
__device__ __forceinline__ void mbar_expect(uint32_t b, uint32_t tx) { asm volatile("mbarrier.arrive.expect_tx.shared::cta.b64 _, [%0], %1;" ::"r"(b), "r"(tx) : "memory"); }
__device__ __forceinline__ void mbar_arrive(uint32_t b) { asm volatile("mbarrier.arrive.shared::cta.b64 _, [%0];" ::"r"(b) : "memory"); }
__device__ __forceinline__ void mbar_arrive16(uint32_t b) { asm volatile("mbarrier.arrive.shared::cta.b64 _, [%0], 16;" ::"r"(b) : "memory"); }
__device__ __forceinline__ void mbar_arrive4_remote(uint32_t b) { asm volatile("mbarrier.arrive.shared::cluster.b64 _, [%0], 4;" ::"r"(b) : "memory"); }
__device__ __forceinline__ void mbar_arrive_remote(uint32_t b) { asm volatile("mbarrier.arrive.shared::cluster.b64 _, [%0];" ::"r"(b) : "memory"); }
#define MBAR_WAIT_ASM(SEM) \
    asm volatile("{\n.reg .pred p;\nWAIT:\nmbarrier.try_wait.parity" SEM ".shared::cta.b64 p, [%0], %1;\n@!p bra WAIT;\n}" ::"r"(b), "r"(parity) : "memory")
__device__ __forceinline__ void mbar_wait(uint32_t b, uint32_t parity) { MBAR_WAIT_ASM(""); }
__device__ __forceinline__ void mbar_wait_bounded(uint32_t b, uint32_t parity, uint32_t& n) {
    asm volatile("{\n.reg .pred p;\nWAIT:\nadd.u32 %0, %0, 1;\nsetp.gt.u32 p, %0, %3;\n@p st.global.u32 [%4], %0;\n"
                 "mbarrier.try_wait.parity.shared::cta.b64 p, [%1], %2;\n@!p bra WAIT;\n}" : "+r"(n) : "r"(b), "r"(parity), "n"(SPIN_LIMIT), "l"(0ull) : "memory");
}
__device__ __forceinline__ uint32_t mapa(uint32_t a, uint32_t rank) { uint32_t r; asm("mapa.shared::cluster.u32 %0, %1, %2;" : "=r"(r) : "r"(a), "r"(rank)); return r; }
__device__ __forceinline__ void tma3d(uint32_t dst, const CUtensorMap* tm, uint32_t bar, int c0, int c1, int c2) {
    asm volatile("cp.async.bulk.tensor.3d.shared::cluster.global.mbarrier::complete_tx::bytes [%0], [%1, {%3, %4, %5}], [%2];" ::"r"(dst), "l"(tm), "r"(bar), "r"(c0), "r"(c1), "r"(c2) : "memory");
}
__device__ __forceinline__ void tma3d_pair(uint32_t dst, const CUtensorMap* tm, uint32_t bar, int c0, int c1, int c2) {
    asm volatile("cp.async.bulk.tensor.3d.shared::cluster.global.mbarrier::complete_tx::bytes.multicast::cluster [%0], [%1, {%3, %4, %5}], [%2], %6;" ::"r"(dst), "l"(tm), "r"(bar), "r"(c0), "r"(c1), "r"(c2), "h"((uint16_t)3) : "memory");
}
__device__ __forceinline__ void bulk_load(uint32_t dst, const void* src, uint32_t bytes, uint32_t bar) {
    asm volatile("cp.async.bulk.shared::cluster.global.mbarrier::complete_tx::bytes [%0], [%1], %2, [%3];" ::"r"(dst), "l"(src), "r"(bytes), "r"(bar) : "memory");
}
__device__ __forceinline__ void bulk_load_pair(uint32_t dst, const void* src, uint32_t bytes, uint32_t bar) {
    asm volatile("cp.async.bulk.shared::cluster.global.mbarrier::complete_tx::bytes.multicast::cluster [%0], [%1], %2, [%3], %4;" ::"r"(dst), "l"(src), "r"(bytes), "r"(bar), "h"((uint16_t)3) : "memory");
}
__device__ __forceinline__ void bulk_store(void* dst, uint32_t src, uint32_t bytes) {
    asm volatile("cp.async.bulk.global.shared::cta.bulk_group [%0], [%1], %2;" ::"l"(dst), "r"(src), "r"(bytes) : "memory");
}
__device__ __forceinline__ uint32_t ld_u16(const void* p) { uint32_t v; asm volatile("ld.global.nc.u16 %0, [%1];" : "=r"(v) : "l"(p)); return v; }
__device__ __forceinline__ uint32_t ld_relaxed(const uint32_t* p) { uint32_t v; asm volatile("ld.relaxed.gpu.global.u32 %0, [%1];" : "=r"(v) : "l"(p) : "memory"); return v; }
__device__ __forceinline__ void bulk_flush() { asm volatile("cp.async.bulk.commit_group;\ncp.async.bulk.wait_group 0;" ::: "memory"); }
__device__ __forceinline__ void signal(uint32_t* flag) { asm volatile("fence.acq_rel.gpu;\nred.relaxed.gpu.global.add.u32 [%0], 1;" ::"l"(flag) : "memory"); }
__device__ __forceinline__ void hint(uint32_t* flag) { asm volatile("red.relaxed.gpu.global.add.u32 [%0], 1;" ::"l"(flag) : "memory"); }
__device__ __forceinline__ uint32_t tag(uint32_t v, uint32_t mask, uint32_t parity) { return (v & ~mask) | (parity & mask); }
__device__ __forceinline__ uint32_t or_diff(uint32_t acc, uint32_t v, uint32_t parity) { asm("lop3.b32 %0, %0, %1, %2, 0xf6;" : "+r"(acc) : "r"(v), "r"(parity)); return acc; }
__device__ __forceinline__ uint4 ld_relaxed4(const void* p) {
    uint4 v;
    asm volatile("ld.relaxed.gpu.global.v4.u32 {%0, %1, %2, %3}, [%4];" : "=r"(v.x), "=r"(v.y), "=r"(v.z), "=r"(v.w) : "l"(p) : "memory");
    return v;
}
__device__ __forceinline__ uint2 ld_relaxed2(const void* p) { uint2 v; asm volatile("ld.relaxed.gpu.global.v2.u32 {%0, %1}, [%2];" : "=r"(v.x), "=r"(v.y) : "l"(p) : "memory"); return v; }
__device__ __forceinline__ void sts4(uint32_t a, uint4 v) { asm volatile("st.shared.v4.b32 [%0], {%1, %2, %3, %4};" ::"r"(a), "r"(v.x), "r"(v.y), "r"(v.z), "r"(v.w) : "memory"); }
__device__ __forceinline__ void stg1(void* p, uint32_t v) { asm volatile("st.global.b32 [%0], %1;" ::"l"(p), "r"(v) : "memory"); }
__device__ __forceinline__ void fence_async_shared() { asm volatile("fence.proxy.async.shared::cta;" ::: "memory"); }
#define BOUND "add.u32 %0, %0, 16;\nsetp.gt.u32 p, %0, %1;\n@p st.global.u32 [%2], %0;\n"
__device__ __forceinline__ void wait_flag(const uint32_t* p, uint32_t target, uint32_t& n) {
    asm volatile("{\n.reg .pred p;\n.reg .u32 v;\nPOLL:\n" BOUND "ld.acquire.gpu.global.u32 v, [%3];\nsetp.ne.u32 p, v, %4;\n@p bra POLL;\nfence.proxy.async.global;\n}"
                 : "+r"(n) : "n"(SPIN_LIMIT), "l"(0ull), "l"(p), "r"(target) : "memory");
}
__device__ __forceinline__ void wait_flag2(const uint32_t* h, uint32_t th, const uint32_t* p, uint32_t target, uint32_t& n) {
    asm volatile("{\n.reg .pred p;\n.reg .u32 u, v;\nPOLL:\n" BOUND "ld.relaxed.gpu.global.u32 u, [%3];\nld.acquire.gpu.global.u32 v, [%5];\nsetp.ne.u32 p, u, %4;\nsetp.ne.or.u32 p, v, %6, p;\n@p bra POLL;\nfence.proxy.async.global;\n}"
                 : "+r"(n) : "n"(SPIN_LIMIT), "l"(0ull), "l"(h), "r"(th), "l"(p), "r"(target) : "memory");
}
__device__ __forceinline__ void bar_sync(int id, int n) { asm volatile("bar.sync %0, %1;" ::"r"(id), "r"(n) : "memory"); }
__device__ __forceinline__ void bar_arrive(int id, int n) { asm volatile("bar.arrive %0, %1;" ::"r"(id), "r"(n) : "memory"); }
__device__ __forceinline__ void wg_fence() { asm volatile("wgmma.fence.sync.aligned;" ::: "memory"); }
__device__ __forceinline__ void wg_commit() { asm volatile("wgmma.commit_group.sync.aligned;" ::: "memory"); }
template <int N> __device__ __forceinline__ void wg_wait() { asm volatile("wgmma.wait_group.sync.aligned %0;" ::"n"(N) : "memory"); }
template <int N> __device__ __forceinline__ void pin(float (&d)[N]) {
#pragma unroll
    for (int i = 0; i < N; i++) asm volatile("" : "+f"(d[i])::"memory");
}
__host__ __device__ constexpr uint32_t desc_hi(uint32_t sbo, uint32_t swz) { return (sbo >> 4) | (swz << 30); }
__host__ __device__ constexpr uint32_t desc_lo(uint32_t off, uint32_t lbo) { return ((SMEM0 + off) >> 4) | ((lbo >> 4) << 16); }
__device__ __forceinline__ uint32_t pack2(float lo, float hi) { uint32_t r; asm("cvt.rn.bf16x2.f32 %0, %1, %2;" : "=r"(r) : "f"(hi), "f"(lo)); return r; }
__device__ __forceinline__ float bf_lo(uint32_t v) { return __uint_as_float(v << 16); }
__device__ __forceinline__ float bf_hi(uint32_t v) { return __uint_as_float(v & 0xffff0000u); }
__device__ __forceinline__ uint32_t half_plus(uint32_t a, uint32_t b) { uint32_t r; asm("fma.rn.bf16x2 %0, %1, %2, %3;" : "=r"(r) : "r"(a), "r"(0x3f003f00u), "r"(b)); return r; }
__device__ __forceinline__ void stsm4(uint32_t a, uint32_t r0, uint32_t r1, uint32_t r2, uint32_t r3) {
    asm volatile("stmatrix.sync.aligned.m8n8.x4.shared.b16 [%0], {%1, %2, %3, %4};" ::"r"(a), "r"(r0), "r"(r1), "r"(r2), "r"(r3) : "memory");
}
__device__ __forceinline__ void stsm2(uint32_t a, uint32_t r0, uint32_t r1) {
    asm volatile("stmatrix.sync.aligned.m8n8.x2.shared.b16 [%0], {%1, %2};" ::"r"(a), "r"(r0), "r"(r1) : "memory");
}
__device__ __forceinline__ uint4 lds4(uint32_t a) { uint4 v; asm volatile("ld.shared.v4.b32 {%0, %1, %2, %3}, [%4];" : "=r"(v.x), "=r"(v.y), "=r"(v.z), "=r"(v.w) : "r"(a) : "memory"); return v; }
__device__ __forceinline__ uint2 lds2(uint32_t a) { uint2 v; asm volatile("ld.shared.v2.b32 {%0, %1}, [%2];" : "=r"(v.x), "=r"(v.y) : "r"(a) : "memory"); return v; }
__device__ __forceinline__ float lds1f(uint32_t a) { float v; asm volatile("ld.shared.f32 %0, [%1];" : "=f"(v) : "r"(a) : "memory"); return v; }
__device__ __forceinline__ void ldsm4(uint32_t* r, uint32_t a) {
    asm volatile("ldmatrix.sync.aligned.m8n8.x4.shared.b16 {%0, %1, %2, %3}, [%4];" : "=r"(r[0]), "=r"(r[1]), "=r"(r[2]), "=r"(r[3]) : "r"(a) : "memory");
}
__device__ __forceinline__ void ldsm4t(uint32_t* r, uint32_t a) {
    asm volatile("ldmatrix.sync.aligned.m8n8.x4.trans.shared.b16 {%0, %1, %2, %3}, [%4];" : "=r"(r[0]), "=r"(r[1]), "=r"(r[2]), "=r"(r[3]) : "r"(a) : "memory");
}
__device__ __forceinline__ void ldsm2t(uint32_t* r, uint32_t a) {
    asm volatile("ldmatrix.sync.aligned.m8n8.x2.trans.shared.b16 {%0, %1}, [%2];" : "=r"(r[0]), "=r"(r[1]) : "r"(a) : "memory");
}
__device__ __forceinline__ uint32_t transpose8(uint32_t v) { uint32_t r; asm volatile("movmatrix.sync.aligned.m8n8.trans.b16 %0, %1;" : "=r"(r) : "r"(v)); return r; }
__device__ __forceinline__ void mma16(float (&c)[4], uint32_t a0, uint32_t a1, uint32_t a2, uint32_t a3, uint32_t b0, uint32_t b1) {
    asm volatile("mma.sync.aligned.m16n8k16.row.col.f32.bf16.bf16.f32 {%0, %1, %2, %3}, {%4, %5, %6, %7}, {%8, %9}, {%0, %1, %2, %3};"
                 : "+f"(c[0]), "+f"(c[1]), "+f"(c[2]), "+f"(c[3]) : "r"(a0), "r"(a1), "r"(a2), "r"(a3), "r"(b0), "r"(b1));
}
__device__ __forceinline__ void mma8(float (&c)[4], uint32_t a0, uint32_t a1, uint32_t b0) {
    asm volatile("mma.sync.aligned.m16n8k8.row.col.f32.bf16.bf16.f32 {%0, %1, %2, %3}, {%4, %5}, {%6}, {%0, %1, %2, %3};"
                 : "+f"(c[0]), "+f"(c[1]), "+f"(c[2]), "+f"(c[3]) : "r"(a0), "r"(a1), "r"(b0));
}
__device__ __forceinline__ void st_async4(uint32_t a, uint32_t bar, uint32_t v0, uint32_t v1, uint32_t v2, uint32_t v3) {
    asm volatile("st.async.weak.shared::cluster.mbarrier::complete_tx::bytes.v4.b32 [%0], {%2, %3, %4, %5}, [%1];" ::"r"(a), "r"(bar), "r"(v0), "r"(v1), "r"(v2), "r"(v3) : "memory");
}
__device__ __forceinline__ void st_async2(uint32_t a, uint32_t bar, uint32_t v0, uint32_t v1) {
    asm volatile("st.async.weak.shared::cluster.mbarrier::complete_tx::bytes.v2.b32 [%0], {%2, %3}, [%1];" ::"r"(a), "r"(bar), "r"(v0), "r"(v1) : "memory");
}
__device__ __forceinline__ float quad_max(float v) { v = fmaxf(v, __shfl_xor_sync(~0u, v, 1)); return fmaxf(v, __shfl_xor_sync(~0u, v, 2)); }
__device__ __forceinline__ float quad_sum(float v) { v += __shfl_xor_sync(~0u, v, 1); return v + __shfl_xor_sync(~0u, v, 2); }
__device__ __forceinline__ float ex2(float v) { float r; asm("ex2.approx.ftz.f32 %0, %1;" : "=f"(r) : "f"(v)); return r; }
__device__ __forceinline__ float rcp(float v) { float r; asm("rcp.approx.ftz.f32 %0, %1;" : "=f"(r) : "f"(v)); return r; }
__device__ __forceinline__ float rsq(float v) { float r; asm("rsqrt.approx.ftz.f32 %0, %1;" : "=f"(r) : "f"(v)); return r; }
__device__ __forceinline__ float gelu2(float u) {
    float z = u * fmaf(u * u, 0.044715f * 0.7978845608028654f, 0.7978845608028654f), t;
    asm("tanh.approx.f32 %0, %1;" : "=f"(t) : "f"(z));
    return fmaf(u, t, u);
}
__device__ __forceinline__ float oct_sum(float v) {
    v += __shfl_xor_sync(~0u, v, 4); v += __shfl_xor_sync(~0u, v, 8); v += __shfl_xor_sync(~0u, v, 16);
    return v;
}

template <int TA, int TB, uint32_t HA, uint32_t HB>
__device__ __forceinline__ void wgmma_n112(float (&d)[56], uint32_t da, uint32_t db, int accumulate) {
    asm volatile("{\n.reg .pred p;\n.reg .b64 a, b;\nmov.b64 a, {%56, %61};\nmov.b64 b, {%57, %62};\nsetp.ne.b32 p, %58, 0;\n"
        "wgmma.mma_async.sync.aligned.m64n112k16.f32.bf16.bf16 {"
        "%0, %1, %2, %3, %4, %5, %6, %7, %8, %9, %10, %11, %12, %13, %14, %15, "
        "%16, %17, %18, %19, %20, %21, %22, %23, %24, %25, %26, %27, %28, %29, %30, %31, "
        "%32, %33, %34, %35, %36, %37, %38, %39, %40, %41, %42, %43, %44, %45, %46, %47, "
        "%48, %49, %50, %51, %52, %53, %54, %55"
        "}, a, b, p, 1, 1, %59, %60;\n}\n"
        : "+f"(d[0]), "+f"(d[1]), "+f"(d[2]), "+f"(d[3]), "+f"(d[4]), "+f"(d[5]), "+f"(d[6]), "+f"(d[7]),
          "+f"(d[8]), "+f"(d[9]), "+f"(d[10]), "+f"(d[11]), "+f"(d[12]), "+f"(d[13]), "+f"(d[14]), "+f"(d[15]),
          "+f"(d[16]), "+f"(d[17]), "+f"(d[18]), "+f"(d[19]), "+f"(d[20]), "+f"(d[21]), "+f"(d[22]), "+f"(d[23]),
          "+f"(d[24]), "+f"(d[25]), "+f"(d[26]), "+f"(d[27]), "+f"(d[28]), "+f"(d[29]), "+f"(d[30]), "+f"(d[31]),
          "+f"(d[32]), "+f"(d[33]), "+f"(d[34]), "+f"(d[35]), "+f"(d[36]), "+f"(d[37]), "+f"(d[38]), "+f"(d[39]),
          "+f"(d[40]), "+f"(d[41]), "+f"(d[42]), "+f"(d[43]), "+f"(d[44]), "+f"(d[45]), "+f"(d[46]), "+f"(d[47]),
          "+f"(d[48]), "+f"(d[49]), "+f"(d[50]), "+f"(d[51]), "+f"(d[52]), "+f"(d[53]), "+f"(d[54]), "+f"(d[55])
        : "r"(da), "r"(db), "r"(accumulate), "n"(TA), "n"(TB), "n"(HA), "n"(HB));
}

template <int TA, int TB, uint32_t HA, uint32_t HB>
__device__ __forceinline__ void wgmma_n184(float (&d)[92], uint32_t da, uint32_t db, int accumulate) {
    asm volatile("{\n.reg .pred p;\n.reg .b64 a, b;\nmov.b64 a, {%92, %97};\nmov.b64 b, {%93, %98};\nsetp.ne.b32 p, %94, 0;\n"
        "wgmma.mma_async.sync.aligned.m64n184k16.f32.bf16.bf16 {"
        "%0, %1, %2, %3, %4, %5, %6, %7, %8, %9, %10, %11, %12, %13, %14, %15, "
        "%16, %17, %18, %19, %20, %21, %22, %23, %24, %25, %26, %27, %28, %29, %30, %31, "
        "%32, %33, %34, %35, %36, %37, %38, %39, %40, %41, %42, %43, %44, %45, %46, %47, "
        "%48, %49, %50, %51, %52, %53, %54, %55, %56, %57, %58, %59, %60, %61, %62, %63, "
        "%64, %65, %66, %67, %68, %69, %70, %71, %72, %73, %74, %75, %76, %77, %78, %79, "
        "%80, %81, %82, %83, %84, %85, %86, %87, %88, %89, %90, %91"
        "}, a, b, p, 1, 1, %95, %96;\n}\n"
        : "+f"(d[0]), "+f"(d[1]), "+f"(d[2]), "+f"(d[3]), "+f"(d[4]), "+f"(d[5]), "+f"(d[6]), "+f"(d[7]),
          "+f"(d[8]), "+f"(d[9]), "+f"(d[10]), "+f"(d[11]), "+f"(d[12]), "+f"(d[13]), "+f"(d[14]), "+f"(d[15]),
          "+f"(d[16]), "+f"(d[17]), "+f"(d[18]), "+f"(d[19]), "+f"(d[20]), "+f"(d[21]), "+f"(d[22]), "+f"(d[23]),
          "+f"(d[24]), "+f"(d[25]), "+f"(d[26]), "+f"(d[27]), "+f"(d[28]), "+f"(d[29]), "+f"(d[30]), "+f"(d[31]),
          "+f"(d[32]), "+f"(d[33]), "+f"(d[34]), "+f"(d[35]), "+f"(d[36]), "+f"(d[37]), "+f"(d[38]), "+f"(d[39]),
          "+f"(d[40]), "+f"(d[41]), "+f"(d[42]), "+f"(d[43]), "+f"(d[44]), "+f"(d[45]), "+f"(d[46]), "+f"(d[47]),
          "+f"(d[48]), "+f"(d[49]), "+f"(d[50]), "+f"(d[51]), "+f"(d[52]), "+f"(d[53]), "+f"(d[54]), "+f"(d[55]),
          "+f"(d[56]), "+f"(d[57]), "+f"(d[58]), "+f"(d[59]), "+f"(d[60]), "+f"(d[61]), "+f"(d[62]), "+f"(d[63]),
          "+f"(d[64]), "+f"(d[65]), "+f"(d[66]), "+f"(d[67]), "+f"(d[68]), "+f"(d[69]), "+f"(d[70]), "+f"(d[71]),
          "+f"(d[72]), "+f"(d[73]), "+f"(d[74]), "+f"(d[75]), "+f"(d[76]), "+f"(d[77]), "+f"(d[78]), "+f"(d[79]),
          "+f"(d[80]), "+f"(d[81]), "+f"(d[82]), "+f"(d[83]), "+f"(d[84]), "+f"(d[85]), "+f"(d[86]), "+f"(d[87]),
          "+f"(d[88]), "+f"(d[89]), "+f"(d[90]), "+f"(d[91])
        : "r"(da), "r"(db), "r"(accumulate), "n"(TA), "n"(TB), "n"(HA), "n"(HB));
}

template <uint32_t HB>
__device__ __forceinline__ void wgmma_rs_n184(float (&d)[92], uint32_t a0, uint32_t a1, uint32_t db) {
    asm volatile("{\n.reg .b64 b;\nmov.b64 b, {%94, %96};\n"
        "wgmma.mma_async.sync.aligned.m64n184k16.f32.bf16.bf16 {"
        "%0, %1, %2, %3, %4, %5, %6, %7, %8, %9, %10, %11, %12, %13, %14, %15, "
        "%16, %17, %18, %19, %20, %21, %22, %23, %24, %25, %26, %27, %28, %29, %30, %31, "
        "%32, %33, %34, %35, %36, %37, %38, %39, %40, %41, %42, %43, %44, %45, %46, %47, "
        "%48, %49, %50, %51, %52, %53, %54, %55, %56, %57, %58, %59, %60, %61, %62, %63, "
        "%64, %65, %66, %67, %68, %69, %70, %71, %72, %73, %74, %75, %76, %77, %78, %79, "
        "%80, %81, %82, %83, %84, %85, %86, %87, %88, %89, %90, %91"
        "}, {%92, %93, %95, %95}, b, 1, 1, 1, 0;\n}\n"
        : "+f"(d[0]), "+f"(d[1]), "+f"(d[2]), "+f"(d[3]), "+f"(d[4]), "+f"(d[5]), "+f"(d[6]), "+f"(d[7]),
          "+f"(d[8]), "+f"(d[9]), "+f"(d[10]), "+f"(d[11]), "+f"(d[12]), "+f"(d[13]), "+f"(d[14]), "+f"(d[15]),
          "+f"(d[16]), "+f"(d[17]), "+f"(d[18]), "+f"(d[19]), "+f"(d[20]), "+f"(d[21]), "+f"(d[22]), "+f"(d[23]),
          "+f"(d[24]), "+f"(d[25]), "+f"(d[26]), "+f"(d[27]), "+f"(d[28]), "+f"(d[29]), "+f"(d[30]), "+f"(d[31]),
          "+f"(d[32]), "+f"(d[33]), "+f"(d[34]), "+f"(d[35]), "+f"(d[36]), "+f"(d[37]), "+f"(d[38]), "+f"(d[39]),
          "+f"(d[40]), "+f"(d[41]), "+f"(d[42]), "+f"(d[43]), "+f"(d[44]), "+f"(d[45]), "+f"(d[46]), "+f"(d[47]),
          "+f"(d[48]), "+f"(d[49]), "+f"(d[50]), "+f"(d[51]), "+f"(d[52]), "+f"(d[53]), "+f"(d[54]), "+f"(d[55]),
          "+f"(d[56]), "+f"(d[57]), "+f"(d[58]), "+f"(d[59]), "+f"(d[60]), "+f"(d[61]), "+f"(d[62]), "+f"(d[63]),
          "+f"(d[64]), "+f"(d[65]), "+f"(d[66]), "+f"(d[67]), "+f"(d[68]), "+f"(d[69]), "+f"(d[70]), "+f"(d[71]),
          "+f"(d[72]), "+f"(d[73]), "+f"(d[74]), "+f"(d[75]), "+f"(d[76]), "+f"(d[77]), "+f"(d[78]), "+f"(d[79]),
          "+f"(d[80]), "+f"(d[81]), "+f"(d[82]), "+f"(d[83]), "+f"(d[84]), "+f"(d[85]), "+f"(d[86]), "+f"(d[87]),
          "+f"(d[88]), "+f"(d[89]), "+f"(d[90]), "+f"(d[91])
        : "r"(a0), "r"(a1), "r"(db), "r"(0), "n"(HB));
}

struct Ring {
    uint32_t slot, ph;
    __device__ __forceinline__ void next() { if (++slot == NSLOT) { slot = 0; ph ^= 1; } }
    __device__ __forceinline__ void next2() { ph ^= slot == 5; slot = __byte_perm(0x06030201u, 0x00040005u, 0x7770 + slot); }
};
struct Slot {
    uint32_t dst, bar, ph;
    __device__ __forceinline__ void next(uint32_t bars) {
        dst += SLOT; bar += 8;
        if (bar == bars + 8 * NSLOT) { dst -= NSLOT * SLOT; bar = bars; ph ^= 1; }
    }
};
__device__ __forceinline__ uint32_t xslot(int i) { return __byte_perm(0x04130e0cu, 0x00130e0cu, 0x7770 + i); }
__device__ __forceinline__ uint32_t wslot(int i) { return __byte_perm(0x06001510u, 0x00151009u, 0x7770 + i); }

constexpr uint32_t HI_SW = desc_hi(1024, 1);

struct Mma {
    uint32_t bars, rel;
    bool lead;
    int wg, w;
    Ring r;
    uint32_t prev;
    __device__ __forceinline__ void release(uint32_t s) { if (lead) mbar_arrive4_remote(rel + B_EMPTY + 8 * s); }
    template <bool G1>
    __device__ __forceinline__ void run(float (&a)[56], int n, int first, int last, int lag, int accumulate, int ts) {
#pragma unroll 1
        for (int i = 0; i < n; i++) {
            if (lag && i == (wg == (G1 || !SWAP2) ? n - lag : -1)) bar_sync(7, 256);
            const uint32_t s = r.slot;
            mbar_wait(bars + B_FULL + 8 * s, r.ph);
            if (G1) r.next(); else r.next2();
            TS0(G1 ? 2 : 8, ts + i + wg * 68);
            const uint32_t dB = s * (SLOT >> 4), dA = dB + wg * 512;
            wg_fence();
#pragma unroll
            for (int k = 0; k < 4; k++) {
                wgmma_n112<1, 1, HI_SW, desc_hi(G1 ? 256 : 1024, 0)>(a, dA + desc_lo(k * 2048, 8192), dB + desc_lo(16384 + k * (G1 ? SLAB : 256), 128), k > 0 || accumulate || i > 0);
                if (k == 1) {
                    wg_commit(); wg_wait<1>();
                    if ((uint32_t)(i - first) < (uint32_t)(last - first)) release(prev);
                    if (lag && i == (wg == (G1 || !SWAP2) ? -1 : n - 1)) bar_arrive(7, 256);
                }
            }
            wg_commit();
            prev = s;
        }
    }
    __device__ __forceinline__ void run_o(float (&a)[56]) {
#pragma unroll 1
        for (int i = 0; i < 2; i++) {
            const uint32_t s = r.slot, dB = s * (SLOT >> 4), dA = dB + wg * 512;
            mbar_wait(bars + B_FULL + 8 * s, r.ph);
            TS0(8, 48 + 2 * i + wg * 68);
            wg_fence();
#pragma unroll
            for (int k = 0; k < 7; k++) {
                if (k == 3) { mbar_wait(bars + B_FULL + 8 * s + 8, r.ph); wg_fence(); }
                wgmma_n112<0, 1, desc_hi(128, 0), desc_hi(256, 0)>(a, dA + desc_lo(k * 2048 + (k > 3) * (SLOT - HALF), k == 3 ? SLOT - 6144 : 1024),
                                                                   dB + desc_lo(16384 + k * SLAB + (k > 2) * (SLOT - 3 * SLAB), 128), k > 0 || i > 0);
                if (k & 1) wg_commit();
                if (k == 1) { wg_wait<1>(); if (i) release(prev); }
                if (k == 5) { wg_wait<1>(); release(s); }
            }
            wg_commit();
            prev = s + 1;
            r.slot++; r.next2();
        }
    }
};

__global__ void __cluster_dims__(2, 1, 1) __launch_bounds__(NTHREADS, 1)
fused_kernel(const __nv_bfloat16* __restrict__ x, const __nv_bfloat16* __restrict__ b1, const __nv_bfloat16* __restrict__ b2, const __nv_bfloat16* __restrict__ wo, __nv_bfloat16* out, Scratch* G,
             const __nv_bfloat16* __restrict__ w1, const __nv_bfloat16* __restrict__ w2,
             const __grid_constant__ Params P) {
    extern __shared__ __align__(1024) uint8_t smem[];
    const uint32_t sbase = (uint32_t)__cvta_generic_to_shared(smem);
    const uint32_t bars = sbase + OFF_BAR;
    const uint32_t rank = blockIdx.x & 1, pr = blockIdx.x >> 1;
    const uint32_t row0 = blockIdx.x * 16;
    if (threadIdx.x == 0) {
        TS(15, 0);
        mbar_init(bars + B_ROW, 1);
        asm volatile("fence.mbarrier_init.release.cluster;" ::: "memory");
        bulk_load(sbase + OFF_Y, x + row0 * D_, TILEB, bars + B_ROW);
        mbar_expect(bars + B_ROW, TILEB);
        TS(1, 97);
    }
    const int lane = threadIdx.x & 31;
    const int warp = __shfl_sync(~0u, threadIdx.x >> 5, 0), w = warp & 3;
    if (elect()) {
        const uint32_t first = bars + warp * 24, count = warp < 8 ? 1 : warp == 8 ? 2 : 16;
#pragma unroll
        for (int i = 0; i < 3; i++) mbar_init(first + 8 * i, count);
        asm volatile("fence.mbarrier_init.release.cluster;" ::: "memory");
    }
    __syncwarp();
    asm volatile("barrier.cluster.arrive.relaxed.aligned;" ::: "memory");
    const uint32_t pv = pr < 4 ? pr * 8 + 36 : pr - 4 + (max((int)pr - 33, 0) * 37 >> 8);
    const uint32_t gp = (pv + 4) & 7, hp = pv >> 3;
    const uint32_t tb = gp * 2 + rank, c = hp * 16 + tb;
    const bool has_g1 = gp > 0;
    const uint32_t nt1 = hp & 3, ft = max((int)gp - 1, 0) * 2 + (hp >> 2);
    const uint32_t nt2 = (hp & 1) * 2 + rank, mt = (gp & 3) * 4 + (hp >> 1), ks = gp >> 2;
    asm volatile("barrier.cluster.wait.aligned;" ::: "memory");

    if (warp == 8) {
        uint32_t kw = gp % ROT * (512 / ROT), kx;
        if (elect()) {
            mbar_expect(bars + B_QFULL, QSLOT);
            tma3d(sbase + xslot(0) * 8192, &P.tmX, bars + B_QFULL, kw, tb * 64, 0);
            tma3d_pair(sbase + wslot(0) * 8192 + rank * 12288, &P.tmWqkv, bars + B_QFULL, (hp * 56) & ~15, kw + rank * 32, 0);
            TS(1, 23);
            uint32_t due = (uint32_t)clock() + PACE, ep = ld_relaxed(&G->epoch[c]);
            uint32_t spins = sbase == (rank << 24 | SMEM0) ? 0 : SPIN_LIMIT;
#pragma unroll 1
            for (int i = 1; i < 8; i++) {
                kx = kw; kw += 64;
                if (i >= 5) mbar_wait_bounded(bars + B_QEMPTY + 8 * (i - 5), 0, spins);
                else { while ((int)((uint32_t)clock() - due) < 0) {} due += PACE; }
                if (kw == D_) kw = 0;
                if (i < 4) kx = kw;
                const int ix = i - (i > 4);
                if (i < 7) mbar_expect(bars + B_QFULL + 8 * i, QSLOT);
                if (i != 4) tma3d(sbase + xslot(ix) * 8192, &P.tmX, bars + B_QFULL + 8 * ix, kx, tb * 64, 0);
                if (i == min(5 + gp / ROT, 7)) mbar_wait_bounded(bars + B_CS, 0, spins);
                if (i < 7) tma3d_pair(sbase + wslot(i) * 8192 + rank * 12288, &P.tmWqkv, bars + B_QFULL + 8 * i, (hp * 56) & ~15, kw + rank * 32, 0);
            }
            ep++;
            Slot r{sbase, bars, 0};
            if (has_g1) {
                const uint8_t* src = G->H[nt1][rank * 16];
                const int row = rank * 1024;
                mbar_arrive(bars + B_FULL + 48); mbar_arrive16(bars + B_EMPTY + 48);
                mbar_expect(bars + B_FULL, 16384 + TILEB);
                tma3d(sbase, &P.tmW1, bars + B_FULL, 0, row, ft * 2);
                wait_flag(G->flag[1] + rank * 2, 20 * ep, spins);
                TS(1, 16);
#pragma unroll 1
                for (int j = 64;; j += 64) {
                    bulk_load(r.dst + 16384, src, TILEB, r.bar + B_FULL);
                    src += TILEB;
                    r.next(bars);
                    if (j == 1024) break;
                    mbar_wait_bounded(r.bar + B_EMPTY, r.ph, spins);
                    if (j < 14 * 64) TS(2, 146 + j / 64);
                    mbar_expect(r.bar + B_FULL, 16384 + TILEB);
                    tma3d(r.dst, &P.tmW1, r.bar + B_FULL, 0, row + j, ft * 2);
                }
#pragma unroll
                for (int i = 0; i < 4; i++) mbar_expect(bars + B_X + 8 * i, (i & 1) ? 3072 : 4096);
            } else {
                due = (uint32_t)clock();
#pragma unroll 1
                for (int j = PF0; j < PF1; j++) {
                    asm volatile("cp.async.bulk.prefetch.L2.global [%0], %1;" ::"l"(w1 + (rank * 1024 + j * 64 + hp * 8) * F_), "n"(16 * F_) : "memory");
                    due += PF;
                    while ((int)((uint32_t)clock() - due) < 0) {}
                }
            }
            const uint8_t *so = G->O[mt][ks * 4] + (LOCREL == 2 ? 0 : rank * HALF), *sw = G->Wo[nt2][ks * 4];
            wait_flag2(G->flag[16 + mt], 8 * ep, G->flag[0], 16 * ep, spins);
            TS(4, 18);
#pragma unroll 1
            for (int j = 0; j < 4 * TILEB; j += TILEB) {
                mbar_wait_bounded(r.bar + B_EMPTY, r.ph, spins);
                mbar_expect(r.bar + B_QFULL, TILEB);
                if (LOCREL == 2) { bulk_load(r.dst, so + j, HALF, r.bar + B_QFULL); bulk_load(r.dst + 8192, so + j + HALF, HALF, r.bar + B_QFULL); }
                else bulk_load_pair(r.dst + rank * 8192, so + j, HALF, r.bar + B_QFULL);
                bulk_load(r.dst + 16384, sw + j, (r.bar & 8) ? TILEB : 3 * SLAB, r.bar + B_FULL);
                r.next(bars);
            }
            if (!has_g1) {
#pragma unroll
                for (int j = PG0; j < PG1; j++)
                    asm volatile("cp.async.bulk.prefetch.L2.global [%0], %1;" ::"l"(w2 + (rank * 896 + j * 128 + hp * 8) * S_), "n"(16 * S_) : "memory");
            }
            Ring q{has_g1 ? 2u : 6u, has_g1}, p = q;
#pragma unroll 1
            for (int j = 0; j < 14 * 128; j += 128) {
                mbar_wait_bounded(bars + B_EMPTY + 8 * q.slot, q.ph, spins);
                if (LEADW && j >= LEADW * 128 && j < LEADN * 128) { mbar_wait_bounded(bars + B_FULL + 8 * p.slot, p.ph, spins); p.next2(); }
                TS(8, 176 + j / 128);
                tma3d(sbase + q.slot * SLOT, &P.tmW2, bars + B_FULL + 8 * q.slot, 0, ks * 896 + j - (j < 896 ? 0 : 832), mt * 2);
                q.next2();
            }
            mbar_wait_bounded(bars + B_END, 0, spins);
        }
    } else if (warp > 8) {
        const uint32_t ep = ld_relaxed(&G->epoch[c]) + 1;
        {
            uint2* cs = G->colsum[hp][0];
            if (w == 2) {
                bar_sync(6, 160);
                TS(1, 8);
                if (elect()) {
                    fence_async_shared();
#pragma unroll
                    for (int i = 0; i < 4; i++) bulk_store(G->H[i][0] + row0 * (SLAB / 16), sbase + OFF_X + i * (SLAB + 64), SLAB);
                    bulk_flush();
                    TS(1, 99);
                    signal(G->flag[1] + (row0 >> 10) * 2 + ((row0 & 1023) >= 320));
                    TS(1, 3);
                }
                __syncwarp();
            } else {
                const uint32_t q4 = lane >> 3, word = rank * 16 + (w & 2) * 4 + (lane & 7);
                uint32_t src = (sbase + wslot(gp / ROT) * 8192 + word * 4 + (q4 >> 1) * 12288 + (q4 & 1) * 2048) ^ (q4 * 288);
                mbar_wait(bars + B_QFULL + 8 * (gp / ROT), 0);
                if (w == 1) TS(1, 66);
#pragma unroll kCsu
                for (int i = 0; i < 96; i += 32) {
                    uint32_t v[16];
#pragma unroll
                    for (int k = 0; k < 16; k++) v[k] = __float_as_uint(lds1f((src ^ ((k & 7) * 144)) + (k >> 3) * 1024));
                    float s0 = bf_lo(v[0]), s1 = bf_hi(v[0]), s2 = bf_lo(v[1]), s3 = bf_hi(v[1]);
#pragma unroll
                    for (int k = 2; k < 16; k += 2) { s0 += bf_lo(v[k]); s1 += bf_hi(v[k]); s2 += bf_lo(v[k + 1]); s3 += bf_hi(v[k + 1]); }
                    s0 += s2; s1 += s3;
                    s0 += __shfl_xor_sync(~0u, s0, 8); s1 += __shfl_xor_sync(~0u, s1, 8);
                    s0 += __shfl_xor_sync(~0u, s0, 16); s1 += __shfl_xor_sync(~0u, s1, 16);
                    if (lane < 8) cs[gp * 96 + i + word] = make_uint2(tag(__float_as_uint(s0), 1, ep), __float_as_uint(s1));
                    src += 4096;
                }
                if (elect()) mbar_arrive(bars + B_CS);
                if (w == 1) TS(1, 24);
            }
            bar_sync(1, 96);
            if (REC_NS) __nanosleep(REC_NS);
            const int i0 = threadIdx.x - 288;
            uint2 u[7];
            uint4 sv;
            uint32_t bad;
            do {
                sv = ld_relaxed4(G->stat + tb * 128 + (i0 & 63) * 2);
                bad = or_diff(sv.x ^ ep, sv.z, ep);
#pragma unroll
                for (int i = 0; i < 7; i++) { u[i] = ld_relaxed2(cs + i * 96 + i0); bad = or_diff(bad, u[i].x, ep); }
            } while (bad & 1);
            if (w < 3) sts4(sbase + OFF_ST + i0 * 16, sv);
#pragma unroll
            for (int e = 0; e < 2; e++) {
                float f = 0.f;
#pragma unroll
                for (int i = 0; i < 7; i++) f += __uint_as_float(e ? u[i].y : u[i].x);
                const uint32_t hi = pack2(f, f);
                sts4(sbase + OFF_X + i0 * 32 + e * 16, make_uint4(hi, pack2(f - bf_hi(hi), f - bf_hi(hi)), 0, 0));
            }
            asm volatile("st.shared.u32 [%0], %1;" ::"r"(bars + 8 * NBAR), "r"(ep) : "memory");
            fence_async_shared();
            __syncwarp();
            bar_arrive(8, 224); bar_arrive(9, 224);
            TS(1, 90 + w);
        }
        const uint8_t* src = G->U[nt2][ks * 14];
        uint32_t spins = 0;
        if (w < 3) {
            uint32_t bad;
            if (w == 1) {
                if (elect()) {
                    wait_flag(G->flag[1] + rank * 2 + 1, 44 * ep, spins);
                    mbar_arrive16(bars + B_EMPTY + 8 * 5);
                    TS(1, 96);
                }
                __syncwarp();
                if (!has_g1) { bar_sync(5, 288); if (elect()) signal(G->flag[0]); __syncwarp(); TS(2, 26); }
            } else {
                bar_sync(3, 288);
                __nanosleep(HALO_NS);
                uint4 v[7];
                do {
                    bad = 0;
#pragma unroll
                    for (int i = 0; i < 7; i++) { v[i] = ld_relaxed4(G->halo[c - (tb > 0)] + i * 512 + lane * 16); bad = or_diff(bad, v[i].x, ep); }
                } while (bad & 1);
#pragma unroll
                for (int i = 0; i < 7; i++) sts4(sbase + OFF_X + i * 512 + lane * 16, v[i]);
                __syncwarp();
                if (elect()) mbar_arrive(bars + B_HALO);
                TS(2, 21);
            }
            mbar_wait(bars + B_HALO, 0);
            uint32_t slot = (has_g1 ? 16 % NSLOT : 0) + w - 1, ph = ~0u;
#pragma unroll 1
            for (int i = w - 1; i < 18;) {
                const uint32_t d0 = sbase + slot * SLOT + (i < 4 ? 0 : 16384), d1 = d0 + (i < 4 ? 8192 : HALF), landed = bars + B_QFULL + 8 * slot;
                mbar_wait(landed, (ph >> slot) & 1);
                ph ^= 1 << slot;
                if (i < 8) TS(4, 82 + i);
                if (i >= 4) TS(8, 156 + i);
                bad = 0;
#pragma unroll
                for (int k = 0; k < 14; k++) bad = or_diff(bad, __float_as_uint(lds1f((k < 7 ? d0 : d1) + k % 7 * 1024 + lane * 32 + (lane >> 2) * 4)), ep);
                if (__any_sync(~0u, bad & 1)) {
                    if (elect()) {
                        const uint8_t* cur = (i < 4 ? G->O[mt][ks * 4] : src - 4 * TILEB) + i * TILEB;
                        fence_async_shared();
                        mbar_expect(landed, TILEB);
                        bulk_load(d0, cur, HALF, landed);
                        bulk_load(d1, cur + HALF, HALF, landed);
                    }
                    TS(4, i < 4 ? 94 : 95);
                } else {
                    if (elect()) mbar_expect(landed + (B_FULL - B_QFULL), i < 4 ? (2 + w) * SLAB : 16384);
                    i += __byte_perm(0x03020202u, 0x00010202u, 0x7770 + slot);
                    slot = __byte_perm(0x05060302u, 0x00040100u, 0x7770 + slot);
                }
            }
        } else {
            bar_sync(2, 288);
            if (elect()) bulk_store(out + row0 * D_, sbase + OFF_Y, TILEB);
            __syncwarp();
            bar_sync(4, 288);
            if (elect()) {
                fence_async_shared();
                bulk_store(G->O[tb][hp], sbase + OFF_X, TILEB);
                bulk_flush();
                TS(2, 7);
                mbar_arrive_remote(mapa(bars + B_FREE, rank ^ 1));
                mbar_arrive(bars + B_FREE);
                hint(G->flag[16 + tb]);
                signal(G->flag[16 + (row0 >> 7)] + 1);
                TS(2, 22);
            }
            __syncwarp();
            uint32_t late = ~0u;
            const uint32_t* hints = G->flag[8 + nt2 * 2 + ks] + lane;
            mbar_wait(bars + (has_g1 ? B_X : B_FREE), 0);
            Ring r{has_g1 ? 2u : 6u, has_g1};
#pragma unroll 1
            for (int i = 0; i < 14; i++) {
                while ((late >> i) & 1) late = __ballot_sync(~0u, ld_relaxed(hints) != 2 * ep) & 127;
                if (i == 0) TS(4, 17);
                mbar_wait(bars + B_EMPTY + 8 * r.slot, r.ph);
                TS(8, 192 + i);
                if (elect()) {
                    mbar_expect(bars + B_QFULL + 8 * r.slot, TILEB);
                    bulk_load(sbase + r.slot * SLOT + 16384, src, TILEB, bars + B_QFULL + 8 * r.slot);
                }
                src += TILEB; r.next2();
            }
            if (elect()) {
                wait_flag(G->flag[16 + mt] + 1, 8 * ep, spins);
                mbar_arrive(bars + B_ROW);
                TS(2, 27);
                G->epoch[c] = ep;
            }
        }
    } else {
        const int wg = warp >> 2;
        Mma M{bars, mapa(bars, rank ^ (lane & 1)), (threadIdx.x & 127) < 2, wg, w, Ring{0, 0}, 0};
        const int r = lane >> 2, t = lane & 3;
        uint32_t ep;
        const uint32_t bias0 = ld_u16(b1 + ft * 128 + warp * 16 + r), bias1 = ld_u16(b1 + ft * 128 + warp * 16 + r + 8);
        if (wg == 1) {
            ep = ld_relaxed(&G->epoch[c]);
            const int r16 = w * 4 + t, nt = (r + 2 * t) & 3, half = ((r + 2 * t) >> 2) & 1;
            const uint32_t row = sbase + OFF_Y + r16 * (2 * D_), part = row + nt * 224 + half * 112;
            const uint32_t hb = sbase + OFF_X + nt * (SLAB + 64) + r16 * 16 + (half ^ (row0 >> 10)) * (7 * 256);
            mbar_wait(bars + B_ROW, 0);
            TS0(1, 67);
            const float x0 = bf_lo(__float_as_uint(lds1f(row)));
            float d[56], s0 = 0.f, s1 = 0.f, q0 = 0.f, q1 = 0.f;
#pragma unroll
            for (int i = 0; i < 7; i++) {
                const uint4 v = lds4(part + i * 16);
                const uint32_t u[4] = {v.x, v.y, v.z, v.w};
#pragma unroll
                for (int k = 0; k < 4; k++) {
                    const float d0 = d[8 * i + 2 * k] = bf_lo(u[k]) - x0, d1 = d[8 * i + 2 * k + 1] = bf_hi(u[k]) - x0;
                    s0 += d0; s1 += d1; q0 = fmaf(d0, d0, q0); q1 = fmaf(d1, d1, q1);
                }
            }
            const float md = oct_sum(s0 + s1) * (1.f / D_), var = fmaf(-md, md, oct_sum(q0 + q1) * (1.f / D_)), nmean = -(x0 + md);
            const float rstd = rsq(var + LN_EPS);
            const float sc = rstd * rsq(fmaf(var * rstd, rstd, LN_EPS)), nb = -md * sc;
            if (lane < 4) G->stat[row0 + r16] = make_uint2(tag(__float_as_uint(rstd), 1, ~ep), pack2(nmean, nmean - bf_hi(pack2(nmean, nmean))));
#pragma unroll
            for (int i = 0; i < 7; i++) {
                uint32_t u[4];
#pragma unroll
                for (int k = 0; k < 4; k++) u[k] = pack2(fmaf(d[8 * i + 2 * k], sc, nb), fmaf(d[8 * i + 2 * k + 1], sc, nb));
                sts4(hb + i * 256, make_uint4(u[0], u[1], u[2], u[3]));
            }
            TS0(1, 25);
            bar_arrive(6, 160);
        }
        const uint32_t kv = sbase + OFF_X + (w * 2 + wg) * KV + lane * 16;
        uint32_t q[8][2], k0[7], k1[7], v0[7];
        {
            float acc[92];
#pragma unroll 1
            for (int kb = 0; kb < 7; kb++) {
                const bool held = kb == (wg ? 7 - HOLD : -1);
                if (held) { wg_wait<0>(); M.release(4 - HOLD); bar_sync(7, 256); }
                mbar_wait(bars + B_QFULL + 8 * kb, 0);
                TS0(1, 68 + wg * 7 + kb);
                const uint32_t dA = (xslot(kb) + wg) * 512, dB = wslot(kb) * 512 + (hp & 1);
                wg_fence();
#pragma unroll
                for (int k = 0; k < 4; k++) {
                    wgmma_n184<0, 1, HI_SW, HI_SW>(acc, dA + desc_lo(k * 32, 16), dB + desc_lo((k & 1) * 2048 + (k >> 1) * 12288, 4096), k > 0 || kb > 0);
                    if (k == 0) { wg_commit(); wg_wait<1>(); if (kb > 0 && !held) M.release(kb - 3); }
                }
                wg_commit();
            }
            if (wg == 0 && !LATEREL) bar_arrive(7, 256);
            bar_sync(8 + wg, 224);
            ep = __float_as_uint(lds1f(bars + 8 * NBAR));
            const uint32_t st = sbase + OFF_ST + (w * 32 + r * 2 + wg) * 8;
            const uint2 s0 = lds2(st), s1 = lds2(st + 128);
            const uint32_t a0 = t < 2 ? s0.y : 0, a1 = t < 2 ? s1.y : 0;
            wg_fence();
            wgmma_rs_n184<desc_hi(128, 0)>(acc, a0, a1, desc_lo(OFF_X, 0) + (hp & 1) * 8);
            wg_commit();
            if (wg == 0 && LATEREL) bar_arrive(7, 256);
            wg_wait<1>();
            M.release(4);
            wg_wait<0>();
            pin(acc);
            TS0(1, 4 + 7 * wg);
            uint32_t hi[14];
#pragma unroll
            for (int p = 2; p >= 0; p--) {
                const float f = p == 0 ? 0.1889822365046136f * 1.4426950408889634f : p, r0 = __uint_as_float(s0.x) * f, r1 = __uint_as_float(s1.x) * f;
#pragma unroll
                for (int g = 0; g < 7; g++) {
                    const int a = (p * 8 + g) * 4;
                    const uint32_t lo2 = pack2(acc[a] * r0, acc[a + 1] * r0), hi2 = pack2(acc[a + 2] * r1, acc[a + 3] * r1);
                    if (p == 0) { q[g][0] = lo2; q[g][1] = hi2; } else { hi[(p - 1) * 7 + g] = hi2; }
                    if (p == 1) { k0[g] = lo2; k1[g] = hi2; }
                    if (p == 2) v0[g] = lo2;
                }
                if (p == 1) {
#pragma unroll
                    for (int i = 0; i < 3; i++) stsm4(kv + 2 * KV + i * 512, hi[4 * i], hi[4 * i + 1], hi[4 * i + 2], hi[4 * i + 3]);
                    stsm2(kv + 2 * KV + 1536, hi[12], hi[13]);
                    if (w == 3) {
#pragma unroll
                        for (int i = 0; i < 14; i++) stg1(G->halo[c] + wg * KV + lane * 4 + i * 128, tag(hi[i], t == 0, ep));
                    }
                    bar_arrive(3, 288);
                }
            }
#pragma unroll
            for (int j = 0; j < 2; j++) { q[7][j] = t < 2 ? 0u : q[3][j]; q[3][j] = t < 2 ? q[3][j] : 0u; }
#pragma unroll
            for (int g = 0; g < 7; g++) v0[g] = transpose8(v0[g]);
        }
        TS0(1, 9 + 11 * wg);
        if (LOCREL == 2) M.rel = bars;
        float a[56];
#pragma unroll
        for (int i = 0; i < 56; i++) asm volatile("" : "=f"(a[i]));
        if (__builtin_expect(!has_g1, 0)) {
            const int g = min(lane >> 1, 13), nt = rank * 2 + wg;
            const uint4* src = (const uint4*)(wo + (hp * 56 - (hp & 1) * 8 + w * 16 + (lane & 1)) * D_ + nt * 112) + g;
            uint4 v[8];
#pragma unroll
            for (int i = 0; i < 8; i++) v[i] = __ldg(src + i * (D_ / 4));
#pragma unroll
            for (int i = 0; i < 8; i++) ((uint4*)G->Wo[nt][hp])[w * (SLAB / 16) + g * 16 + (lane & 1) + 2 * i] = v[i];
            bar_arrive(5, 288);
        }
        M.run<true>(a, has_g1 ? PAUSE : 0, 1, 16, 0, 0, 32);
        {
            uint32_t kp[8], vv[14];
            TS0(2, 140 + wg);
            mbar_wait(bars + B_HALO, 0);
            TS0(2, 142 + wg);
            ldsm4(kp, kv); ldsm4(kp + 4, kv + (lane < 24 ? 512 : 0));
            const uint32_t va = kv + 896 + (lane & 8) * (2 * KV / 8 - 16) - (lane & 16) * 8;
            ldsm4t(vv, va); ldsm4t(vv + 4, va + 256); ldsm4t(vv + 8, va + 512); ldsm2t(vv + 12, va + 768);
            const bool e0 = 2 * t > r, e1 = 2 * t >= r;
            const uint32_t mk = (e0 ? 0xffffu : 0u) | (e1 ? 0xffff0000u : 0u);
            wg_wait<0>();
            pin(a);
            if (has_g1) M.release(M.prev);
            TS0(2, 144 + wg);
            bar_sync(2, 288);
            mbar_wait(bars + B_HALO, 0);
            TS0(2, 12 + 16 * wg);
            float sv[2][4];
#pragma unroll
            for (int h = 0; h < 2; h++) {
                const int ga = h * 4, gb = h * 4 + 1, gc = h * 4 + 2, gd = h * 4 + 3;
                float s[3][4] = {};
                mma16(s[0], q[ga][0], q[ga][1], q[gb][0], q[gb][1], kp[ga], kp[gb]);
                mma16(s[1], q[ga][0], q[ga][1], q[gb][0], q[gb][1], k0[ga], k0[gb]);
                mma16(s[2], q[ga][0], q[ga][1], q[gb][0], q[gb][1], k1[ga], k1[gb]);
                mma16(s[0], q[gc][0], q[gc][1], q[gd][0], q[gd][1], kp[gc], kp[gd]);
                mma16(s[1], q[gc][0], q[gc][1], q[gd][0], q[gd][1], k0[gc], k0[3]);
                mma16(s[2], q[gc][0], q[gc][1], q[gd][0], q[gd][1], k1[gc], k1[3]);
                if ((tb | w) == 0) s[0][0] = s[0][1] = -1e30f;
                sv[h][0] = e0 ? s[0][0] : s[1][0];
                sv[h][1] = e1 ? s[0][1] : s[1][1];
                sv[h][2] = e0 ? s[1][2] : s[2][2];
                sv[h][3] = e1 ? s[1][3] : s[2][3];
            }
            uint32_t pp[2][2];
#pragma unroll
            for (int i = 0; i < 4; i++) {
                float* v = &sv[i >> 1][(i & 1) * 2];
                const float m = quad_max(fmaxf(v[0], v[1]));
                const float p0 = ex2(v[0] - m), p1 = ex2(v[1] - m);
                const float inv = rcp(quad_sum(p0 + p1));
                pp[i >> 1][i & 1] = pack2(p0 * inv, p1 * inv);
            }
            uint32_t o[8][2];
#pragma unroll
            for (int i = 0; i < 8; i++) {
                const int h = i >> 2, g = i - h;
                float d[4] = {};
                mma16(d, pp[h][0] & mk, 0u, 0u, pp[h][1] & ~mk, vv[2 * g], vv[2 * g + 1]);
                mma8(d, pp[h][0] & ~mk, pp[h][1] & mk, v0[g]);
                o[i][0] = pack2(d[0], d[1]); o[i][1] = pack2(d[2], d[3]);
            }
            if (t >= 2) { o[3][0] = o[4][0]; o[3][1] = o[4][1]; }
            const int word = wg * 4 + t - (w & 1) * 4 - (r >> 2);
#pragma unroll
            for (int i = 0; i < 8; i++) { o[i][0] = tag(o[i][0], word == 0, ep); o[i][1] = tag(o[i][1], word == 2, ep); }
            const uint32_t dst = sbase + OFF_X + (w >> 1) * HALF + ((w & 1) * 32 + (lane & 15) * 2 + wg) * 16 + (lane >> 4) * 1024;
            stsm4(dst, o[0][0], o[0][1], o[1][0], o[1][1]);
            stsm4(dst + 2048, o[2][0], o[2][1], o[3][0], o[3][1]);
            stsm4(dst + 4096, o[5][0], o[5][1], o[6][0], o[6][1]);
            stsm2(dst + 6144, o[7][0], o[7][1]);
            if (ENDBAR) bar_sync(4, 288); else bar_arrive(4, 288);
            TS0(2, 10 + 19 * wg);
        }
        if (has_g1) {
            M.run<true>(a, 16 - PAUSE, 1, 16, LAG1, 1, 32 + PAUSE);
            mbar_wait(bars + B_FREE, 0);
            const uint32_t xb = sbase + OFF_X + wg * 8192 + (threadIdx.x & 127) * 16, xbar = bars + B_X + 16 * wg;
            const uint32_t rx = mapa(xb, rank ^ 1), rbar = mapa(xbar, rank ^ 1);
            wg_wait<0>();
            pin(a);
            M.release(M.prev);
            TS0(4, 5 + wg);
#pragma unroll
            for (int i = 0; i < 3; i++)
                st_async4(rx + i * 2048, rbar + 8 * (i >> 1), pack2(a[28 + 8 * i], a[29 + 8 * i]), pack2(a[30 + 8 * i], a[31 + 8 * i]), pack2(a[32 + 8 * i], a[33 + 8 * i]), pack2(a[34 + 8 * i], a[35 + 8 * i]));
            const uint32_t tail = 6144 - (threadIdx.x & 127) * 8;
            st_async2(rx + tail, rbar + 8, pack2(a[52], a[53]), pack2(a[54], a[55]));
            uint8_t* dst = G->U[nt1][((ft >= 7) + wg) * 7 + ft] + rank * HALF + w * 256 + lane * 4;
            uint32_t u[14];
#pragma unroll
            for (int i = 0; i < 28; i++) a[i] += bf_lo((i & 2) ? bias1 : bias0);
#pragma unroll
            for (int i = 0; i < 14; i++) {
                if (i % 8 == 0) {
                    if (i) TS0(4, 134 + wg);
                    mbar_wait(xbar + i, 0);
                    TS0(4, (i ? 136 : 1) + wg);
#pragma unroll
                    for (int k = i / 4; k < i / 4 + 2; k++) {
                        if (k < 3) { const uint4 v = lds4(xb + k * 2048); u[4 * k] = v.x; u[4 * k + 1] = v.y; u[4 * k + 2] = v.z; u[4 * k + 3] = v.w; }
                        else { const uint2 v = lds2(xb + tail); u[12] = v.x; u[13] = v.y; }
                    }
                    if (i && lane < 2) mbar_arrive_remote(M.rel + B_EMPTY + 48);
                }
                if (i == HINT && threadIdx.x == 0) hint(G->flag[8 + nt1 * 2] + ft + (ft >= 7) * 25);
                stg1(dst + (i >> 1) * 1024 + (i & 1) * 128, tag(pack2(gelu2(a[2 * i] + bf_lo(u[i])), gelu2(a[2 * i + 1] + bf_hi(u[i]))), (lane & 7) == w * 2 + (i & 1), ep));
            }
            TS0(4, 30 + wg);
        } else {
            mbar_wait(bars + B_FREE, 0);
            if (lane < 2) mbar_arrive_remote(M.rel + B_EMPTY + 48);
        }
        uint32_t c0 = ld_u16(b2 + mt * 128 + warp * 16 + r), c1 = ld_u16(b2 + mt * 128 + warp * 16 + r + 8);
        if (LOCREL == 1) M.rel = bars;
        M.run_o(a);
        if (wg == 1) TS0(4, 13);
        c0 *= ks == 0 ? 0x10001u : 0u; c1 *= ks == 0 ? 0x10001u : 0u;
        M.run<false>(a, 14, 0, 14 - NSLOT, LAG2, 1, 52);
        mbar_wait(bars + B_ROW, 1);
        const uint32_t stg = sbase + ((has_g1 ? STG1 : STG0) + (w >> 1) * STGS) * SLOT + wg * 8192 + (w & 1) * SLAB;
        const uint32_t sa = stg + (lane & 15) * 224 + (lane >> 4) * 16;
        wg_wait<0>();
        pin(a);
        TS0(8, 14 + wg);
#pragma unroll
        for (int i = 0; i < 7; i++)
            stsm4(sa + i * 32, half_plus(pack2(a[8 * i], a[8 * i + 1]), c0), half_plus(pack2(a[8 * i + 2], a[8 * i + 3]), c1),
                  half_plus(pack2(a[8 * i + 4], a[8 * i + 5]), c0), half_plus(pack2(a[8 * i + 6], a[8 * i + 7]), c1));
        fence_async_shared();
        __syncwarp();
        if (elect()) {
            asm volatile("cp.reduce.async.bulk.tensor.2d.global.shared::cta.add.tile.bulk_group [%0, {%2, %3}], [%1];\ncp.async.bulk.commit_group;" ::"l"(&P.tmOut), "r"(stg), "r"(nt2 * 112), "r"(mt * 128 + warp * 16) : "memory");
            if (w == 0) mbar_arrive(bars + B_END);
            asm volatile("cp.async.bulk.wait_group.read 0;" ::: "memory");
        }
        if (wg == !SWAP2) TS0(15, 19);
        TSDUMP();
    }
}

typedef CUresult (*EncodeFn)(CUtensorMap*, CUtensorMapDataType, cuuint32_t, void*, const cuuint64_t*, const cuuint64_t*, const cuuint32_t*, const cuuint32_t*,
                             CUtensorMapInterleave, CUtensorMapSwizzle, CUtensorMapL2promotion, CUtensorMapFloatOOBfill);

void make_map(EncodeFn enc, CUtensorMap* tm, const void* base, bool swizzle, int d0, int d1, int d2, int s1, int s2, int b0, int b1, int b2) {
    const cuuint64_t dims[3] = {(cuuint64_t)d0, (cuuint64_t)d1, (cuuint64_t)d2}, strides[2] = {(cuuint64_t)s1 * 2, (cuuint64_t)s2 * 2};
    const cuuint32_t box[3] = {(cuuint32_t)b0, (cuuint32_t)b1, (cuuint32_t)b2}, es[3] = {1, 1, 1};
    enc(tm, CU_TENSOR_MAP_DATA_TYPE_BFLOAT16, d2 ? 3 : 2, (void*)base, dims, strides, box, es, CU_TENSOR_MAP_INTERLEAVE_NONE,
        swizzle ? CU_TENSOR_MAP_SWIZZLE_128B : CU_TENSOR_MAP_SWIZZLE_NONE, CU_TENSOR_MAP_L2_PROMOTION_L2_128B, CU_TENSOR_MAP_FLOAT_OOB_FILL_NONE);
}

}

extern "C" void kernel_launch(void* const* d_in, const int* in_sizes, int n_in, void* d_out, int out_size) {
    static EncodeFn enc = nullptr;
    static Scratch* scratch = nullptr;
    if (!enc) {
        void* fn = nullptr;
        cudaDriverEntryPointQueryResult qr;
        cudaGetDriverEntryPoint("cuTensorMapEncodeTiled", &fn, cudaEnableDefault, &qr);
        enc = (EncodeFn)fn;
        cudaGetSymbolAddress((void**)&scratch, g_s);
        cudaFuncSetAttribute(fused_kernel, cudaFuncAttributeMaxDynamicSharedMemorySize, SMEM_BYTES);
    }
    Params P;
    const __nv_bfloat16* x = (const __nv_bfloat16*)d_in[0];
    make_map(enc, &P.tmX, x, true, D_, S_ / 2, 2, 2 * D_, D_, 64, 64, 2);
    make_map(enc, &P.tmWqkv, d_in[1], true, D_, D_, 3, 3 * D_, D_, 64, 32, 3);
    make_map(enc, &P.tmW1, d_in[4], true, 64, S_, F_ / 64, F_, 64, 64, 64, 2);
    make_map(enc, &P.tmW2, d_in[6], true, 64, F_, S_ / 64, S_, 64, 64, 64, 2);
    make_map(enc, &P.tmOut, d_out, false, D_, S_, 0, D_, 0, 112, 16, 1);
    fused_kernel<<<NCTA, NTHREADS, SMEM_BYTES, cudaStreamPerThread>>>(x, (const __nv_bfloat16*)d_in[5], (const __nv_bfloat16*)d_in[7], (const __nv_bfloat16*)d_in[2], (__nv_bfloat16*)d_out, scratch,
                                                                      (const __nv_bfloat16*)d_in[4], (const __nv_bfloat16*)d_in[6], P);
}
```

```cpp
#include <cuda_runtime.h>
#include <cuda_bf16.h>
#include <cuda.h>
#include <stdint.h>

#define HALO_NS 300
#define HINT 4
#define HOLD 2
#define LATEREL 1
#define PF 400
#define PF0 2
#define PF1 8
#define ENDBAR 1
#define PG0 3
#define PG1 5
#define STG1 4
#define STG0 4
#define STGS 1
#define LEADW 4
#define LEADN 7
#define LOCREL 1
#define SWAP2 0
#define TSQ 0
#define PACE 600
#define PAUSE 8
#define LAG1 4
#define LAG2 6

namespace {

constexpr int S_ = 2048, D_ = 448, F_ = 1792;
constexpr int NCTA = 128, NTHREADS = 384;
constexpr int NSLOT = 6, SLOT = 32768, QSLOT = 40960, TILEB = 14336, SLAB = 3584, HALF = 7168;
constexpr int KV = 1792, HSTG = SLAB + 32;
constexpr int OFF_X = NSLOT * SLOT;
constexpr int OFF_Y = OFF_X + 10 * KV;
constexpr int OFF_ST = OFF_Y + TILEB;
constexpr int OFF_BAR = OFF_ST + 1024;
constexpr int SMEM_BYTES = OFF_BAR + 1280;
constexpr uint32_t SMEM0 = 1024;
constexpr int B_QFULL = 0, B_FULL = 56, B_HALO = 128, B_X = 136, B_CS = 168, B_FREE = 192, B_END = 200, B_QEMPTY = 216, B_EMPTY = 232, B_ROW = 288, NBAR = 37;
constexpr float LN_EPS = 1e-5f;
constexpr int SPIN_LIMIT = 1 << 22;

struct Scratch {
    uint8_t H[4][32][TILEB];
    uint8_t U[4][28][TILEB];
    uint8_t O[16][8][TILEB];
    uint8_t Wo[4][8][TILEB];
    uint8_t halo[NCTA][2 * KV];
    uint2 stat[S_];
    uint2 colsum[8][8][96];
    uint32_t flag[32][32];
    uint32_t epoch[NCTA];
};
__device__ __align__(1024) Scratch g_s;

#define TS(g, i)
#define TS0(g, i)
#define TSDUMP()

struct Params {
    CUtensorMap tmX, tmWqkv, tmW1, tmW2, tmOut;
};

__device__ __forceinline__ bool elect() {
    uint32_t p;
    asm volatile("{\n.reg .pred p;\nelect.sync _|p, 0xffffffff;\nselp.u32 %0, 1, 0, p;\n}" : "=r"(p));
    return p;
}
__device__ __forceinline__ void mbar_init(uint32_t b, uint32_t c) { asm volatile("mbarrier.init.shared::cta.b64 [%0], %1;" ::"r"(b), "r"(c) : "memory"); }
__device__ __forceinline__ void mbar_expect(uint32_t b, uint32_t tx) { asm volatile("mbarrier.arrive.expect_tx.shared::cta.b64 _, [%0], %1;" ::"r"(b), "r"(tx) : "memory"); }
__device__ __forceinline__ void mbar_arrive(uint32_t b) { asm volatile("mbarrier.arrive.shared::cta.b64 _, [%0];" ::"r"(b) : "memory"); }
__device__ __forceinline__ void mbar_arrive16(uint32_t b) { asm volatile("mbarrier.arrive.shared::cta.b64 _, [%0], 16;" ::"r"(b) : "memory"); }
__device__ __forceinline__ void mbar_arrive4_remote(uint32_t b) { asm volatile("mbarrier.arrive.shared::cluster.b64 _, [%0], 4;" ::"r"(b) : "memory"); }
__device__ __forceinline__ void mbar_arrive_remote(uint32_t b) { asm volatile("mbarrier.arrive.shared::cluster.b64 _, [%0];" ::"r"(b) : "memory"); }
#define MBAR_WAIT_ASM(SEM) \
    asm volatile("{\n.reg .pred p;\nWAIT:\nmbarrier.try_wait.parity" SEM ".shared::cta.b64 p, [%0], %1;\n@!p bra WAIT;\n}" ::"r"(b), "r"(parity) : "memory")
__device__ __forceinline__ void mbar_wait(uint32_t b, uint32_t parity) { MBAR_WAIT_ASM(""); }
__device__ __forceinline__ void mbar_wait_bounded(uint32_t b, uint32_t parity, uint32_t& n) {
    asm volatile("{\n.reg .pred p;\nWAIT:\nadd.u32 %0, %0, 1;\nsetp.gt.u32 p, %0, %3;\n@p st.global.u32 [%4], %0;\n"
                 "mbarrier.try_wait.parity.shared::cta.b64 p, [%1], %2;\n@!p bra WAIT;\n}" : "+r"(n) : "r"(b), "r"(parity), "n"(SPIN_LIMIT), "l"(0ull) : "memory");
}
__device__ __forceinline__ uint32_t mapa(uint32_t a, uint32_t rank) { uint32_t r; asm("mapa.shared::cluster.u32 %0, %1, %2;" : "=r"(r) : "r"(a), "r"(rank)); return r; }
__device__ __forceinline__ void tma3d(uint32_t dst, const CUtensorMap* tm, uint32_t bar, int c0, int c1, int c2) {
    asm volatile("cp.async.bulk.tensor.3d.shared::cluster.global.mbarrier::complete_tx::bytes [%0], [%1, {%3, %4, %5}], [%2];" ::"r"(dst), "l"(tm), "r"(bar), "r"(c0), "r"(c1), "r"(c2) : "memory");
}
__device__ __forceinline__ void tma3d_pair(uint32_t dst, const CUtensorMap* tm, uint32_t bar, int c0, int c1, int c2) {
    asm volatile("cp.async.bulk.tensor.3d.shared::cluster.global.mbarrier::complete_tx::bytes.multicast::cluster [%0], [%1, {%3, %4, %5}], [%2], %6;" ::"r"(dst), "l"(tm), "r"(bar), "r"(c0), "r"(c1), "r"(c2), "h"((uint16_t)3) : "memory");
}
__device__ __forceinline__ void bulk_load(uint32_t dst, const void* src, uint32_t bytes, uint32_t bar) {
    asm volatile("cp.async.bulk.shared::cluster.global.mbarrier::complete_tx::bytes [%0], [%1], %2, [%3];" ::"r"(dst), "l"(src), "r"(bytes), "r"(bar) : "memory");
}
__device__ __forceinline__ void bulk_load_pair(uint32_t dst, const void* src, uint32_t bytes, uint32_t bar) {
    asm volatile("cp.async.bulk.shared::cluster.global.mbarrier::complete_tx::bytes.multicast::cluster [%0], [%1], %2, [%3], %4;" ::"r"(dst), "l"(src), "r"(bytes), "r"(bar), "h"((uint16_t)3) : "memory");
}
__device__ __forceinline__ void bulk_store(void* dst, uint32_t src, uint32_t bytes) {
    asm volatile("cp.async.bulk.global.shared::cta.bulk_group [%0], [%1], %2;" ::"l"(dst), "r"(src), "r"(bytes) : "memory");
}
__device__ __forceinline__ uint32_t ld_u16(const void* p) { uint32_t v; asm volatile("ld.global.nc.u16 %0, [%1];" : "=r"(v) : "l"(p)); return v; }
__device__ __forceinline__ uint32_t ld_relaxed(const uint32_t* p) { uint32_t v; asm volatile("ld.relaxed.gpu.global.u32 %0, [%1];" : "=r"(v) : "l"(p) : "memory"); return v; }
__device__ __forceinline__ void bulk_flush() { asm volatile("cp.async.bulk.commit_group;\ncp.async.bulk.wait_group 0;" ::: "memory"); }
__device__ __forceinline__ void signal(uint32_t* flag) { asm volatile("fence.acq_rel.gpu;\nred.relaxed.gpu.global.add.u32 [%0], 1;" ::"l"(flag) : "memory"); }
__device__ __forceinline__ void hint(uint32_t* flag) { asm volatile("red.relaxed.gpu.global.add.u32 [%0], 1;" ::"l"(flag) : "memory"); }
__device__ __forceinline__ uint32_t tag(uint32_t v, uint32_t mask, uint32_t parity) { return (v & ~mask) | (parity & mask); }
__device__ __forceinline__ uint32_t or_diff(uint32_t acc, uint32_t v, uint32_t parity) { asm("lop3.b32 %0, %0, %1, %2, 0xf6;" : "+r"(acc) : "r"(v), "r"(parity)); return acc; }
__device__ __forceinline__ uint4 ld_relaxed4(const void* p) {
    uint4 v;
    asm volatile("ld.relaxed.gpu.global.v4.u32 {%0, %1, %2, %3}, [%4];" : "=r"(v.x), "=r"(v.y), "=r"(v.z), "=r"(v.w) : "l"(p) : "memory");
    return v;
}
__device__ __forceinline__ uint2 ld_relaxed2(const void* p) { uint2 v; asm volatile("ld.relaxed.gpu.global.v2.u32 {%0, %1}, [%2];" : "=r"(v.x), "=r"(v.y) : "l"(p) : "memory"); return v; }
__device__ __forceinline__ void sts4(uint32_t a, uint4 v) { asm volatile("st.shared.v4.b32 [%0], {%1, %2, %3, %4};" ::"r"(a), "r"(v.x), "r"(v.y), "r"(v.z), "r"(v.w) : "memory"); }
__device__ __forceinline__ void sts1(uint32_t a, uint32_t v) { asm volatile("st.shared.b32 [%0], %1;" ::"r"(a), "r"(v) : "memory"); }
__device__ __forceinline__ void sts2(uint32_t a, uint32_t v0, uint32_t v1) { asm volatile("st.shared.v2.b32 [%0], {%1, %2};" ::"r"(a), "r"(v0), "r"(v1) : "memory"); }
__device__ __forceinline__ void stg1(void* p, uint32_t v) { asm volatile("st.global.b32 [%0], %1;" ::"l"(p), "r"(v) : "memory"); }
__device__ __forceinline__ void fence_async_shared() { asm volatile("fence.proxy.async.shared::cta;" ::: "memory"); }
#define BOUND "add.u32 %0, %0, 16;\nsetp.gt.u32 p, %0, %1;\n@p st.global.u32 [%2], %0;\n"
__device__ __forceinline__ void wait_flag(const uint32_t* p, uint32_t target, uint32_t& n) {
    asm volatile("{\n.reg .pred p;\n.reg .u32 v;\nPOLL:\n" BOUND "ld.acquire.gpu.global.u32 v, [%3];\nsetp.ne.u32 p, v, %4;\n@p bra POLL;\nfence.proxy.async.global;\n}"
                 : "+r"(n) : "n"(SPIN_LIMIT), "l"(0ull), "l"(p), "r"(target) : "memory");
}
__device__ __forceinline__ void wait_flag2(const uint32_t* h, uint32_t th, const uint32_t* p, uint32_t target, uint32_t& n) {
    asm volatile("{\n.reg .pred p;\n.reg .u32 u, v;\nPOLL:\n" BOUND "ld.relaxed.gpu.global.u32 u, [%3];\nld.acquire.gpu.global.u32 v, [%5];\nsetp.ne.u32 p, u, %4;\nsetp.ne.or.u32 p, v, %6, p;\n@p bra POLL;\nfence.proxy.async.global;\n}"
                 : "+r"(n) : "n"(SPIN_LIMIT), "l"(0ull), "l"(h), "r"(th), "l"(p), "r"(target) : "memory");
}
__device__ __forceinline__ void bar_sync(int id, int n) { asm volatile("bar.sync %0, %1;" ::"r"(id), "r"(n) : "memory"); }
__device__ __forceinline__ void bar_arrive(int id, int n) { asm volatile("bar.arrive %0, %1;" ::"r"(id), "r"(n) : "memory"); }
__device__ __forceinline__ void wg_fence() { asm volatile("wgmma.fence.sync.aligned;" ::: "memory"); }
__device__ __forceinline__ void wg_commit() { asm volatile("wgmma.commit_group.sync.aligned;" ::: "memory"); }
template <int N> __device__ __forceinline__ void wg_wait() { asm volatile("wgmma.wait_group.sync.aligned %0;" ::"n"(N) : "memory"); }
template <int N> __device__ __forceinline__ void pin(float (&d)[N]) {
#pragma unroll
    for (int i = 0; i < N; i++) asm volatile("" : "+f"(d[i])::"memory");
}
__host__ __device__ constexpr uint32_t desc_hi(uint32_t sbo, uint32_t swz) { return (sbo >> 4) | (swz << 30); }
__host__ __device__ constexpr uint32_t desc_lo(uint32_t off, uint32_t lbo) { return ((SMEM0 + off) >> 4) | ((lbo >> 4) << 16); }
__device__ __forceinline__ uint32_t pack2(float lo, float hi) { uint32_t r; asm("cvt.rn.bf16x2.f32 %0, %1, %2;" : "=r"(r) : "f"(hi), "f"(lo)); return r; }
__device__ __forceinline__ float bf_lo(uint32_t v) { return __uint_as_float(v << 16); }
__device__ __forceinline__ float bf_hi(uint32_t v) { return __uint_as_float(v & 0xffff0000u); }
__device__ __forceinline__ uint32_t half_plus(uint32_t a, uint32_t b) { uint32_t r; asm("fma.rn.bf16x2 %0, %1, %2, %3;" : "=r"(r) : "r"(a), "r"(0x3f003f00u), "r"(b)); return r; }
__device__ __forceinline__ void stsm4(uint32_t a, uint32_t r0, uint32_t r1, uint32_t r2, uint32_t r3) {
    asm volatile("stmatrix.sync.aligned.m8n8.x4.shared.b16 [%0], {%1, %2, %3, %4};" ::"r"(a), "r"(r0), "r"(r1), "r"(r2), "r"(r3) : "memory");
}
__device__ __forceinline__ void stsm2(uint32_t a, uint32_t r0, uint32_t r1) {
    asm volatile("stmatrix.sync.aligned.m8n8.x2.shared.b16 [%0], {%1, %2};" ::"r"(a), "r"(r0), "r"(r1) : "memory");
}
__device__ __forceinline__ uint4 lds4(uint32_t a) { uint4 v; asm volatile("ld.shared.v4.b32 {%0, %1, %2, %3}, [%4];" : "=r"(v.x), "=r"(v.y), "=r"(v.z), "=r"(v.w) : "r"(a) : "memory"); return v; }
__device__ __forceinline__ uint2 lds2(uint32_t a) { uint2 v; asm volatile("ld.shared.v2.b32 {%0, %1}, [%2];" : "=r"(v.x), "=r"(v.y) : "r"(a) : "memory"); return v; }
__device__ __forceinline__ float lds1f(uint32_t a) { float v; asm volatile("ld.shared.f32 %0, [%1];" : "=f"(v) : "r"(a) : "memory"); return v; }
__device__ __forceinline__ void ldsm4(uint32_t* r, uint32_t a) {
    asm volatile("ldmatrix.sync.aligned.m8n8.x4.shared.b16 {%0, %1, %2, %3}, [%4];" : "=r"(r[0]), "=r"(r[1]), "=r"(r[2]), "=r"(r[3]) : "r"(a) : "memory");
}
__device__ __forceinline__ void ldsm4t(uint32_t* r, uint32_t a) {
    asm volatile("ldmatrix.sync.aligned.m8n8.x4.trans.shared.b16 {%0, %1, %2, %3}, [%4];" : "=r"(r[0]), "=r"(r[1]), "=r"(r[2]), "=r"(r[3]) : "r"(a) : "memory");
}
__device__ __forceinline__ void ldsm2t(uint32_t* r, uint32_t a) {
    asm volatile("ldmatrix.sync.aligned.m8n8.x2.trans.shared.b16 {%0, %1}, [%2];" : "=r"(r[0]), "=r"(r[1]) : "r"(a) : "memory");
}
__device__ __forceinline__ uint32_t transpose8(uint32_t v) { uint32_t r; asm volatile("movmatrix.sync.aligned.m8n8.trans.b16 %0, %1;" : "=r"(r) : "r"(v)); return r; }
__device__ __forceinline__ void mma16(float (&c)[4], uint32_t a0, uint32_t a1, uint32_t a2, uint32_t a3, uint32_t b0, uint32_t b1) {
    asm volatile("mma.sync.aligned.m16n8k16.row.col.f32.bf16.bf16.f32 {%0, %1, %2, %3}, {%4, %5, %6, %7}, {%8, %9}, {%0, %1, %2, %3};"
                 : "+f"(c[0]), "+f"(c[1]), "+f"(c[2]), "+f"(c[3]) : "r"(a0), "r"(a1), "r"(a2), "r"(a3), "r"(b0), "r"(b1));
}
__device__ __forceinline__ void mma8(float (&c)[4], uint32_t a0, uint32_t a1, uint32_t b0) {
    asm volatile("mma.sync.aligned.m16n8k8.row.col.f32.bf16.bf16.f32 {%0, %1, %2, %3}, {%4, %5}, {%6}, {%0, %1, %2, %3};"
                 : "+f"(c[0]), "+f"(c[1]), "+f"(c[2]), "+f"(c[3]) : "r"(a0), "r"(a1), "r"(b0));
}
__device__ __forceinline__ void st_async4(uint32_t a, uint32_t bar, uint32_t v0, uint32_t v1, uint32_t v2, uint32_t v3) {
    asm volatile("st.async.weak.shared::cluster.mbarrier::complete_tx::bytes.v4.b32 [%0], {%2, %3, %4, %5}, [%1];" ::"r"(a), "r"(bar), "r"(v0), "r"(v1), "r"(v2), "r"(v3) : "memory");
}
__device__ __forceinline__ void st_async2(uint32_t a, uint32_t bar, uint32_t v0, uint32_t v1) {
    asm volatile("st.async.weak.shared::cluster.mbarrier::complete_tx::bytes.v2.b32 [%0], {%2, %3}, [%1];" ::"r"(a), "r"(bar), "r"(v0), "r"(v1) : "memory");
}
__device__ __forceinline__ float quad_max(float v) { v = fmaxf(v, __shfl_xor_sync(~0u, v, 1)); return fmaxf(v, __shfl_xor_sync(~0u, v, 2)); }
__device__ __forceinline__ float quad_sum(float v) { v += __shfl_xor_sync(~0u, v, 1); return v + __shfl_xor_sync(~0u, v, 2); }
__device__ __forceinline__ float ex2(float v) { float r; asm("ex2.approx.ftz.f32 %0, %1;" : "=f"(r) : "f"(v)); return r; }
__device__ __forceinline__ float rcp(float v) { float r; asm("rcp.approx.ftz.f32 %0, %1;" : "=f"(r) : "f"(v)); return r; }
__device__ __forceinline__ float rsq(float v) { float r; asm("rsqrt.approx.ftz.f32 %0, %1;" : "=f"(r) : "f"(v)); return r; }
__device__ __forceinline__ float gelu2(float u) {
    float z = u * fmaf(u * u, 0.044715f * 0.7978845608028654f, 0.7978845608028654f), t;
    asm("tanh.approx.f32 %0, %1;" : "=f"(t) : "f"(z));
    return fmaf(u, t, u);
}
__device__ __forceinline__ float row_sum(float v) {
    v = quad_sum(v); v += __shfl_xor_sync(~0u, v, 4);
    return v + __shfl_xor_sync(~0u, v, 24);
}

template <int TA, int TB, uint32_t HA, uint32_t HB>
__device__ __forceinline__ void wgmma_n112(float (&d)[56], uint32_t da, uint32_t db, int accumulate) {
    asm volatile("{\n.reg .pred p;\n.reg .b64 a, b;\nmov.b64 a, {%56, %61};\nmov.b64 b, {%57, %62};\nsetp.ne.b32 p, %58, 0;\n"
        "wgmma.mma_async.sync.aligned.m64n112k16.f32.bf16.bf16 {"
        "%0, %1, %2, %3, %4, %5, %6, %7, %8, %9, %10, %11, %12, %13, %14, %15, "
        "%16, %17, %18, %19, %20, %21, %22, %23, %24, %25, %26, %27, %28, %29, %30, %31, "
        "%32, %33, %34, %35, %36, %37, %38, %39, %40, %41, %42, %43, %44, %45, %46, %47, "
        "%48, %49, %50, %51, %52, %53, %54, %55"
        "}, a, b, p, 1, 1, %59, %60;\n}\n"
        : "+f"(d[0]), "+f"(d[1]), "+f"(d[2]), "+f"(d[3]), "+f"(d[4]), "+f"(d[5]), "+f"(d[6]), "+f"(d[7]),
          "+f"(d[8]), "+f"(d[9]), "+f"(d[10]), "+f"(d[11]), "+f"(d[12]), "+f"(d[13]), "+f"(d[14]), "+f"(d[15]),
          "+f"(d[16]), "+f"(d[17]), "+f"(d[18]), "+f"(d[19]), "+f"(d[20]), "+f"(d[21]), "+f"(d[22]), "+f"(d[23]),
          "+f"(d[24]), "+f"(d[25]), "+f"(d[26]), "+f"(d[27]), "+f"(d[28]), "+f"(d[29]), "+f"(d[30]), "+f"(d[31]),
          "+f"(d[32]), "+f"(d[33]), "+f"(d[34]), "+f"(d[35]), "+f"(d[36]), "+f"(d[37]), "+f"(d[38]), "+f"(d[39]),
          "+f"(d[40]), "+f"(d[41]), "+f"(d[42]), "+f"(d[43]), "+f"(d[44]), "+f"(d[45]), "+f"(d[46]), "+f"(d[47]),
          "+f"(d[48]), "+f"(d[49]), "+f"(d[50]), "+f"(d[51]), "+f"(d[52]), "+f"(d[53]), "+f"(d[54]), "+f"(d[55])
        : "r"(da), "r"(db), "r"(accumulate), "n"(TA), "n"(TB), "n"(HA), "n"(HB));
}

template <int TA, int TB, uint32_t HA, uint32_t HB>
__device__ __forceinline__ void wgmma_n184(float (&d)[92], uint32_t da, uint32_t db, int accumulate) {
    asm volatile("{\n.reg .pred p;\n.reg .b64 a, b;\nmov.b64 a, {%92, %97};\nmov.b64 b, {%93, %98};\nsetp.ne.b32 p, %94, 0;\n"
        "wgmma.mma_async.sync.aligned.m64n184k16.f32.bf16.bf16 {"
        "%0, %1, %2, %3, %4, %5, %6, %7, %8, %9, %10, %11, %12, %13, %14, %15, "
        "%16, %17, %18, %19, %20, %21, %22, %23, %24, %25, %26, %27, %28, %29, %30, %31, "
        "%32, %33, %34, %35, %36, %37, %38, %39, %40, %41, %42, %43, %44, %45, %46, %47, "
        "%48, %49, %50, %51, %52, %53, %54, %55, %56, %57, %58, %59, %60, %61, %62, %63, "
        "%64, %65, %66, %67, %68, %69, %70, %71, %72, %73, %74, %75, %76, %77, %78, %79, "
        "%80, %81, %82, %83, %84, %85, %86, %87, %88, %89, %90, %91"
        "}, a, b, p, 1, 1, %95, %96;\n}\n"
        : "+f"(d[0]), "+f"(d[1]), "+f"(d[2]), "+f"(d[3]), "+f"(d[4]), "+f"(d[5]), "+f"(d[6]), "+f"(d[7]),
          "+f"(d[8]), "+f"(d[9]), "+f"(d[10]), "+f"(d[11]), "+f"(d[12]), "+f"(d[13]), "+f"(d[14]), "+f"(d[15]),
          "+f"(d[16]), "+f"(d[17]), "+f"(d[18]), "+f"(d[19]), "+f"(d[20]), "+f"(d[21]), "+f"(d[22]), "+f"(d[23]),
          "+f"(d[24]), "+f"(d[25]), "+f"(d[26]), "+f"(d[27]), "+f"(d[28]), "+f"(d[29]), "+f"(d[30]), "+f"(d[31]),
          "+f"(d[32]), "+f"(d[33]), "+f"(d[34]), "+f"(d[35]), "+f"(d[36]), "+f"(d[37]), "+f"(d[38]), "+f"(d[39]),
          "+f"(d[40]), "+f"(d[41]), "+f"(d[42]), "+f"(d[43]), "+f"(d[44]), "+f"(d[45]), "+f"(d[46]), "+f"(d[47]),
          "+f"(d[48]), "+f"(d[49]), "+f"(d[50]), "+f"(d[51]), "+f"(d[52]), "+f"(d[53]), "+f"(d[54]), "+f"(d[55]),
          "+f"(d[56]), "+f"(d[57]), "+f"(d[58]), "+f"(d[59]), "+f"(d[60]), "+f"(d[61]), "+f"(d[62]), "+f"(d[63]),
          "+f"(d[64]), "+f"(d[65]), "+f"(d[66]), "+f"(d[67]), "+f"(d[68]), "+f"(d[69]), "+f"(d[70]), "+f"(d[71]),
          "+f"(d[72]), "+f"(d[73]), "+f"(d[74]), "+f"(d[75]), "+f"(d[76]), "+f"(d[77]), "+f"(d[78]), "+f"(d[79]),
          "+f"(d[80]), "+f"(d[81]), "+f"(d[82]), "+f"(d[83]), "+f"(d[84]), "+f"(d[85]), "+f"(d[86]), "+f"(d[87]),
          "+f"(d[88]), "+f"(d[89]), "+f"(d[90]), "+f"(d[91])
        : "r"(da), "r"(db), "r"(accumulate), "n"(TA), "n"(TB), "n"(HA), "n"(HB));
}

template <uint32_t HB>
__device__ __forceinline__ void wgmma_rs_n184(float (&d)[92], uint32_t a0, uint32_t a1, uint32_t db) {
    asm volatile("{\n.reg .b64 b;\nmov.b64 b, {%94, %96};\n"
        "wgmma.mma_async.sync.aligned.m64n184k16.f32.bf16.bf16 {"
        "%0, %1, %2, %3, %4, %5, %6, %7, %8, %9, %10, %11, %12, %13, %14, %15, "
        "%16, %17, %18, %19, %20, %21, %22, %23, %24, %25, %26, %27, %28, %29, %30, %31, "
        "%32, %33, %34, %35, %36, %37, %38, %39, %40, %41, %42, %43, %44, %45, %46, %47, "
        "%48, %49, %50, %51, %52, %53, %54, %55, %56, %57, %58, %59, %60, %61, %62, %63, "
        "%64, %65, %66, %67, %68, %69, %70, %71, %72, %73, %74, %75, %76, %77, %78, %79, "
        "%80, %81, %82, %83, %84, %85, %86, %87, %88, %89, %90, %91"
        "}, {%92, %93, %95, %95}, b, 1, 1, 1, 0;\n}\n"
        : "+f"(d[0]), "+f"(d[1]), "+f"(d[2]), "+f"(d[3]), "+f"(d[4]), "+f"(d[5]), "+f"(d[6]), "+f"(d[7]),
          "+f"(d[8]), "+f"(d[9]), "+f"(d[10]), "+f"(d[11]), "+f"(d[12]), "+f"(d[13]), "+f"(d[14]), "+f"(d[15]),
          "+f"(d[16]), "+f"(d[17]), "+f"(d[18]), "+f"(d[19]), "+f"(d[20]), "+f"(d[21]), "+f"(d[22]), "+f"(d[23]),
          "+f"(d[24]), "+f"(d[25]), "+f"(d[26]), "+f"(d[27]), "+f"(d[28]), "+f"(d[29]), "+f"(d[30]), "+f"(d[31]),
          "+f"(d[32]), "+f"(d[33]), "+f"(d[34]), "+f"(d[35]), "+f"(d[36]), "+f"(d[37]), "+f"(d[38]), "+f"(d[39]),
          "+f"(d[40]), "+f"(d[41]), "+f"(d[42]), "+f"(d[43]), "+f"(d[44]), "+f"(d[45]), "+f"(d[46]), "+f"(d[47]),
          "+f"(d[48]), "+f"(d[49]), "+f"(d[50]), "+f"(d[51]), "+f"(d[52]), "+f"(d[53]), "+f"(d[54]), "+f"(d[55]),
          "+f"(d[56]), "+f"(d[57]), "+f"(d[58]), "+f"(d[59]), "+f"(d[60]), "+f"(d[61]), "+f"(d[62]), "+f"(d[63]),
          "+f"(d[64]), "+f"(d[65]), "+f"(d[66]), "+f"(d[67]), "+f"(d[68]), "+f"(d[69]), "+f"(d[70]), "+f"(d[71]),
          "+f"(d[72]), "+f"(d[73]), "+f"(d[74]), "+f"(d[75]), "+f"(d[76]), "+f"(d[77]), "+f"(d[78]), "+f"(d[79]),
          "+f"(d[80]), "+f"(d[81]), "+f"(d[82]), "+f"(d[83]), "+f"(d[84]), "+f"(d[85]), "+f"(d[86]), "+f"(d[87]),
          "+f"(d[88]), "+f"(d[89]), "+f"(d[90]), "+f"(d[91])
        : "r"(a0), "r"(a1), "r"(db), "r"(0), "n"(HB));
}

struct Ring {
    uint32_t slot, ph;
    __device__ __forceinline__ void next() { if (++slot == NSLOT) { slot = 0; ph ^= 1; } }
    __device__ __forceinline__ void next2() { ph ^= slot == 5; slot = __byte_perm(0x06030201u, 0x00040005u, 0x7770 + slot); }
};
struct Slot {
    uint32_t dst, bar, ph;
    __device__ __forceinline__ void next(uint32_t bars) {
        dst += SLOT; bar += 8;
        if (bar == bars + 8 * NSLOT) { dst -= NSLOT * SLOT; bar = bars; ph ^= 1; }
    }
};
__device__ __forceinline__ uint32_t xslot(int i) { return __byte_perm(0x04130e0cu, 0x00130e0cu, 0x7770 + i); }
__device__ __forceinline__ uint32_t wslot(int i) { return __byte_perm(0x06001510u, 0x00151009u, 0x7770 + i); }

constexpr uint32_t HI_SW = desc_hi(1024, 1);

struct Mma {
    uint32_t bars, rel;
    bool lead;
    int wg, w;
    Ring r;
    uint32_t prev;
    __device__ __forceinline__ void release(uint32_t s) { if (lead) mbar_arrive4_remote(rel + B_EMPTY + 8 * s); }
    template <bool G1>
    __device__ __forceinline__ void run(float (&a)[56], int n, int first, int last, int lag, int accumulate, int ts) {
#pragma unroll 1
        for (int i = 0; i < n; i++) {
            if (lag && i == (wg == (G1 || !SWAP2) ? n - lag : -1)) bar_sync(7, 256);
            const uint32_t s = r.slot;
            mbar_wait(bars + B_FULL + 8 * s, r.ph);
            if (G1) r.next(); else r.next2();
            TS0(G1 ? 2 : 8, ts + i + wg * 68);
            const uint32_t dB = s * (SLOT >> 4), dA = dB + wg * 512;
            wg_fence();
#pragma unroll
            for (int k = 0; k < 4; k++) {
                wgmma_n112<1, 1, HI_SW, desc_hi(G1 ? 256 : 1024, 0)>(a, dA + desc_lo(k * 2048, 8192), dB + desc_lo(16384 + k * (G1 ? SLAB : 256), 128), k > 0 || accumulate || i > 0);
                if (k == 1) {
                    wg_commit(); wg_wait<1>();
                    if ((uint32_t)(i - first) < (uint32_t)(last - first)) release(prev);
                    if (lag && i == (wg == (G1 || !SWAP2) ? -1 : n - 1)) bar_arrive(7, 256);
                }
            }
            wg_commit();
            prev = s;
        }
    }
    __device__ __forceinline__ void run_o(float (&a)[56]) {
#pragma unroll 1
        for (int i = 0; i < 2; i++) {
            const uint32_t s = r.slot, dB = s * (SLOT >> 4), dA = dB + wg * 512;
            mbar_wait(bars + B_FULL + 8 * s, r.ph);
            TS0(8, 48 + 2 * i + wg * 68);
            wg_fence();
#pragma unroll
            for (int k = 0; k < 7; k++) {
                if (k == 3) { mbar_wait(bars + B_FULL + 8 * s + 8, r.ph); wg_fence(); }
                wgmma_n112<0, 1, desc_hi(128, 0), desc_hi(256, 0)>(a, dA + desc_lo(k * 2048 + (k > 3) * (SLOT - HALF), k == 3 ? SLOT - 6144 : 1024),
                                                                   dB + desc_lo(16384 + k * SLAB + (k > 2) * (SLOT - 3 * SLAB), 128), k > 0 || i > 0);
                if (k & 1) wg_commit();
                if (k == 1) { wg_wait<1>(); if (i) release(prev); }
                if (k == 5) { wg_wait<1>(); release(s); }
            }
            wg_commit();
            prev = s + 1;
            r.slot++; r.next2();
        }
    }
};

__global__ void __cluster_dims__(2, 1, 1) __launch_bounds__(NTHREADS, 1)
fused_kernel(const __nv_bfloat16* __restrict__ x, const __nv_bfloat16* __restrict__ b1, const __nv_bfloat16* __restrict__ b2, const __nv_bfloat16* __restrict__ wo, __nv_bfloat16* out, Scratch* G,
             const __nv_bfloat16* __restrict__ w1, const __nv_bfloat16* __restrict__ w2,
             const __grid_constant__ Params P) {
    extern __shared__ __align__(1024) uint8_t smem[];
    const uint32_t sbase = (uint32_t)__cvta_generic_to_shared(smem);
    const uint32_t bars = sbase + OFF_BAR;
    const uint32_t rank = blockIdx.x & 1, pr = blockIdx.x >> 1;
    const uint32_t row0 = blockIdx.x * 16;
    if (threadIdx.x == 0) {
        TS(15, 0);
        mbar_init(bars + B_ROW, 1);
        asm volatile("fence.mbarrier_init.release.cluster;" ::: "memory");
        bulk_load(sbase + OFF_Y, x + row0 * D_, TILEB, bars + B_ROW);
        mbar_expect(bars + B_ROW, TILEB);
        TS(1, 97);
    }
    const int lane = threadIdx.x & 31;
    const int warp = __shfl_sync(~0u, threadIdx.x >> 5, 0), w = warp & 3;
    if (elect()) {
        const uint32_t first = bars + warp * 24, count = warp < 7 ? 1 : warp < 9 ? 18 - 2 * warp : 16;
#pragma unroll
        for (int i = 0; i < 3; i++) mbar_init(first + 8 * i, count);
        asm volatile("fence.mbarrier_init.release.cluster;" ::: "memory");
    }
    __syncwarp();
    asm volatile("barrier.cluster.arrive.relaxed.aligned;" ::: "memory");
    const uint32_t pv = pr < 4 ? pr * 8 + 36 : pr - 4 + (max((int)pr - 33, 0) * 37 >> 8);
    const uint32_t gp = (pv + 4) & 7, hp = pv >> 3;
    const uint32_t tb = gp * 2 + rank, c = hp * 16 + tb;
    const bool has_g1 = gp > 0;
    const uint32_t nt1 = hp & 3, ft = max((int)gp - 1, 0) * 2 + (hp >> 2);
    const uint32_t nt2 = (hp & 1) * 2 + rank, mt = (gp & 3) * 4 + (hp >> 1), ks = gp >> 2;
    asm volatile("barrier.cluster.wait.aligned;" ::: "memory");

    if (warp == 8) {
        uint32_t kw = (gp & 1) * 256, kx;
        if (elect()) {
            mbar_expect(bars + B_QFULL, QSLOT);
            tma3d(sbase + xslot(0) * 8192, &P.tmX, bars + B_QFULL, kw, tb * 64, 0);
            tma3d_pair(sbase + wslot(0) * 8192 + rank * 12288, &P.tmWqkv, bars + B_QFULL, (hp * 56) & ~15, kw + rank * 32, 0);
            TS(1, 23);
            uint32_t due = (uint32_t)clock() + PACE, ep = ld_relaxed(&G->epoch[c]);
            uint32_t spins = sbase == (rank << 24 | SMEM0) ? 0 : SPIN_LIMIT;
#pragma unroll 1
            for (int i = 1; i < 8; i++) {
                kx = kw; kw += 64;
                if (i >= 5) mbar_wait_bounded(bars + B_QEMPTY + 8 * (i - 5), 0, spins);
                else { while ((int)((uint32_t)clock() - due) < 0) {} due += PACE; }
                if (kw == D_) kw = 0;
                if (i < 4) kx = kw;
                const int ix = i - (i > 4);
                if (i < 7) mbar_expect(bars + B_QFULL + 8 * i, QSLOT);
                if (i != 4) tma3d(sbase + xslot(ix) * 8192, &P.tmX, bars + B_QFULL + 8 * ix, kx, tb * 64, 0);
                if (i & (i >> 2)) mbar_wait_bounded(bars + B_CS - 20 + 4 * i, 0, spins);
                if (i < 7) tma3d_pair(sbase + wslot(i) * 8192 + rank * 12288, &P.tmWqkv, bars + B_QFULL + 8 * i, (hp * 56) & ~15, kw + rank * 32, 0);
            }
            ep++;
            Slot r{sbase, bars, 0};
            if (has_g1) {
                const uint8_t* src = G->H[nt1][rank * 16];
                const int row = rank * 1024;
                mbar_arrive(bars + B_FULL + 48); mbar_arrive16(bars + B_EMPTY + 48);
                mbar_expect(bars + B_FULL, 16384 + TILEB);
                tma3d(sbase, &P.tmW1, bars + B_FULL, 0, row, ft * 2);
                wait_flag(G->flag[1] + rank * 2, 20 * ep, spins);
                TS(1, 16);
#pragma unroll 1
                for (int j = 64;; j += 64) {
                    bulk_load(r.dst + 16384, src, TILEB, r.bar + B_FULL);
                    src += TILEB;
                    r.next(bars);
                    if (j == 1024) break;
                    mbar_wait_bounded(r.bar + B_EMPTY, r.ph, spins);
                    if (j < 14 * 64) TS(2, 146 + j / 64);
                    mbar_expect(r.bar + B_FULL, 16384 + TILEB);
                    tma3d(r.dst, &P.tmW1, r.bar + B_FULL, 0, row + j, ft * 2);
                }
#pragma unroll
                for (int i = 0; i < 4; i++) mbar_expect(bars + B_X + 8 * i, (i & 1) ? 3072 : 4096);
            } else {
                due = (uint32_t)clock();
#pragma unroll 1
                for (int j = PF0; j < PF1; j++) {
                    asm volatile("cp.async.bulk.prefetch.L2.global [%0], %1;" ::"l"(w1 + (rank * 1024 + j * 64 + hp * 8) * F_), "n"(16 * F_) : "memory");
                    due += PF;
                    while ((int)((uint32_t)clock() - due) < 0) {}
                }
            }
            const uint8_t *so = G->O[mt][ks * 4] + (LOCREL == 2 ? 0 : rank * HALF), *sw = G->Wo[nt2][ks * 4];
            wait_flag2(G->flag[16 + mt], 8 * ep, G->flag[0], 16 * ep, spins);
            TS(4, 18);
#pragma unroll 1
            for (int j = 0; j < 4 * TILEB; j += TILEB) {
                mbar_wait_bounded(r.bar + B_EMPTY, r.ph, spins);
                mbar_expect(r.bar + B_QFULL, TILEB);
                if (LOCREL == 2) { bulk_load(r.dst, so + j, HALF, r.bar + B_QFULL); bulk_load(r.dst + 8192, so + j + HALF, HALF, r.bar + B_QFULL); }
                else bulk_load_pair(r.dst + rank * 8192, so + j, HALF, r.bar + B_QFULL);
                bulk_load(r.dst + 16384, sw + j, (r.bar & 8) ? TILEB : 3 * SLAB, r.bar + B_FULL);
                r.next(bars);
            }
            if (!has_g1) {
#pragma unroll
                for (int j = PG0; j < PG1; j++)
                    asm volatile("cp.async.bulk.prefetch.L2.global [%0], %1;" ::"l"(w2 + (rank * 896 + j * 128 + hp * 8) * S_), "n"(16 * S_) : "memory");
            }
            Ring q{has_g1 ? 2u : 6u, has_g1}, p = q;
#pragma unroll 1
            for (int j = 0; j < 14 * 128; j += 128) {
                mbar_wait_bounded(bars + B_EMPTY + 8 * q.slot, q.ph, spins);
                if (LEADW && j >= LEADW * 128 && j < LEADN * 128) { mbar_wait_bounded(bars + B_FULL + 8 * p.slot, p.ph, spins); p.next2(); }
                TS(8, 176 + j / 128);
                tma3d(sbase + q.slot * SLOT, &P.tmW2, bars + B_FULL + 8 * q.slot, 0, ks * 896 + j - (j < 896 ? 0 : 832), mt * 2);
                q.next2();
            }
            mbar_wait_bounded(bars + B_END, 0, spins);
        }
    } else if (warp > 8) {
        const uint32_t ep = ld_relaxed(&G->epoch[c]) + 1;
        {
            uint2* cs = G->colsum[hp][0];
            if (w == 2) {
                bar_sync(6, 288);
                TS(1, 8);
                stg1((uint32_t*)(G->stat + row0) + lane, tag(__float_as_uint(lds1f(sbase + OFF_ST + lane * 4)), ~lane & 1, ep));
                if (elect()) {
                    fence_async_shared();
#pragma unroll
                    for (int i = 0; i < 4; i++) bulk_store(G->H[i][0] + row0 * (SLAB / 16), sbase + OFF_X + i * HSTG, SLAB);
                    bulk_flush();
                    TS(1, 99);
                    signal(G->flag[1] + (row0 >> 10) * 2 + ((row0 & 1023) >= 320));
                }
                __syncwarp();
            } else {
                const uint32_t word = rank * 16 + (w & 2) * 4 + (lane & 7), done = mapa(bars + B_CS, rank ^ (lane & 1));
                const uint32_t src = (sbase + word * 4 + (gp >> 2) * 12288 + (gp & 2) * 1024) ^ ((lane >> 3) * 288);
                float s[6] = {};
#pragma unroll 1
                for (int i = 0; i < 4 - (gp & 1); i++) {
                    const uint32_t a0 = src + wslot(i) * 8192, a1 = a0 ^ 144;
                    mbar_wait(bars + B_QFULL + 8 * i, 0);
                    if (w == 1) TS(1, 66);
                    uint32_t v[12];
#pragma unroll
                    for (int k = 0; k < 12; k++) v[k] = __float_as_uint(lds1f(((k & 1) ? a1 : a0) + (k & 2) * 512 + (k >> 2) * 4096));
#pragma unroll
                    for (int k = 0; k < 12; k++) { s[(k >> 2) * 2] += bf_lo(v[k]); s[(k >> 2) * 2 + 1] += bf_hi(v[k]); }
                    __syncwarp();
                    if (i == 1 && lane < 2) mbar_arrive_remote(done);
                }
                if (lane < 2) mbar_arrive_remote(done + 8);
#pragma unroll
                for (int k = 0; k < 6; k++) { s[k] += __shfl_xor_sync(~0u, s[k], 8); s[k] += __shfl_xor_sync(~0u, s[k], 16); }
                const float s0 = lane < 8 ? s[0] : lane < 16 ? s[2] : s[4], s1 = lane < 8 ? s[1] : lane < 16 ? s[3] : s[5];
                if (lane < 24) cs[gp * 96 + (lane >> 3) * 32 + word] = make_uint2(tag(__float_as_uint(s0), 1, ep), __float_as_uint(s1));
                if (w == 1) TS(1, 24);
                mbar_wait(bars + B_QFULL + 24, 0);
            }
            bar_sync(1, 96);
            if (w == 1) TS(1, 98);
            const int i0 = threadIdx.x - 288;
            uint2 u[8];
            uint4 sv;
            uint32_t bad;
            do {
                sv = ld_relaxed4(G->stat + tb * 128 + (i0 & 63) * 2);
                bad = or_diff(sv.x ^ ep, sv.z, ep);
#pragma unroll
                for (int i = 0; i < 8; i++) { u[i] = ld_relaxed2(cs + i * 96 + i0); bad = or_diff(bad, u[i].x, ep); }
                if (bad & 1) TS(1, 3);
            } while (bad & 1);
            if (w < 3) sts4(sbase + OFF_ST + i0 * 16, sv);
#pragma unroll
            for (int e = 0; e < 2; e++) {
                float f = 0.f;
#pragma unroll
                for (int i = 0; i < 8; i++) f += __uint_as_float(e ? u[i].y : u[i].x);
                const uint32_t hi = pack2(f, f);
                sts4(sbase + OFF_X + i0 * 32 + e * 16, make_uint4(hi, pack2(f - bf_hi(hi), f - bf_hi(hi)), 0, 0));
            }
            sts1(bars + 8 * NBAR, ep);
            fence_async_shared();
            __syncwarp();
            bar_arrive(8, 224); bar_arrive(9, 224);
            TS(1, 90 + w);
        }
        const uint8_t* src = G->U[nt2][ks * 14];
        uint32_t spins = 0;
        uint32_t bad;
        if (w < 3) {
            if (w == 1) {
                if (elect()) {
                    wait_flag(G->flag[1] + rank * 2 + 1, 44 * ep, spins);
                    mbar_arrive16(bars + B_EMPTY + 8 * 5);
                    TS(1, 96);
                }
                __syncwarp();
                if (!has_g1) { bar_sync(5, 288); if (elect()) signal(G->flag[0]); __syncwarp(); TS(2, 26); }
            }
            mbar_wait(bars + B_HALO, 0);
            uint32_t slot = (has_g1 ? 16 % NSLOT : 0) + w - 1, ph = ~0u;
#pragma unroll 1
            for (int i = w - 1; i < 18;) {
                const uint32_t d0 = sbase + slot * SLOT + (i < 4 ? 0 : 16384), d1 = d0 + (i < 4 ? 8192 : HALF), landed = bars + B_QFULL + 8 * slot;
                mbar_wait(landed, (ph >> slot) & 1);
                ph ^= 1 << slot;
                if (i < 8) TS(4, 82 + i);
                if (i >= 4) TS(8, 156 + i);
                bad = 0;
#pragma unroll
                for (int k = 0; k < 14; k++) bad = or_diff(bad, __float_as_uint(lds1f((k < 7 ? d0 : d1) + k % 7 * 1024 + lane * 32 + (lane >> 2) * 4)), ep);
                if (__any_sync(~0u, bad & 1)) {
                    if (elect()) {
                        const uint8_t* cur = (i < 4 ? G->O[mt][ks * 4] : src - 4 * TILEB) + i * TILEB;
                        fence_async_shared();
                        mbar_expect(landed, TILEB);
                        bulk_load(d0, cur, HALF, landed);
                        bulk_load(d1, cur + HALF, HALF, landed);
                    }
                    TS(4, i < 4 ? 94 : 95);
                } else {
                    if (elect()) mbar_expect(landed + (B_FULL - B_QFULL), i < 4 ? (2 + w) * SLAB : 16384);
                    i += __byte_perm(0x03020202u, 0x00010202u, 0x7770 + slot);
                    slot = __byte_perm(0x05060302u, 0x00040100u, 0x7770 + slot);
                }
            }
        } else {
            bar_sync(3, 288);
            __nanosleep(HALO_NS);
            uint4 v[7];
            do {
                bad = 0;
#pragma unroll
                for (int i = 0; i < 7; i++) { v[i] = ld_relaxed4(G->halo[c - (tb > 0)] + i * 512 + lane * 16); bad = or_diff(bad, v[i].x, ep); }
            } while (bad & 1);
#pragma unroll
            for (int i = 0; i < 7; i++) sts4(sbase + OFF_X + i * 512 + lane * 16, v[i]);
            __syncwarp();
            if (elect()) mbar_arrive(bars + B_HALO);
            TS(2, 21);
            bar_sync(2, 288);
            if (elect()) bulk_store(out + row0 * D_, sbase + OFF_Y, TILEB);
            __syncwarp();
            bar_sync(4, 288);
            if (elect()) {
                fence_async_shared();
                bulk_store(G->O[tb][hp], sbase + OFF_X, TILEB);
                bulk_flush();
                TS(2, 7);
                mbar_arrive_remote(mapa(bars + B_FREE, rank ^ 1));
                mbar_arrive(bars + B_FREE);
                hint(G->flag[16 + tb]);
                signal(G->flag[16 + (row0 >> 7)] + 1);
                TS(2, 22);
            }
            __syncwarp();
            uint32_t late = ~0u;
            const uint32_t* hints = G->flag[8 + nt2 * 2 + ks] + lane;
            mbar_wait(bars + (has_g1 ? B_X : B_FREE), 0);
            Ring r{has_g1 ? 2u : 6u, has_g1};
#pragma unroll 1
            for (int i = 0; i < 14; i++) {
                while ((late >> i) & 1) late = __ballot_sync(~0u, ld_relaxed(hints) != 2 * ep) & 127;
                if (i == 0) TS(4, 17);
                mbar_wait(bars + B_EMPTY + 8 * r.slot, r.ph);
                TS(8, 192 + i);
                if (elect()) {
                    mbar_expect(bars + B_QFULL + 8 * r.slot, TILEB);
                    bulk_load(sbase + r.slot * SLOT + 16384, src, TILEB, bars + B_QFULL + 8 * r.slot);
                }
                src += TILEB; r.next2();
            }
            if (elect()) {
                wait_flag(G->flag[16 + mt] + 1, 8 * ep, spins);
                mbar_arrive(bars + B_ROW);
                TS(2, 27);
                G->epoch[c] = ep;
            }
        }
    } else {
        const int wg = warp >> 2;
        Mma M{bars, mapa(bars, rank ^ (lane & 1)), (threadIdx.x & 127) < 2, wg, w, Ring{0, 0}, 0};
        const int r = lane >> 2, t = lane & 3;
        uint32_t ep;
        const uint32_t bias0 = ld_u16(b1 + ft * 128 + warp * 16 + r), bias1 = ld_u16(b1 + ft * 128 + warp * 16 + r + 8);
        const uint32_t kv = sbase + OFF_X + (w * 2 + wg) * KV + lane * 16;
        uint32_t q[8][2], k0[7], k1[7], v0[7];
        {
            const int half = (lane >> 3) & 1, r16 = warp * 2 + (half ^ (lane >> 4)), nt = (lane >> 1) & 3;
            const uint32_t row = sbase + OFF_Y + r16 * (2 * D_), part = row + nt * 224 + half * 112 + (lane & 1) * 8;
            const uint32_t hb = sbase + OFF_X + nt * HSTG + r16 * 16 + (half ^ (row0 >> 10)) * (7 * 256) + (lane & 1) * 8;
            mbar_wait(bars + B_ROW, 0);
            TS0(1, 67);
            const float x0 = bf_lo(__float_as_uint(lds1f(row)));
            float d[28], m1 = 0.f, n1 = 0.f, m2 = 0.f, n2 = 0.f;
#pragma unroll
            for (int i = 0; i < 7; i++) {
                const uint2 v = lds2(part + i * 16);
#pragma unroll
                for (int k = 0; k < 2; k++) {
                    const float d0 = d[4 * i + 2 * k] = bf_lo(k ? v.y : v.x) - x0, d1 = d[4 * i + 2 * k + 1] = bf_hi(k ? v.y : v.x) - x0;
                    m1 += d0; n1 += d1; m2 = fmaf(d0, d0, m2); n2 = fmaf(d1, d1, n2);
                }
            }
            const float md = row_sum(m1 + n1) * (1.f / D_), var = fmaf(-md, md, row_sum(m2 + n2) * (1.f / D_)), nmean = -(x0 + md);
            const float rstd = rsq(var + LN_EPS);
            const float sc = rstd * rsq(fmaf(var * rstd, rstd, LN_EPS)), nb = -md * sc;
            sts2(sbase + OFF_ST + r16 * 8, __float_as_uint(rstd), pack2(nmean, nmean - bf_hi(pack2(nmean, nmean))));
#pragma unroll
            for (int i = 0; i < 7; i++) sts2(hb + i * 256, pack2(fmaf(d[4 * i], sc, nb), fmaf(d[4 * i + 1], sc, nb)), pack2(fmaf(d[4 * i + 2], sc, nb), fmaf(d[4 * i + 3], sc, nb)));
            TS0(1, 25);
            bar_arrive(6, 288);
            float acc[92];
#pragma unroll 1
            for (int kb = 0; kb < 7; kb++) {
                const bool held = kb == (wg ? 7 - HOLD : -1);
                if (held) { wg_wait<0>(); M.release(4 - HOLD); TS0(1, 138); bar_sync(7, 256); }
                mbar_wait(bars + B_QFULL + 8 * kb, 0);
                if (!TSQ || !kb) TS0(1, 68 + wg * 7 + kb);
                const uint32_t dA = (xslot(kb) + wg) * 512, dB = wslot(kb) * 512 + (hp & 1);
                wg_fence();
#pragma unroll
                for (int k = 0; k < 4; k++) {
                    wgmma_n184<0, 1, HI_SW, HI_SW>(acc, dA + desc_lo(k * 32, 16), dB + desc_lo((k & 1) * 2048 + (k >> 1) * 12288, 4096), k > 0 || kb > 0);
                    if (k == 0) { wg_commit(); wg_wait<1>(); if (kb > 0 && !held) M.release(kb - 3); if (TSQ && kb) TS0(1, 68 + wg * 7 + kb); }
                }
                wg_commit();
            }
            if (wg == 0 && !LATEREL) bar_arrive(7, 256);
            if (wg == 0) TS0(1, 139);
            bar_sync(8 + wg, 224);
            if (wg == 0) TS0(1, 174);
            ep = __float_as_uint(lds1f(bars + 8 * NBAR));
            const uint32_t st = sbase + OFF_ST + (w * 32 + r * 2 + wg) * 8;
            const uint2 s0 = lds2(st), s1 = lds2(st + 128);
            const uint32_t a0 = t < 2 ? s0.y : 0, a1 = t < 2 ? s1.y : 0;
            wg_fence();
            wgmma_rs_n184<desc_hi(128, 0)>(acc, a0, a1, desc_lo(OFF_X, 0) + (hp & 1) * 8);
            wg_commit();
            if (wg == 0 && LATEREL) bar_arrive(7, 256);
            if (wg == 0) TS0(1, 175);
            wg_wait<1>();
            TS0(1, 190 + wg);
            M.release(4);
            wg_wait<0>();
            pin(acc);
            TS0(1, 4 + 7 * wg);
            uint32_t hi[14];
#pragma unroll
            for (int p = 2; p >= 0; p--) {
                const float f = p == 0 ? 0.1889822365046136f * 1.4426950408889634f : p, r0 = __uint_as_float(s0.x) * f, r1 = __uint_as_float(s1.x) * f;
#pragma unroll
                for (int g = 0; g < 7; g++) {
                    const int a = (p * 8 + g) * 4;
                    const uint32_t lo2 = pack2(acc[a] * r0, acc[a + 1] * r0), hi2 = pack2(acc[a + 2] * r1, acc[a + 3] * r1);
                    if (p == 0) { q[g][0] = lo2; q[g][1] = hi2; } else { hi[(p - 1) * 7 + g] = hi2; }
                    if (p == 1) { k0[g] = lo2; k1[g] = hi2; }
                    if (p == 2) v0[g] = lo2;
                }
                if (p == 1) {
#pragma unroll
                    for (int i = 0; i < 3; i++) stsm4(kv + 2 * KV + i * 512, hi[4 * i], hi[4 * i + 1], hi[4 * i + 2], hi[4 * i + 3]);
                    stsm2(kv + 2 * KV + 1536, hi[12], hi[13]);
                    if (w == 3) {
#pragma unroll
                        for (int i = 0; i < 14; i++) stg1(G->halo[c] + wg * KV + lane * 4 + i * 128, tag(hi[i], t == 0, ep));
                    }
                    bar_arrive(3, 288);
                }
            }
#pragma unroll
            for (int j = 0; j < 2; j++) { q[7][j] = t < 2 ? 0u : q[3][j]; q[3][j] = t < 2 ? q[3][j] : 0u; }
#pragma unroll
            for (int g = 0; g < 7; g++) v0[g] = transpose8(v0[g]);
        }
        TS0(1, 9 + 11 * wg);
        if (LOCREL == 2) M.rel = bars;
        float a[56];
#pragma unroll
        for (int i = 0; i < 56; i++) asm volatile("" : "=f"(a[i]));
        if (__builtin_expect(!has_g1, 0)) {
            const int g = min(lane >> 1, 13), nt = rank * 2 + wg;
            const uint4* src = (const uint4*)(wo + (hp * 56 - (hp & 1) * 8 + w * 16 + (lane & 1)) * D_ + nt * 112) + g;
            uint4 v[8];
#pragma unroll
            for (int i = 0; i < 8; i++) v[i] = __ldg(src + i * (D_ / 4));
#pragma unroll
            for (int i = 0; i < 8; i++) ((uint4*)G->Wo[nt][hp])[w * (SLAB / 16) + g * 16 + (lane & 1) + 2 * i] = v[i];
            bar_arrive(5, 288);
        }
        M.run<true>(a, has_g1 ? PAUSE : 0, 1, 16, 0, 0, 32);
        {
            uint32_t kp[8], vv[14];
            TS0(2, 140 + wg);
            mbar_wait(bars + B_HALO, 0);
            TS0(2, 142 + wg);
            ldsm4(kp, kv); ldsm4(kp + 4, kv + (lane < 24 ? 512 : 0));
            const uint32_t va = kv + 896 + (lane & 8) * (2 * KV / 8 - 16) - (lane & 16) * 8;
            ldsm4t(vv, va); ldsm4t(vv + 4, va + 256); ldsm4t(vv + 8, va + 512); ldsm2t(vv + 12, va + 768);
            const bool e0 = 2 * t > r, e1 = 2 * t >= r;
            const uint32_t mk = (e0 ? 0xffffu : 0u) | (e1 ? 0xffff0000u : 0u);
            wg_wait<0>();
            pin(a);
            if (has_g1) M.release(M.prev);
            TS0(2, 144 + wg);
            bar_sync(2, 288);
            mbar_wait(bars + B_HALO, 0);
            TS0(2, 12 + 16 * wg);
            float sv[2][4];
#pragma unroll
            for (int h = 0; h < 2; h++) {
                const int ga = h * 4, gb = h * 4 + 1, gc = h * 4 + 2, gd = h * 4 + 3;
                float s[3][4] = {};
                mma16(s[0], q[ga][0], q[ga][1], q[gb][0], q[gb][1], kp[ga], kp[gb]);
                mma16(s[1], q[ga][0], q[ga][1], q[gb][0], q[gb][1], k0[ga], k0[gb]);
                mma16(s[2], q[ga][0], q[ga][1], q[gb][0], q[gb][1], k1[ga], k1[gb]);
                mma16(s[0], q[gc][0], q[gc][1], q[gd][0], q[gd][1], kp[gc], kp[gd]);
                mma16(s[1], q[gc][0], q[gc][1], q[gd][0], q[gd][1], k0[gc], k0[3]);
                mma16(s[2], q[gc][0], q[gc][1], q[gd][0], q[gd][1], k1[gc], k1[3]);
                if ((tb | w) == 0) s[0][0] = s[0][1] = -1e30f;
                sv[h][0] = e0 ? s[0][0] : s[1][0];
                sv[h][1] = e1 ? s[0][1] : s[1][1];
                sv[h][2] = e0 ? s[1][2] : s[2][2];
                sv[h][3] = e1 ? s[1][3] : s[2][3];
            }
            uint32_t pp[2][2];
#pragma unroll
            for (int i = 0; i < 4; i++) {
                float* v = &sv[i >> 1][(i & 1) * 2];
                const float m = quad_max(fmaxf(v[0], v[1]));
                const float p0 = ex2(v[0] - m), p1 = ex2(v[1] - m);
                const float inv = rcp(quad_sum(p0 + p1));
                pp[i >> 1][i & 1] = pack2(p0 * inv, p1 * inv);
            }
            uint32_t o[8][2];
#pragma unroll
            for (int i = 0; i < 8; i++) {
                const int h = i >> 2, g = i - h;
                float d[4] = {};
                mma16(d, pp[h][0] & mk, 0u, 0u, pp[h][1] & ~mk, vv[2 * g], vv[2 * g + 1]);
                mma8(d, pp[h][0] & ~mk, pp[h][1] & mk, v0[g]);
                o[i][0] = pack2(d[0], d[1]); o[i][1] = pack2(d[2], d[3]);
            }
            if (t >= 2) { o[3][0] = o[4][0]; o[3][1] = o[4][1]; }
            const int word = wg * 4 + t - (w & 1) * 4 - (r >> 2);
#pragma unroll
            for (int i = 0; i < 8; i++) { o[i][0] = tag(o[i][0], word == 0, ep); o[i][1] = tag(o[i][1], word == 2, ep); }
            const uint32_t dst = sbase + OFF_X + (w >> 1) * HALF + ((w & 1) * 32 + (lane & 15) * 2 + wg) * 16 + (lane >> 4) * 1024;
            stsm4(dst, o[0][0], o[0][1], o[1][0], o[1][1]);
            stsm4(dst + 2048, o[2][0], o[2][1], o[3][0], o[3][1]);
            stsm4(dst + 4096, o[5][0], o[5][1], o[6][0], o[6][1]);
            stsm2(dst + 6144, o[7][0], o[7][1]);
            if (ENDBAR) bar_sync(4, 288); else bar_arrive(4, 288);
            TS0(2, 10 + 19 * wg);
        }
        if (has_g1) {
            M.run<true>(a, 16 - PAUSE, 1, 16, LAG1, 1, 32 + PAUSE);
            mbar_wait(bars + B_FREE, 0);
            const uint32_t xb = sbase + OFF_X + wg * 8192 + (threadIdx.x & 127) * 16, xbar = bars + B_X + 16 * wg;
            const uint32_t rx = mapa(xb, rank ^ 1), rbar = mapa(xbar, rank ^ 1);
            wg_wait<0>();
            pin(a);
            M.release(M.prev);
            TS0(4, 5 + wg);
#pragma unroll
            for (int i = 0; i < 3; i++)
                st_async4(rx + i * 2048, rbar + 8 * (i >> 1), pack2(a[28 + 8 * i], a[29 + 8 * i]), pack2(a[30 + 8 * i], a[31 + 8 * i]), pack2(a[32 + 8 * i], a[33 + 8 * i]), pack2(a[34 + 8 * i], a[35 + 8 * i]));
            const uint32_t tail = 6144 - (threadIdx.x & 127) * 8;
            st_async2(rx + tail, rbar + 8, pack2(a[52], a[53]), pack2(a[54], a[55]));
            uint8_t* dst = G->U[nt1][((ft >= 7) + wg) * 7 + ft] + rank * HALF + w * 256 + lane * 4;
            uint32_t u[14];
#pragma unroll
            for (int i = 0; i < 28; i++) a[i] += bf_lo((i & 2) ? bias1 : bias0);
#pragma unroll
            for (int i = 0; i < 14; i++) {
                if (i % 8 == 0) {
                    if (i) TS0(4, 134 + wg);
                    mbar_wait(xbar + i, 0);
                    TS0(4, (i ? 136 : 1) + wg);
#pragma unroll
                    for (int k = i / 4; k < i / 4 + 2; k++) {
                        if (k < 3) { const uint4 v = lds4(xb + k * 2048); u[4 * k] = v.x; u[4 * k + 1] = v.y; u[4 * k + 2] = v.z; u[4 * k + 3] = v.w; }
                        else { const uint2 v = lds2(xb + tail); u[12] = v.x; u[13] = v.y; }
                    }
                    if (i && lane < 2) mbar_arrive_remote(M.rel + B_EMPTY + 48);
                }
                if (i == HINT && threadIdx.x == 0) hint(G->flag[8 + nt1 * 2] + ft + (ft >= 7) * 25);
                stg1(dst + (i >> 1) * 1024 + (i & 1) * 128, tag(pack2(gelu2(a[2 * i] + bf_lo(u[i])), gelu2(a[2 * i + 1] + bf_hi(u[i]))), (lane & 7) == w * 2 + (i & 1), ep));
            }
            TS0(4, 30 + wg);
        } else {
            mbar_wait(bars + B_FREE, 0);
            if (lane < 2) mbar_arrive_remote(M.rel + B_EMPTY + 48);
        }
        uint32_t c0 = ld_u16(b2 + mt * 128 + warp * 16 + r), c1 = ld_u16(b2 + mt * 128 + warp * 16 + r + 8);
        if (LOCREL == 1) M.rel = bars;
        M.run_o(a);
        if (wg == 1) TS0(4, 13);
        c0 *= ks == 0 ? 0x10001u : 0u; c1 *= ks == 0 ? 0x10001u : 0u;
        M.run<false>(a, 14, 0, 14 - NSLOT, LAG2, 1, 52);
        mbar_wait(bars + B_ROW, 1);
        const uint32_t stg = sbase + ((has_g1 ? STG1 : STG0) + (w >> 1) * STGS) * SLOT + wg * 8192 + (w & 1) * SLAB;
        const uint32_t sa = stg + (lane & 15) * 224 + (lane >> 4) * 16;
        wg_wait<0>();
        pin(a);
        TS0(8, 14 + wg);
#pragma unroll
        for (int i = 0; i < 7; i++)
            stsm4(sa + i * 32, half_plus(pack2(a[8 * i], a[8 * i + 1]), c0), half_plus(pack2(a[8 * i + 2], a[8 * i + 3]), c1),
                  half_plus(pack2(a[8 * i + 4], a[8 * i + 5]), c0), half_plus(pack2(a[8 * i + 6], a[8 * i + 7]), c1));
        fence_async_shared();
        __syncwarp();
        if (elect()) {
            asm volatile("cp.reduce.async.bulk.tensor.2d.global.shared::cta.add.tile.bulk_group [%0, {%2, %3}], [%1];\ncp.async.bulk.commit_group;" ::"l"(&P.tmOut), "r"(stg), "r"(nt2 * 112), "r"(mt * 128 + warp * 16) : "memory");
            if (w == 0) mbar_arrive(bars + B_END);
            asm volatile("cp.async.bulk.wait_group.read 0;" ::: "memory");
        }
        if (wg == !SWAP2) TS0(15, 19);
        TSDUMP();
    }
}

typedef CUresult (*EncodeFn)(CUtensorMap*, CUtensorMapDataType, cuuint32_t, void*, const cuuint64_t*, const cuuint64_t*, const cuuint32_t*, const cuuint32_t*,
                             CUtensorMapInterleave, CUtensorMapSwizzle, CUtensorMapL2promotion, CUtensorMapFloatOOBfill);

void make_map(EncodeFn enc, CUtensorMap* tm, const void* base, bool swizzle, int d0, int d1, int d2, int s1, int s2, int b0, int b1, int b2) {
    const cuuint64_t dims[3] = {(cuuint64_t)d0, (cuuint64_t)d1, (cuuint64_t)d2}, strides[2] = {(cuuint64_t)s1 * 2, (cuuint64_t)s2 * 2};
    const cuuint32_t box[3] = {(cuuint32_t)b0, (cuuint32_t)b1, (cuuint32_t)b2}, es[3] = {1, 1, 1};
    enc(tm, CU_TENSOR_MAP_DATA_TYPE_BFLOAT16, d2 ? 3 : 2, (void*)base, dims, strides, box, es, CU_TENSOR_MAP_INTERLEAVE_NONE,
        swizzle ? CU_TENSOR_MAP_SWIZZLE_128B : CU_TENSOR_MAP_SWIZZLE_NONE, CU_TENSOR_MAP_L2_PROMOTION_L2_128B, CU_TENSOR_MAP_FLOAT_OOB_FILL_NONE);
}

}

extern "C" void kernel_launch(void* const* d_in, const int* in_sizes, int n_in, void* d_out, int out_size) {
    static EncodeFn enc = nullptr;
    static Scratch* scratch = nullptr;
    if (!enc) {
        void* fn = nullptr;
        cudaDriverEntryPointQueryResult qr;
        cudaGetDriverEntryPoint("cuTensorMapEncodeTiled", &fn, cudaEnableDefault, &qr);
        enc = (EncodeFn)fn;
        cudaGetSymbolAddress((void**)&scratch, g_s);
        cudaFuncSetAttribute(fused_kernel, cudaFuncAttributeMaxDynamicSharedMemorySize, SMEM_BYTES);
    }
    Params P;
    const __nv_bfloat16* x = (const __nv_bfloat16*)d_in[0];
    make_map(enc, &P.tmX, x, true, D_, S_ / 2, 2, 2 * D_, D_, 64, 64, 2);
    make_map(enc, &P.tmWqkv, d_in[1], true, D_, D_, 3, 3 * D_, D_, 64, 32, 3);
    make_map(enc, &P.tmW1, d_in[4], true, 64, S_, F_ / 64, F_, 64, 64, 64, 2);
    make_map(enc, &P.tmW2, d_in[6], true, 64, F_, S_ / 64, S_, 64, 64, 64, 2);
    make_map(enc, &P.tmOut, d_out, false, D_, S_, 0, D_, 0, 112, 16, 1);
    fused_kernel<<<NCTA, NTHREADS, SMEM_BYTES, cudaStreamPerThread>>>(x, (const __nv_bfloat16*)d_in[5], (const __nv_bfloat16*)d_in[7], (const __nv_bfloat16*)d_in[2], (__nv_bfloat16*)d_out, scratch,
                                                                      (const __nv_bfloat16*)d_in[4], (const __nv_bfloat16*)d_in[6], P);
}
```

```cpp
#include <cuda_runtime.h>
#include <cuda_bf16.h>
#include <cuda.h>
#include <stdint.h>

#define HALO_NS 300
#define HINT 4
#define HOLD 1
#define LATEREL 1
#define PF 400
#define PF0 2
#define PF1 8
#define ENDBAR 1
#define PG0 3
#define PG1 5
#define STG1 4
#define STG0 4
#define STGS 1
#define LEADW 4
#define LEADN 7
#define TSQ 0
#define PACE 600
#define PAUSE 8
#define LAG1 4
#define LAG2 6

namespace {

constexpr int S_ = 2048, D_ = 448, F_ = 1792;
constexpr int NCTA = 128, NTHREADS = 384;
constexpr int NSLOT = 6, SLOT = 32768, WSLOT = 24576, TILEB = 14336, SLAB = 3584, HALF = 7168;
constexpr int KV = 1792, HSTG = SLAB + 32;
constexpr int OFF_X = NSLOT * SLOT;
constexpr int OFF_Y = OFF_X + 10 * KV;
constexpr int OFF_ST = OFF_Y + TILEB;
constexpr int OFF_BAR = OFF_ST + 1024;
constexpr int SMEM_BYTES = OFF_BAR + 1280;
constexpr uint32_t SMEM0 = 1024;
constexpr int B_QFULL = 0, B_FULL = 56, B_HALO = 128, B_X = 136, B_CS = 168, B_FREE = 192, B_END = 200, B_QEMPTY = 216, B_EMPTY = 232, B_ROW = 288, NBAR = 37;
constexpr float LN_EPS = 1e-5f, QK_SCALE = 0.1889822365046136f * 1.4426950408889634f;
constexpr int SPIN_LIMIT = 1 << 22;

struct Scratch {
    uint8_t H[4][32][TILEB];
    uint8_t U[4][28][TILEB];
    uint8_t O[16][8][TILEB];
    uint8_t Wo[4][8][TILEB];
    uint8_t halo[NCTA][2 * KV];
    uint2 stat[S_];
    uint2 colsum[8][8][96];
    uint32_t flag[32][32];
    uint32_t epoch[NCTA];
};
__device__ __align__(1024) Scratch g_s;

#define TS(g, i)
#define TS0(g, i)
#define TSDUMP()

struct Params {
    CUtensorMap tmX, tmWqkv, tmW1, tmW2, tmOut;
};

__device__ __forceinline__ bool elect() {
    uint32_t p;
    asm volatile("{\n.reg .pred p;\nelect.sync _|p, 0xffffffff;\nselp.u32 %0, 1, 0, p;\n}" : "=r"(p));
    return p;
}
__device__ __forceinline__ void mbar_init(uint32_t b, uint32_t c) { asm volatile("mbarrier.init.shared::cta.b64 [%0], %1;" ::"r"(b), "r"(c) : "memory"); }
__device__ __forceinline__ void mbar_expect(uint32_t b, uint32_t tx) { asm volatile("mbarrier.arrive.expect_tx.shared::cta.b64 _, [%0], %1;" ::"r"(b), "r"(tx) : "memory"); }
__device__ __forceinline__ void mbar_arrive(uint32_t b) { asm volatile("mbarrier.arrive.shared::cta.b64 _, [%0];" ::"r"(b) : "memory"); }
__device__ __forceinline__ void mbar_arrive16(uint32_t b) { asm volatile("mbarrier.arrive.shared::cta.b64 _, [%0], 16;" ::"r"(b) : "memory"); }
__device__ __forceinline__ void mbar_arrive4_remote(uint32_t b) { asm volatile("mbarrier.arrive.shared::cluster.b64 _, [%0], 4;" ::"r"(b) : "memory"); }
__device__ __forceinline__ void mbar_arrive_remote(uint32_t b) { asm volatile("mbarrier.arrive.shared::cluster.b64 _, [%0];" ::"r"(b) : "memory"); }
#define MBAR_WAIT_ASM(SEM) \
    asm volatile("{\n.reg .pred p;\nWAIT:\nmbarrier.try_wait.parity" SEM ".shared::cta.b64 p, [%0], %1;\n@!p bra WAIT;\n}" ::"r"(b), "r"(parity) : "memory")
__device__ __forceinline__ void mbar_wait(uint32_t b, uint32_t parity) { MBAR_WAIT_ASM(""); }
__device__ __forceinline__ void mbar_wait_bounded(uint32_t b, uint32_t parity, uint32_t& n) {
    asm volatile("{\n.reg .pred p;\nWAIT:\nadd.u32 %0, %0, 1;\nsetp.gt.u32 p, %0, %3;\n@p st.global.u32 [%4], %0;\n"
                 "mbarrier.try_wait.parity.shared::cta.b64 p, [%1], %2;\n@!p bra WAIT;\n}" : "+r"(n) : "r"(b), "r"(parity), "n"(SPIN_LIMIT), "l"(0ull) : "memory");
}
__device__ __forceinline__ uint32_t mapa(uint32_t a, uint32_t rank) { uint32_t r; asm("mapa.shared::cluster.u32 %0, %1, %2;" : "=r"(r) : "r"(a), "r"(rank)); return r; }
__device__ __forceinline__ void tma3d(uint32_t dst, const CUtensorMap* tm, uint32_t bar, int c0, int c1, int c2) {
    asm volatile("cp.async.bulk.tensor.3d.shared::cluster.global.mbarrier::complete_tx::bytes [%0], [%1, {%3, %4, %5}], [%2];" ::"r"(dst), "l"(tm), "r"(bar), "r"(c0), "r"(c1), "r"(c2) : "memory");
}
__device__ __forceinline__ void tma3d_pair(uint32_t dst, const CUtensorMap* tm, uint32_t bar, int c0, int c1, int c2) {
    asm volatile("cp.async.bulk.tensor.3d.shared::cluster.global.mbarrier::complete_tx::bytes.multicast::cluster [%0], [%1, {%3, %4, %5}], [%2], %6;" ::"r"(dst), "l"(tm), "r"(bar), "r"(c0), "r"(c1), "r"(c2), "h"((uint16_t)3) : "memory");
}
__device__ __forceinline__ void bulk_load(uint32_t dst, const void* src, uint32_t bytes, uint32_t bar) {
    asm volatile("cp.async.bulk.shared::cluster.global.mbarrier::complete_tx::bytes [%0], [%1], %2, [%3];" ::"r"(dst), "l"(src), "r"(bytes), "r"(bar) : "memory");
}
__device__ __forceinline__ void bulk_store(void* dst, uint32_t src, uint32_t bytes) {
    asm volatile("cp.async.bulk.global.shared::cta.bulk_group [%0], [%1], %2;" ::"l"(dst), "r"(src), "r"(bytes) : "memory");
}
__device__ __forceinline__ uint32_t ld_u16(const void* p) { uint32_t v; asm volatile("ld.global.nc.u16 %0, [%1];" : "=r"(v) : "l"(p)); return v; }
__device__ __forceinline__ uint32_t ld_relaxed(const uint32_t* p) { uint32_t v; asm volatile("ld.relaxed.gpu.global.u32 %0, [%1];" : "=r"(v) : "l"(p) : "memory"); return v; }
__device__ __forceinline__ void bulk_flush() { asm volatile("cp.async.bulk.commit_group;\ncp.async.bulk.wait_group 0;" ::: "memory"); }
__device__ __forceinline__ void signal(uint32_t* flag) { asm volatile("fence.acq_rel.gpu;\nred.relaxed.gpu.global.add.u32 [%0], 1;" ::"l"(flag) : "memory"); }
__device__ __forceinline__ void hint(uint32_t* flag) { asm volatile("red.relaxed.gpu.global.add.u32 [%0], 1;" ::"l"(flag) : "memory"); }
__device__ __forceinline__ uint32_t tag(uint32_t v, uint32_t mask, uint32_t parity) { return (v & ~mask) | (parity & mask); }
__device__ __forceinline__ uint32_t or_diff(uint32_t acc, uint32_t v, uint32_t parity) { asm("lop3.b32 %0, %0, %1, %2, 0xf6;" : "+r"(acc) : "r"(v), "r"(parity)); return acc; }
__device__ __forceinline__ uint4 ld_relaxed4(const void* p) {
    uint4 v;
    asm volatile("ld.relaxed.gpu.global.v4.u32 {%0, %1, %2, %3}, [%4];" : "=r"(v.x), "=r"(v.y), "=r"(v.z), "=r"(v.w) : "l"(p) : "memory");
    return v;
}
__device__ __forceinline__ uint2 ld_relaxed2(const void* p) { uint2 v; asm volatile("ld.relaxed.gpu.global.v2.u32 {%0, %1}, [%2];" : "=r"(v.x), "=r"(v.y) : "l"(p) : "memory"); return v; }
__device__ __forceinline__ void sts4(uint32_t a, uint4 v) { asm volatile("st.shared.v4.b32 [%0], {%1, %2, %3, %4};" ::"r"(a), "r"(v.x), "r"(v.y), "r"(v.z), "r"(v.w) : "memory"); }
__device__ __forceinline__ void sts1(uint32_t a, uint32_t v) { asm volatile("st.shared.b32 [%0], %1;" ::"r"(a), "r"(v) : "memory"); }
__device__ __forceinline__ void sts2(uint32_t a, uint32_t v0, uint32_t v1) { asm volatile("st.shared.v2.b32 [%0], {%1, %2};" ::"r"(a), "r"(v0), "r"(v1) : "memory"); }
__device__ __forceinline__ void stg1(void* p, uint32_t v) { asm volatile("st.global.b32 [%0], %1;" ::"l"(p), "r"(v) : "memory"); }
__device__ __forceinline__ void fence_async_shared() { asm volatile("fence.proxy.async.shared::cta;" ::: "memory"); }
#define BOUND "add.u32 %0, %0, 16;\nsetp.gt.u32 p, %0, %1;\n@p st.global.u32 [%2], %0;\n"
__device__ __forceinline__ void wait_flag(const uint32_t* p, uint32_t target, uint32_t& n) {
    asm volatile("{\n.reg .pred p;\n.reg .u32 v;\nPOLL:\n" BOUND "ld.acquire.gpu.global.u32 v, [%3];\nsetp.ne.u32 p, v, %4;\n@p bra POLL;\nfence.proxy.async.global;\n}"
                 : "+r"(n) : "n"(SPIN_LIMIT), "l"(0ull), "l"(p), "r"(target) : "memory");
}
__device__ __forceinline__ void wait_flag2(const uint32_t* h, uint32_t th, const uint32_t* p, uint32_t target, uint32_t& n) {
    asm volatile("{\n.reg .pred p;\n.reg .u32 u, v;\nPOLL:\n" BOUND "ld.relaxed.gpu.global.u32 u, [%3];\nld.acquire.gpu.global.u32 v, [%5];\nsetp.ne.u32 p, u, %4;\nsetp.ne.or.u32 p, v, %6, p;\n@p bra POLL;\nfence.proxy.async.global;\n}"
                 : "+r"(n) : "n"(SPIN_LIMIT), "l"(0ull), "l"(h), "r"(th), "l"(p), "r"(target) : "memory");
}
__device__ __forceinline__ void bar_sync(int id, int n) { asm volatile("bar.sync %0, %1;" ::"r"(id), "r"(n) : "memory"); }
__device__ __forceinline__ void bar_arrive(int id, int n) { asm volatile("bar.arrive %0, %1;" ::"r"(id), "r"(n) : "memory"); }
__device__ __forceinline__ void wg_fence() { asm volatile("wgmma.fence.sync.aligned;" ::: "memory"); }
__device__ __forceinline__ void wg_commit() { asm volatile("wgmma.commit_group.sync.aligned;" ::: "memory"); }
template <int N> __device__ __forceinline__ void wg_wait() { asm volatile("wgmma.wait_group.sync.aligned %0;" ::"n"(N) : "memory"); }
template <int N> __device__ __forceinline__ void pin(float (&d)[N]) {
#pragma unroll
    for (int i = 0; i < N; i++) asm volatile("" : "+f"(d[i])::"memory");
}
__host__ __device__ constexpr uint32_t desc_hi(uint32_t sbo, uint32_t swz) { return (sbo >> 4) | (swz << 30); }
__host__ __device__ constexpr uint32_t desc_lo(uint32_t off, uint32_t lbo) { return ((SMEM0 + off) >> 4) | ((lbo >> 4) << 16); }
__device__ __forceinline__ uint32_t pack2(float lo, float hi) { uint32_t r; asm("cvt.rn.bf16x2.f32 %0, %1, %2;" : "=r"(r) : "f"(hi), "f"(lo)); return r; }
__device__ __forceinline__ float bf_lo(uint32_t v) { return __uint_as_float(v << 16); }
__device__ __forceinline__ float bf_hi(uint32_t v) { return __uint_as_float(v & 0xffff0000u); }
__device__ __forceinline__ uint32_t half_plus(uint32_t a, uint32_t b) { uint32_t r; asm("fma.rn.bf16x2 %0, %1, %2, %3;" : "=r"(r) : "r"(a), "r"(0x3f003f00u), "r"(b)); return r; }
__device__ __forceinline__ void stsm4(uint32_t a, uint32_t r0, uint32_t r1, uint32_t r2, uint32_t r3) {
    asm volatile("stmatrix.sync.aligned.m8n8.x4.shared.b16 [%0], {%1, %2, %3, %4};" ::"r"(a), "r"(r0), "r"(r1), "r"(r2), "r"(r3) : "memory");
}
__device__ __forceinline__ void stsm2(uint32_t a, uint32_t r0, uint32_t r1) {
    asm volatile("stmatrix.sync.aligned.m8n8.x2.shared.b16 [%0], {%1, %2};" ::"r"(a), "r"(r0), "r"(r1) : "memory");
}
__device__ __forceinline__ uint4 lds4(uint32_t a) { uint4 v; asm volatile("ld.shared.v4.b32 {%0, %1, %2, %3}, [%4];" : "=r"(v.x), "=r"(v.y), "=r"(v.z), "=r"(v.w) : "r"(a) : "memory"); return v; }
__device__ __forceinline__ uint2 lds2(uint32_t a) { uint2 v; asm volatile("ld.shared.v2.b32 {%0, %1}, [%2];" : "=r"(v.x), "=r"(v.y) : "r"(a) : "memory"); return v; }
__device__ __forceinline__ float lds1f(uint32_t a) { float v; asm volatile("ld.shared.f32 %0, [%1];" : "=f"(v) : "r"(a) : "memory"); return v; }
__device__ __forceinline__ void ldsm4(uint32_t* r, uint32_t a) {
    asm volatile("ldmatrix.sync.aligned.m8n8.x4.shared.b16 {%0, %1, %2, %3}, [%4];" : "=r"(r[0]), "=r"(r[1]), "=r"(r[2]), "=r"(r[3]) : "r"(a) : "memory");
}
__device__ __forceinline__ void ldsm4t(uint32_t* r, uint32_t a) {
    asm volatile("ldmatrix.sync.aligned.m8n8.x4.trans.shared.b16 {%0, %1, %2, %3}, [%4];" : "=r"(r[0]), "=r"(r[1]), "=r"(r[2]), "=r"(r[3]) : "r"(a) : "memory");
}
__device__ __forceinline__ void ldsm2t(uint32_t* r, uint32_t a) {
    asm volatile("ldmatrix.sync.aligned.m8n8.x2.trans.shared.b16 {%0, %1}, [%2];" : "=r"(r[0]), "=r"(r[1]) : "r"(a) : "memory");
}
__device__ __forceinline__ uint32_t transpose8(uint32_t v) { uint32_t r; asm volatile("movmatrix.sync.aligned.m8n8.trans.b16 %0, %1;" : "=r"(r) : "r"(v)); return r; }
__device__ __forceinline__ void mma16(float (&c)[4], uint32_t a0, uint32_t a1, uint32_t a2, uint32_t a3, uint32_t b0, uint32_t b1) {
    asm volatile("mma.sync.aligned.m16n8k16.row.col.f32.bf16.bf16.f32 {%0, %1, %2, %3}, {%4, %5, %6, %7}, {%8, %9}, {%0, %1, %2, %3};"
                 : "+f"(c[0]), "+f"(c[1]), "+f"(c[2]), "+f"(c[3]) : "r"(a0), "r"(a1), "r"(a2), "r"(a3), "r"(b0), "r"(b1));
}
__device__ __forceinline__ void mma8(float (&c)[4], uint32_t a0, uint32_t a1, uint32_t b0) {
    asm volatile("mma.sync.aligned.m16n8k8.row.col.f32.bf16.bf16.f32 {%0, %1, %2, %3}, {%4, %5}, {%6}, {%0, %1, %2, %3};"
                 : "+f"(c[0]), "+f"(c[1]), "+f"(c[2]), "+f"(c[3]) : "r"(a0), "r"(a1), "r"(b0));
}
__device__ __forceinline__ void st_async4(uint32_t a, uint32_t bar, uint32_t v0, uint32_t v1, uint32_t v2, uint32_t v3) {
    asm volatile("st.async.weak.shared::cluster.mbarrier::complete_tx::bytes.v4.b32 [%0], {%2, %3, %4, %5}, [%1];" ::"r"(a), "r"(bar), "r"(v0), "r"(v1), "r"(v2), "r"(v3) : "memory");
}
__device__ __forceinline__ void st_async2(uint32_t a, uint32_t bar, uint32_t v0, uint32_t v1) {
    asm volatile("st.async.weak.shared::cluster.mbarrier::complete_tx::bytes.v2.b32 [%0], {%2, %3}, [%1];" ::"r"(a), "r"(bar), "r"(v0), "r"(v1) : "memory");
}
__device__ __forceinline__ float quad_max(float v) { v = fmaxf(v, __shfl_xor_sync(~0u, v, 1)); return fmaxf(v, __shfl_xor_sync(~0u, v, 2)); }
__device__ __forceinline__ float quad_sum(float v) { v += __shfl_xor_sync(~0u, v, 1); return v + __shfl_xor_sync(~0u, v, 2); }
__device__ __forceinline__ float ex2(float v) { float r; asm("ex2.approx.ftz.f32 %0, %1;" : "=f"(r) : "f"(v)); return r; }
__device__ __forceinline__ float rcp(float v) { float r; asm("rcp.approx.ftz.f32 %0, %1;" : "=f"(r) : "f"(v)); return r; }
__device__ __forceinline__ float rsq(float v) { float r; asm("rsqrt.approx.ftz.f32 %0, %1;" : "=f"(r) : "f"(v)); return r; }
__device__ __forceinline__ float gelu2(float u) {
    float z = u * fmaf(u * u, 0.044715f * 0.7978845608028654f, 0.7978845608028654f), t;
    asm("tanh.approx.f32 %0, %1;" : "=f"(t) : "f"(z));
    return fmaf(u, t, u);
}
__device__ __forceinline__ float row_sum(float v) {
    v = quad_sum(v); v += __shfl_xor_sync(~0u, v, 4);
    return v + __shfl_xor_sync(~0u, v, 24);
}

template <int TA, int TB, uint32_t HA, uint32_t HB>
__device__ __forceinline__ void wgmma_n112(float (&d)[56], uint32_t da, uint32_t db, int accumulate) {
    asm volatile("{\n.reg .pred p;\n.reg .b64 a, b;\nmov.b64 a, {%56, %61};\nmov.b64 b, {%57, %62};\nsetp.ne.b32 p, %58, 0;\n"
        "wgmma.mma_async.sync.aligned.m64n112k16.f32.bf16.bf16 {"
        "%0, %1, %2, %3, %4, %5, %6, %7, %8, %9, %10, %11, %12, %13, %14, %15, "
        "%16, %17, %18, %19, %20, %21, %22, %23, %24, %25, %26, %27, %28, %29, %30, %31, "
        "%32, %33, %34, %35, %36, %37, %38, %39, %40, %41, %42, %43, %44, %45, %46, %47, "
        "%48, %49, %50, %51, %52, %53, %54, %55"
        "}, a, b, p, 1, 1, %59, %60;\n}\n"
        : "+f"(d[0]), "+f"(d[1]), "+f"(d[2]), "+f"(d[3]), "+f"(d[4]), "+f"(d[5]), "+f"(d[6]), "+f"(d[7]),
          "+f"(d[8]), "+f"(d[9]), "+f"(d[10]), "+f"(d[11]), "+f"(d[12]), "+f"(d[13]), "+f"(d[14]), "+f"(d[15]),
          "+f"(d[16]), "+f"(d[17]), "+f"(d[18]), "+f"(d[19]), "+f"(d[20]), "+f"(d[21]), "+f"(d[22]), "+f"(d[23]),
          "+f"(d[24]), "+f"(d[25]), "+f"(d[26]), "+f"(d[27]), "+f"(d[28]), "+f"(d[29]), "+f"(d[30]), "+f"(d[31]),
          "+f"(d[32]), "+f"(d[33]), "+f"(d[34]), "+f"(d[35]), "+f"(d[36]), "+f"(d[37]), "+f"(d[38]), "+f"(d[39]),
          "+f"(d[40]), "+f"(d[41]), "+f"(d[42]), "+f"(d[43]), "+f"(d[44]), "+f"(d[45]), "+f"(d[46]), "+f"(d[47]),
          "+f"(d[48]), "+f"(d[49]), "+f"(d[50]), "+f"(d[51]), "+f"(d[52]), "+f"(d[53]), "+f"(d[54]), "+f"(d[55])
        : "r"(da), "r"(db), "r"(accumulate), "n"(TA), "n"(TB), "n"(HA), "n"(HB));
}

template <int TA, int TB, uint32_t HA, uint32_t HB>
__device__ __forceinline__ void wgmma_n168(float (&d)[84], uint32_t da, uint32_t db, int accumulate) {
    asm volatile("{\n.reg .pred p;\n.reg .b64 a, b;\nmov.b64 a, {%84, %89};\nmov.b64 b, {%85, %90};\nsetp.ne.b32 p, %86, 0;\n"
        "wgmma.mma_async.sync.aligned.m64n168k16.f32.bf16.bf16 {"
        "%0, %1, %2, %3, %4, %5, %6, %7, %8, %9, %10, %11, %12, %13, %14, %15, "
        "%16, %17, %18, %19, %20, %21, %22, %23, %24, %25, %26, %27, %28, %29, %30, %31, "
        "%32, %33, %34, %35, %36, %37, %38, %39, %40, %41, %42, %43, %44, %45, %46, %47, "
        "%48, %49, %50, %51, %52, %53, %54, %55, %56, %57, %58, %59, %60, %61, %62, %63, "
        "%64, %65, %66, %67, %68, %69, %70, %71, %72, %73, %74, %75, %76, %77, %78, %79, "
        "%80, %81, %82, %83"
        "}, a, b, p, 1, 1, %87, %88;\n}\n"
        : "+f"(d[0]), "+f"(d[1]), "+f"(d[2]), "+f"(d[3]), "+f"(d[4]), "+f"(d[5]), "+f"(d[6]), "+f"(d[7]),
          "+f"(d[8]), "+f"(d[9]), "+f"(d[10]), "+f"(d[11]), "+f"(d[12]), "+f"(d[13]), "+f"(d[14]), "+f"(d[15]),
          "+f"(d[16]), "+f"(d[17]), "+f"(d[18]), "+f"(d[19]), "+f"(d[20]), "+f"(d[21]), "+f"(d[22]), "+f"(d[23]),
          "+f"(d[24]), "+f"(d[25]), "+f"(d[26]), "+f"(d[27]), "+f"(d[28]), "+f"(d[29]), "+f"(d[30]), "+f"(d[31]),
          "+f"(d[32]), "+f"(d[33]), "+f"(d[34]), "+f"(d[35]), "+f"(d[36]), "+f"(d[37]), "+f"(d[38]), "+f"(d[39]),
          "+f"(d[40]), "+f"(d[41]), "+f"(d[42]), "+f"(d[43]), "+f"(d[44]), "+f"(d[45]), "+f"(d[46]), "+f"(d[47]),
          "+f"(d[48]), "+f"(d[49]), "+f"(d[50]), "+f"(d[51]), "+f"(d[52]), "+f"(d[53]), "+f"(d[54]), "+f"(d[55]),
          "+f"(d[56]), "+f"(d[57]), "+f"(d[58]), "+f"(d[59]), "+f"(d[60]), "+f"(d[61]), "+f"(d[62]), "+f"(d[63]),
          "+f"(d[64]), "+f"(d[65]), "+f"(d[66]), "+f"(d[67]), "+f"(d[68]), "+f"(d[69]), "+f"(d[70]), "+f"(d[71]),
          "+f"(d[72]), "+f"(d[73]), "+f"(d[74]), "+f"(d[75]), "+f"(d[76]), "+f"(d[77]), "+f"(d[78]), "+f"(d[79]),
          "+f"(d[80]), "+f"(d[81]), "+f"(d[82]), "+f"(d[83])
        : "r"(da), "r"(db), "r"(accumulate), "n"(TA), "n"(TB), "n"(HA), "n"(HB));
}

template <uint32_t HB>
__device__ __forceinline__ void wgmma_rs_n168(float (&d)[84], uint32_t a0, uint32_t a1, uint32_t db) {
    asm volatile("{\n.reg .b64 b;\nmov.b64 b, {%86, %88};\n"
        "wgmma.mma_async.sync.aligned.m64n168k16.f32.bf16.bf16 {"
        "%0, %1, %2, %3, %4, %5, %6, %7, %8, %9, %10, %11, %12, %13, %14, %15, "
        "%16, %17, %18, %19, %20, %21, %22, %23, %24, %25, %26, %27, %28, %29, %30, %31, "
        "%32, %33, %34, %35, %36, %37, %38, %39, %40, %41, %42, %43, %44, %45, %46, %47, "
        "%48, %49, %50, %51, %52, %53, %54, %55, %56, %57, %58, %59, %60, %61, %62, %63, "
        "%64, %65, %66, %67, %68, %69, %70, %71, %72, %73, %74, %75, %76, %77, %78, %79, "
        "%80, %81, %82, %83"
        "}, {%84, %85, %87, %87}, b, 1, 1, 1, 0;\n}\n"
        : "+f"(d[0]), "+f"(d[1]), "+f"(d[2]), "+f"(d[3]), "+f"(d[4]), "+f"(d[5]), "+f"(d[6]), "+f"(d[7]),
          "+f"(d[8]), "+f"(d[9]), "+f"(d[10]), "+f"(d[11]), "+f"(d[12]), "+f"(d[13]), "+f"(d[14]), "+f"(d[15]),
          "+f"(d[16]), "+f"(d[17]), "+f"(d[18]), "+f"(d[19]), "+f"(d[20]), "+f"(d[21]), "+f"(d[22]), "+f"(d[23]),
          "+f"(d[24]), "+f"(d[25]), "+f"(d[26]), "+f"(d[27]), "+f"(d[28]), "+f"(d[29]), "+f"(d[30]), "+f"(d[31]),
          "+f"(d[32]), "+f"(d[33]), "+f"(d[34]), "+f"(d[35]), "+f"(d[36]), "+f"(d[37]), "+f"(d[38]), "+f"(d[39]),
          "+f"(d[40]), "+f"(d[41]), "+f"(d[42]), "+f"(d[43]), "+f"(d[44]), "+f"(d[45]), "+f"(d[46]), "+f"(d[47]),
          "+f"(d[48]), "+f"(d[49]), "+f"(d[50]), "+f"(d[51]), "+f"(d[52]), "+f"(d[53]), "+f"(d[54]), "+f"(d[55]),
          "+f"(d[56]), "+f"(d[57]), "+f"(d[58]), "+f"(d[59]), "+f"(d[60]), "+f"(d[61]), "+f"(d[62]), "+f"(d[63]),
          "+f"(d[64]), "+f"(d[65]), "+f"(d[66]), "+f"(d[67]), "+f"(d[68]), "+f"(d[69]), "+f"(d[70]), "+f"(d[71]),
          "+f"(d[72]), "+f"(d[73]), "+f"(d[74]), "+f"(d[75]), "+f"(d[76]), "+f"(d[77]), "+f"(d[78]), "+f"(d[79]),
          "+f"(d[80]), "+f"(d[81]), "+f"(d[82]), "+f"(d[83])
        : "r"(a0), "r"(a1), "r"(db), "r"(0), "n"(HB));
}

struct Ring {
    uint32_t slot, ph;
    __device__ __forceinline__ void next() { if (++slot == NSLOT) { slot = 0; ph ^= 1; } }
    __device__ __forceinline__ void next2() { ph ^= slot == 5; slot = __byte_perm(0x06030201u, 0x00040005u, 0x7770 + slot); }
};
struct Slot {
    uint32_t dst, bar, ph;
    __device__ __forceinline__ void next(uint32_t bars) {
        dst += SLOT; bar += 8;
        if (bar == bars + 8 * NSLOT) { dst -= NSLOT * SLOT; bar = bars; ph ^= 1; }
    }
};
__device__ __forceinline__ uint32_t xslot(int i) { return __byte_perm(0x04130e0cu, 0x00130e0cu, 0x7770 + i); }
__device__ __forceinline__ uint32_t wslot(int i) { return __byte_perm(0x06001510u, 0x00151009u, 0x7770 + i); }

constexpr uint32_t HI_SW = desc_hi(1024, 1);

struct Mma {
    uint32_t bars, rel;
    bool lead;
    int wg, w;
    Ring r;
    uint32_t prev;
    __device__ __forceinline__ void release(uint32_t s) { if (lead) mbar_arrive4_remote(rel + B_EMPTY + 8 * s); }
    template <bool G1>
    __device__ __forceinline__ void run(float (&a)[56], int n, int first, int last, int lag, int accumulate, int ts) {
#pragma unroll 1
        for (int i = 0; i < n; i++) {
            if (lag && i == (wg ? n - lag : -1)) bar_sync(7, 256);
            const uint32_t s = r.slot;
            mbar_wait(bars + B_FULL + 8 * s, r.ph);
            if (G1) r.next(); else r.next2();
            if (!TSQ || !i) TS0(G1 ? 2 : 8, ts + i + wg * 68);
            const uint32_t dB = s * (SLOT >> 4), dA = dB + wg * 512;
            wg_fence();
#pragma unroll
            for (int k = 0; k < 4; k++) {
                wgmma_n112<1, 1, HI_SW, desc_hi(G1 ? 256 : 1024, 0)>(a, dA + desc_lo(k * 2048, 8192), dB + desc_lo(16384 + k * (G1 ? SLAB : 256), 128), k > 0 || accumulate || i > 0);
                if (k == 1) {
                    wg_commit(); wg_wait<1>();
                    if ((uint32_t)(i - first) < (uint32_t)(last - first)) release(prev);
                    if (lag && i == (wg ? -1 : n - 1)) bar_arrive(7, 256);
                    if (TSQ && i) TS0(G1 ? 2 : 8, ts + i + wg * 68);
                }
            }
            wg_commit();
            prev = s;
        }
    }
    __device__ __forceinline__ void run_o(float (&a)[56]) {
#pragma unroll 1
        for (int i = 0; i < 2; i++) {
            const uint32_t s = r.slot, dB = s * (SLOT >> 4), dA = dB + wg * 512;
            mbar_wait(bars + B_FULL + 8 * s, r.ph);
            TS0(8, 48 + 2 * i + wg * 68);
            wg_fence();
#pragma unroll
            for (int k = 0; k < 7; k++) {
                if (k == 3) { mbar_wait(bars + B_FULL + 8 * s + 8, r.ph); wg_fence(); }
                wgmma_n112<0, 1, desc_hi(128, 0), desc_hi(256, 0)>(a, dA + desc_lo(k * 2048 + (k > 3) * (SLOT - HALF), k == 3 ? SLOT - 6144 : 1024),
                                                                   dB + desc_lo(16384 + k * SLAB + (k > 2) * (SLOT - 3 * SLAB), 128), k > 0 || i > 0);
                if (k & 1) wg_commit();
                if (k == 1) { wg_wait<1>(); if (i) release(prev); }
                if (k == 5) { wg_wait<1>(); release(s); }
            }
            wg_commit();
            prev = s + 1;
            r.slot++; r.next2();
        }
    }
};

__global__ void __cluster_dims__(2, 1, 1) __launch_bounds__(NTHREADS, 1)
fused_kernel(const __nv_bfloat16* __restrict__ x, const __nv_bfloat16* __restrict__ b1, const __nv_bfloat16* __restrict__ b2, const __nv_bfloat16* __restrict__ wo, __nv_bfloat16* out, Scratch* G,
             const __nv_bfloat16* __restrict__ w1, const __nv_bfloat16* __restrict__ w2,
             const __grid_constant__ Params P) {
    extern __shared__ __align__(1024) uint8_t smem[];
    const uint32_t sbase = (uint32_t)__cvta_generic_to_shared(smem);
    const uint32_t bars = sbase + OFF_BAR;
    const uint32_t rank = blockIdx.x & 1, pr = blockIdx.x >> 1;
    const uint32_t row0 = blockIdx.x * 16;
    if (threadIdx.x == 0) {
        TS(15, 0);
        mbar_init(bars + B_ROW, 1);
        asm volatile("fence.mbarrier_init.release.cluster;" ::: "memory");
        bulk_load(sbase + OFF_Y, x + row0 * D_, TILEB, bars + B_ROW);
        mbar_expect(bars + B_ROW, TILEB);
        TS(1, 97);
    }
    const int lane = threadIdx.x & 31;
    const int warp = __shfl_sync(~0u, threadIdx.x >> 5, 0), w = warp & 3;
    if (elect()) {
        const uint32_t first = bars + warp * 24, count = warp < 7 ? 1 : warp < 9 ? 18 - 2 * warp : 16;
#pragma unroll
        for (int i = 0; i < 3; i++) mbar_init(first + 8 * i, count);
        asm volatile("fence.mbarrier_init.release.cluster;" ::: "memory");
    }
    __syncwarp();
    asm volatile("barrier.cluster.arrive.relaxed.aligned;" ::: "memory");
    const uint32_t pv = pr < 4 ? pr * 8 + 36 : pr - 4 + (max((int)pr - 33, 0) * 37 >> 8);
    const uint32_t gp = (pv + 4) & 7, hp = pv >> 3;
    const uint32_t tb = gp * 2 + rank, c = hp * 16 + tb;
    const bool has_g1 = gp > 0;
    const uint32_t nt1 = hp & 3, ft = max((int)gp - 1, 0) * 2 + (hp >> 2);
    const uint32_t nt2 = (hp & 1) * 2 + rank, mt = (gp & 3) * 4 + (hp >> 1), ks = gp >> 2;
    asm volatile("barrier.cluster.wait.aligned;" ::: "memory");

    if (warp == 8) {
        uint32_t kw = (gp & 1) * 192, kx;
        if (elect()) {
            mbar_expect(bars + B_QFULL, WSLOT);
            tma3d(sbase + xslot(0) * 8192, &P.tmX, bars + B_FULL, 0, tb * 64, 0);
            tma3d_pair(sbase + wslot(0) * 8192 + rank * 12288, &P.tmWqkv, bars + B_QFULL, (hp * 56) & ~15, rank * 32, 0);
            TS(1, 23);
            uint32_t due = (uint32_t)clock() + PACE, ep = ld_relaxed(&G->epoch[c]);
            uint32_t spins = sbase == (rank << 24 | SMEM0) ? 0 : SPIN_LIMIT;
#pragma unroll 1
            for (int i = 1; i < 8; i++) {
                kx = kw; kw += 64;
                if (i >= 5) mbar_wait_bounded(bars + B_QEMPTY + 8 * (i - 5), 0, spins);
                else { while ((int)((uint32_t)clock() - due) < 0) {} due += PACE; }
                if (kw == D_) kw = 64;
                if (i < 4) kx = kw;
                const int ix = i - (i > 4);
                if (i < 7) mbar_expect(bars + B_QFULL + 8 * i, WSLOT);
                if (i != 4) tma3d(sbase + xslot(ix) * 8192, &P.tmX, bars + B_FULL + 8 * ix, kx, tb * 64, 0);
                if (i & (i >> 2)) mbar_wait_bounded(bars + B_CS - 20 + 4 * i, 0, spins);
                if (i < 7) tma3d_pair(sbase + wslot(i) * 8192 + rank * 12288, &P.tmWqkv, bars + B_QFULL + 8 * i, (hp * 56) & ~15, kw + rank * 32, 0);
            }
            ep++;
            Slot r{sbase, bars, 0};
            if (has_g1) {
                const uint8_t* src = G->H[nt1][rank * 16];
                const int row = rank * 1024;
                mbar_expect(bars + B_FULL, 16384 + TILEB);
                tma3d(sbase, &P.tmW1, bars + B_FULL, 0, row, ft * 2);
                wait_flag(G->flag[1] + rank * 2, 20 * ep, spins);
                TS(1, 16);
#pragma unroll 1
                for (int j = 64;; j += 64) {
                    bulk_load(r.dst + 16384, src, TILEB, r.bar + B_FULL);
                    src += TILEB;
                    r.next(bars);
                    if (j == 1024) break;
                    mbar_wait_bounded(r.bar + B_EMPTY, r.ph, spins);
                    if (j < 14 * 64) TS(2, 146 + j / 64);
                    mbar_expect(r.bar + B_FULL, 16384 + TILEB);
                    tma3d(r.dst, &P.tmW1, r.bar + B_FULL, 0, row + j, ft * 2);
                }
                mbar_arrive(bars + B_FULL + 48); mbar_arrive16(bars + B_EMPTY + 48);
#pragma unroll
                for (int i = 0; i < 4; i++) mbar_expect(bars + B_X + 8 * i, (i & 1) ? 3072 : 4096);
            } else {
                due = (uint32_t)clock();
#pragma unroll 1
                for (int j = PF0; j < PF1; j++) {
                    asm volatile("cp.async.bulk.prefetch.L2.global [%0], %1;" ::"l"(w1 + (rank * 1024 + j * 64 + hp * 8) * F_), "n"(16 * F_) : "memory");
                    due += PF;
                    while ((int)((uint32_t)clock() - due) < 0) {}
                }
            }
            const uint8_t *so = G->O[mt][ks * 4], *sw = G->Wo[nt2][ks * 4];
            wait_flag2(G->flag[16 + mt], 8 * ep, G->flag[0], 16 * ep, spins);
            TS(4, 18);
#pragma unroll 1
            for (int j = 0; j < 4 * TILEB; j += TILEB) {
                mbar_wait_bounded(r.bar + B_EMPTY, r.ph, spins);
                mbar_expect(r.bar + B_QFULL, TILEB);
                bulk_load(r.dst, so + j, HALF, r.bar + B_QFULL);
                bulk_load(r.dst + 8192, so + j + HALF, HALF, r.bar + B_QFULL);
                bulk_load(r.dst + 16384, sw + j, (r.bar & 8) ? TILEB : 3 * SLAB, r.bar + B_FULL);
                r.next(bars);
            }
            if (!has_g1) {
#pragma unroll
                for (int j = PG0; j < PG1; j++)
                    asm volatile("cp.async.bulk.prefetch.L2.global [%0], %1;" ::"l"(w2 + (rank * 896 + j * 128 + hp * 8) * S_), "n"(16 * S_) : "memory");
            }
            Ring q{has_g1 ? 2u : 6u, has_g1}, p{q.slot, !has_g1};
#pragma unroll 1
            for (int j = 0; j < 14 * 128; j += 128) {
                mbar_wait_bounded(bars + B_EMPTY + 8 * q.slot, q.ph, spins);
                if (LEADW && j >= LEADW * 128 && j < LEADN * 128) { mbar_wait_bounded(bars + B_FULL + 8 * p.slot, p.ph, spins); p.next2(); }
                TS(8, 176 + j / 128);
                tma3d(sbase + q.slot * SLOT, &P.tmW2, bars + B_FULL + 8 * q.slot, 0, ks * 896 + j - (j < 896 ? 0 : 832), mt * 2);
                q.next2();
            }
            mbar_wait_bounded(bars + B_END, 0, spins);
        }
    } else if (warp > 8) {
        const uint32_t ep = ld_relaxed(&G->epoch[c]) + 1;
        const uint8_t* src = G->U[nt2][ks * 14];
        uint32_t spins = 0, bad;
        {
            uint2* cs = G->colsum[hp][0];
            if (w == 2) {
                bar_sync(6, 288);
                TS(1, 8);
                stg1((uint32_t*)(G->stat + row0) + lane, tag(__float_as_uint(lds1f(sbase + OFF_ST + lane * 4)), ~lane & 1, ep));
                if (elect()) {
                    fence_async_shared();
#pragma unroll
                    for (int i = 0; i < 4; i++) bulk_store(G->H[i][0] + row0 * (SLAB / 16), sbase + OFF_X + i * HSTG, SLAB);
                    bulk_flush();
                    TS(1, 99);
                    signal(G->flag[1] + (row0 >> 10) * 2 + ((row0 & 1023) >= 320));
                }
                __syncwarp();
            } else {
                const uint32_t word = rank * 16 + (w & 2) * 4 + (lane & 7), done = mapa(bars + B_CS, rank ^ (lane & 1));
                const uint32_t from = (sbase + word * 4 + (gp >> 2) * 12288 + (gp & 2) * 1024) ^ ((lane >> 3) * 288);
                auto swz = [](uint32_t a) { return a ^ ((a >> 3) & 0x70); };
                const uint32_t lin = sbase + lane * 128 + (hp & 1) * 16, f0 = swz(lin + 80) + 8192, f1 = swz(lin + 96) + 8192, to = swz(lin + 112);
                float s[6] = {};
#pragma unroll 1
                for (int i = 0; i < 7; i++) {
                    const uint32_t o = wslot(i) * 8192, a0 = from + o, a1 = a0 ^ 144;
                    mbar_wait(bars + B_QFULL + 8 * i, 0);
                    if ((i ^ (w >> 1)) & 1) {
                        const uint4 v0 = lds4(f0 + o), v1 = lds4(f1 + o), v2 = lds4(f0 + o + 12288), v3 = lds4(f1 + o + 12288);
                        sts4(to + o, v0); sts4(to + o + 4096, v1); sts4(to + o + 12288, v2); sts4(to + o + 16384, v3);
                        fence_async_shared();
                        __syncwarp();
                        if (elect()) mbar_expect(bars + B_FULL + 8 * i, 16384);
                    }
                    if (i > 3 || i < (gp & 1)) continue;
                    if (w == 1) TS(1, 66);
                    uint32_t v[12];
#pragma unroll
                    for (int k = 0; k < 12; k++) v[k] = __float_as_uint(lds1f(((k & 1) ? a1 : a0) + (k & 2) * 512 + (k >> 2) * 4096));
#pragma unroll
                    for (int k = 0; k < 12; k++) { s[(k >> 2) * 2] += bf_lo(v[k]); s[(k >> 2) * 2 + 1] += bf_hi(v[k]); }
                    __syncwarp();
                    if ((i & 1) && lane < 2) mbar_arrive_remote(done + (i & 2) * 4);
                    if (i < 3) continue;
#pragma unroll
                    for (int k = 0; k < 6; k++) { s[k] += __shfl_xor_sync(~0u, s[k], 8); s[k] += __shfl_xor_sync(~0u, s[k], 16); }
                    const float s0 = lane < 8 ? s[0] : lane < 16 ? s[2] : s[4], s1 = lane < 8 ? s[1] : lane < 16 ? s[3] : s[5];
                    if (lane < 24) cs[gp * 96 + (lane >> 3) * 32 + word] = make_uint2(tag(__float_as_uint(s0), 1, ep), __float_as_uint(s1));
                    if (w == 1) TS(1, 24);
                }
            }
            bar_sync(1, 96);
            if (w == 1) TS(1, 98);
            const int i0 = threadIdx.x - 288, j0 = i0 - (hp & 1) * 4;
            cs += i0 + ((j0 & 92) == 28 ? (j0 & 32 ? 28 : 56) : 0);
            uint2 u[8];
            uint4 sv;
            do {
                sv = ld_relaxed4(G->stat + tb * 128 + (i0 & 63) * 2);
                bad = sv.x ^ ep;
#pragma unroll
                for (int i = 0; i < 8; i++) { u[i] = ld_relaxed2(cs + i * 96); bad = or_diff(bad, u[i].x, ep); }
                if (bad & 1) TS(1, 3);
            } while (bad & 1);
            if (w < 3) sts4(sbase + OFF_ST + i0 * 16, sv);
#pragma unroll
            for (int e = 0; e < 2; e++) {
                float f = 0.f;
#pragma unroll
                for (int i = 0; i < 8; i++) f += __uint_as_float(e ? u[i].y : u[i].x);
                const uint32_t hi = pack2(f, f);
                sts4(sbase + OFF_X + i0 * 32 + e * 16, make_uint4(hi, pack2(f - bf_hi(hi), f - bf_hi(hi)), 0, 0));
            }
            sts1(bars + 8 * NBAR, ep);
            fence_async_shared();
            __syncwarp();
            bar_arrive(8, 224); bar_arrive(9, 224);
            TS(1, 90 + w);
        }
        if (w < 3) {
            if (w == 1) {
                if (elect()) {
                    wait_flag(G->flag[1] + rank * 2 + 1, 44 * ep, spins);
                    mbar_arrive16(bars + B_EMPTY + 8 * 5);
                    TS(1, 96);
                }
                __syncwarp();
                if (!has_g1) { bar_sync(5, 288); if (elect()) signal(G->flag[0]); __syncwarp(); TS(2, 26); }
            }
            mbar_wait(bars + B_HALO, 0);
            uint32_t slot = (has_g1 ? 16 % NSLOT : 0) + w - 1, ph = ~0u;
#pragma unroll 1
            for (int i = w - 1; i < 18;) {
                const uint32_t d0 = sbase + slot * SLOT + (i < 4 ? 0 : 16384), d1 = d0 + (i < 4 ? 8192 : HALF), landed = bars + B_QFULL + 8 * slot;
                mbar_wait(landed, (ph >> slot) & 1);
                ph ^= 1 << slot;
                if (i < 8) TS(4, 82 + i);
                if (i >= 4) TS(8, 156 + i);
                bad = 0;
#pragma unroll
                for (int k = 0; k < 14; k++) bad = or_diff(bad, __float_as_uint(lds1f((k < 7 ? d0 : d1) + k % 7 * 1024 + lane * 32 + (lane >> 2) * 4)), ep);
                if (__any_sync(~0u, bad & 1)) {
                    if (elect()) {
                        const uint8_t* cur = (i < 4 ? G->O[mt][ks * 4] : src - 4 * TILEB) + i * TILEB;
                        fence_async_shared();
                        mbar_expect(landed, TILEB);
                        bulk_load(d0, cur, HALF, landed);
                        bulk_load(d1, cur + HALF, HALF, landed);
                    }
                    TS(4, i < 4 ? 94 : 95);
                } else {
                    if (elect()) mbar_expect(landed + (B_FULL - B_QFULL), i < 4 ? (2 + w) * SLAB : 16384);
                    i += __byte_perm(0x03020202u, 0x00010202u, 0x7770 + slot);
                    slot = __byte_perm(0x05060302u, 0x00040100u, 0x7770 + slot);
                }
            }
        } else {
            bar_sync(3, 288);
            __nanosleep(HALO_NS);
            uint4 v[7];
            do {
                bad = 0;
#pragma unroll
                for (int i = 0; i < 7; i++) { v[i] = ld_relaxed4(G->halo[c - (tb > 0)] + i * 512 + lane * 16); bad = or_diff(bad, v[i].x, ep); }
            } while (bad & 1);
#pragma unroll
            for (int i = 0; i < 7; i++) sts4(sbase + OFF_X + i * 512 + lane * 16, v[i]);
            __syncwarp();
            if (elect()) mbar_arrive(bars + B_HALO);
            TS(2, 21);
            bar_sync(2, 288);
            if (elect()) bulk_store(out + row0 * D_, sbase + OFF_Y, TILEB);
            __syncwarp();
            bar_sync(4, 288);
            if (elect()) {
                fence_async_shared();
                bulk_store(G->O[tb][hp], sbase + OFF_X, TILEB);
                bulk_flush();
                TS(2, 7);
                mbar_arrive_remote(mapa(bars + B_FREE, rank ^ 1));
                mbar_arrive(bars + B_FREE);
                hint(G->flag[16 + tb]);
                signal(G->flag[16 + (row0 >> 7)] + 1);
                TS(2, 22);
            }
            __syncwarp();
            uint32_t late = ~0u;
            const uint32_t* hints = G->flag[8 + nt2 * 2 + ks] + lane;
            mbar_wait(bars + (has_g1 ? B_X : B_FREE), 0);
            Ring r{has_g1 ? 2u : 6u, has_g1};
#pragma unroll 1
            for (int i = 0; i < 14; i++) {
                while ((late >> i) & 1) late = __ballot_sync(~0u, ld_relaxed(hints) != 2 * ep) & 127;
                if (i == 0) TS(4, 17);
                mbar_wait(bars + B_EMPTY + 8 * r.slot, r.ph);
                TS(8, 192 + i);
                if (elect()) {
                    mbar_expect(bars + B_QFULL + 8 * r.slot, TILEB);
                    bulk_load(sbase + r.slot * SLOT + 16384, src, TILEB, bars + B_QFULL + 8 * r.slot);
                }
                src += TILEB; r.next2();
            }
            if (elect()) {
                wait_flag(G->flag[16 + mt] + 1, 8 * ep, spins);
                mbar_arrive(bars + B_ROW);
                TS(2, 27);
                G->epoch[c] = ep;
            }
        }
    } else {
        const int wg = warp >> 2;
        Mma M{bars, mapa(bars, rank ^ (lane & 1)), (threadIdx.x & 127) < 2, wg, w, Ring{0, 1}, 0};
        const int r = lane >> 2, t = lane & 3;
        uint32_t ep;
        const uint32_t bias0 = ld_u16(b1 + ft * 128 + warp * 16 + r), bias1 = ld_u16(b1 + ft * 128 + warp * 16 + r + 8);
        const uint32_t kv = sbase + OFF_X + (w * 2 + wg) * KV + lane * 16;
        uint32_t q[8][2], k0[7], k1[14], v0[7];
        float f0, f1;
        {
            const int half = (lane >> 3) & 1, r16 = warp * 2 + (half ^ (lane >> 4)), nt = (lane >> 1) & 3;
            const uint32_t row = sbase + OFF_Y + r16 * (2 * D_), part = row + nt * 224 + half * 112 + (lane & 1) * 8;
            const uint32_t hb = sbase + OFF_X + nt * HSTG + r16 * 16 + (half ^ (row0 >> 10)) * (7 * 256) + (lane & 1) * 8;
            mbar_wait(bars + B_ROW, 0);
            TS0(1, 67);
            const float x0 = bf_lo(__float_as_uint(lds1f(row)));
            float d[28], m1 = 0.f, n1 = 0.f, m2 = 0.f, n2 = 0.f;
#pragma unroll
            for (int i = 0; i < 7; i++) {
                const uint2 v = lds2(part + i * 16);
#pragma unroll
                for (int k = 0; k < 2; k++) {
                    const float d0 = d[4 * i + 2 * k] = bf_lo(k ? v.y : v.x) - x0, d1 = d[4 * i + 2 * k + 1] = bf_hi(k ? v.y : v.x) - x0;
                    m1 += d0; n1 += d1; m2 = fmaf(d0, d0, m2); n2 = fmaf(d1, d1, n2);
                }
            }
            const float md = row_sum(m1 + n1) * (1.f / D_), var = fmaf(-md, md, row_sum(m2 + n2) * (1.f / D_)), nmean = -(x0 + md);
            const float rstd = rsq(var + LN_EPS);
            const float sc = rstd * rsq(fmaf(var * rstd, rstd, LN_EPS)), nb = -md * sc;
            sts2(sbase + OFF_ST + r16 * 8, __float_as_uint(rstd), pack2(nmean, nmean - bf_hi(pack2(nmean, nmean))));
#pragma unroll
            for (int i = 0; i < 7; i++) sts2(hb + i * 256, pack2(fmaf(d[4 * i], sc, nb), fmaf(d[4 * i + 1], sc, nb)), pack2(fmaf(d[4 * i + 2], sc, nb), fmaf(d[4 * i + 3], sc, nb)));
            TS0(1, 25);
            bar_arrive(6, 288);
            float acc[84];
#pragma unroll 1
            for (int kb = 0; kb < 7; kb++) {
                const bool held = kb == (wg ? 7 - HOLD : -1);
                if (held) { wg_wait<0>(); M.release(4 - HOLD); TS0(1, 138); bar_sync(7, 256); }
                mbar_wait(bars + B_FULL + 8 * kb, 0);
                if (!TSQ || !kb) TS0(1, 68 + wg * 7 + kb);
                const uint32_t dA = (xslot(kb) + wg) * 512, dB = wslot(kb) * 512 + (hp & 1);
                wg_fence();
#pragma unroll
                for (int k = 0; k < 4; k++) {
                    wgmma_n168<0, 1, HI_SW, HI_SW>(acc, dA + desc_lo(k * 32, 16), dB + desc_lo((k & 1) * 2048 + (k >> 1) * 12288, 4096), k > 0 || kb > 0);
                    if (k == 0) { wg_commit(); wg_wait<1>(); if (kb > 0 && !held) M.release(kb - 3); if (TSQ && kb) TS0(1, 68 + wg * 7 + kb); }
                }
                wg_commit();
            }
            if (wg == 0 && !LATEREL) bar_arrive(7, 256);
            if (wg == 0) TS0(1, 139);
            bar_sync(8 + wg, 224);
            if (wg == 0) TS0(1, 174);
            ep = __float_as_uint(lds1f(bars + 8 * NBAR));
            const uint32_t st = sbase + OFF_ST + (w * 32 + r * 2 + wg) * 8;
            const uint2 s0 = lds2(st), s1 = lds2(st + 128);
            const uint32_t a0 = t < 2 ? s0.y : 0, a1 = t < 2 ? s1.y : 0;
            wg_fence();
            wgmma_rs_n168<desc_hi(128, 0)>(acc, a0, a1, desc_lo(OFF_X, 0) + (hp & 1) * 8);
            wg_commit();
            if (wg == 0 && LATEREL) bar_arrive(7, 256);
            if (wg == 0) TS0(1, 175);
            wg_wait<1>();
            TS0(1, 190 + wg);
            M.release(4);
            wg_wait<0>();
            pin(acc);
            TS0(1, 4 + 7 * wg);
            f0 = __uint_as_float(s0.x); f1 = __uint_as_float(s1.x);
#pragma unroll
            for (int g = 13; g >= 0; g--) {
                const float* a = acc + (g < 7 ? g + 8 : g < 12 ? g + 9 : g * 8 - 89) * 4;
                const float r0 = g < 7 ? f0 : f0 + f0, r1 = g < 7 ? f1 : f1 + f1;
                (g < 7 ? k0[g] : v0[g - 7]) = pack2(a[0] * r0, a[1] * r0);
                k1[g] = pack2(a[2] * r1, a[3] * r1);
            }
#pragma unroll
            for (int i = 0; i < 3; i++) stsm4(kv + 2 * KV + i * 512, k1[4 * i], k1[4 * i + 1], k1[4 * i + 2], k1[4 * i + 3]);
            stsm2(kv + 2 * KV + 1536, k1[12], k1[13]);
            if (w == 3) {
#pragma unroll
                for (int i = 0; i < 14; i++) stg1(G->halo[c] + wg * KV + lane * 4 + i * 128, tag(k1[i], t == 0, ep));
            }
            bar_arrive(3, 288);
#pragma unroll
            for (int g = 0; g < 7; g++) { q[g][0] = pack2(acc[4 * g], acc[4 * g + 1]); q[g][1] = pack2(acc[4 * g + 2], acc[4 * g + 3]); }
#pragma unroll
            for (int j = 0; j < 2; j++) { q[7][j] = t < 2 ? 0u : q[3][j]; q[3][j] = t < 2 ? q[3][j] : 0u; }
#pragma unroll
            for (int g = 0; g < 7; g++) v0[g] = transpose8(v0[g]);
        }
        TS0(1, 9 + 11 * wg);
        M.rel = bars;
        float a[56];
#pragma unroll
        for (int i = 0; i < 56; i++) asm volatile("" : "=f"(a[i]));
        if (__builtin_expect(!has_g1, 0)) {
            const int g = min(lane >> 1, 13), nt = rank * 2 + wg;
            const uint4* src = (const uint4*)(wo + (hp * 56 - (hp & 1) * 8 + w * 16 + (lane & 1)) * D_ + nt * 112) + g;
            uint4 v[8];
#pragma unroll
            for (int i = 0; i < 8; i++) v[i] = __ldg(src + i * (D_ / 4));
#pragma unroll
            for (int i = 0; i < 8; i++) ((uint4*)G->Wo[nt][hp])[w * (SLAB / 16) + g * 16 + (lane & 1) + 2 * i] = v[i];
            bar_arrive(5, 288);
        }
        M.run<true>(a, has_g1 ? PAUSE : 0, 1, 16, 0, 0, 32);
        {
            uint32_t kp[8], vv[14];
            TS0(2, 140 + wg);
            mbar_wait(bars + B_HALO, 0);
            TS0(2, 142 + wg);
            ldsm4(kp, kv); ldsm4(kp + 4, kv + (lane < 24 ? 512 : 0));
            const uint32_t va = kv + 896 + (lane & 8) * (2 * KV / 8 - 16) - (lane & 16) * 8;
            ldsm4t(vv, va); ldsm4t(vv + 4, va + 256); ldsm4t(vv + 8, va + 512); ldsm2t(vv + 12, va + 768);
            const bool e0 = 2 * t > r, e1 = 2 * t >= r;
            const uint32_t mk = (e0 ? 0xffffu : 0u) | (e1 ? 0xffff0000u : 0u);
            wg_wait<0>();
            pin(a);
            if (has_g1) M.release(M.prev);
            TS0(2, 144 + wg);
            bar_sync(2, 288);
            mbar_wait(bars + B_HALO, 0);
            TS0(2, 12 + 16 * wg);
            float sv[2][4];
#pragma unroll
            for (int h = 0; h < 2; h++) {
                const int ga = h * 4, gb = h * 4 + 1, gc = h * 4 + 2, gd = h * 4 + 3;
                float s[3][4] = {};
                mma16(s[0], q[ga][0], q[ga][1], q[gb][0], q[gb][1], kp[ga], kp[gb]);
                mma16(s[1], q[ga][0], q[ga][1], q[gb][0], q[gb][1], k0[ga], k0[gb]);
                mma16(s[2], q[ga][0], q[ga][1], q[gb][0], q[gb][1], k1[ga], k1[gb]);
                mma16(s[0], q[gc][0], q[gc][1], q[gd][0], q[gd][1], kp[gc], kp[gd]);
                mma16(s[1], q[gc][0], q[gc][1], q[gd][0], q[gd][1], k0[gc], k0[3]);
                mma16(s[2], q[gc][0], q[gc][1], q[gd][0], q[gd][1], k1[gc], k1[3]);
                if ((tb | w) == 0) s[0][0] = s[0][1] = -1e30f;
                sv[h][0] = e0 ? s[0][0] : s[1][0];
                sv[h][1] = e1 ? s[0][1] : s[1][1];
                sv[h][2] = e0 ? s[1][2] : s[2][2];
                sv[h][3] = e1 ? s[1][3] : s[2][3];
            }
            uint32_t pp[2][2];
#pragma unroll
            for (int i = 0; i < 4; i++) {
                float* v = &sv[i >> 1][(i & 1) * 2];
                const float f = ((i & 1) ? f1 : f0) * QK_SCALE, m = quad_max(fmaxf(v[0], v[1])) * f;
                const float p0 = ex2(fmaf(v[0], f, -m)), p1 = ex2(fmaf(v[1], f, -m));
                const float inv = rcp(quad_sum(p0 + p1));
                pp[i >> 1][i & 1] = pack2(p0 * inv, p1 * inv);
            }
            uint32_t o[8][2];
#pragma unroll
            for (int i = 0; i < 8; i++) {
                const int h = i >> 2, g = i - h;
                float d[4] = {};
                mma16(d, pp[h][0] & mk, 0u, 0u, pp[h][1] & ~mk, vv[2 * g], vv[2 * g + 1]);
                mma8(d, pp[h][0] & ~mk, pp[h][1] & mk, v0[g]);
                o[i][0] = pack2(d[0], d[1]); o[i][1] = pack2(d[2], d[3]);
            }
            if (t >= 2) { o[3][0] = o[4][0]; o[3][1] = o[4][1]; }
            const int word = wg * 4 + t - (w & 1) * 4 - (r >> 2);
#pragma unroll
            for (int i = 0; i < 8; i++) { o[i][0] = tag(o[i][0], word == 0, ep); o[i][1] = tag(o[i][1], word == 2, ep); }
            const uint32_t dst = sbase + OFF_X + (w >> 1) * HALF + ((w & 1) * 32 + (lane & 15) * 2 + wg) * 16 + (lane >> 4) * 1024;
            stsm4(dst, o[0][0], o[0][1], o[1][0], o[1][1]);
            stsm4(dst + 2048, o[2][0], o[2][1], o[3][0], o[3][1]);
            stsm4(dst + 4096, o[5][0], o[5][1], o[6][0], o[6][1]);
            stsm2(dst + 6144, o[7][0], o[7][1]);
            if (ENDBAR) bar_sync(4, 288); else bar_arrive(4, 288);
            TS0(2, 10 + 19 * wg);
        }
        if (has_g1) {
            M.run<true>(a, 16 - PAUSE, 1, 16, LAG1, 1, 32 + PAUSE);
            mbar_wait(bars + B_FREE, 0);
            const uint32_t xb = sbase + OFF_X + wg * 8192 + (threadIdx.x & 127) * 16, xbar = bars + B_X + 16 * wg;
            const uint32_t rx = mapa(xb, rank ^ 1), rbar = mapa(xbar, rank ^ 1);
            wg_wait<0>();
            pin(a);
            M.release(M.prev);
            TS0(4, 5 + wg);
#pragma unroll
            for (int i = 0; i < 3; i++)
                st_async4(rx + i * 2048, rbar + 8 * (i >> 1), pack2(a[28 + 8 * i], a[29 + 8 * i]), pack2(a[30 + 8 * i], a[31 + 8 * i]), pack2(a[32 + 8 * i], a[33 + 8 * i]), pack2(a[34 + 8 * i], a[35 + 8 * i]));
            const uint32_t tail = 6144 - (threadIdx.x & 127) * 8;
            st_async2(rx + tail, rbar + 8, pack2(a[52], a[53]), pack2(a[54], a[55]));
            uint8_t* dst = G->U[nt1][((ft >= 7) + wg) * 7 + ft] + rank * HALF + w * 256 + lane * 4;
            uint32_t u[14];
#pragma unroll
            for (int i = 0; i < 28; i++) a[i] += bf_lo((i & 2) ? bias1 : bias0);
#pragma unroll
            for (int i = 0; i < 14; i++) {
                if (i % 8 == 0) {
                    if (i) TS0(4, 134 + wg);
                    mbar_wait(xbar + i, 0);
                    TS0(4, (i ? 136 : 1) + wg);
#pragma unroll
                    for (int k = i / 4; k < i / 4 + 2; k++) {
                        if (k < 3) { const uint4 v = lds4(xb + k * 2048); u[4 * k] = v.x; u[4 * k + 1] = v.y; u[4 * k + 2] = v.z; u[4 * k + 3] = v.w; }
                        else { const uint2 v = lds2(xb + tail); u[12] = v.x; u[13] = v.y; }
                    }
                    if (i && lane < 2) mbar_arrive_remote(M.rel + B_EMPTY + 48);
                }
                if (i == HINT && threadIdx.x == 0) hint(G->flag[8 + nt1 * 2] + ft + (ft >= 7) * 25);
                stg1(dst + (i >> 1) * 1024 + (i & 1) * 128, tag(pack2(gelu2(a[2 * i] + bf_lo(u[i])), gelu2(a[2 * i + 1] + bf_hi(u[i]))), (lane & 7) == w * 2 + (i & 1), ep));
            }
            TS0(4, 30 + wg);
        } else {
            mbar_wait(bars + B_FREE, 0);
            if (lane < 2) mbar_arrive_remote(M.rel + B_EMPTY + 48);
        }
        uint32_t c0 = ld_u16(b2 + mt * 128 + warp * 16 + r), c1 = ld_u16(b2 + mt * 128 + warp * 16 + r + 8);
        M.run_o(a);
        if (wg == 1) TS0(4, 13);
        c0 *= ks == 0 ? 0x10001u : 0u; c1 *= ks == 0 ? 0x10001u : 0u;
        M.run<false>(a, 14, 0, 14 - NSLOT, LAG2, 1, 52);
        mbar_wait(bars + B_ROW, 1);
        const uint32_t stg = sbase + ((has_g1 ? STG1 : STG0) + (w >> 1) * STGS) * SLOT + wg * 8192 + (w & 1) * SLAB;
        const uint32_t sa = stg + (lane & 15) * 224 + (lane >> 4) * 16;
        wg_wait<0>();
        pin(a);
        TS0(8, 14 + wg);
#pragma unroll
        for (int i = 0; i < 7; i++)
            stsm4(sa + i * 32, half_plus(pack2(a[8 * i], a[8 * i + 1]), c0), half_plus(pack2(a[8 * i + 2], a[8 * i + 3]), c1),
                  half_plus(pack2(a[8 * i + 4], a[8 * i + 5]), c0), half_plus(pack2(a[8 * i + 6], a[8 * i + 7]), c1));
        fence_async_shared();
        __syncwarp();
        if (elect()) {
            asm volatile("cp.reduce.async.bulk.tensor.2d.global.shared::cta.add.tile.bulk_group [%0, {%2, %3}], [%1];\ncp.async.bulk.commit_group;" ::"l"(&P.tmOut), "r"(stg), "r"(nt2 * 112), "r"(mt * 128 + warp * 16) : "memory");
            if (w == 0) mbar_arrive(bars + B_END);
            asm volatile("cp.async.bulk.wait_group.read 0;" ::: "memory");
        }
        if (wg == 1) TS0(15, 19);
        TSDUMP();
    }
}

typedef CUresult (*EncodeFn)(CUtensorMap*, CUtensorMapDataType, cuuint32_t, void*, const cuuint64_t*, const cuuint64_t*, const cuuint32_t*, const cuuint32_t*,
                             CUtensorMapInterleave, CUtensorMapSwizzle, CUtensorMapL2promotion, CUtensorMapFloatOOBfill);

void make_map(EncodeFn enc, CUtensorMap* tm, const void* base, bool swizzle, int d0, int d1, int d2, int s1, int s2, int b0, int b1, int b2) {
    const cuuint64_t dims[3] = {(cuuint64_t)d0, (cuuint64_t)d1, (cuuint64_t)d2}, strides[2] = {(cuuint64_t)s1 * 2, (cuuint64_t)s2 * 2};
    const cuuint32_t box[3] = {(cuuint32_t)b0, (cuuint32_t)b1, (cuuint32_t)b2}, es[3] = {1, 1, 1};
    enc(tm, CU_TENSOR_MAP_DATA_TYPE_BFLOAT16, d2 ? 3 : 2, (void*)base, dims, strides, box, es, CU_TENSOR_MAP_INTERLEAVE_NONE,
        swizzle ? CU_TENSOR_MAP_SWIZZLE_128B : CU_TENSOR_MAP_SWIZZLE_NONE, CU_TENSOR_MAP_L2_PROMOTION_L2_128B, CU_TENSOR_MAP_FLOAT_OOB_FILL_NONE);
}

}

extern "C" void kernel_launch(void* const* d_in, const int* in_sizes, int n_in, void* d_out, int out_size) {
    static EncodeFn enc = nullptr;
    static Scratch* scratch = nullptr;
    if (!enc) {
        void* fn = nullptr;
        cudaDriverEntryPointQueryResult qr;
        cudaGetDriverEntryPoint("cuTensorMapEncodeTiled", &fn, cudaEnableDefault, &qr);
        enc = (EncodeFn)fn;
        cudaGetSymbolAddress((void**)&scratch, g_s);
        cudaFuncSetAttribute(fused_kernel, cudaFuncAttributeMaxDynamicSharedMemorySize, SMEM_BYTES);
    }
    Params P;
    const __nv_bfloat16* x = (const __nv_bfloat16*)d_in[0];
    make_map(enc, &P.tmX, x, true, D_, S_ / 2, 2, 2 * D_, D_, 64, 64, 2);
    make_map(enc, &P.tmWqkv, d_in[1], true, D_, D_, 3, 3 * D_, D_, 64, 32, 3);
    make_map(enc, &P.tmW1, d_in[4], true, 64, S_, F_ / 64, F_, 64, 64, 64, 2);
    make_map(enc, &P.tmW2, d_in[6], true, 64, F_, S_ / 64, S_, 64, 64, 64, 2);
    make_map(enc, &P.tmOut, d_out, false, D_, S_, 0, D_, 0, 112, 16, 1);
    fused_kernel<<<NCTA, NTHREADS, SMEM_BYTES, cudaStreamPerThread>>>(x, (const __nv_bfloat16*)d_in[5], (const __nv_bfloat16*)d_in[7], (const __nv_bfloat16*)d_in[2], (__nv_bfloat16*)d_out, scratch,
                                                                      (const __nv_bfloat16*)d_in[4], (const __nv_bfloat16*)d_in[6], P);
}
```

```cpp
#include <cuda_runtime.h>
#include <cuda_bf16.h>
#include <cuda.h>
#include <stdint.h>

#define HALO_NS 300
#define HINT 4
#define HOLD 1
#define LATEREL 1
#define PF 400
#define PF0 2
#define PF1 8
#define ENDBAR 1
#define LEADW 4
#define LEADN 7
#define TSQ 0
#define PACE 600
#define PAUSE 8
#define LAG1 4

namespace {

constexpr int S_ = 2048, D_ = 448, F_ = 1792;
constexpr int NCTA = 128, NTHREADS = 384;
constexpr int NSLOT = 6, SLOT = 32768, WSLOT = 24576, TILEB = 14336, SLAB = 3584, HALF = 7168;
constexpr int KV = 1792, HSTG = SLAB + 32;
constexpr int OFF_X = NSLOT * SLOT;
constexpr int OFF_Y = OFF_X + 10 * KV;
constexpr int OFF_ST = OFF_Y + TILEB;
constexpr int OFF_BAR = OFF_ST + 1024;
constexpr int SMEM_BYTES = OFF_BAR + 1280;
constexpr uint32_t SMEM0 = 1024;
constexpr int B_QFULL = 0, B_FULL = 56, B_HALO = 128, B_X = 136, B_CS = 168, B_FREE = 192, B_END = 200, B_QEMPTY = 216, B_EMPTY = 232, B_ROW = 288, NBAR = 37;
constexpr float LN_EPS = 1e-5f, QK_SCALE = 0.1889822365046136f * 1.4426950408889634f;
constexpr int SPIN_LIMIT = 1 << 22;

struct Scratch {
    uint8_t H[4][32][TILEB];
    uint8_t U[4][28][TILEB];
    uint8_t O[16][8][TILEB];
    uint8_t Wo[4][8][TILEB];
    uint8_t halo[NCTA][2 * KV];
    uint2 stat[S_];
    uint2 colsum[8][8][96];
    uint32_t flag[32][32];
    uint32_t epoch[NCTA];
};
__device__ __align__(1024) Scratch g_s;

#define TS(g, i)
#define TS0(g, i)
#define TSDUMP()

struct Params {
    CUtensorMap tmX, tmWqkv, tmW1, tmW2, tmOut;
};

__device__ __forceinline__ bool elect() {
    uint32_t p;
    asm volatile("{\n.reg .pred p;\nelect.sync _|p, 0xffffffff;\nselp.u32 %0, 1, 0, p;\n}" : "=r"(p));
    return p;
}
__device__ __forceinline__ void mbar_init(uint32_t b, uint32_t c) { asm volatile("mbarrier.init.shared::cta.b64 [%0], %1;" ::"r"(b), "r"(c) : "memory"); }
__device__ __forceinline__ void mbar_expect(uint32_t b, uint32_t tx) { asm volatile("mbarrier.arrive.expect_tx.shared::cta.b64 _, [%0], %1;" ::"r"(b), "r"(tx) : "memory"); }
__device__ __forceinline__ void mbar_arrive(uint32_t b) { asm volatile("mbarrier.arrive.shared::cta.b64 _, [%0];" ::"r"(b) : "memory"); }
template <int N> __device__ __forceinline__ void mbar_arrive_n(uint32_t b) { asm volatile("mbarrier.arrive.shared::cta.b64 _, [%0], %1;" ::"r"(b), "n"(N) : "memory"); }
__device__ __forceinline__ void mbar_arrive4_remote(uint32_t b) { asm volatile("mbarrier.arrive.shared::cluster.b64 _, [%0], 4;" ::"r"(b) : "memory"); }
__device__ __forceinline__ void mbar_arrive_remote(uint32_t b) { asm volatile("mbarrier.arrive.shared::cluster.b64 _, [%0];" ::"r"(b) : "memory"); }
#define MBAR_WAIT_ASM(SEM) \
    asm volatile("{\n.reg .pred p;\nWAIT:\nmbarrier.try_wait.parity" SEM ".shared::cta.b64 p, [%0], %1;\n@!p bra WAIT;\n}" ::"r"(b), "r"(parity) : "memory")
__device__ __forceinline__ void mbar_wait(uint32_t b, uint32_t parity) { MBAR_WAIT_ASM(""); }
__device__ __forceinline__ void mbar_wait_bounded(uint32_t b, uint32_t parity, uint32_t& n) {
    asm volatile("{\n.reg .pred p;\nWAIT:\nadd.u32 %0, %0, 1;\nsetp.gt.u32 p, %0, %3;\n@p st.global.u32 [%4], %0;\n"
                 "mbarrier.try_wait.parity.shared::cta.b64 p, [%1], %2;\n@!p bra WAIT;\n}" : "+r"(n) : "r"(b), "r"(parity), "n"(SPIN_LIMIT), "l"(0ull) : "memory");
}
__device__ __forceinline__ uint32_t mapa(uint32_t a, uint32_t rank) { uint32_t r; asm("mapa.shared::cluster.u32 %0, %1, %2;" : "=r"(r) : "r"(a), "r"(rank)); return r; }
__device__ __forceinline__ void tma3d(uint32_t dst, const CUtensorMap* tm, uint32_t bar, int c0, int c1, int c2) {
    asm volatile("cp.async.bulk.tensor.3d.shared::cluster.global.mbarrier::complete_tx::bytes [%0], [%1, {%3, %4, %5}], [%2];" ::"r"(dst), "l"(tm), "r"(bar), "r"(c0), "r"(c1), "r"(c2) : "memory");
}
__device__ __forceinline__ void tma3d_pair(uint32_t dst, const CUtensorMap* tm, uint32_t bar, int c0, int c1, int c2) {
    asm volatile("cp.async.bulk.tensor.3d.shared::cluster.global.mbarrier::complete_tx::bytes.multicast::cluster [%0], [%1, {%3, %4, %5}], [%2], %6;" ::"r"(dst), "l"(tm), "r"(bar), "r"(c0), "r"(c1), "r"(c2), "h"((uint16_t)3) : "memory");
}
__device__ __forceinline__ void bulk_load(uint32_t dst, const void* src, uint32_t bytes, uint32_t bar) {
    asm volatile("cp.async.bulk.shared::cluster.global.mbarrier::complete_tx::bytes [%0], [%1], %2, [%3];" ::"r"(dst), "l"(src), "r"(bytes), "r"(bar) : "memory");
}
__device__ __forceinline__ void bulk_store(void* dst, uint32_t src, uint32_t bytes) {
    asm volatile("cp.async.bulk.global.shared::cta.bulk_group [%0], [%1], %2;" ::"l"(dst), "r"(src), "r"(bytes) : "memory");
}
__device__ __forceinline__ uint32_t ld_u16(const void* p) { uint32_t v; asm volatile("ld.global.nc.u16 %0, [%1];" : "=r"(v) : "l"(p)); return v; }
__device__ __forceinline__ uint32_t ld_relaxed(const uint32_t* p) { uint32_t v; asm volatile("ld.relaxed.gpu.global.u32 %0, [%1];" : "=r"(v) : "l"(p) : "memory"); return v; }
__device__ __forceinline__ void bulk_flush() { asm volatile("cp.async.bulk.commit_group;\ncp.async.bulk.wait_group 0;" ::: "memory"); }
__device__ __forceinline__ void signal(uint32_t* flag) { asm volatile("fence.acq_rel.gpu;\nred.relaxed.gpu.global.add.u32 [%0], 1;" ::"l"(flag) : "memory"); }
__device__ __forceinline__ void hint(uint32_t* flag) { asm volatile("red.relaxed.gpu.global.add.u32 [%0], 1;" ::"l"(flag) : "memory"); }
__device__ __forceinline__ uint32_t tag(uint32_t v, uint32_t mask, uint32_t parity) { return (v & ~mask) | (parity & mask); }
__device__ __forceinline__ uint32_t or_diff(uint32_t acc, uint32_t v, uint32_t parity) { asm("lop3.b32 %0, %0, %1, %2, 0xf6;" : "+r"(acc) : "r"(v), "r"(parity)); return acc; }
__device__ __forceinline__ uint4 ld_relaxed4(const void* p) {
    uint4 v;
    asm volatile("ld.relaxed.gpu.global.v4.u32 {%0, %1, %2, %3}, [%4];" : "=r"(v.x), "=r"(v.y), "=r"(v.z), "=r"(v.w) : "l"(p) : "memory");
    return v;
}
__device__ __forceinline__ uint2 ld_relaxed2(const void* p) { uint2 v; asm volatile("ld.relaxed.gpu.global.v2.u32 {%0, %1}, [%2];" : "=r"(v.x), "=r"(v.y) : "l"(p) : "memory"); return v; }
__device__ __forceinline__ void sts4(uint32_t a, uint4 v) { asm volatile("st.shared.v4.b32 [%0], {%1, %2, %3, %4};" ::"r"(a), "r"(v.x), "r"(v.y), "r"(v.z), "r"(v.w) : "memory"); }
__device__ __forceinline__ void sts1(uint32_t a, uint32_t v) { asm volatile("st.shared.b32 [%0], %1;" ::"r"(a), "r"(v) : "memory"); }
__device__ __forceinline__ void sts2(uint32_t a, uint32_t v0, uint32_t v1) { asm volatile("st.shared.v2.b32 [%0], {%1, %2};" ::"r"(a), "r"(v0), "r"(v1) : "memory"); }
__device__ __forceinline__ void stg1(void* p, uint32_t v) { asm volatile("st.global.b32 [%0], %1;" ::"l"(p), "r"(v) : "memory"); }
__device__ __forceinline__ void fence_async_shared() { asm volatile("fence.proxy.async.shared::cta;" ::: "memory"); }
#define BOUND "add.u32 %0, %0, 16;\nsetp.gt.u32 p, %0, %1;\n@p st.global.u32 [%2], %0;\n"
__device__ __forceinline__ void wait_flag(const uint32_t* p, uint32_t target, uint32_t& n) {
    asm volatile("{\n.reg .pred p;\n.reg .u32 v;\nPOLL:\n" BOUND "ld.acquire.gpu.global.u32 v, [%3];\nsetp.ne.u32 p, v, %4;\n@p bra POLL;\nfence.proxy.async.global;\n}"
                 : "+r"(n) : "n"(SPIN_LIMIT), "l"(0ull), "l"(p), "r"(target) : "memory");
}
__device__ __forceinline__ void wait_flag2(const uint32_t* h, uint32_t th, const uint32_t* p, uint32_t target, uint32_t& n) {
    asm volatile("{\n.reg .pred p;\n.reg .u32 u, v;\nPOLL:\n" BOUND "ld.relaxed.gpu.global.u32 u, [%3];\nld.acquire.gpu.global.u32 v, [%5];\nsetp.ne.u32 p, u, %4;\nsetp.ne.or.u32 p, v, %6, p;\n@p bra POLL;\nfence.proxy.async.global;\n}"
                 : "+r"(n) : "n"(SPIN_LIMIT), "l"(0ull), "l"(h), "r"(th), "l"(p), "r"(target) : "memory");
}
__device__ __forceinline__ void bar_sync(int id, int n) { asm volatile("bar.sync %0, %1;" ::"r"(id), "r"(n) : "memory"); }
__device__ __forceinline__ void bar_arrive(int id, int n) { asm volatile("bar.arrive %0, %1;" ::"r"(id), "r"(n) : "memory"); }
__device__ __forceinline__ void wg_fence() { asm volatile("wgmma.fence.sync.aligned;" ::: "memory"); }
__device__ __forceinline__ void wg_commit() { asm volatile("wgmma.commit_group.sync.aligned;" ::: "memory"); }
template <int N> __device__ __forceinline__ void wg_wait() { asm volatile("wgmma.wait_group.sync.aligned %0;" ::"n"(N) : "memory"); }
template <int N> __device__ __forceinline__ void pin(float (&d)[N]) {
#pragma unroll
    for (int i = 0; i < N; i++) asm volatile("" : "+f"(d[i])::"memory");
}
__host__ __device__ constexpr uint32_t desc_hi(uint32_t sbo, uint32_t swz) { return (sbo >> 4) | (swz << 30); }
__host__ __device__ constexpr uint32_t desc_lo(uint32_t off, uint32_t lbo) { return ((SMEM0 + off) >> 4) | ((lbo >> 4) << 16); }
__device__ __forceinline__ uint32_t pack2(float lo, float hi) { uint32_t r; asm("cvt.rn.bf16x2.f32 %0, %1, %2;" : "=r"(r) : "f"(hi), "f"(lo)); return r; }
__device__ __forceinline__ float bf_lo(uint32_t v) { return __uint_as_float(v << 16); }
__device__ __forceinline__ float bf_hi(uint32_t v) { return __uint_as_float(v & 0xffff0000u); }
__device__ __forceinline__ uint32_t half_plus(uint32_t a, uint32_t b) { uint32_t r; asm("fma.rn.bf16x2 %0, %1, %2, %3;" : "=r"(r) : "r"(a), "r"(0x3f003f00u), "r"(b)); return r; }
__device__ __forceinline__ void stsm4(uint32_t a, uint32_t r0, uint32_t r1, uint32_t r2, uint32_t r3) {
    asm volatile("stmatrix.sync.aligned.m8n8.x4.shared.b16 [%0], {%1, %2, %3, %4};" ::"r"(a), "r"(r0), "r"(r1), "r"(r2), "r"(r3) : "memory");
}
__device__ __forceinline__ void stsm2(uint32_t a, uint32_t r0, uint32_t r1) {
    asm volatile("stmatrix.sync.aligned.m8n8.x2.shared.b16 [%0], {%1, %2};" ::"r"(a), "r"(r0), "r"(r1) : "memory");
}
__device__ __forceinline__ uint4 lds4(uint32_t a) { uint4 v; asm volatile("ld.shared.v4.b32 {%0, %1, %2, %3}, [%4];" : "=r"(v.x), "=r"(v.y), "=r"(v.z), "=r"(v.w) : "r"(a) : "memory"); return v; }
__device__ __forceinline__ uint2 lds2(uint32_t a) { uint2 v; asm volatile("ld.shared.v2.b32 {%0, %1}, [%2];" : "=r"(v.x), "=r"(v.y) : "r"(a) : "memory"); return v; }
__device__ __forceinline__ float lds1f(uint32_t a) { float v; asm volatile("ld.shared.f32 %0, [%1];" : "=f"(v) : "r"(a) : "memory"); return v; }
__device__ __forceinline__ void ldsm4(uint32_t* r, uint32_t a) {
    asm volatile("ldmatrix.sync.aligned.m8n8.x4.shared.b16 {%0, %1, %2, %3}, [%4];" : "=r"(r[0]), "=r"(r[1]), "=r"(r[2]), "=r"(r[3]) : "r"(a) : "memory");
}
__device__ __forceinline__ void ldsm4t(uint32_t* r, uint32_t a) {
    asm volatile("ldmatrix.sync.aligned.m8n8.x4.trans.shared.b16 {%0, %1, %2, %3}, [%4];" : "=r"(r[0]), "=r"(r[1]), "=r"(r[2]), "=r"(r[3]) : "r"(a) : "memory");
}
__device__ __forceinline__ void ldsm2t(uint32_t* r, uint32_t a) {
    asm volatile("ldmatrix.sync.aligned.m8n8.x2.trans.shared.b16 {%0, %1}, [%2];" : "=r"(r[0]), "=r"(r[1]) : "r"(a) : "memory");
}
__device__ __forceinline__ uint32_t transpose8(uint32_t v) { uint32_t r; asm volatile("movmatrix.sync.aligned.m8n8.trans.b16 %0, %1;" : "=r"(r) : "r"(v)); return r; }
__device__ __forceinline__ void mma16(float (&c)[4], uint32_t a0, uint32_t a1, uint32_t a2, uint32_t a3, uint32_t b0, uint32_t b1) {
    asm volatile("mma.sync.aligned.m16n8k16.row.col.f32.bf16.bf16.f32 {%0, %1, %2, %3}, {%4, %5, %6, %7}, {%8, %9}, {%0, %1, %2, %3};"
                 : "+f"(c[0]), "+f"(c[1]), "+f"(c[2]), "+f"(c[3]) : "r"(a0), "r"(a1), "r"(a2), "r"(a3), "r"(b0), "r"(b1));
}
__device__ __forceinline__ void mma8(float (&c)[4], uint32_t a0, uint32_t a1, uint32_t b0) {
    asm volatile("mma.sync.aligned.m16n8k8.row.col.f32.bf16.bf16.f32 {%0, %1, %2, %3}, {%4, %5}, {%6}, {%0, %1, %2, %3};"
                 : "+f"(c[0]), "+f"(c[1]), "+f"(c[2]), "+f"(c[3]) : "r"(a0), "r"(a1), "r"(b0));
}
__device__ __forceinline__ void st_async4(uint32_t a, uint32_t bar, uint32_t v0, uint32_t v1, uint32_t v2, uint32_t v3) {
    asm volatile("st.async.weak.shared::cluster.mbarrier::complete_tx::bytes.v4.b32 [%0], {%2, %3, %4, %5}, [%1];" ::"r"(a), "r"(bar), "r"(v0), "r"(v1), "r"(v2), "r"(v3) : "memory");
}
__device__ __forceinline__ void st_async2(uint32_t a, uint32_t bar, uint32_t v0, uint32_t v1) {
    asm volatile("st.async.weak.shared::cluster.mbarrier::complete_tx::bytes.v2.b32 [%0], {%2, %3}, [%1];" ::"r"(a), "r"(bar), "r"(v0), "r"(v1) : "memory");
}
__device__ __forceinline__ float quad_max(float v) { v = fmaxf(v, __shfl_xor_sync(~0u, v, 1)); return fmaxf(v, __shfl_xor_sync(~0u, v, 2)); }
__device__ __forceinline__ float quad_sum(float v) { v += __shfl_xor_sync(~0u, v, 1); return v + __shfl_xor_sync(~0u, v, 2); }
__device__ __forceinline__ float ex2(float v) { float r; asm("ex2.approx.ftz.f32 %0, %1;" : "=f"(r) : "f"(v)); return r; }
__device__ __forceinline__ float rcp(float v) { float r; asm("rcp.approx.ftz.f32 %0, %1;" : "=f"(r) : "f"(v)); return r; }
__device__ __forceinline__ float rsq(float v) { float r; asm("rsqrt.approx.ftz.f32 %0, %1;" : "=f"(r) : "f"(v)); return r; }
__device__ __forceinline__ float gelu2(float u) {
    float z = u * fmaf(u * u, 0.044715f * 0.7978845608028654f, 0.7978845608028654f), t;
    asm("tanh.approx.f32 %0, %1;" : "=f"(t) : "f"(z));
    return fmaf(u, t, u);
}
__device__ __forceinline__ float row_sum(float v) {
    v = quad_sum(v); v += __shfl_xor_sync(~0u, v, 4);
    return v + __shfl_xor_sync(~0u, v, 24);
}

template <int TA, int TB, uint32_t HA, uint32_t HB>
__device__ __forceinline__ void wgmma_n112(float (&d)[56], uint32_t da, uint32_t db, int accumulate) {
    asm volatile("{\n.reg .pred p;\n.reg .b64 a, b;\nmov.b64 a, {%56, %61};\nmov.b64 b, {%57, %62};\nsetp.ne.b32 p, %58, 0;\n"
        "wgmma.mma_async.sync.aligned.m64n112k16.f32.bf16.bf16 {"
        "%0, %1, %2, %3, %4, %5, %6, %7, %8, %9, %10, %11, %12, %13, %14, %15, "
        "%16, %17, %18, %19, %20, %21, %22, %23, %24, %25, %26, %27, %28, %29, %30, %31, "
        "%32, %33, %34, %35, %36, %37, %38, %39, %40, %41, %42, %43, %44, %45, %46, %47, "
        "%48, %49, %50, %51, %52, %53, %54, %55"
        "}, a, b, p, 1, 1, %59, %60;\n}\n"
        : "+f"(d[0]), "+f"(d[1]), "+f"(d[2]), "+f"(d[3]), "+f"(d[4]), "+f"(d[5]), "+f"(d[6]), "+f"(d[7]),
          "+f"(d[8]), "+f"(d[9]), "+f"(d[10]), "+f"(d[11]), "+f"(d[12]), "+f"(d[13]), "+f"(d[14]), "+f"(d[15]),
          "+f"(d[16]), "+f"(d[17]), "+f"(d[18]), "+f"(d[19]), "+f"(d[20]), "+f"(d[21]), "+f"(d[22]), "+f"(d[23]),
          "+f"(d[24]), "+f"(d[25]), "+f"(d[26]), "+f"(d[27]), "+f"(d[28]), "+f"(d[29]), "+f"(d[30]), "+f"(d[31]),
          "+f"(d[32]), "+f"(d[33]), "+f"(d[34]), "+f"(d[35]), "+f"(d[36]), "+f"(d[37]), "+f"(d[38]), "+f"(d[39]),
          "+f"(d[40]), "+f"(d[41]), "+f"(d[42]), "+f"(d[43]), "+f"(d[44]), "+f"(d[45]), "+f"(d[46]), "+f"(d[47]),
          "+f"(d[48]), "+f"(d[49]), "+f"(d[50]), "+f"(d[51]), "+f"(d[52]), "+f"(d[53]), "+f"(d[54]), "+f"(d[55])
        : "r"(da), "r"(db), "r"(accumulate), "n"(TA), "n"(TB), "n"(HA), "n"(HB));
}

template <int TA, int TB, uint32_t HA, uint32_t HB>
__device__ __forceinline__ void wgmma_n168(float (&d)[84], uint32_t da, uint32_t db, int accumulate) {
    asm volatile("{\n.reg .pred p;\n.reg .b64 a, b;\nmov.b64 a, {%84, %89};\nmov.b64 b, {%85, %90};\nsetp.ne.b32 p, %86, 0;\n"
        "wgmma.mma_async.sync.aligned.m64n168k16.f32.bf16.bf16 {"
        "%0, %1, %2, %3, %4, %5, %6, %7, %8, %9, %10, %11, %12, %13, %14, %15, "
        "%16, %17, %18, %19, %20, %21, %22, %23, %24, %25, %26, %27, %28, %29, %30, %31, "
        "%32, %33, %34, %35, %36, %37, %38, %39, %40, %41, %42, %43, %44, %45, %46, %47, "
        "%48, %49, %50, %51, %52, %53, %54, %55, %56, %57, %58, %59, %60, %61, %62, %63, "
        "%64, %65, %66, %67, %68, %69, %70, %71, %72, %73, %74, %75, %76, %77, %78, %79, "
        "%80, %81, %82, %83"
        "}, a, b, p, 1, 1, %87, %88;\n}\n"
        : "+f"(d[0]), "+f"(d[1]), "+f"(d[2]), "+f"(d[3]), "+f"(d[4]), "+f"(d[5]), "+f"(d[6]), "+f"(d[7]),
          "+f"(d[8]), "+f"(d[9]), "+f"(d[10]), "+f"(d[11]), "+f"(d[12]), "+f"(d[13]), "+f"(d[14]), "+f"(d[15]),
          "+f"(d[16]), "+f"(d[17]), "+f"(d[18]), "+f"(d[19]), "+f"(d[20]), "+f"(d[21]), "+f"(d[22]), "+f"(d[23]),
          "+f"(d[24]), "+f"(d[25]), "+f"(d[26]), "+f"(d[27]), "+f"(d[28]), "+f"(d[29]), "+f"(d[30]), "+f"(d[31]),
          "+f"(d[32]), "+f"(d[33]), "+f"(d[34]), "+f"(d[35]), "+f"(d[36]), "+f"(d[37]), "+f"(d[38]), "+f"(d[39]),
          "+f"(d[40]), "+f"(d[41]), "+f"(d[42]), "+f"(d[43]), "+f"(d[44]), "+f"(d[45]), "+f"(d[46]), "+f"(d[47]),
          "+f"(d[48]), "+f"(d[49]), "+f"(d[50]), "+f"(d[51]), "+f"(d[52]), "+f"(d[53]), "+f"(d[54]), "+f"(d[55]),
          "+f"(d[56]), "+f"(d[57]), "+f"(d[58]), "+f"(d[59]), "+f"(d[60]), "+f"(d[61]), "+f"(d[62]), "+f"(d[63]),
          "+f"(d[64]), "+f"(d[65]), "+f"(d[66]), "+f"(d[67]), "+f"(d[68]), "+f"(d[69]), "+f"(d[70]), "+f"(d[71]),
          "+f"(d[72]), "+f"(d[73]), "+f"(d[74]), "+f"(d[75]), "+f"(d[76]), "+f"(d[77]), "+f"(d[78]), "+f"(d[79]),
          "+f"(d[80]), "+f"(d[81]), "+f"(d[82]), "+f"(d[83])
        : "r"(da), "r"(db), "r"(accumulate), "n"(TA), "n"(TB), "n"(HA), "n"(HB));
}

template <uint32_t HB>
__device__ __forceinline__ void wgmma_rs_n168(float (&d)[84], uint32_t a0, uint32_t a1, uint32_t db) {
    asm volatile("{\n.reg .b64 b;\nmov.b64 b, {%86, %88};\n"
        "wgmma.mma_async.sync.aligned.m64n168k16.f32.bf16.bf16 {"
        "%0, %1, %2, %3, %4, %5, %6, %7, %8, %9, %10, %11, %12, %13, %14, %15, "
        "%16, %17, %18, %19, %20, %21, %22, %23, %24, %25, %26, %27, %28, %29, %30, %31, "
        "%32, %33, %34, %35, %36, %37, %38, %39, %40, %41, %42, %43, %44, %45, %46, %47, "
        "%48, %49, %50, %51, %52, %53, %54, %55, %56, %57, %58, %59, %60, %61, %62, %63, "
        "%64, %65, %66, %67, %68, %69, %70, %71, %72, %73, %74, %75, %76, %77, %78, %79, "
        "%80, %81, %82, %83"
        "}, {%84, %85, %87, %87}, b, 1, 1, 1, 0;\n}\n"
        : "+f"(d[0]), "+f"(d[1]), "+f"(d[2]), "+f"(d[3]), "+f"(d[4]), "+f"(d[5]), "+f"(d[6]), "+f"(d[7]),
          "+f"(d[8]), "+f"(d[9]), "+f"(d[10]), "+f"(d[11]), "+f"(d[12]), "+f"(d[13]), "+f"(d[14]), "+f"(d[15]),
          "+f"(d[16]), "+f"(d[17]), "+f"(d[18]), "+f"(d[19]), "+f"(d[20]), "+f"(d[21]), "+f"(d[22]), "+f"(d[23]),
          "+f"(d[24]), "+f"(d[25]), "+f"(d[26]), "+f"(d[27]), "+f"(d[28]), "+f"(d[29]), "+f"(d[30]), "+f"(d[31]),
          "+f"(d[32]), "+f"(d[33]), "+f"(d[34]), "+f"(d[35]), "+f"(d[36]), "+f"(d[37]), "+f"(d[38]), "+f"(d[39]),
          "+f"(d[40]), "+f"(d[41]), "+f"(d[42]), "+f"(d[43]), "+f"(d[44]), "+f"(d[45]), "+f"(d[46]), "+f"(d[47]),
          "+f"(d[48]), "+f"(d[49]), "+f"(d[50]), "+f"(d[51]), "+f"(d[52]), "+f"(d[53]), "+f"(d[54]), "+f"(d[55]),
          "+f"(d[56]), "+f"(d[57]), "+f"(d[58]), "+f"(d[59]), "+f"(d[60]), "+f"(d[61]), "+f"(d[62]), "+f"(d[63]),
          "+f"(d[64]), "+f"(d[65]), "+f"(d[66]), "+f"(d[67]), "+f"(d[68]), "+f"(d[69]), "+f"(d[70]), "+f"(d[71]),
          "+f"(d[72]), "+f"(d[73]), "+f"(d[74]), "+f"(d[75]), "+f"(d[76]), "+f"(d[77]), "+f"(d[78]), "+f"(d[79]),
          "+f"(d[80]), "+f"(d[81]), "+f"(d[82]), "+f"(d[83])
        : "r"(a0), "r"(a1), "r"(db), "r"(0), "n"(HB));
}

struct Ring {
    uint32_t slot, ph;
    __device__ __forceinline__ void next() { if (++slot == NSLOT) { slot = 0; ph ^= 1; } }
    __device__ __forceinline__ void next2() { ph ^= slot == 5; slot = __byte_perm(0x06030201u, 0x00040005u, 0x7770 + slot); }
};
struct Slot {
    uint32_t dst, bar, ph;
    __device__ __forceinline__ void next(uint32_t bars) {
        dst += SLOT; bar += 8;
        if (bar == bars + 8 * NSLOT) { dst -= NSLOT * SLOT; bar = bars; ph ^= 1; }
    }
};
__device__ __forceinline__ uint32_t xslot(int i) { return __byte_perm(0x04130e0cu, 0x00130e0cu, 0x7770 + i); }
__device__ __forceinline__ uint32_t wslot(int i) { return __byte_perm(0x06001510u, 0x00151009u, 0x7770 + i); }

constexpr uint32_t HI_SW = desc_hi(1024, 1);

struct Mma {
    uint32_t bars, rel;
    bool lead;
    int wg, w;
    Ring r;
    uint32_t prev;
    __device__ __forceinline__ void release_pair(uint32_t s) { if (lead) mbar_arrive4_remote(rel + B_EMPTY + 8 * s); }
    __device__ __forceinline__ void release(uint32_t s) { if (lead) mbar_arrive_n<4>(bars + B_EMPTY + 8 * s); }
    template <bool G1>
    __device__ __forceinline__ void run(float (&a)[56], int n, int first, int last, int lag, int accumulate, int ts) {
#pragma unroll 1
        for (int i = 0; i < n; i++) {
            if (lag && i == (wg ? n - lag : -1)) {
                if (!G1) { wg_wait<0>(); release(prev); last = first; }
                bar_sync(7, 256);
            }
            const bool seen = !G1 && last == first;
            const uint32_t s = seen ? n - 1 - i : r.slot;
            if (!seen) mbar_wait(bars + B_FULL + 8 * s, r.ph);
            if (G1) r.next(); else r.next2();
            if (!TSQ || !i) TS0(G1 ? 2 : 8, ts + i + wg * 68);
            const uint32_t dB = s * (SLOT >> 4), dA = dB + wg * 512;
            wg_fence();
#pragma unroll
            for (int k = 0; k < 4; k++) {
                wgmma_n112<1, 1, HI_SW, desc_hi(G1 ? 256 : 1024, 0)>(a, dA + desc_lo(k * 2048, 8192), dB + desc_lo(16384 + k * (G1 ? SLAB : 256), 128), k > 0 || accumulate || i > 0);
                if (k == 1) {
                    wg_commit(); wg_wait<1>();
                    if ((uint32_t)(i - first) < (uint32_t)(last - first)) release(prev);
                    if (G1 && lag && i == (wg ? -1 : n - 1)) bar_arrive(7, 256);
                    if (TSQ && i) TS0(G1 ? 2 : 8, ts + i + wg * 68);
                }
            }
            wg_commit();
            prev = s;
        }
    }
    __device__ __forceinline__ void run_o(float (&a)[56]) {
#pragma unroll 1
        for (int i = 0; i < 2; i++) {
            const uint32_t s = r.slot, dB = s * (SLOT >> 4), dA = dB + wg * (HALF >> 4);
            mbar_wait(bars + B_FULL + 8 * s, r.ph);
            TS0(8, 48 + 2 * i + wg * 68);
            wg_fence();
#pragma unroll
            for (int k = 0; k < 7; k++) {
                if (k == 3) { mbar_wait(bars + B_FULL + 8 * s + 8, r.ph); wg_fence(); }
                wgmma_n112<0, 1, desc_hi(128, 0), desc_hi(256, 0)>(a, dA + desc_lo(k * 2048 + (k > 3) * (SLOT - HALF), k == 3 ? SLOT - 6144 : 1024),
                                                                   dB + desc_lo(16384 + k * SLAB + (k > 2) * (SLOT - 3 * SLAB), 128), k > 0 || i > 0);
                if (k & 1) wg_commit();
                if (k == 1) { wg_wait<1>(); if (i) release(prev); }
                if (k == 5) { wg_wait<1>(); release(s); }
            }
            wg_commit();
            prev = s + 1;
            r.slot++; r.next2();
        }
    }
};

__global__ void __cluster_dims__(2, 1, 1) __launch_bounds__(NTHREADS, 1)
fused_kernel(const __nv_bfloat16* __restrict__ x, const __nv_bfloat16* __restrict__ b1, const __nv_bfloat16* __restrict__ b2, const __nv_bfloat16* __restrict__ wo, __nv_bfloat16* out, Scratch* G,
             const __nv_bfloat16* __restrict__ w1,
             const __grid_constant__ Params P) {
    extern __shared__ __align__(1024) uint8_t smem[];
    const uint32_t sbase = (uint32_t)__cvta_generic_to_shared(smem);
    const uint32_t bars = sbase + OFF_BAR;
    const uint32_t rank = blockIdx.x & 1, pr = blockIdx.x >> 1;
    const uint32_t row0 = blockIdx.x * 16;
    if (threadIdx.x == 0) {
        TS(15, 0);
        mbar_init(bars + B_ROW, 1);
        asm volatile("fence.mbarrier_init.release.cluster;" ::: "memory");
        bulk_load(sbase + OFF_Y, x + row0 * D_, TILEB, bars + B_ROW);
        mbar_expect(bars + B_ROW, TILEB);
        TS(1, 97);
    }
    const int lane = threadIdx.x & 31;
    const int warp = __shfl_sync(~0u, threadIdx.x >> 5, 0), w = warp & 3;
    if (elect()) {
        const uint32_t first = bars + warp * 24, count = warp < 7 ? 1 : warp < 9 ? 18 - 2 * warp : 16;
#pragma unroll
        for (int i = 0; i < 3; i++) mbar_init(first + 8 * i, count);
        asm volatile("fence.mbarrier_init.release.cluster;" ::: "memory");
    }
    __syncwarp();
    asm volatile("barrier.cluster.arrive.relaxed.aligned;" ::: "memory");
    const uint32_t pv = pr < 4 ? pr * 8 + 36 : pr - 4 + (max((int)pr - 33, 0) * 37 >> 8);
    const uint32_t gp = (pv + 4) & 7, hp = pv >> 3;
    const uint32_t tb = gp * 2 + rank, c = hp * 16 + tb;
    const bool has_g1 = gp > 0;
    const uint32_t nt1 = hp & 3, ft = max((int)gp - 1, 0) * 2 + (hp >> 2);
    const uint32_t nt2 = (hp & 1) * 2 + rank, mt = (gp & 3) * 4 + (hp >> 1), ks = gp >> 2;
    asm volatile("barrier.cluster.wait.aligned;" ::: "memory");

    if (warp == 8) {
        uint32_t kw = (gp & 1) * 192, kx;
        if (elect()) {
            mbar_expect(bars + B_QFULL, WSLOT);
            tma3d(sbase + xslot(0) * 8192, &P.tmX, bars + B_FULL, 0, tb * 64, 0);
            tma3d_pair(sbase + wslot(0) * 8192 + rank * 12288, &P.tmWqkv, bars + B_QFULL, (hp * 56) & ~15, rank * 32, 0);
            TS(1, 23);
            uint32_t due = (uint32_t)clock() + PACE, ep = ld_relaxed(&G->epoch[c]);
            uint32_t spins = sbase == (rank << 24 | SMEM0) ? 0 : SPIN_LIMIT;
#pragma unroll 1
            for (int i = 1; i < 8; i++) {
                kx = kw; kw += 64;
                if (i >= 5) mbar_wait_bounded(bars + B_QEMPTY + 8 * (i - 5), 0, spins);
                else { while ((int)((uint32_t)clock() - due) < 0) {} due += PACE; }
                if (kw == D_) kw = 64;
                if (i < 4) kx = kw;
                const int ix = i - (i > 4);
                if (i < 7) mbar_expect(bars + B_QFULL + 8 * i, WSLOT);
                if (i != 4) tma3d(sbase + xslot(ix) * 8192, &P.tmX, bars + B_FULL + 8 * ix, kx, tb * 64, 0);
                if (i & (i >> 2)) mbar_wait_bounded(bars + B_CS - 20 + 4 * i, 0, spins);
                if (i < 7) tma3d_pair(sbase + wslot(i) * 8192 + rank * 12288, &P.tmWqkv, bars + B_QFULL + 8 * i, (hp * 56) & ~15, kw + rank * 32, 0);
            }
            ep++;
            Slot r{sbase, bars, 0};
            if (has_g1) {
                const uint8_t* src = G->H[nt1][rank * 16];
                const int row = rank * 1024;
                mbar_expect(bars + B_FULL, 16384 + TILEB);
                tma3d(sbase, &P.tmW1, bars + B_FULL, 0, row, ft * 2);
                wait_flag(G->flag[1] + rank * 2, 20 * ep, spins);
                TS(1, 16);
#pragma unroll 1
                for (int j = 64;; j += 64) {
                    bulk_load(r.dst + 16384, src, TILEB, r.bar + B_FULL);
                    src += TILEB;
                    r.next(bars);
                    if (j == 1024) break;
                    mbar_wait_bounded(r.bar + B_EMPTY, r.ph, spins);
                    if (j < 14 * 64) TS(2, 146 + j / 64);
                    mbar_expect(r.bar + B_FULL, 16384 + TILEB);
                    tma3d(r.dst, &P.tmW1, r.bar + B_FULL, 0, row + j, ft * 2);
                }
                mbar_arrive(bars + B_FULL + 48); mbar_arrive_n<16>(bars + B_EMPTY + 48);
#pragma unroll
                for (int i = 0; i < 4; i++) mbar_expect(bars + B_X + 8 * i, (i & 1) ? 3072 : 4096);
            } else {
                due = (uint32_t)clock();
#pragma unroll 1
                for (int j = PF0; j < PF1; j++) {
                    asm volatile("cp.async.bulk.prefetch.L2.global [%0], %1;" ::"l"(w1 + (rank * 1024 + j * 64 + hp * 8) * F_), "n"(16 * F_) : "memory");
                    due += PF;
                    while ((int)((uint32_t)clock() - due) < 0) {}
                }
            }
            const uint8_t *so = G->O[mt][ks * 4], *sw = G->Wo[nt2][ks * 4];
            wait_flag2(G->flag[16 + mt], 8 * ep, G->flag[0], 16 * ep, spins);
            TS(4, 18);
#pragma unroll 1
            for (int j = 0; j < 4 * TILEB; j += TILEB) {
                mbar_wait_bounded(r.bar + B_EMPTY, r.ph, spins);
                mbar_expect(r.bar + B_QFULL, TILEB);
                bulk_load(r.dst, so + j, TILEB, r.bar + B_QFULL);
                bulk_load(r.dst + 16384, sw + j, (r.bar & 8) ? TILEB : 3 * SLAB, r.bar + B_FULL);
                r.next(bars);
            }
            Ring q{has_g1 ? 2u : 6u, has_g1}, p{q.slot, !has_g1};
#pragma unroll 1
            for (int j = 0; j < 14 * 128; j += 128) {
                mbar_wait_bounded(bars + B_EMPTY + 8 * q.slot, q.ph, spins);
                if (LEADW && j >= LEADW * 128 && j < LEADN * 128) { mbar_wait_bounded(bars + B_FULL + 8 * p.slot, p.ph, spins); p.next2(); }
                TS(8, 176 + j / 128);
                tma3d(sbase + q.slot * SLOT, &P.tmW2, bars + B_FULL + 8 * q.slot, 0, ks * 896 + j - (j < 896 ? 0 : 832), mt * 2);
                q.next2();
            }
            mbar_wait_bounded(bars + B_END, 0, spins);
        }
    } else if (warp > 8) {
        const uint32_t ep = ld_relaxed(&G->epoch[c]) + 1;
        const uint8_t* src = G->U[nt2][ks * 14];
        uint32_t spins = 0, bad;
        {
            uint2* cs = G->colsum[hp][0];
            if (w == 2) {
                bar_sync(6, 288);
                TS(1, 8);
                stg1((uint32_t*)(G->stat + row0) + lane, tag(__float_as_uint(lds1f(sbase + OFF_ST + lane * 4)), ~lane & 1, ep));
                if (elect()) {
                    fence_async_shared();
#pragma unroll
                    for (int i = 0; i < 4; i++) bulk_store(G->H[i][0] + row0 * (SLAB / 16), sbase + OFF_X + i * HSTG, SLAB);
                    bulk_flush();
                    TS(1, 99);
                    signal(G->flag[1] + (row0 >> 10) * 2 + ((row0 & 1023) >= 320));
                }
                __syncwarp();
            } else {
                const uint32_t word = rank * 16 + (w & 2) * 4 + (lane & 7), done = mapa(bars + B_CS, rank ^ (lane & 1));
                const uint32_t from = (sbase + word * 4 + (gp >> 2) * 12288 + (gp & 2) * 1024) ^ ((lane >> 3) * 288);
                auto swz = [](uint32_t a) { return a ^ ((a >> 3) & 0x70); };
                const uint32_t lin = sbase + lane * 128 + (hp & 1) * 16, f0 = swz(lin + 80) + 8192, f1 = swz(lin + 96) + 8192, to = swz(lin + 112);
                float s[6] = {};
#pragma unroll 1
                for (int i = 0; i < 7; i++) {
                    const uint32_t o = wslot(i) * 8192, a0 = from + o, a1 = a0 ^ 144;
                    mbar_wait(bars + B_QFULL + 8 * i, 0);
                    if ((i ^ (w >> 1)) & 1) {
                        const uint4 v0 = lds4(f0 + o), v1 = lds4(f1 + o), v2 = lds4(f0 + o + 12288), v3 = lds4(f1 + o + 12288);
                        sts4(to + o, v0); sts4(to + o + 4096, v1); sts4(to + o + 12288, v2); sts4(to + o + 16384, v3);
                        fence_async_shared();
                        __syncwarp();
                        if (elect()) mbar_expect(bars + B_FULL + 8 * i, 16384);
                    }
                    if (i > 3 || i < (gp & 1)) continue;
                    if (w == 1) TS(1, 66);
                    uint32_t v[12];
#pragma unroll
                    for (int k = 0; k < 12; k++) v[k] = __float_as_uint(lds1f(((k & 1) ? a1 : a0) + (k & 2) * 512 + (k >> 2) * 4096));
#pragma unroll
                    for (int k = 0; k < 12; k++) { s[(k >> 2) * 2] += bf_lo(v[k]); s[(k >> 2) * 2 + 1] += bf_hi(v[k]); }
                    __syncwarp();
                    if ((i & 1) && lane < 2) mbar_arrive_remote(done + (i & 2) * 4);
                    if (i < 3) continue;
#pragma unroll
                    for (int k = 0; k < 6; k++) { s[k] += __shfl_xor_sync(~0u, s[k], 8); s[k] += __shfl_xor_sync(~0u, s[k], 16); }
                    const float s0 = lane < 8 ? s[0] : lane < 16 ? s[2] : s[4], s1 = lane < 8 ? s[1] : lane < 16 ? s[3] : s[5];
                    if (lane < 24) cs[gp * 96 + (lane >> 3) * 32 + word] = make_uint2(tag(__float_as_uint(s0), 1, ep), __float_as_uint(s1));
                    if (w == 1) TS(1, 24);
                }
            }
            bar_sync(1, 96);
            if (w == 1) TS(1, 98);
            const int i0 = threadIdx.x - 288, j0 = i0 - (hp & 1) * 4;
            cs += i0 + ((j0 & 92) == 28 ? (j0 & 32 ? 28 : 56) : 0);
            uint2 u[8];
            uint4 sv;
            do {
                sv = ld_relaxed4(G->stat + tb * 128 + (i0 & 63) * 2);
                bad = sv.x ^ ep;
#pragma unroll
                for (int i = 0; i < 8; i++) { u[i] = ld_relaxed2(cs + i * 96); bad = or_diff(bad, u[i].x, ep); }
                if (bad & 1) TS(1, 3);
            } while (bad & 1);
            if (w < 3) sts4(sbase + OFF_ST + i0 * 16, sv);
#pragma unroll
            for (int e = 0; e < 2; e++) {
                float f = 0.f;
#pragma unroll
                for (int i = 0; i < 8; i++) f += __uint_as_float(e ? u[i].y : u[i].x);
                const uint32_t hi = pack2(f, f);
                sts4(sbase + OFF_X + i0 * 32 + e * 16, make_uint4(hi, pack2(f - bf_hi(hi), f - bf_hi(hi)), 0, 0));
            }
            sts1(bars + 8 * NBAR, ep);
            fence_async_shared();
            __syncwarp();
            bar_arrive(8, 224); bar_arrive(9, 224);
            TS(1, 90 + w);
        }
        if (w < 3) {
            if (w == 1) {
                if (elect()) {
                    wait_flag(G->flag[1] + rank * 2 + 1, 44 * ep, spins);
                    mbar_arrive_n<16>(bars + B_EMPTY + 8 * 5);
                    TS(1, 96);
                }
                __syncwarp();
                if (!has_g1) { bar_sync(5, 288); if (elect()) signal(G->flag[0]); __syncwarp(); TS(2, 26); }
            }
            mbar_wait(bars + B_HALO, 0);
            uint32_t slot = (has_g1 ? 16 % NSLOT : 0) + w - 1, ph = ~0u;
#pragma unroll 1
            for (int i = w - 1; i < 18;) {
                const uint32_t d0 = sbase + slot * SLOT + (i < 4 ? 0 : 16384), landed = bars + B_QFULL + 8 * slot;
                mbar_wait(landed, (ph >> slot) & 1);
                ph ^= 1 << slot;
                if (i < 8) TS(4, 82 + i);
                if (i >= 4) TS(8, 156 + i);
                bad = 0;
#pragma unroll
                for (int k = 0; k < 14; k++) bad = or_diff(bad, __float_as_uint(lds1f(d0 + k * 1024 + lane * 32 + (lane >> 2) * 4)), ep);
                if (__any_sync(~0u, bad & 1)) {
                    if (elect()) {
                        const uint8_t* cur = (i < 4 ? G->O[mt][ks * 4] : src - 4 * TILEB) + i * TILEB;
                        fence_async_shared();
                        mbar_expect(landed, TILEB);
                        bulk_load(d0, cur, TILEB, landed);
                    }
                    TS(4, i < 4 ? 94 : 95);
                } else {
                    if (elect()) mbar_expect(landed + (B_FULL - B_QFULL), i < 4 ? (2 + w) * SLAB : 16384);
                    i += __byte_perm(0x03020202u, 0x00010202u, 0x7770 + slot);
                    slot = __byte_perm(0x05060302u, 0x00040100u, 0x7770 + slot);
                }
            }
        } else {
            bar_sync(3, 288);
            __nanosleep(HALO_NS);
            uint4 v[7];
            do {
                bad = 0;
#pragma unroll
                for (int i = 0; i < 7; i++) { v[i] = ld_relaxed4(G->halo[c - (tb > 0)] + i * 512 + lane * 16); bad = or_diff(bad, v[i].x, ep); }
            } while (bad & 1);
#pragma unroll
            for (int i = 0; i < 7; i++) sts4(sbase + OFF_X + i * 512 + lane * 16, v[i]);
            __syncwarp();
            if (elect()) mbar_arrive(bars + B_HALO);
            TS(2, 21);
            bar_sync(2, 288);
            if (elect()) bulk_store(out + row0 * D_, sbase + OFF_Y, TILEB);
            __syncwarp();
            bar_sync(4, 288);
            if (elect()) {
                fence_async_shared();
                bulk_store(G->O[tb][hp], sbase + OFF_X, TILEB);
                bulk_flush();
                TS(2, 7);
                mbar_arrive_remote(mapa(bars + B_FREE, rank ^ 1));
                mbar_arrive(bars + B_FREE);
                hint(G->flag[16 + tb]);
                signal(G->flag[16 + (row0 >> 7)] + 1);
                TS(2, 22);
            }
            __syncwarp();
            uint32_t late = ~0u;
            const uint32_t* hints = G->flag[8 + nt2 * 2 + ks] + lane;
            mbar_wait(bars + (has_g1 ? B_X : B_FREE), 0);
            Ring r{has_g1 ? 2u : 6u, has_g1};
#pragma unroll 1
            for (int i = 0; i < 14; i++) {
                while ((late >> i) & 1) late = __ballot_sync(~0u, ld_relaxed(hints) != 2 * ep) & 127;
                if (i == 0) TS(4, 17);
                mbar_wait(bars + B_EMPTY + 8 * r.slot, r.ph);
                TS(8, 192 + i);
                if (elect()) {
                    mbar_expect(bars + B_QFULL + 8 * r.slot, TILEB);
                    bulk_load(sbase + r.slot * SLOT + 16384, src, TILEB, bars + B_QFULL + 8 * r.slot);
                }
                src += TILEB; r.next2();
            }
            if (elect()) {
                wait_flag(G->flag[16 + mt] + 1, 8 * ep, spins);
                mbar_arrive(bars + B_ROW);
                TS(2, 27);
                G->epoch[c] = ep;
            }
        }
    } else {
        const int wg = warp >> 2;
        Mma M{bars, mapa(bars, rank ^ (lane & 1)), (threadIdx.x & 127) < 2, wg, w, Ring{0, 1}, 0};
        const int r = lane >> 2, t = lane & 3;
        uint32_t ep;
        const uint32_t bias0 = ld_u16(b1 + ft * 128 + warp * 16 + r), bias1 = ld_u16(b1 + ft * 128 + warp * 16 + r + 8);
        const uint32_t kv = sbase + OFF_X + (w * 2 + wg) * KV + lane * 16;
        uint32_t q[8][2], k0[7], k1[14], v0[7];
        float f0, f1;
        {
            const int half = (lane >> 3) & 1, r16 = warp * 2 + (half ^ (lane >> 4)), nt = (lane >> 1) & 3;
            const uint32_t row = sbase + OFF_Y + r16 * (2 * D_), part = row + nt * 224 + half * 112 + (lane & 1) * 8;
            const uint32_t hb = sbase + OFF_X + nt * HSTG + r16 * 16 + (half ^ (row0 >> 10)) * (7 * 256) + (lane & 1) * 8;
            mbar_wait(bars + B_ROW, 0);
            TS0(1, 67);
            const float x0 = bf_lo(__float_as_uint(lds1f(row)));
            float d[28], m1 = 0.f, n1 = 0.f, m2 = 0.f, n2 = 0.f;
#pragma unroll
            for (int i = 0; i < 7; i++) {
                const uint2 v = lds2(part + i * 16);
#pragma unroll
                for (int k = 0; k < 2; k++) {
                    const float d0 = d[4 * i + 2 * k] = bf_lo(k ? v.y : v.x) - x0, d1 = d[4 * i + 2 * k + 1] = bf_hi(k ? v.y : v.x) - x0;
                    m1 += d0; n1 += d1; m2 = fmaf(d0, d0, m2); n2 = fmaf(d1, d1, n2);
                }
            }
            const float md = row_sum(m1 + n1) * (1.f / D_), var = fmaf(-md, md, row_sum(m2 + n2) * (1.f / D_)), nmean = -(x0 + md);
            const float rstd = rsq(var + LN_EPS);
            const float sc = rstd * rsq(fmaf(var * rstd, rstd, LN_EPS)), nb = -md * sc;
            sts2(sbase + OFF_ST + r16 * 8, __float_as_uint(rstd), pack2(nmean, nmean - bf_hi(pack2(nmean, nmean))));
#pragma unroll
            for (int i = 0; i < 7; i++) sts2(hb + i * 256, pack2(fmaf(d[4 * i], sc, nb), fmaf(d[4 * i + 1], sc, nb)), pack2(fmaf(d[4 * i + 2], sc, nb), fmaf(d[4 * i + 3], sc, nb)));
            TS0(1, 25);
            bar_arrive(6, 288);
            float acc[84];
#pragma unroll 1
            for (int kb = 0; kb < 7; kb++) {
                const bool held = kb == (wg ? 7 - HOLD : -1);
                if (held) { wg_wait<0>(); M.release_pair(4 - HOLD); TS0(1, 138); bar_sync(7, 256); }
                mbar_wait(bars + B_FULL + 8 * kb, 0);
                if (!TSQ || !kb) TS0(1, 68 + wg * 7 + kb);
                const uint32_t dA = (xslot(kb) + wg) * 512, dB = wslot(kb) * 512 + (hp & 1);
                wg_fence();
#pragma unroll
                for (int k = 0; k < 4; k++) {
                    wgmma_n168<0, 1, HI_SW, HI_SW>(acc, dA + desc_lo(k * 32, 16), dB + desc_lo((k & 1) * 2048 + (k >> 1) * 12288, 4096), k > 0 || kb > 0);
                    if (k == 0) { wg_commit(); wg_wait<1>(); if (kb > 0 && !held) M.release_pair(kb - 3); if (TSQ && kb) TS0(1, 68 + wg * 7 + kb); }
                }
                wg_commit();
            }
            if (wg == 0 && !LATEREL) bar_arrive(7, 256);
            if (wg == 0) TS0(1, 139);
            bar_sync(8 + wg, 224);
            if (wg == 0) TS0(1, 174);
            ep = __float_as_uint(lds1f(bars + 8 * NBAR));
            const uint32_t st = sbase + OFF_ST + (w * 32 + r * 2 + wg) * 8;
            const uint2 s0 = lds2(st), s1 = lds2(st + 128);
            const uint32_t a0 = t < 2 ? s0.y : 0, a1 = t < 2 ? s1.y : 0;
            wg_fence();
            wgmma_rs_n168<desc_hi(128, 0)>(acc, a0, a1, desc_lo(OFF_X, 0) + (hp & 1) * 8);
            wg_commit();
            if (wg == 0 && LATEREL) bar_arrive(7, 256);
            if (wg == 0) TS0(1, 175);
            wg_wait<1>();
            TS0(1, 190 + wg);
            M.release_pair(4);
            wg_wait<0>();
            pin(acc);
            TS0(1, 4 + 7 * wg);
            f0 = __uint_as_float(s0.x); f1 = __uint_as_float(s1.x);
#pragma unroll
            for (int g = 13; g >= 0; g--) {
                const float* a = acc + (g < 7 ? g + 8 : g < 12 ? g + 9 : g * 8 - 89) * 4;
                const float r0 = g < 7 ? f0 : f0 + f0, r1 = g < 7 ? f1 : f1 + f1;
                (g < 7 ? k0[g] : v0[g - 7]) = pack2(a[0] * r0, a[1] * r0);
                k1[g] = pack2(a[2] * r1, a[3] * r1);
            }
#pragma unroll
            for (int i = 0; i < 3; i++) stsm4(kv + 2 * KV + i * 512, k1[4 * i], k1[4 * i + 1], k1[4 * i + 2], k1[4 * i + 3]);
            stsm2(kv + 2 * KV + 1536, k1[12], k1[13]);
            if (w == 3) {
#pragma unroll
                for (int i = 0; i < 14; i++) stg1(G->halo[c] + wg * KV + lane * 4 + i * 128, tag(k1[i], t == 0, ep));
            }
            bar_arrive(3, 288);
#pragma unroll
            for (int g = 0; g < 7; g++) { q[g][0] = pack2(acc[4 * g], acc[4 * g + 1]); q[g][1] = pack2(acc[4 * g + 2], acc[4 * g + 3]); }
#pragma unroll
            for (int j = 0; j < 2; j++) { q[7][j] = t < 2 ? 0u : q[3][j]; q[3][j] = t < 2 ? q[3][j] : 0u; }
#pragma unroll
            for (int g = 0; g < 7; g++) v0[g] = transpose8(v0[g]);
        }
        TS0(1, 9 + 11 * wg);
        float a[56];
#pragma unroll
        for (int i = 0; i < 56; i++) asm volatile("" : "=f"(a[i]));
        if (__builtin_expect(!has_g1, 0)) {
            const int g = min(lane >> 1, 13), nt = rank * 2 + wg;
            const uint4* src = (const uint4*)(wo + (hp * 56 - (hp & 1) * 8 + w * 16 + (lane & 1)) * D_ + nt * 112) + g;
            uint4 v[8];
#pragma unroll
            for (int i = 0; i < 8; i++) v[i] = __ldg(src + i * (D_ / 4));
#pragma unroll
            for (int i = 0; i < 8; i++) ((uint4*)G->Wo[nt][hp])[w * (SLAB / 16) + g * 16 + (lane & 1) + 2 * i] = v[i];
            bar_arrive(5, 288);
        }
        M.run<true>(a, has_g1 ? PAUSE : 0, 1, 16, 0, 0, 32);
        {
            uint32_t kp[8], vv[14];
            TS0(2, 140 + wg);
            mbar_wait(bars + B_HALO, 0);
            TS0(2, 142 + wg);
            ldsm4(kp, kv); ldsm4(kp + 4, kv + (lane < 24 ? 512 : 0));
            const uint32_t va = kv + 896 + (lane & 8) * (2 * KV / 8 - 16) - (lane & 16) * 8;
            ldsm4t(vv, va); ldsm4t(vv + 4, va + 256); ldsm4t(vv + 8, va + 512); ldsm2t(vv + 12, va + 768);
            const bool e0 = 2 * t > r, e1 = 2 * t >= r;
            const uint32_t mk = (e0 ? 0xffffu : 0u) | (e1 ? 0xffff0000u : 0u);
            wg_wait<0>();
            pin(a);
            if (has_g1) M.release(M.prev);
            TS0(2, 144 + wg);
            bar_sync(2, 288);
            mbar_wait(bars + B_HALO, 0);
            TS0(2, 12 + 16 * wg);
            float sv[2][4];
#pragma unroll
            for (int h = 0; h < 2; h++) {
                const int ga = h * 4, gb = h * 4 + 1, gc = h * 4 + 2, gd = h * 4 + 3;
                float s[3][4] = {};
                mma16(s[0], q[ga][0], q[ga][1], q[gb][0], q[gb][1], kp[ga], kp[gb]);
                mma16(s[1], q[ga][0], q[ga][1], q[gb][0], q[gb][1], k0[ga], k0[gb]);
                mma16(s[2], q[ga][0], q[ga][1], q[gb][0], q[gb][1], k1[ga], k1[gb]);
                mma16(s[0], q[gc][0], q[gc][1], q[gd][0], q[gd][1], kp[gc], kp[gd]);
                mma16(s[1], q[gc][0], q[gc][1], q[gd][0], q[gd][1], k0[gc], k0[3]);
                mma16(s[2], q[gc][0], q[gc][1], q[gd][0], q[gd][1], k1[gc], k1[3]);
                if ((tb | w) == 0) s[0][0] = s[0][1] = -1e30f;
                sv[h][0] = e0 ? s[0][0] : s[1][0];
                sv[h][1] = e1 ? s[0][1] : s[1][1];
                sv[h][2] = e0 ? s[1][2] : s[2][2];
                sv[h][3] = e1 ? s[1][3] : s[2][3];
            }
            uint32_t pp[2][2];
#pragma unroll
            for (int i = 0; i < 4; i++) {
                float* v = &sv[i >> 1][(i & 1) * 2];
                const float f = ((i & 1) ? f1 : f0) * QK_SCALE, m = quad_max(fmaxf(v[0], v[1])) * f;
                const float p0 = ex2(fmaf(v[0], f, -m)), p1 = ex2(fmaf(v[1], f, -m));
                const float inv = rcp(quad_sum(p0 + p1));
                pp[i >> 1][i & 1] = pack2(p0 * inv, p1 * inv);
            }
            uint32_t o[8][2];
#pragma unroll
            for (int i = 0; i < 8; i++) {
                const int h = i >> 2, g = i - h;
                float d[4] = {};
                mma16(d, pp[h][0] & mk, 0u, 0u, pp[h][1] & ~mk, vv[2 * g], vv[2 * g + 1]);
                mma8(d, pp[h][0] & ~mk, pp[h][1] & mk, v0[g]);
                o[i][0] = pack2(d[0], d[1]); o[i][1] = pack2(d[2], d[3]);
            }
            if (t >= 2) { o[3][0] = o[4][0]; o[3][1] = o[4][1]; }
            const int word = wg * 4 + t - (w & 1) * 4 - (r >> 2);
#pragma unroll
            for (int i = 0; i < 8; i++) { o[i][0] = tag(o[i][0], word == 0, ep); o[i][1] = tag(o[i][1], word == 2, ep); }
            const uint32_t dst = sbase + OFF_X + (w >> 1) * HALF + ((w & 1) * 32 + (lane & 15) * 2 + wg) * 16 + (lane >> 4) * 1024;
            stsm4(dst, o[0][0], o[0][1], o[1][0], o[1][1]);
            stsm4(dst + 2048, o[2][0], o[2][1], o[3][0], o[3][1]);
            stsm4(dst + 4096, o[5][0], o[5][1], o[6][0], o[6][1]);
            stsm2(dst + 6144, o[7][0], o[7][1]);
            if (ENDBAR) bar_sync(4, 288); else bar_arrive(4, 288);
            TS0(2, 10 + 19 * wg);
        }
        if (has_g1) {
            M.run<true>(a, 16 - PAUSE, 1, 16, LAG1, 1, 32 + PAUSE);
            mbar_wait(bars + B_FREE, 0);
            const uint32_t xb = sbase + OFF_X + wg * 8192 + (threadIdx.x & 127) * 16, xbar = bars + B_X + 16 * wg;
            const uint32_t rx = mapa(xb, rank ^ 1), rbar = mapa(xbar, rank ^ 1);
            wg_wait<0>();
            pin(a);
            M.release(M.prev);
            TS0(4, 5 + wg);
#pragma unroll
            for (int i = 0; i < 3; i++)
                st_async4(rx + i * 2048, rbar + 8 * (i >> 1), pack2(a[28 + 8 * i], a[29 + 8 * i]), pack2(a[30 + 8 * i], a[31 + 8 * i]), pack2(a[32 + 8 * i], a[33 + 8 * i]), pack2(a[34 + 8 * i], a[35 + 8 * i]));
            const uint32_t tail = 6144 - (threadIdx.x & 127) * 8;
            st_async2(rx + tail, rbar + 8, pack2(a[52], a[53]), pack2(a[54], a[55]));
            uint8_t* dst = G->U[nt1][((ft >= 7) + wg) * 7 + ft] + rank * HALF + w * 256 + lane * 4;
            uint32_t u[14];
#pragma unroll
            for (int i = 0; i < 28; i++) a[i] += bf_lo((i & 2) ? bias1 : bias0);
#pragma unroll
            for (int i = 0; i < 14; i++) {
                if (i % 8 == 0) {
                    if (i) TS0(4, 134 + wg);
                    mbar_wait(xbar + i, 0);
                    TS0(4, (i ? 136 : 1) + wg);
#pragma unroll
                    for (int k = i / 4; k < i / 4 + 2; k++) {
                        if (k < 3) { const uint4 v = lds4(xb + k * 2048); u[4 * k] = v.x; u[4 * k + 1] = v.y; u[4 * k + 2] = v.z; u[4 * k + 3] = v.w; }
                        else { const uint2 v = lds2(xb + tail); u[12] = v.x; u[13] = v.y; }
                    }
                    if (i && lane < 2) mbar_arrive(bars + B_EMPTY + 48);
                }
                if (i == HINT && threadIdx.x == 0) hint(G->flag[8 + nt1 * 2] + ft + (ft >= 7) * 25);
                stg1(dst + (i >> 1) * 1024 + (i & 1) * 128, tag(pack2(gelu2(a[2 * i] + bf_lo(u[i])), gelu2(a[2 * i + 1] + bf_hi(u[i]))), (lane & 7) == w * 2 + (i & 1), ep));
            }
            TS0(4, 30 + wg);
        } else {
            mbar_wait(bars + B_FREE, 0);
            if (lane < 2) mbar_arrive(bars + B_EMPTY + 48);
        }
        uint32_t c0 = ld_u16(b2 + mt * 128 + warp * 16 + r), c1 = ld_u16(b2 + mt * 128 + warp * 16 + r + 8);
        M.run_o(a);
        if (wg == 1) TS0(4, 13);
        c0 *= ks == 0 ? 0x10001u : 0u; c1 *= ks == 0 ? 0x10001u : 0u;
        M.run<false>(a, 14, 0, 14 - NSLOT, NSLOT + 1, 1, 52);
        mbar_wait(bars + B_ROW, 1);
        const uint32_t stg = sbase + (4 + (w >> 1)) * SLOT + wg * 8192 + (w & 1) * SLAB;
        const uint32_t sa = stg + (lane & 15) * 224 + (lane >> 4) * 16;
        wg_wait<0>();
        pin(a);
        TS0(8, 14 + wg);
#pragma unroll
        for (int i = 0; i < 7; i++)
            stsm4(sa + i * 32, half_plus(pack2(a[8 * i], a[8 * i + 1]), c0), half_plus(pack2(a[8 * i + 2], a[8 * i + 3]), c1),
                  half_plus(pack2(a[8 * i + 4], a[8 * i + 5]), c0), half_plus(pack2(a[8 * i + 6], a[8 * i + 7]), c1));
        if (wg == 0) bar_arrive(7, 256);
        if (!wg) TS0(8, 206);
        fence_async_shared();
        __syncwarp();
        if (elect()) {
            asm volatile("cp.reduce.async.bulk.tensor.2d.global.shared::cta.add.tile.bulk_group [%0, {%2, %3}], [%1];\ncp.async.bulk.commit_group;" ::"l"(&P.tmOut), "r"(stg), "r"(nt2 * 112), "r"(mt * 128 + warp * 16) : "memory");
            if (w == 0) mbar_arrive(bars + B_END);
            asm volatile("cp.async.bulk.wait_group.read 0;" ::: "memory");
        }
        TS0(15, wg ? 19 : 207);
        TSDUMP();
    }
}

typedef CUresult (*EncodeFn)(CUtensorMap*, CUtensorMapDataType, cuuint32_t, void*, const cuuint64_t*, const cuuint64_t*, const cuuint32_t*, const cuuint32_t*,
                             CUtensorMapInterleave, CUtensorMapSwizzle, CUtensorMapL2promotion, CUtensorMapFloatOOBfill);

void make_map(EncodeFn enc, CUtensorMap* tm, const void* base, bool swizzle, int d0, int d1, int d2, int s1, int s2, int b0, int b1, int b2) {
    const cuuint64_t dims[3] = {(cuuint64_t)d0, (cuuint64_t)d1, (cuuint64_t)d2}, strides[2] = {(cuuint64_t)s1 * 2, (cuuint64_t)s2 * 2};
    const cuuint32_t box[3] = {(cuuint32_t)b0, (cuuint32_t)b1, (cuuint32_t)b2}, es[3] = {1, 1, 1};
    enc(tm, CU_TENSOR_MAP_DATA_TYPE_BFLOAT16, d2 ? 3 : 2, (void*)base, dims, strides, box, es, CU_TENSOR_MAP_INTERLEAVE_NONE,
        swizzle ? CU_TENSOR_MAP_SWIZZLE_128B : CU_TENSOR_MAP_SWIZZLE_NONE, CU_TENSOR_MAP_L2_PROMOTION_L2_128B, CU_TENSOR_MAP_FLOAT_OOB_FILL_NONE);
}

}

extern "C" void kernel_launch(void* const* d_in, const int* in_sizes, int n_in, void* d_out, int out_size) {
    static EncodeFn enc = nullptr;
    static Scratch* scratch = nullptr;
    if (!enc) {
        void* fn = nullptr;
        cudaDriverEntryPointQueryResult qr;
        cudaGetDriverEntryPoint("cuTensorMapEncodeTiled", &fn, cudaEnableDefault, &qr);
        enc = (EncodeFn)fn;
        cudaGetSymbolAddress((void**)&scratch, g_s);
        cudaFuncSetAttribute(fused_kernel, cudaFuncAttributeMaxDynamicSharedMemorySize, SMEM_BYTES);
    }
    Params P;
    const __nv_bfloat16* x = (const __nv_bfloat16*)d_in[0];
    make_map(enc, &P.tmX, x, true, D_, S_ / 2, 2, 2 * D_, D_, 64, 64, 2);
    make_map(enc, &P.tmWqkv, d_in[1], true, D_, D_, 3, 3 * D_, D_, 64, 32, 3);
    make_map(enc, &P.tmW1, d_in[4], true, 64, S_, F_ / 64, F_, 64, 64, 64, 2);
    make_map(enc, &P.tmW2, d_in[6], true, 64, F_, S_ / 64, S_, 64, 64, 64, 2);
    make_map(enc, &P.tmOut, d_out, false, D_, S_, 0, D_, 0, 112, 16, 1);
    fused_kernel<<<NCTA, NTHREADS, SMEM_BYTES, cudaStreamPerThread>>>(x, (const __nv_bfloat16*)d_in[5], (const __nv_bfloat16*)d_in[7], (const __nv_bfloat16*)d_in[2], (__nv_bfloat16*)d_out, scratch,
                                                                      (const __nv_bfloat16*)d_in[4], P);
}
```

```cpp
#include <cuda_runtime.h>
#include <cuda_bf16.h>
#include <cuda.h>
#include <stdint.h>

#define HALO_NS 300
#define HINT 5
#define HOLD 1
#define LATEREL 1
#define PF 400
#define PF0 2
#define PF1 8
#define ENDBAR 1
#define LEADW 4
#define LEADN 7
#define TSQ 0
#define PACE 600
#define PAUSE 8
#define LAG1 4

namespace {

constexpr int S_ = 2048, D_ = 448, F_ = 1792;
constexpr int NCTA = 128, NTHREADS = 384;
constexpr int NSLOT = 6, SLOT = 32768, WSLOT = 24576, TILEB = 14336, SLAB = 3584, HALF = 7168;
constexpr int KV = 1792, HSTG = SLAB + 32, PITCH = 240;
constexpr int OFF_X = NSLOT * SLOT;
constexpr int OFF_Y = OFF_X + 10 * KV;
constexpr int OFF_ST = OFF_Y + TILEB;
constexpr int OFF_BAR = OFF_ST + 1024;
constexpr int SMEM_BYTES = OFF_BAR + 1280;
constexpr uint32_t SMEM0 = 1024;
constexpr int B_QFULL = 0, B_FULL = 56, B_HALO = 128, B_X = 136, B_CS = 168, B_FREE = 192, B_END = 200, B_QEMPTY = 216, B_EMPTY = 232, B_ROW = 288, NBAR = 37;
constexpr float LN_EPS = 1e-5f, QK_SCALE = 0.1889822365046136f * 1.4426950408889634f;
constexpr int SPIN_LIMIT = 1 << 22;

struct Scratch {
    uint8_t H[4][32][TILEB];
    uint8_t U[4][28][TILEB];
    uint8_t O[16][8][TILEB];
    uint8_t Wo[4][8][TILEB];
    uint8_t halo[NCTA][2 * KV];
    uint2 stat[S_];
    uint2 colsum[8][8][96];
    uint32_t flag[32][32];
    uint32_t epoch[NCTA];
};
__device__ __align__(1024) Scratch g_s;

#define TS(g, i)
#define TS0(g, i)
#define TSDUMP()

struct Params {
    CUtensorMap tmX, tmWqkv, tmW1, tmW2, tmOut;
};

__device__ __forceinline__ bool elect() {
    uint32_t p;
    asm volatile("{\n.reg .pred p;\nelect.sync _|p, 0xffffffff;\nselp.u32 %0, 1, 0, p;\n}" : "=r"(p));
    return p;
}
__device__ __forceinline__ void mbar_init(uint32_t b, uint32_t c) { asm volatile("mbarrier.init.shared::cta.b64 [%0], %1;" ::"r"(b), "r"(c) : "memory"); }
__device__ __forceinline__ void mbar_expect(uint32_t b, uint32_t tx) { asm volatile("mbarrier.arrive.expect_tx.shared::cta.b64 _, [%0], %1;" ::"r"(b), "r"(tx) : "memory"); }
__device__ __forceinline__ void mbar_arrive(uint32_t b) { asm volatile("mbarrier.arrive.shared::cta.b64 _, [%0];" ::"r"(b) : "memory"); }
template <int N> __device__ __forceinline__ void mbar_arrive_n(uint32_t b) { asm volatile("mbarrier.arrive.shared::cta.b64 _, [%0], %1;" ::"r"(b), "n"(N) : "memory"); }
__device__ __forceinline__ void mbar_arrive4_remote(uint32_t b) { asm volatile("mbarrier.arrive.shared::cluster.b64 _, [%0], 4;" ::"r"(b) : "memory"); }
__device__ __forceinline__ void mbar_arrive_remote(uint32_t b) { asm volatile("mbarrier.arrive.shared::cluster.b64 _, [%0];" ::"r"(b) : "memory"); }
#define MBAR_WAIT_ASM(SEM) \
    asm volatile("{\n.reg .pred p;\nWAIT:\nmbarrier.try_wait.parity" SEM ".shared::cta.b64 p, [%0], %1;\n@!p bra WAIT;\n}" ::"r"(b), "r"(parity) : "memory")
__device__ __forceinline__ void mbar_wait(uint32_t b, uint32_t parity) { MBAR_WAIT_ASM(""); }
__device__ __forceinline__ void mbar_wait_bounded(uint32_t b, uint32_t parity, uint32_t& n) {
    asm volatile("{\n.reg .pred p;\nWAIT:\nadd.u32 %0, %0, 1;\nsetp.gt.u32 p, %0, %3;\n@p st.global.u32 [%4], %0;\n"
                 "mbarrier.try_wait.parity.shared::cta.b64 p, [%1], %2;\n@!p bra WAIT;\n}" : "+r"(n) : "r"(b), "r"(parity), "n"(SPIN_LIMIT), "l"(0ull) : "memory");
}
__device__ __forceinline__ uint32_t mapa(uint32_t a, uint32_t rank) { uint32_t r; asm("mapa.shared::cluster.u32 %0, %1, %2;" : "=r"(r) : "r"(a), "r"(rank)); return r; }
__device__ __forceinline__ void tma3d(uint32_t dst, const CUtensorMap* tm, uint32_t bar, int c0, int c1, int c2) {
    asm volatile("cp.async.bulk.tensor.3d.shared::cluster.global.mbarrier::complete_tx::bytes [%0], [%1, {%3, %4, %5}], [%2];" ::"r"(dst), "l"(tm), "r"(bar), "r"(c0), "r"(c1), "r"(c2) : "memory");
}
__device__ __forceinline__ void tma3d_pair(uint32_t dst, const CUtensorMap* tm, uint32_t bar, int c0, int c1, int c2) {
    asm volatile("cp.async.bulk.tensor.3d.shared::cluster.global.mbarrier::complete_tx::bytes.multicast::cluster [%0], [%1, {%3, %4, %5}], [%2], %6;" ::"r"(dst), "l"(tm), "r"(bar), "r"(c0), "r"(c1), "r"(c2), "h"((uint16_t)3) : "memory");
}
__device__ __forceinline__ void bulk_load(uint32_t dst, const void* src, uint32_t bytes, uint32_t bar) {
    asm volatile("cp.async.bulk.shared::cluster.global.mbarrier::complete_tx::bytes [%0], [%1], %2, [%3];" ::"r"(dst), "l"(src), "r"(bytes), "r"(bar) : "memory");
}
__device__ __forceinline__ void bulk_store(void* dst, uint32_t src, uint32_t bytes) {
    asm volatile("cp.async.bulk.global.shared::cta.bulk_group [%0], [%1], %2;" ::"l"(dst), "r"(src), "r"(bytes) : "memory");
}
__device__ __forceinline__ uint32_t ld_u16(const void* p) { uint32_t v; asm volatile("ld.global.nc.u16 %0, [%1];" : "=r"(v) : "l"(p)); return v; }
__device__ __forceinline__ uint32_t ld_relaxed(const uint32_t* p) { uint32_t v; asm volatile("ld.relaxed.gpu.global.u32 %0, [%1];" : "=r"(v) : "l"(p) : "memory"); return v; }
__device__ __forceinline__ void bulk_flush() { asm volatile("cp.async.bulk.commit_group;\ncp.async.bulk.wait_group 0;" ::: "memory"); }
__device__ __forceinline__ void signal(uint32_t* flag) { asm volatile("fence.acq_rel.gpu;\nred.relaxed.gpu.global.add.u32 [%0], 1;" ::"l"(flag) : "memory"); }
__device__ __forceinline__ void hint(uint32_t* flag) { asm volatile("red.relaxed.gpu.global.add.u32 [%0], 1;" ::"l"(flag) : "memory"); }
__device__ __forceinline__ uint32_t tag(uint32_t v, uint32_t mask, uint32_t parity) { return (v & ~mask) | (parity & mask); }
__device__ __forceinline__ uint32_t or_diff(uint32_t acc, uint32_t v, uint32_t parity) { asm("lop3.b32 %0, %0, %1, %2, 0xf6;" : "+r"(acc) : "r"(v), "r"(parity)); return acc; }
__device__ __forceinline__ uint4 ld_relaxed4(const void* p) {
    uint4 v;
    asm volatile("ld.relaxed.gpu.global.v4.u32 {%0, %1, %2, %3}, [%4];" : "=r"(v.x), "=r"(v.y), "=r"(v.z), "=r"(v.w) : "l"(p) : "memory");
    return v;
}
__device__ __forceinline__ uint2 ld_relaxed2(const void* p) { uint2 v; asm volatile("ld.relaxed.gpu.global.v2.u32 {%0, %1}, [%2];" : "=r"(v.x), "=r"(v.y) : "l"(p) : "memory"); return v; }
__device__ __forceinline__ void sts4(uint32_t a, uint4 v) { asm volatile("st.shared.v4.b32 [%0], {%1, %2, %3, %4};" ::"r"(a), "r"(v.x), "r"(v.y), "r"(v.z), "r"(v.w) : "memory"); }
__device__ __forceinline__ void sts1(uint32_t a, uint32_t v) { asm volatile("st.shared.b32 [%0], %1;" ::"r"(a), "r"(v) : "memory"); }
__device__ __forceinline__ void sts2(uint32_t a, uint32_t v0, uint32_t v1) { asm volatile("st.shared.v2.b32 [%0], {%1, %2};" ::"r"(a), "r"(v0), "r"(v1) : "memory"); }
__device__ __forceinline__ void stg1(void* p, uint32_t v) { asm volatile("st.global.b32 [%0], %1;" ::"l"(p), "r"(v) : "memory"); }
__device__ __forceinline__ void fence_async_shared() { asm volatile("fence.proxy.async.shared::cta;" ::: "memory"); }
#define BOUND "add.u32 %0, %0, 16;\nsetp.gt.u32 p, %0, %1;\n@p st.global.u32 [%2], %0;\n"
__device__ __forceinline__ void wait_flag(const uint32_t* p, uint32_t target, uint32_t& n) {
    asm volatile("{\n.reg .pred p;\n.reg .u32 v;\nPOLL:\n" BOUND "ld.acquire.gpu.global.u32 v, [%3];\nsetp.ne.u32 p, v, %4;\n@p bra POLL;\nfence.proxy.async.global;\n}"
                 : "+r"(n) : "n"(SPIN_LIMIT), "l"(0ull), "l"(p), "r"(target) : "memory");
}
__device__ __forceinline__ void wait_flag2(const uint32_t* h, uint32_t th, const uint32_t* p, uint32_t target, uint32_t& n) {
    asm volatile("{\n.reg .pred p;\n.reg .u32 u, v;\nPOLL:\n" BOUND "ld.relaxed.gpu.global.u32 u, [%3];\nld.acquire.gpu.global.u32 v, [%5];\nsetp.ne.u32 p, u, %4;\nsetp.ne.or.u32 p, v, %6, p;\n@p bra POLL;\nfence.proxy.async.global;\n}"
                 : "+r"(n) : "n"(SPIN_LIMIT), "l"(0ull), "l"(h), "r"(th), "l"(p), "r"(target) : "memory");
}
__device__ __forceinline__ void bar_sync(int id, int n) { asm volatile("bar.sync %0, %1;" ::"r"(id), "r"(n) : "memory"); }
__device__ __forceinline__ void bar_arrive(int id, int n) { asm volatile("bar.arrive %0, %1;" ::"r"(id), "r"(n) : "memory"); }
__device__ __forceinline__ void wg_fence() { asm volatile("wgmma.fence.sync.aligned;" ::: "memory"); }
__device__ __forceinline__ void wg_commit() { asm volatile("wgmma.commit_group.sync.aligned;" ::: "memory"); }
template <int N> __device__ __forceinline__ void wg_wait() { asm volatile("wgmma.wait_group.sync.aligned %0;" ::"n"(N) : "memory"); }
template <int N> __device__ __forceinline__ void pin(float (&d)[N]) {
#pragma unroll
    for (int i = 0; i < N; i++) asm volatile("" : "+f"(d[i])::"memory");
}
__host__ __device__ constexpr uint32_t desc_hi(uint32_t sbo, uint32_t swz) { return (sbo >> 4) | (swz << 30); }
__host__ __device__ constexpr uint32_t desc_lo(uint32_t off, uint32_t lbo) { return ((SMEM0 + off) >> 4) | ((lbo >> 4) << 16); }
__device__ __forceinline__ uint32_t pack2(float lo, float hi) { uint32_t r; asm("cvt.rn.bf16x2.f32 %0, %1, %2;" : "=r"(r) : "f"(hi), "f"(lo)); return r; }
__device__ __forceinline__ float bf_lo(uint32_t v) { return __uint_as_float(v << 16); }
__device__ __forceinline__ float bf_hi(uint32_t v) { return __uint_as_float(v & 0xffff0000u); }
__device__ __forceinline__ void stsm4(uint32_t a, uint32_t r0, uint32_t r1, uint32_t r2, uint32_t r3) {
    asm volatile("stmatrix.sync.aligned.m8n8.x4.shared.b16 [%0], {%1, %2, %3, %4};" ::"r"(a), "r"(r0), "r"(r1), "r"(r2), "r"(r3) : "memory");
}
__device__ __forceinline__ void stsm2(uint32_t a, uint32_t r0, uint32_t r1) {
    asm volatile("stmatrix.sync.aligned.m8n8.x2.shared.b16 [%0], {%1, %2};" ::"r"(a), "r"(r0), "r"(r1) : "memory");
}
__device__ __forceinline__ uint4 lds4(uint32_t a) { uint4 v; asm volatile("ld.shared.v4.b32 {%0, %1, %2, %3}, [%4];" : "=r"(v.x), "=r"(v.y), "=r"(v.z), "=r"(v.w) : "r"(a) : "memory"); return v; }
__device__ __forceinline__ uint2 lds2(uint32_t a) { uint2 v; asm volatile("ld.shared.v2.b32 {%0, %1}, [%2];" : "=r"(v.x), "=r"(v.y) : "r"(a) : "memory"); return v; }
__device__ __forceinline__ float lds1f(uint32_t a) { float v; asm volatile("ld.shared.f32 %0, [%1];" : "=f"(v) : "r"(a) : "memory"); return v; }
__device__ __forceinline__ void ldsm4(uint32_t* r, uint32_t a) {
    asm volatile("ldmatrix.sync.aligned.m8n8.x4.shared.b16 {%0, %1, %2, %3}, [%4];" : "=r"(r[0]), "=r"(r[1]), "=r"(r[2]), "=r"(r[3]) : "r"(a) : "memory");
}
__device__ __forceinline__ void ldsm4t(uint32_t* r, uint32_t a) {
    asm volatile("ldmatrix.sync.aligned.m8n8.x4.trans.shared.b16 {%0, %1, %2, %3}, [%4];" : "=r"(r[0]), "=r"(r[1]), "=r"(r[2]), "=r"(r[3]) : "r"(a) : "memory");
}
__device__ __forceinline__ void ldsm2t(uint32_t* r, uint32_t a) {
    asm volatile("ldmatrix.sync.aligned.m8n8.x2.trans.shared.b16 {%0, %1}, [%2];" : "=r"(r[0]), "=r"(r[1]) : "r"(a) : "memory");
}
__device__ __forceinline__ uint32_t transpose8(uint32_t v) { uint32_t r; asm volatile("movmatrix.sync.aligned.m8n8.trans.b16 %0, %1;" : "=r"(r) : "r"(v)); return r; }
__device__ __forceinline__ void mma16(float (&c)[4], uint32_t a0, uint32_t a1, uint32_t a2, uint32_t a3, uint32_t b0, uint32_t b1) {
    asm volatile("mma.sync.aligned.m16n8k16.row.col.f32.bf16.bf16.f32 {%0, %1, %2, %3}, {%4, %5, %6, %7}, {%8, %9}, {%0, %1, %2, %3};"
                 : "+f"(c[0]), "+f"(c[1]), "+f"(c[2]), "+f"(c[3]) : "r"(a0), "r"(a1), "r"(a2), "r"(a3), "r"(b0), "r"(b1));
}
__device__ __forceinline__ void mma8(float (&c)[4], uint32_t a0, uint32_t a1, uint32_t b0) {
    asm volatile("mma.sync.aligned.m16n8k8.row.col.f32.bf16.bf16.f32 {%0, %1, %2, %3}, {%4, %5}, {%6}, {%0, %1, %2, %3};"
                 : "+f"(c[0]), "+f"(c[1]), "+f"(c[2]), "+f"(c[3]) : "r"(a0), "r"(a1), "r"(b0));
}
__device__ __forceinline__ void st_async4(uint32_t a, uint32_t bar, uint32_t v0, uint32_t v1, uint32_t v2, uint32_t v3) {
    asm volatile("st.async.weak.shared::cluster.mbarrier::complete_tx::bytes.v4.b32 [%0], {%2, %3, %4, %5}, [%1];" ::"r"(a), "r"(bar), "r"(v0), "r"(v1), "r"(v2), "r"(v3) : "memory");
}
__device__ __forceinline__ void st_async2(uint32_t a, uint32_t bar, uint32_t v0, uint32_t v1) {
    asm volatile("st.async.weak.shared::cluster.mbarrier::complete_tx::bytes.v2.b32 [%0], {%2, %3}, [%1];" ::"r"(a), "r"(bar), "r"(v0), "r"(v1) : "memory");
}
__device__ __forceinline__ float quad_max(float v) { v = fmaxf(v, __shfl_xor_sync(~0u, v, 1)); return fmaxf(v, __shfl_xor_sync(~0u, v, 2)); }
__device__ __forceinline__ float quad_sum(float v) { v += __shfl_xor_sync(~0u, v, 1); return v + __shfl_xor_sync(~0u, v, 2); }
__device__ __forceinline__ float ex2(float v) { float r; asm("ex2.approx.ftz.f32 %0, %1;" : "=f"(r) : "f"(v)); return r; }
__device__ __forceinline__ float rcp(float v) { float r; asm("rcp.approx.ftz.f32 %0, %1;" : "=f"(r) : "f"(v)); return r; }
__device__ __forceinline__ float rsq(float v) { float r; asm("rsqrt.approx.ftz.f32 %0, %1;" : "=f"(r) : "f"(v)); return r; }
__device__ __forceinline__ float gelu2(float v) {
    float z = v * fmaf(v * v, 8 * 0.044715f * 0.7978845608028654f, 2 * 0.7978845608028654f), t;
    asm("tanh.approx.f32 %0, %1;" : "=f"(t) : "f"(z));
    return fmaf(v, t, v);
}
__device__ __forceinline__ float row_sum(float v) {
    v = quad_sum(v); v += __shfl_xor_sync(~0u, v, 4);
    return v + __shfl_xor_sync(~0u, v, 24);
}

template <int TA, int TB, uint32_t HA, uint32_t HB>
__device__ __forceinline__ void wgmma_n112(float (&d)[56], uint32_t da, uint32_t db, int accumulate) {
    asm volatile("{\n.reg .pred p;\n.reg .b64 a, b;\nmov.b64 a, {%56, %61};\nmov.b64 b, {%57, %62};\nsetp.ne.b32 p, %58, 0;\n"
        "wgmma.mma_async.sync.aligned.m64n112k16.f32.bf16.bf16 {"
        "%0, %1, %2, %3, %4, %5, %6, %7, %8, %9, %10, %11, %12, %13, %14, %15, "
        "%16, %17, %18, %19, %20, %21, %22, %23, %24, %25, %26, %27, %28, %29, %30, %31, "
        "%32, %33, %34, %35, %36, %37, %38, %39, %40, %41, %42, %43, %44, %45, %46, %47, "
        "%48, %49, %50, %51, %52, %53, %54, %55"
        "}, a, b, p, 1, 1, %59, %60;\n}\n"
        : "+f"(d[0]), "+f"(d[1]), "+f"(d[2]), "+f"(d[3]), "+f"(d[4]), "+f"(d[5]), "+f"(d[6]), "+f"(d[7]),
          "+f"(d[8]), "+f"(d[9]), "+f"(d[10]), "+f"(d[11]), "+f"(d[12]), "+f"(d[13]), "+f"(d[14]), "+f"(d[15]),
          "+f"(d[16]), "+f"(d[17]), "+f"(d[18]), "+f"(d[19]), "+f"(d[20]), "+f"(d[21]), "+f"(d[22]), "+f"(d[23]),
          "+f"(d[24]), "+f"(d[25]), "+f"(d[26]), "+f"(d[27]), "+f"(d[28]), "+f"(d[29]), "+f"(d[30]), "+f"(d[31]),
          "+f"(d[32]), "+f"(d[33]), "+f"(d[34]), "+f"(d[35]), "+f"(d[36]), "+f"(d[37]), "+f"(d[38]), "+f"(d[39]),
          "+f"(d[40]), "+f"(d[41]), "+f"(d[42]), "+f"(d[43]), "+f"(d[44]), "+f"(d[45]), "+f"(d[46]), "+f"(d[47]),
          "+f"(d[48]), "+f"(d[49]), "+f"(d[50]), "+f"(d[51]), "+f"(d[52]), "+f"(d[53]), "+f"(d[54]), "+f"(d[55])
        : "r"(da), "r"(db), "r"(accumulate), "n"(TA), "n"(TB), "n"(HA), "n"(HB));
}

template <int TA, int TB, uint32_t HA, uint32_t HB>
__device__ __forceinline__ void wgmma_n168(float (&d)[84], uint32_t da, uint32_t db, int accumulate) {
    asm volatile("{\n.reg .pred p;\n.reg .b64 a, b;\nmov.b64 a, {%84, %89};\nmov.b64 b, {%85, %90};\nsetp.ne.b32 p, %86, 0;\n"
        "wgmma.mma_async.sync.aligned.m64n168k16.f32.bf16.bf16 {"
        "%0, %1, %2, %3, %4, %5, %6, %7, %8, %9, %10, %11, %12, %13, %14, %15, "
        "%16, %17, %18, %19, %20, %21, %22, %23, %24, %25, %26, %27, %28, %29, %30, %31, "
        "%32, %33, %34, %35, %36, %37, %38, %39, %40, %41, %42, %43, %44, %45, %46, %47, "
        "%48, %49, %50, %51, %52, %53, %54, %55, %56, %57, %58, %59, %60, %61, %62, %63, "
        "%64, %65, %66, %67, %68, %69, %70, %71, %72, %73, %74, %75, %76, %77, %78, %79, "
        "%80, %81, %82, %83"
        "}, a, b, p, 1, 1, %87, %88;\n}\n"
        : "+f"(d[0]), "+f"(d[1]), "+f"(d[2]), "+f"(d[3]), "+f"(d[4]), "+f"(d[5]), "+f"(d[6]), "+f"(d[7]),
          "+f"(d[8]), "+f"(d[9]), "+f"(d[10]), "+f"(d[11]), "+f"(d[12]), "+f"(d[13]), "+f"(d[14]), "+f"(d[15]),
          "+f"(d[16]), "+f"(d[17]), "+f"(d[18]), "+f"(d[19]), "+f"(d[20]), "+f"(d[21]), "+f"(d[22]), "+f"(d[23]),
          "+f"(d[24]), "+f"(d[25]), "+f"(d[26]), "+f"(d[27]), "+f"(d[28]), "+f"(d[29]), "+f"(d[30]), "+f"(d[31]),
          "+f"(d[32]), "+f"(d[33]), "+f"(d[34]), "+f"(d[35]), "+f"(d[36]), "+f"(d[37]), "+f"(d[38]), "+f"(d[39]),
          "+f"(d[40]), "+f"(d[41]), "+f"(d[42]), "+f"(d[43]), "+f"(d[44]), "+f"(d[45]), "+f"(d[46]), "+f"(d[47]),
          "+f"(d[48]), "+f"(d[49]), "+f"(d[50]), "+f"(d[51]), "+f"(d[52]), "+f"(d[53]), "+f"(d[54]), "+f"(d[55]),
          "+f"(d[56]), "+f"(d[57]), "+f"(d[58]), "+f"(d[59]), "+f"(d[60]), "+f"(d[61]), "+f"(d[62]), "+f"(d[63]),
          "+f"(d[64]), "+f"(d[65]), "+f"(d[66]), "+f"(d[67]), "+f"(d[68]), "+f"(d[69]), "+f"(d[70]), "+f"(d[71]),
          "+f"(d[72]), "+f"(d[73]), "+f"(d[74]), "+f"(d[75]), "+f"(d[76]), "+f"(d[77]), "+f"(d[78]), "+f"(d[79]),
          "+f"(d[80]), "+f"(d[81]), "+f"(d[82]), "+f"(d[83])
        : "r"(da), "r"(db), "r"(accumulate), "n"(TA), "n"(TB), "n"(HA), "n"(HB));
}

template <uint32_t HB>
__device__ __forceinline__ void wgmma_rs_n168(float (&d)[84], uint32_t a0, uint32_t a1, uint32_t db) {
    asm volatile("{\n.reg .b64 b;\nmov.b64 b, {%86, %88};\n"
        "wgmma.mma_async.sync.aligned.m64n168k16.f32.bf16.bf16 {"
        "%0, %1, %2, %3, %4, %5, %6, %7, %8, %9, %10, %11, %12, %13, %14, %15, "
        "%16, %17, %18, %19, %20, %21, %22, %23, %24, %25, %26, %27, %28, %29, %30, %31, "
        "%32, %33, %34, %35, %36, %37, %38, %39, %40, %41, %42, %43, %44, %45, %46, %47, "
        "%48, %49, %50, %51, %52, %53, %54, %55, %56, %57, %58, %59, %60, %61, %62, %63, "
        "%64, %65, %66, %67, %68, %69, %70, %71, %72, %73, %74, %75, %76, %77, %78, %79, "
        "%80, %81, %82, %83"
        "}, {%84, %85, %87, %87}, b, 1, 1, 1, 0;\n}\n"
        : "+f"(d[0]), "+f"(d[1]), "+f"(d[2]), "+f"(d[3]), "+f"(d[4]), "+f"(d[5]), "+f"(d[6]), "+f"(d[7]),
          "+f"(d[8]), "+f"(d[9]), "+f"(d[10]), "+f"(d[11]), "+f"(d[12]), "+f"(d[13]), "+f"(d[14]), "+f"(d[15]),
          "+f"(d[16]), "+f"(d[17]), "+f"(d[18]), "+f"(d[19]), "+f"(d[20]), "+f"(d[21]), "+f"(d[22]), "+f"(d[23]),
          "+f"(d[24]), "+f"(d[25]), "+f"(d[26]), "+f"(d[27]), "+f"(d[28]), "+f"(d[29]), "+f"(d[30]), "+f"(d[31]),
          "+f"(d[32]), "+f"(d[33]), "+f"(d[34]), "+f"(d[35]), "+f"(d[36]), "+f"(d[37]), "+f"(d[38]), "+f"(d[39]),
          "+f"(d[40]), "+f"(d[41]), "+f"(d[42]), "+f"(d[43]), "+f"(d[44]), "+f"(d[45]), "+f"(d[46]), "+f"(d[47]),
          "+f"(d[48]), "+f"(d[49]), "+f"(d[50]), "+f"(d[51]), "+f"(d[52]), "+f"(d[53]), "+f"(d[54]), "+f"(d[55]),
          "+f"(d[56]), "+f"(d[57]), "+f"(d[58]), "+f"(d[59]), "+f"(d[60]), "+f"(d[61]), "+f"(d[62]), "+f"(d[63]),
          "+f"(d[64]), "+f"(d[65]), "+f"(d[66]), "+f"(d[67]), "+f"(d[68]), "+f"(d[69]), "+f"(d[70]), "+f"(d[71]),
          "+f"(d[72]), "+f"(d[73]), "+f"(d[74]), "+f"(d[75]), "+f"(d[76]), "+f"(d[77]), "+f"(d[78]), "+f"(d[79]),
          "+f"(d[80]), "+f"(d[81]), "+f"(d[82]), "+f"(d[83])
        : "r"(a0), "r"(a1), "r"(db), "r"(0), "n"(HB));
}

struct Ring {
    uint32_t slot, ph;
    __device__ __forceinline__ void next() { if (++slot == NSLOT) { slot = 0; ph ^= 1; } }
    __device__ __forceinline__ void next2() { ph ^= slot == 5; slot = __byte_perm(0x06030201u, 0x00040005u, 0x7770 + slot); }
};
struct Slot {
    uint32_t dst, bar, ph;
    __device__ __forceinline__ void next(uint32_t bars) {
        dst += SLOT; bar += 8;
        if (bar == bars + 8 * NSLOT) { dst -= NSLOT * SLOT; bar = bars; ph ^= 1; }
    }
};
__device__ __forceinline__ uint32_t xslot(int i) { return __byte_perm(0x04130e0cu, 0x00130e0cu, 0x7770 + i); }
__device__ __forceinline__ uint32_t wslot(int i) { return __byte_perm(0x06001510u, 0x00151009u, 0x7770 + i); }

constexpr uint32_t HI_SW = desc_hi(1024, 1);

struct Mma {
    uint32_t bars, rel;
    bool lead;
    int wg, half, w;
    Ring r;
    uint32_t prev;
    __device__ __forceinline__ void release_pair(uint32_t s) { if (lead) mbar_arrive4_remote(rel + B_EMPTY + 8 * s); }
    __device__ __forceinline__ void release(uint32_t s) { if (lead) mbar_arrive_n<4>(bars + B_EMPTY + 8 * s); }
    template <bool G1>
    __device__ __forceinline__ void run(float (&a)[56], int n, int first, int last, int lag, int accumulate, int ts, const __nv_bfloat16* bias = nullptr) {
#pragma unroll 1
        for (int i = 0; i < n; i++) {
            if (lag && i == (wg ? n - lag : -1)) {
                if (!G1) {
                    const uint32_t c0 = ld_u16(bias), c1 = ld_u16(bias + 8);
                    wg_wait<0>(); release(prev); last = first;
                    pin(a);
#pragma unroll
                    for (int k = 0; k < 56; k++) a[k] += bf_lo((k & 2) ? c1 : c0);
                    pin(a);
                }
                bar_sync(7, 256);
            }
            const bool seen = !G1 && last == first;
            const uint32_t s = seen ? n - 1 - i : r.slot;
            if (!seen) mbar_wait(bars + B_FULL + 8 * s, r.ph);
            if (G1) r.next(); else r.next2();
            if (!TSQ || !i) TS0(G1 ? 2 : 8, ts + i + wg * 68);
            const uint32_t dB = s * (SLOT >> 4), dA = dB + half * 512;
            wg_fence();
#pragma unroll
            for (int k = 0; k < 4; k++) {
                wgmma_n112<1, 1, HI_SW, desc_hi(G1 ? 256 : 1024, 0)>(a, dA + desc_lo(k * 2048, 8192), dB + desc_lo(16384 + k * (G1 ? SLAB : 256), 128), k > 0 || accumulate || i > 0);
                if (k == 1) {
                    wg_commit(); wg_wait<1>();
                    if ((uint32_t)(i - first) < (uint32_t)(last - first)) release(prev);
                    if (G1 && lag && i == (wg ? -1 : n - 1)) bar_arrive(7, 256);
                    if (TSQ && i) TS0(G1 ? 2 : 8, ts + i + wg * 68);
                }
            }
            wg_commit();
            prev = s;
        }
    }
    __device__ __forceinline__ void run_o(float (&a)[56]) {
#pragma unroll 1
        for (int i = 0; i < 2; i++) {
            const uint32_t s = r.slot, dB = s * (SLOT >> 4), dA = dB + half * (HALF >> 4);
            mbar_wait(bars + B_FULL + 8 * s, r.ph);
            TS0(8, 48 + 2 * i + wg * 68);
            wg_fence();
#pragma unroll
            for (int k = 0; k < 7; k++) {
                if (k == 3) { mbar_wait(bars + B_FULL + 8 * s + 8, r.ph); wg_fence(); }
                wgmma_n112<0, 1, desc_hi(128, 0), desc_hi(256, 0)>(a, dA + desc_lo(k * 2048 + (k > 3) * (SLOT - HALF), k == 3 ? SLOT - 6144 : 1024),
                                                                   dB + desc_lo(16384 + k * SLAB + (k > 2) * (SLOT - 3 * SLAB), 128), k > 0 || i > 0);
                if (k & 1) wg_commit();
                if (k == 1) { wg_wait<1>(); if (i) release(prev); }
                if (k == 5) { wg_wait<1>(); release(s); }
            }
            wg_commit();
            prev = s + 1;
            r.slot++; r.next2();
        }
    }
};

__global__ void __cluster_dims__(2, 1, 1) __launch_bounds__(NTHREADS, 1)
fused_kernel(const __nv_bfloat16* __restrict__ x, const __nv_bfloat16* __restrict__ b1, const __nv_bfloat16* __restrict__ b2, const __nv_bfloat16* __restrict__ wo, __nv_bfloat16* out, Scratch* G,
             const __nv_bfloat16* __restrict__ w1,
             const __grid_constant__ Params P) {
    extern __shared__ __align__(1024) uint8_t smem[];
    const uint32_t sbase = (uint32_t)__cvta_generic_to_shared(smem);
    const uint32_t bars = sbase + OFF_BAR;
    const uint32_t rank = blockIdx.x & 1, pr = blockIdx.x >> 1;
    const uint32_t row0 = blockIdx.x * 16;
    if (threadIdx.x == 0) {
        TS(15, 0);
        mbar_init(bars + B_ROW, 1);
        asm volatile("fence.mbarrier_init.release.cluster;" ::: "memory");
        bulk_load(sbase + OFF_Y, x + row0 * D_, TILEB, bars + B_ROW);
        mbar_expect(bars + B_ROW, TILEB);
        TS(1, 97);
    }
    const int lane = threadIdx.x & 31;
    const int warp = __shfl_sync(~0u, threadIdx.x >> 5, 0), w = warp & 3;
    if (elect()) {
        const uint32_t first = bars + warp * 24, count = warp < 7 ? 1 : warp < 9 ? 18 - 2 * warp : 16;
#pragma unroll
        for (int i = 0; i < 3; i++) mbar_init(first + 8 * i, count);
        asm volatile("fence.mbarrier_init.release.cluster;" ::: "memory");
    }
    __syncwarp();
    asm volatile("barrier.cluster.arrive.relaxed.aligned;" ::: "memory");
    const uint32_t pv = pr < 4 ? pr * 8 + 36 : pr - 4 + (max((int)pr - 33, 0) * 37 >> 8);
    const uint32_t gp = (pv + 4) & 7, hp = pv >> 3;
    const uint32_t tb = gp * 2 + rank, c = hp * 16 + tb;
    const bool has_g1 = gp > 0;
    const uint32_t nt1 = hp & 3, ft = max((int)gp - 1, 0) * 2 + (hp >> 2);
    const uint32_t nt2 = (hp & 1) * 2 + rank, mt = (gp & 3) * 4 + (hp >> 1), ks = gp >> 2;
    asm volatile("barrier.cluster.wait.aligned;" ::: "memory");

    if (warp == 8) {
        uint32_t kw = (gp & 1) * 192, kx;
        if (elect()) {
            mbar_expect(bars + B_QFULL, WSLOT);
            tma3d(sbase + xslot(0) * 8192, &P.tmX, bars + B_FULL, 0, tb * 64, 0);
            tma3d_pair(sbase + wslot(0) * 8192 + rank * 12288, &P.tmWqkv, bars + B_QFULL, (hp * 56) & ~15, rank * 32, 0);
            TS(1, 23);
            uint32_t due = (uint32_t)clock() + PACE, ep = ld_relaxed(&G->epoch[c]);
            uint32_t spins = sbase == (rank << 24 | SMEM0) ? 0 : SPIN_LIMIT;
#pragma unroll 1
            for (int i = 1; i < 8; i++) {
                kx = kw; kw += 64;
                if (i >= 5) mbar_wait_bounded(bars + B_QEMPTY + 8 * (i - 5), 0, spins);
                else { while ((int)((uint32_t)clock() - due) < 0) {} due += PACE; }
                if (kw == D_) kw = 64;
                if (i < 4) kx = kw;
                const int ix = i - (i > 4);
                if (i < 7) mbar_expect(bars + B_QFULL + 8 * i, WSLOT);
                if (i != 4) tma3d(sbase + xslot(ix) * 8192, &P.tmX, bars + B_FULL + 8 * ix, kx, tb * 64, 0);
                if (i & (i >> 2)) mbar_wait_bounded(bars + B_CS - 20 + 4 * i, 0, spins);
                if (i < 7) tma3d_pair(sbase + wslot(i) * 8192 + rank * 12288, &P.tmWqkv, bars + B_QFULL + 8 * i, (hp * 56) & ~15, kw + rank * 32, 0);
            }
            ep++;
            Slot r{sbase, bars, 0};
            if (has_g1) {
                const uint8_t* src = G->H[nt1][rank * 16];
                const int row = rank * 1024;
                mbar_expect(bars + B_FULL, 16384 + TILEB);
                tma3d(sbase, &P.tmW1, bars + B_FULL, 0, row, ft * 2);
                wait_flag(G->flag[1] + rank * 2, 20 * ep, spins);
                TS(1, 16);
#pragma unroll 1
                for (int j = 64;; j += 64) {
                    bulk_load(r.dst + 16384, src, TILEB, r.bar + B_FULL);
                    src += TILEB;
                    r.next(bars);
                    if (j == 1024) break;
                    mbar_wait_bounded(r.bar + B_EMPTY, r.ph, spins);
                    if (j < 14 * 64) TS(2, 146 + j / 64);
                    mbar_expect(r.bar + B_FULL, 16384 + TILEB);
                    tma3d(r.dst, &P.tmW1, r.bar + B_FULL, 0, row + j, ft * 2);
                }
                mbar_arrive(bars + B_FULL + 48); mbar_arrive_n<16>(bars + B_EMPTY + 48);
#pragma unroll
                for (int i = 0; i < 4; i++) mbar_expect(bars + B_X + 8 * i, (i & 1) ? 3072 : 4096);
            } else {
                due = (uint32_t)clock();
#pragma unroll 1
                for (int j = PF0; j < PF1; j++) {
                    asm volatile("cp.async.bulk.prefetch.L2.global [%0], %1;" ::"l"(w1 + (rank * 1024 + j * 64 + hp * 8) * F_), "n"(16 * F_) : "memory");
                    due += PF;
                    while ((int)((uint32_t)clock() - due) < 0) {}
                }
            }
            const uint8_t *so = G->O[mt][ks * 4], *sw = G->Wo[nt2][ks * 4];
            wait_flag2(G->flag[16 + mt], 8 * ep, G->flag[0], 16 * ep, spins);
            TS(4, 18);
#pragma unroll 1
            for (int j = 0; j < 4 * TILEB; j += TILEB) {
                mbar_wait_bounded(r.bar + B_EMPTY, r.ph, spins);
                mbar_expect(r.bar + B_QFULL, TILEB);
                bulk_load(r.dst, so + j, TILEB, r.bar + B_QFULL);
                bulk_load(r.dst + 16384, sw + j, (r.bar & 8) ? TILEB : 3 * SLAB, r.bar + B_FULL);
                r.next(bars);
            }
            Ring q{has_g1 ? 2u : 6u, has_g1}, p{q.slot, !has_g1};
#pragma unroll 1
            for (int j = 0; j < 14 * 128; j += 128) {
                mbar_wait_bounded(bars + B_EMPTY + 8 * q.slot, q.ph, spins);
                if (LEADW && j >= LEADW * 128 && j < LEADN * 128) { mbar_wait_bounded(bars + B_FULL + 8 * p.slot, p.ph, spins); p.next2(); }
                TS(8, 176 + j / 128);
                tma3d(sbase + q.slot * SLOT, &P.tmW2, bars + B_FULL + 8 * q.slot, 0, ks * 896 + j - (j < 896 ? 0 : 832), mt * 2);
                q.next2();
            }
            mbar_wait_bounded(bars + B_END, 0, spins);
        }
    } else if (warp > 8) {
        const uint32_t ep = ld_relaxed(&G->epoch[c]) + 1;
        const uint8_t* src = G->U[nt2][ks * 14];
        uint32_t spins = 0, bad;
        {
            uint2* cs = G->colsum[hp][0];
            if (w == 2) {
                bar_sync(6, 288);
                TS(1, 8);
                stg1((uint32_t*)(G->stat + row0) + lane, tag(__float_as_uint(lds1f(sbase + OFF_ST + lane * 4)), ~lane & 1, ep));
                if (elect()) {
                    fence_async_shared();
#pragma unroll
                    for (int i = 0; i < 4; i++) bulk_store(G->H[i][0] + row0 * (SLAB / 16), sbase + OFF_X + i * HSTG, SLAB);
                    bulk_flush();
                    TS(1, 99);
                    signal(G->flag[1] + (row0 >> 10) * 2 + ((row0 & 1023) >= 320));
                }
                __syncwarp();
            } else {
                const uint32_t word = rank * 16 + (w & 2) * 4 + (lane & 7), done = mapa(bars + B_CS, rank ^ (lane & 1));
                const uint32_t from = (sbase + word * 4 + (gp >> 2) * 12288 + (gp & 2) * 1024) ^ ((lane >> 3) * 288);
                auto swz = [](uint32_t a) { return a ^ ((a >> 3) & 0x70); };
                const uint32_t lin = sbase + lane * 128 + (hp & 1) * 16, f0 = swz(lin + 80) + 8192, f1 = swz(lin + 96) + 8192, to = swz(lin + 112);
                float s[6] = {};
#pragma unroll 1
                for (int i = 0; i < 7; i++) {
                    const uint32_t o = wslot(i) * 8192, a0 = from + o, a1 = a0 ^ 144;
                    mbar_wait(bars + B_QFULL + 8 * i, 0);
                    if ((i ^ (w >> 1)) & 1) {
                        const uint4 v0 = lds4(f0 + o), v1 = lds4(f1 + o), v2 = lds4(f0 + o + 12288), v3 = lds4(f1 + o + 12288);
                        sts4(to + o, v0); sts4(to + o + 4096, v1); sts4(to + o + 12288, v2); sts4(to + o + 16384, v3);
                        fence_async_shared();
                        __syncwarp();
                        if (elect()) mbar_expect(bars + B_FULL + 8 * i, 16384);
                    }
                    if (i > 3 || i < (gp & 1)) continue;
                    if (w == 1) TS(1, 66);
                    uint32_t v[12];
#pragma unroll
                    for (int k = 0; k < 12; k++) v[k] = __float_as_uint(lds1f(((k & 1) ? a1 : a0) + (k & 2) * 512 + (k >> 2) * 4096));
#pragma unroll
                    for (int k = 0; k < 12; k++) { s[(k >> 2) * 2] += bf_lo(v[k]); s[(k >> 2) * 2 + 1] += bf_hi(v[k]); }
                    __syncwarp();
                    if ((i & 1) && lane < 2) mbar_arrive_remote(done + (i & 2) * 4);
                    if (i < 3) continue;
#pragma unroll
                    for (int k = 0; k < 6; k++) { s[k] += __shfl_xor_sync(~0u, s[k], 8); s[k] += __shfl_xor_sync(~0u, s[k], 16); }
                    const float s0 = lane < 8 ? s[0] : lane < 16 ? s[2] : s[4], s1 = lane < 8 ? s[1] : lane < 16 ? s[3] : s[5];
                    if (lane < 24) cs[gp * 96 + (lane >> 3) * 32 + word] = make_uint2(tag(__float_as_uint(s0), 1, ep), __float_as_uint(s1));
                    if (w == 1) TS(1, 24);
                }
            }
            bar_sync(1, 96);
            if (w == 1) TS(1, 98);
            const int i0 = threadIdx.x - 288, j0 = i0 - (hp & 1) * 4;
            cs += i0 + ((j0 & 92) == 28 ? (j0 & 32 ? 28 : 56) : 0);
            uint2 u[8];
            uint4 sv;
            do {
                sv = ld_relaxed4(G->stat + tb * 128 + (i0 & 63) * 2);
                bad = sv.x ^ ep;
#pragma unroll
                for (int i = 0; i < 8; i++) { u[i] = ld_relaxed2(cs + i * 96); bad = or_diff(bad, u[i].x, ep); }
                if (bad & 1) TS(1, 3);
            } while (bad & 1);
            if (w < 3) sts4(sbase + OFF_ST + i0 * 16, sv);
#pragma unroll
            for (int e = 0; e < 2; e++) {
                float f = 0.f;
#pragma unroll
                for (int i = 0; i < 8; i++) f += __uint_as_float(e ? u[i].y : u[i].x);
                const uint32_t hi = pack2(f, f);
                sts4(sbase + OFF_X + i0 * 32 + e * 16, make_uint4(hi, pack2(f - bf_hi(hi), f - bf_hi(hi)), 0, 0));
            }
            sts1(bars + 8 * NBAR, ep);
            fence_async_shared();
            __syncwarp();
            bar_arrive(8, 224); bar_arrive(9, 224);
            TS(1, 90 + w);
        }
        if (w < 3) {
            if (w == 1) {
                if (elect()) {
                    wait_flag(G->flag[1] + rank * 2 + 1, 44 * ep, spins);
                    mbar_arrive_n<16>(bars + B_EMPTY + 8 * 5);
                    TS(1, 96);
                }
                __syncwarp();
                if (!has_g1) { bar_sync(5, 288); if (elect()) signal(G->flag[0]); __syncwarp(); TS(2, 26); }
            }
            mbar_wait(bars + B_HALO, 0);
            uint32_t slot = (has_g1 ? 16 % NSLOT : 0) + w - 1, ph = ~0u;
#pragma unroll 1
            for (int i = w - 1; i < 18;) {
                const uint32_t d0 = sbase + slot * SLOT + (i < 4 ? 0 : 16384), landed = bars + B_QFULL + 8 * slot;
                mbar_wait(landed, (ph >> slot) & 1);
                ph ^= 1 << slot;
                if (i < 8) TS(4, 82 + i);
                if (i >= 4) TS(8, 156 + i);
                bad = 0;
#pragma unroll
                for (int k = 0; k < 14; k++) bad = or_diff(bad, __float_as_uint(lds1f(d0 + k * 1024 + lane * 32 + (lane >> 2) * 4)), ep);
                if (__any_sync(~0u, bad & 1)) {
                    if (elect()) {
                        const uint8_t* cur = (i < 4 ? G->O[mt][ks * 4] : src - 4 * TILEB) + i * TILEB;
                        fence_async_shared();
                        mbar_expect(landed, TILEB);
                        bulk_load(d0, cur, TILEB, landed);
                    }
                    TS(4, i < 4 ? 94 : 95);
                } else {
                    if (elect()) mbar_expect(landed + (B_FULL - B_QFULL), i < 4 ? (2 + w) * SLAB : 16384);
                    i += __byte_perm(0x03020202u, 0x00010202u, 0x7770 + slot);
                    slot = __byte_perm(0x05060302u, 0x00040100u, 0x7770 + slot);
                }
            }
        } else {
            bar_sync(3, 288);
            __nanosleep(HALO_NS);
            uint4 v[7];
            do {
                bad = 0;
#pragma unroll
                for (int i = 0; i < 7; i++) { v[i] = ld_relaxed4(G->halo[c - (tb > 0)] + i * 512 + lane * 16); bad = or_diff(bad, v[i].x, ep); }
            } while (bad & 1);
#pragma unroll
            for (int i = 0; i < 7; i++) sts4(sbase + OFF_X + i * 512 + lane * 16, v[i]);
            __syncwarp();
            if (elect()) mbar_arrive(bars + B_HALO);
            TS(2, 21);
            bar_sync(2, 288);
            if (elect()) bulk_store(out + row0 * D_, sbase + OFF_Y, TILEB);
            __syncwarp();
            bar_sync(4, 288);
            if (elect()) {
                fence_async_shared();
                bulk_store(G->O[tb][hp], sbase + OFF_X, TILEB);
                bulk_flush();
                TS(2, 7);
                mbar_arrive_remote(mapa(bars + B_FREE, rank ^ 1));
                mbar_arrive(bars + B_FREE);
                hint(G->flag[16 + tb]);
                signal(G->flag[16 + (row0 >> 7)] + 1);
                TS(2, 22);
            }
            __syncwarp();
            uint32_t late = ~0u;
            const uint32_t* hints = G->flag[8 + nt2 * 2 + ks] + lane;
            mbar_wait(bars + (has_g1 ? B_X : B_FREE), 0);
            Ring r{has_g1 ? 2u : 6u, has_g1};
#pragma unroll 1
            for (int i = 0; i < 14; i++) {
                while ((late >> i) & 1) late = __ballot_sync(~0u, ld_relaxed(hints) != 2 * ep) & 127;
                if (i == 0) TS(4, 17);
                mbar_wait(bars + B_EMPTY + 8 * r.slot, r.ph);
                TS(8, 192 + i);
                if (elect()) {
                    mbar_expect(bars + B_QFULL + 8 * r.slot, TILEB);
                    bulk_load(sbase + r.slot * SLOT + 16384, src, TILEB, bars + B_QFULL + 8 * r.slot);
                }
                src += TILEB; r.next2();
            }
            if (elect()) {
                wait_flag(G->flag[16 + mt] + 1, 8 * ep, spins);
                mbar_arrive(bars + B_ROW);
                TS(2, 27);
                G->epoch[c] = ep;
            }
        }
    } else {
        const int wg = warp >> 2;
        Mma M{bars, mapa(bars, rank ^ (lane & 1)), (threadIdx.x & 127) < 2, wg, wg, w, Ring{0, 1}, 0};
        const int r = lane >> 2, t = lane & 3;
        uint32_t ep;
        const uint32_t bias0 = ld_u16(b1 + ft * 128 + warp * 16 + r), bias1 = ld_u16(b1 + ft * 128 + warp * 16 + r + 8);
        const uint32_t kv = sbase + OFF_X + (w * 2 + wg) * KV + lane * 16;
        uint32_t q[8][2], k0[7], k1[14], v0[7];
        float f0, f1;
        {
            const int half = (lane >> 3) & 1, r16 = warp * 2 + (half ^ (lane >> 4)), nt = (lane >> 1) & 3;
            const uint32_t row = sbase + OFF_Y + r16 * (2 * D_), part = row + nt * 224 + half * 112 + (lane & 1) * 8;
            const uint32_t hb = sbase + OFF_X + nt * HSTG + r16 * 16 + (half ^ (row0 >> 10)) * (7 * 256) + (lane & 1) * 8;
            mbar_wait(bars + B_ROW, 0);
            TS0(1, 67);
            const float x0 = bf_lo(__float_as_uint(lds1f(row)));
            float d[28], m1 = 0.f, n1 = 0.f, m2 = 0.f, n2 = 0.f;
#pragma unroll
            for (int i = 0; i < 7; i++) {
                const uint2 v = lds2(part + i * 16);
#pragma unroll
                for (int k = 0; k < 2; k++) {
                    const float d0 = d[4 * i + 2 * k] = bf_lo(k ? v.y : v.x) - x0, d1 = d[4 * i + 2 * k + 1] = bf_hi(k ? v.y : v.x) - x0;
                    m1 += d0; n1 += d1; m2 = fmaf(d0, d0, m2); n2 = fmaf(d1, d1, n2);
                }
            }
            const float md = row_sum(m1 + n1) * (1.f / D_), var = fmaf(-md, md, row_sum(m2 + n2) * (1.f / D_)), nmean = -(x0 + md);
            const float rstd = rsq(var + LN_EPS);
            const float sc = rstd * rsq(fmaf(var * rstd, 4 * rstd, 4 * LN_EPS)), nb = -md * sc;
            sts2(sbase + OFF_ST + r16 * 8, __float_as_uint(rstd), pack2(nmean, nmean - bf_hi(pack2(nmean, nmean))));
#pragma unroll
            for (int i = 0; i < 7; i++) sts2(hb + i * 256, pack2(fmaf(d[4 * i], sc, nb), fmaf(d[4 * i + 1], sc, nb)), pack2(fmaf(d[4 * i + 2], sc, nb), fmaf(d[4 * i + 3], sc, nb)));
            TS0(1, 25);
            bar_arrive(6, 288);
            float acc[84];
#pragma unroll 1
            for (int kb = 0; kb < 7; kb++) {
                const bool held = kb == (wg ? 7 - HOLD : -1);
                if (held) { wg_wait<0>(); M.release_pair(4 - HOLD); TS0(1, 138); bar_sync(7, 256); }
                mbar_wait(bars + B_FULL + 8 * kb, 0);
                if (!TSQ || !kb) TS0(1, 68 + wg * 7 + kb);
                const uint32_t dA = (xslot(kb) + wg) * 512, dB = wslot(kb) * 512 + (hp & 1);
                wg_fence();
#pragma unroll
                for (int k = 0; k < 4; k++) {
                    wgmma_n168<0, 1, HI_SW, HI_SW>(acc, dA + desc_lo(k * 32, 16), dB + desc_lo((k & 1) * 2048 + (k >> 1) * 12288, 4096), k > 0 || kb > 0);
                    if (k == 0) { wg_commit(); wg_wait<1>(); if (kb > 0 && !held) M.release_pair(kb - 3); if (TSQ && kb) TS0(1, 68 + wg * 7 + kb); }
                }
                wg_commit();
            }
            if (wg == 0 && !LATEREL) bar_arrive(7, 256);
            if (wg == 0) TS0(1, 139);
            bar_sync(8 + wg, 224);
            if (wg == 0) TS0(1, 174);
            ep = __float_as_uint(lds1f(bars + 8 * NBAR));
            const uint32_t st = sbase + OFF_ST + (w * 32 + r * 2 + wg) * 8;
            const uint2 s0 = lds2(st), s1 = lds2(st + 128);
            const uint32_t a0 = t < 2 ? s0.y : 0, a1 = t < 2 ? s1.y : 0;
            wg_fence();
            wgmma_rs_n168<desc_hi(128, 0)>(acc, a0, a1, desc_lo(OFF_X, 0) + (hp & 1) * 8);
            wg_commit();
            if (wg == 0 && LATEREL) bar_arrive(7, 256);
            if (wg == 0) TS0(1, 175);
            wg_wait<1>();
            TS0(1, 190 + wg);
            M.release_pair(4);
            wg_wait<0>();
            pin(acc);
            TS0(1, 4 + 7 * wg);
            f0 = __uint_as_float(s0.x); f1 = __uint_as_float(s1.x);
#pragma unroll
            for (int g = 13; g >= 0; g--) {
                const float* a = acc + (g < 7 ? g + 8 : g < 12 ? g + 9 : g * 8 - 89) * 4;
                (g < 7 ? k0[g] : v0[g - 7]) = pack2(a[0] * f0, a[1] * f0);
                k1[g] = pack2(a[2] * f1, a[3] * f1);
            }
#pragma unroll
            for (int i = 0; i < 3; i++) stsm4(kv + 2 * KV + i * 512, k1[4 * i], k1[4 * i + 1], k1[4 * i + 2], k1[4 * i + 3]);
            stsm2(kv + 2 * KV + 1536, k1[12], k1[13]);
            if (w == 3) {
#pragma unroll
                for (int i = 0; i < 14; i++) stg1(G->halo[c] + wg * KV + lane * 4 + i * 128, tag(k1[i], t == 0, ep));
            }
            bar_arrive(3, 288);
#pragma unroll
            for (int g = 0; g < 7; g++) { q[g][0] = pack2(acc[4 * g], acc[4 * g + 1]); q[g][1] = pack2(acc[4 * g + 2], acc[4 * g + 3]); }
#pragma unroll
            for (int j = 0; j < 2; j++) { q[7][j] = t < 2 ? 0u : q[3][j]; q[3][j] = t < 2 ? q[3][j] : 0u; }
#pragma unroll
            for (int g = 0; g < 7; g++) v0[g] = transpose8(v0[g]);
        }
        TS0(1, 9 + 11 * wg);
        float a[56];
#pragma unroll
        for (int i = 0; i < 56; i++) asm volatile("" : "=f"(a[i]));
        if (__builtin_expect(!has_g1, 0)) {
            const int g = min(lane >> 1, 13), nt = rank * 2 + wg;
            const uint4* src = (const uint4*)(wo + (hp * 56 - (hp & 1) * 8 + w * 16 + (lane & 1)) * D_ + nt * 112) + g;
            uint4 v[8];
#pragma unroll
            for (int i = 0; i < 8; i++) v[i] = __ldg(src + i * (D_ / 4));
#pragma unroll
            for (int i = 0; i < 8; i++) ((uint4*)G->Wo[nt][hp])[w * (SLAB / 16) + g * 16 + (lane & 1) + 2 * i] = v[i];
            bar_arrive(5, 288);
        }
        M.run<true>(a, has_g1 ? PAUSE : 0, 1, 16, 0, 0, 32);
        {
            uint32_t kp[8], vv[14];
            TS0(2, 140 + wg);
            mbar_wait(bars + B_HALO, 0);
            TS0(2, 142 + wg);
            ldsm4(kp, kv); ldsm4(kp + 4, kv + (lane < 24 ? 512 : 0));
            const uint32_t va = kv + 896 + (lane & 8) * (2 * KV / 8 - 16) - (lane & 16) * 8;
            ldsm4t(vv, va); ldsm4t(vv + 4, va + 256); ldsm4t(vv + 8, va + 512); ldsm2t(vv + 12, va + 768);
            const bool e0 = 2 * t > r, e1 = 2 * t >= r;
            const uint32_t mk = (e0 ? 0xffffu : 0u) | (e1 ? 0xffff0000u : 0u);
            wg_wait<0>();
            pin(a);
            if (has_g1) M.release(M.prev);
            TS0(2, 144 + wg);
            bar_sync(2, 288);
            mbar_wait(bars + B_HALO, 0);
            TS0(2, 12 + 16 * wg);
            float sv[2][4];
#pragma unroll
            for (int h = 0; h < 2; h++) {
                const int ga = h * 4, gb = h * 4 + 1, gc = h * 4 + 2, gd = h * 4 + 3;
                float s[3][4] = {};
                mma16(s[0], q[ga][0], q[ga][1], q[gb][0], q[gb][1], kp[ga], kp[gb]);
                mma16(s[1], q[ga][0], q[ga][1], q[gb][0], q[gb][1], k0[ga], k0[gb]);
                mma16(s[2], q[ga][0], q[ga][1], q[gb][0], q[gb][1], k1[ga], k1[gb]);
                mma16(s[0], q[gc][0], q[gc][1], q[gd][0], q[gd][1], kp[gc], kp[gd]);
                mma16(s[1], q[gc][0], q[gc][1], q[gd][0], q[gd][1], k0[gc], k0[3]);
                mma16(s[2], q[gc][0], q[gc][1], q[gd][0], q[gd][1], k1[gc], k1[3]);
                if ((tb | w) == 0) s[0][0] = s[0][1] = -1e30f;
                sv[h][0] = e0 ? s[0][0] : s[1][0];
                sv[h][1] = e1 ? s[0][1] : s[1][1];
                sv[h][2] = e0 ? s[1][2] : s[2][2];
                sv[h][3] = e1 ? s[1][3] : s[2][3];
            }
            uint32_t pp[2][2];
#pragma unroll
            for (int i = 0; i < 4; i++) {
                float* v = &sv[i >> 1][(i & 1) * 2];
                const float f = ((i & 1) ? f1 : f0) * QK_SCALE, m = quad_max(fmaxf(v[0], v[1])) * f;
                const float p0 = ex2(fmaf(v[0], f, -m)), p1 = ex2(fmaf(v[1], f, -m));
                const float inv = rcp(quad_sum(p0 + p1));
                pp[i >> 1][i & 1] = pack2(p0 * inv, p1 * inv);
            }
            uint32_t o[8][2];
#pragma unroll
            for (int i = 0; i < 8; i++) {
                const int h = i >> 2, g = i - h;
                float d[4] = {};
                mma16(d, pp[h][0] & mk, 0u, 0u, pp[h][1] & ~mk, vv[2 * g], vv[2 * g + 1]);
                mma8(d, pp[h][0] & ~mk, pp[h][1] & mk, v0[g]);
                o[i][0] = pack2(d[0], d[1]); o[i][1] = pack2(d[2], d[3]);
            }
            if (t >= 2) { o[3][0] = o[4][0]; o[3][1] = o[4][1]; }
            const int word = wg * 4 + t - (w & 1) * 4 - (r >> 2);
#pragma unroll
            for (int i = 0; i < 8; i++) { o[i][0] = tag(o[i][0], word == 0, ep); o[i][1] = tag(o[i][1], word == 2, ep); }
            const uint32_t dst = sbase + OFF_X + (w >> 1) * HALF + ((w & 1) * 32 + (lane & 15) * 2 + wg) * 16 + (lane >> 4) * 1024;
            stsm4(dst, o[0][0], o[0][1], o[1][0], o[1][1]);
            stsm4(dst + 2048, o[2][0], o[2][1], o[3][0], o[3][1]);
            stsm4(dst + 4096, o[5][0], o[5][1], o[6][0], o[6][1]);
            stsm2(dst + 6144, o[7][0], o[7][1]);
            if (ENDBAR) bar_sync(4, 288); else bar_arrive(4, 288);
            TS0(2, 10 + 19 * wg);
        }
        if (has_g1) {
            M.run<true>(a, 16 - PAUSE, 1, 16, LAG1, 1, 32 + PAUSE);
            mbar_wait(bars + B_FREE, 0);
            const uint32_t xb = sbase + OFF_X + wg * 8192 + (threadIdx.x & 127) * 16, xbar = bars + B_X + 16 * wg;
            const uint32_t rx = mapa(xb, rank ^ 1), rbar = mapa(xbar, rank ^ 1);
            wg_wait<0>();
            pin(a);
            M.release(M.prev);
            TS0(4, 5 + wg);
#pragma unroll
            for (int i = 0; i < 3; i++)
                st_async4(rx + i * 2048, rbar + 8 * (i >> 1), pack2(a[28 + 8 * i], a[29 + 8 * i]), pack2(a[30 + 8 * i], a[31 + 8 * i]), pack2(a[32 + 8 * i], a[33 + 8 * i]), pack2(a[34 + 8 * i], a[35 + 8 * i]));
            const uint32_t tail = 6144 - (threadIdx.x & 127) * 8;
            st_async2(rx + tail, rbar + 8, pack2(a[52], a[53]), pack2(a[54], a[55]));
            uint8_t* dst = G->U[nt1][((ft >= 7) + wg) * 7 + ft] + rank * HALF + w * 256 + lane * 4;
            uint32_t u[14];
#pragma unroll
            for (int i = 0; i < 28; i++) a[i] = fmaf(bf_lo((i & 2) ? bias1 : bias0), 0.5f, a[i]);
#pragma unroll
            for (int i = 0; i < 14; i++) {
                if (i % 8 == 0) {
                    if (i) TS0(4, 134 + wg);
                    mbar_wait(xbar + i, 0);
                    TS0(4, (i ? 136 : 1) + wg);
#pragma unroll
                    for (int k = i / 4; k < i / 4 + 2; k++) {
                        if (k < 3) { const uint4 v = lds4(xb + k * 2048); u[4 * k] = v.x; u[4 * k + 1] = v.y; u[4 * k + 2] = v.z; u[4 * k + 3] = v.w; }
                        else { const uint2 v = lds2(xb + tail); u[12] = v.x; u[13] = v.y; }
                    }
                    if (i && lane < 2) mbar_arrive(bars + B_EMPTY + 48);
                }
                if (i == HINT && threadIdx.x == 0) hint(G->flag[8 + nt1 * 2] + ft + (ft >= 7) * 25);
                stg1(dst + (i >> 1) * 1024 + (i & 1) * 128, tag(pack2(gelu2(a[2 * i] + bf_lo(u[i])), gelu2(a[2 * i + 1] + bf_hi(u[i]))), (lane & 7) == w * 2 + (i & 1), ep));
            }
            TS0(4, 30 + wg);
        } else {
            mbar_wait(bars + B_FREE, 0);
            if (lane < 2) mbar_arrive(bars + B_EMPTY + 48);
        }
        M.half = wg ^ ks;
        const uint32_t orow = mt * 128 + M.half * 64 + w * 16;
        M.run_o(a);
        if (wg == 1) TS0(4, 13);
        M.run<false>(a, 14, 0, 14 - NSLOT, NSLOT + 1, 1, 52, b2 + orow + r);
        mbar_wait(bars + B_ROW, 1);
        const uint32_t stg = sbase + (4 + (w >> 1)) * SLOT + M.half * 8192 + (w & 1) * (PITCH * 16);
        const uint32_t sa = stg + (lane & 15) * PITCH + (lane >> 4) * 16;
        wg_wait<1>();
        if (wg == 0) bar_arrive(7, 256);
        wg_wait<0>();
        pin(a);
        TS0(8, 14 + wg);
#pragma unroll
        for (int i = 0; i < 7; i++)
            stsm4(sa + i * 32, pack2(a[8 * i], a[8 * i + 1]), pack2(a[8 * i + 2], a[8 * i + 3]), pack2(a[8 * i + 4], a[8 * i + 5]), pack2(a[8 * i + 6], a[8 * i + 7]));
        if (!wg) TS0(8, 206);
        fence_async_shared();
        __syncwarp();
        if (elect()) {
            asm volatile("cp.reduce.async.bulk.tensor.3d.global.shared::cta.add.tile.bulk_group [%0, {%4, %2, %3}], [%1];\ncp.async.bulk.commit_group;" ::"l"(&P.tmOut), "r"(stg), "r"(nt2), "r"(orow), "r"(0) : "memory");
            if (w == 0) mbar_arrive(bars + B_END);
            asm volatile("cp.async.bulk.wait_group.read 0;" ::: "memory");
        }
        TS0(15, wg ? 19 : 207);
        TSDUMP();
    }
}

typedef CUresult (*EncodeFn)(CUtensorMap*, CUtensorMapDataType, cuuint32_t, void*, const cuuint64_t*, const cuuint64_t*, const cuuint32_t*, const cuuint32_t*,
                             CUtensorMapInterleave, CUtensorMapSwizzle, CUtensorMapL2promotion, CUtensorMapFloatOOBfill);

void make_map(EncodeFn enc, CUtensorMap* tm, const void* base, bool swizzle, int d0, int d1, int d2, int s1, int s2, int b0, int b1, int b2) {
    const cuuint64_t dims[3] = {(cuuint64_t)d0, (cuuint64_t)d1, (cuuint64_t)d2}, strides[2] = {(cuuint64_t)s1 * 2, (cuuint64_t)s2 * 2};
    const cuuint32_t box[3] = {(cuuint32_t)b0, (cuuint32_t)b1, (cuuint32_t)b2}, es[3] = {1, 1, 1};
    enc(tm, CU_TENSOR_MAP_DATA_TYPE_BFLOAT16, d2 ? 3 : 2, (void*)base, dims, strides, box, es, CU_TENSOR_MAP_INTERLEAVE_NONE,
        swizzle ? CU_TENSOR_MAP_SWIZZLE_128B : CU_TENSOR_MAP_SWIZZLE_NONE, CU_TENSOR_MAP_L2_PROMOTION_L2_128B, CU_TENSOR_MAP_FLOAT_OOB_FILL_NONE);
}

}

extern "C" void kernel_launch(void* const* d_in, const int* in_sizes, int n_in, void* d_out, int out_size) {
    static EncodeFn enc = nullptr;
    static Scratch* scratch = nullptr;
    if (!enc) {
        void* fn = nullptr;
        cudaDriverEntryPointQueryResult qr;
        cudaGetDriverEntryPoint("cuTensorMapEncodeTiled", &fn, cudaEnableDefault, &qr);
        enc = (EncodeFn)fn;
        cudaGetSymbolAddress((void**)&scratch, g_s);
        cudaFuncSetAttribute(fused_kernel, cudaFuncAttributeMaxDynamicSharedMemorySize, SMEM_BYTES);
    }
    Params P;
    const __nv_bfloat16* x = (const __nv_bfloat16*)d_in[0];
    make_map(enc, &P.tmX, x, true, D_, S_ / 2, 2, 2 * D_, D_, 64, 64, 2);
    make_map(enc, &P.tmWqkv, d_in[1], true, D_, D_, 3, 3 * D_, D_, 64, 32, 3);
    make_map(enc, &P.tmW1, d_in[4], true, 64, S_, F_ / 64, F_, 64, 64, 64, 2);
    make_map(enc, &P.tmW2, d_in[6], true, 64, F_, S_ / 64, S_, 64, 64, 64, 2);
    make_map(enc, &P.tmOut, d_out, false, 112, 4, S_, 112, D_, PITCH / 2, 1, 16);
    fused_kernel<<<NCTA, NTHREADS, SMEM_BYTES, cudaStreamPerThread>>>(x, (const __nv_bfloat16*)d_in[5], (const __nv_bfloat16*)d_in[7], (const __nv_bfloat16*)d_in[2], (__nv_bfloat16*)d_out, scratch,
                                                                      (const __nv_bfloat16*)d_in[4], P);
}
```

```cpp
#include <cuda_runtime.h>
#include <cuda_bf16.h>
#include <cuda.h>
#include <stdint.h>

#define HALO_NS 300
#define HINT 5
#define HOLD 1
#define LATEREL 1
#define PF 400
#define PF0 2
#define PF1 8
#define ENDBAR 1
#define LEADW 4
#define LEADN 7
#define TSQ 0
#define PACE 600
#define PAUSE 8
#define LAG1 4

namespace {

constexpr int S_ = 2048, D_ = 448, F_ = 1792;
constexpr int NCTA = 128, NTHREADS = 384;
constexpr int NSLOT = 6, SLOT = 32768, WSLOT = 24576, TILEB = 14336, SLAB = 3584, HALF = 7168;
constexpr int KV = 1792, HSTG = SLAB + 32, PITCH = 240;
constexpr int OFF_X = NSLOT * SLOT;
constexpr int OFF_Y = OFF_X + 10 * KV;
constexpr int OFF_ST = OFF_Y + TILEB;
constexpr int OFF_BAR = OFF_ST + 1024;
constexpr int SMEM_BYTES = OFF_BAR + 1280;
constexpr uint32_t SMEM0 = 1024;
constexpr int B_QFULL = 0, B_FULL = 56, B_HALO = 128, B_X = 136, B_CS = 168, B_FREE = 192, B_END = 200, B_QEMPTY = 216, B_EMPTY = 232, B_ROW = 288, NBAR = 37;
constexpr float LN_EPS = 1e-5f, QK_SCALE = 0.1889822365046136f * 1.4426950408889634f;
constexpr int SPIN_LIMIT = 1 << 22;

struct Scratch {
    uint8_t H[4][32][TILEB];
    uint8_t U[4][28][TILEB];
    uint8_t O[16][8][TILEB];
    uint8_t Wo[4][8][TILEB];
    uint8_t halo[NCTA][2 * KV];
    uint2 stat[S_];
    uint2 colsum[8][8][96];
    uint32_t flag[32][32];
    uint32_t epoch[NCTA];
};
__device__ __align__(1024) Scratch g_s;

#define TS(g, i)
#define TS0(g, i)
#define TSDUMP()

struct Params {
    CUtensorMap tmX, tmWqkv, tmW1, tmW2, tmOut;
};

__device__ __forceinline__ bool elect() {
    uint32_t p;
    asm volatile("{\n.reg .pred p;\nelect.sync _|p, 0xffffffff;\nselp.u32 %0, 1, 0, p;\n}" : "=r"(p));
    return p;
}
__device__ __forceinline__ void mbar_init(uint32_t b, uint32_t c) { asm volatile("mbarrier.init.shared::cta.b64 [%0], %1;" ::"r"(b), "r"(c) : "memory"); }
__device__ __forceinline__ void mbar_expect(uint32_t b, uint32_t tx) { asm volatile("mbarrier.arrive.expect_tx.shared::cta.b64 _, [%0], %1;" ::"r"(b), "r"(tx) : "memory"); }
__device__ __forceinline__ void mbar_arrive(uint32_t b) { asm volatile("mbarrier.arrive.shared::cta.b64 _, [%0];" ::"r"(b) : "memory"); }
template <int N> __device__ __forceinline__ void mbar_arrive_n(uint32_t b) { asm volatile("mbarrier.arrive.shared::cta.b64 _, [%0], %1;" ::"r"(b), "n"(N) : "memory"); }
__device__ __forceinline__ void mbar_arrive4_remote(uint32_t b) { asm volatile("mbarrier.arrive.shared::cluster.b64 _, [%0], 4;" ::"r"(b) : "memory"); }
__device__ __forceinline__ void mbar_arrive_remote(uint32_t b) { asm volatile("mbarrier.arrive.shared::cluster.b64 _, [%0];" ::"r"(b) : "memory"); }
#define MBAR_WAIT_ASM(SEM) \
    asm volatile("{\n.reg .pred p;\nWAIT:\nmbarrier.try_wait.parity" SEM ".shared::cta.b64 p, [%0], %1;\n@!p bra WAIT;\n}" ::"r"(b), "r"(parity) : "memory")
__device__ __forceinline__ void mbar_wait(uint32_t b, uint32_t parity) { MBAR_WAIT_ASM(""); }
__device__ __forceinline__ void mbar_wait_bounded(uint32_t b, uint32_t parity, uint32_t& n) {
    asm volatile("{\n.reg .pred p;\nWAIT:\nadd.u32 %0, %0, 1;\nsetp.gt.u32 p, %0, %3;\n@p st.global.u32 [%4], %0;\n"
                 "mbarrier.try_wait.parity.shared::cta.b64 p, [%1], %2;\n@!p bra WAIT;\n}" : "+r"(n) : "r"(b), "r"(parity), "n"(SPIN_LIMIT), "l"(0ull) : "memory");
}
__device__ __forceinline__ uint32_t mapa(uint32_t a, uint32_t rank) { uint32_t r; asm("mapa.shared::cluster.u32 %0, %1, %2;" : "=r"(r) : "r"(a), "r"(rank)); return r; }
__device__ __forceinline__ void tma3d(uint32_t dst, const CUtensorMap* tm, uint32_t bar, int c0, int c1, int c2) {
    asm volatile("cp.async.bulk.tensor.3d.shared::cluster.global.mbarrier::complete_tx::bytes [%0], [%1, {%3, %4, %5}], [%2];" ::"r"(dst), "l"(tm), "r"(bar), "r"(c0), "r"(c1), "r"(c2) : "memory");
}
__device__ __forceinline__ void tma3d_pair(uint32_t dst, const CUtensorMap* tm, uint32_t bar, int c0, int c1, int c2) {
    asm volatile("cp.async.bulk.tensor.3d.shared::cluster.global.mbarrier::complete_tx::bytes.multicast::cluster [%0], [%1, {%3, %4, %5}], [%2], %6;" ::"r"(dst), "l"(tm), "r"(bar), "r"(c0), "r"(c1), "r"(c2), "h"((uint16_t)3) : "memory");
}
__device__ __forceinline__ void bulk_load(uint32_t dst, const void* src, uint32_t bytes, uint32_t bar) {
    asm volatile("cp.async.bulk.shared::cluster.global.mbarrier::complete_tx::bytes [%0], [%1], %2, [%3];" ::"r"(dst), "l"(src), "r"(bytes), "r"(bar) : "memory");
}
__device__ __forceinline__ void bulk_store(void* dst, uint32_t src, uint32_t bytes) {
    asm volatile("cp.async.bulk.global.shared::cta.bulk_group [%0], [%1], %2;" ::"l"(dst), "r"(src), "r"(bytes) : "memory");
}
__device__ __forceinline__ uint32_t ld_u16(const void* p) { uint32_t v; asm volatile("ld.global.nc.u16 %0, [%1];" : "=r"(v) : "l"(p)); return v; }
__device__ __forceinline__ uint32_t ld_relaxed(const uint32_t* p) { uint32_t v; asm volatile("ld.relaxed.gpu.global.u32 %0, [%1];" : "=r"(v) : "l"(p) : "memory"); return v; }
__device__ __forceinline__ void bulk_flush() { asm volatile("cp.async.bulk.commit_group;\ncp.async.bulk.wait_group 0;" ::: "memory"); }
__device__ __forceinline__ void signal(uint32_t* flag) { asm volatile("fence.acq_rel.gpu;\nred.relaxed.gpu.global.add.u32 [%0], 1;" ::"l"(flag) : "memory"); }
__device__ __forceinline__ void hint(uint32_t* flag) { asm volatile("red.relaxed.gpu.global.add.u32 [%0], 1;" ::"l"(flag) : "memory"); }
__device__ __forceinline__ uint32_t tag(uint32_t v, uint32_t mask, uint32_t parity) { return (v & ~mask) | (parity & mask); }
__device__ __forceinline__ uint32_t or_diff(uint32_t acc, uint32_t v, uint32_t parity) { asm("lop3.b32 %0, %0, %1, %2, 0xf6;" : "+r"(acc) : "r"(v), "r"(parity)); return acc; }
__device__ __forceinline__ uint4 ld_relaxed4(const void* p) {
    uint4 v;
    asm volatile("ld.relaxed.gpu.global.v4.u32 {%0, %1, %2, %3}, [%4];" : "=r"(v.x), "=r"(v.y), "=r"(v.z), "=r"(v.w) : "l"(p) : "memory");
    return v;
}
__device__ __forceinline__ uint2 ld_relaxed2(const void* p) { uint2 v; asm volatile("ld.relaxed.gpu.global.v2.u32 {%0, %1}, [%2];" : "=r"(v.x), "=r"(v.y) : "l"(p) : "memory"); return v; }
__device__ __forceinline__ void sts4(uint32_t a, uint4 v) { asm volatile("st.shared.v4.b32 [%0], {%1, %2, %3, %4};" ::"r"(a), "r"(v.x), "r"(v.y), "r"(v.z), "r"(v.w) : "memory"); }
__device__ __forceinline__ void sts1(uint32_t a, uint32_t v) { asm volatile("st.shared.b32 [%0], %1;" ::"r"(a), "r"(v) : "memory"); }
__device__ __forceinline__ void sts2(uint32_t a, uint32_t v0, uint32_t v1) { asm volatile("st.shared.v2.b32 [%0], {%1, %2};" ::"r"(a), "r"(v0), "r"(v1) : "memory"); }
__device__ __forceinline__ void stg1(void* p, uint32_t v) { asm volatile("st.global.b32 [%0], %1;" ::"l"(p), "r"(v) : "memory"); }
__device__ __forceinline__ void fence_async_shared() { asm volatile("fence.proxy.async.shared::cta;" ::: "memory"); }
#define BOUND "add.u32 %0, %0, 16;\nsetp.gt.u32 p, %0, %1;\n@p st.global.u32 [%2], %0;\n"
__device__ __forceinline__ void wait_flag(const uint32_t* p, uint32_t target, uint32_t& n) {
    asm volatile("{\n.reg .pred p;\n.reg .u32 v;\nPOLL:\n" BOUND "ld.acquire.gpu.global.u32 v, [%3];\nsetp.ne.u32 p, v, %4;\n@p bra POLL;\nfence.proxy.async.global;\n}"
                 : "+r"(n) : "n"(SPIN_LIMIT), "l"(0ull), "l"(p), "r"(target) : "memory");
}
__device__ __forceinline__ void wait_flag2(const uint32_t* h, uint32_t th, const uint32_t* p, uint32_t target, uint32_t& n) {
    asm volatile("{\n.reg .pred p;\n.reg .u32 u, v;\nPOLL:\n" BOUND "ld.relaxed.gpu.global.u32 u, [%3];\nld.acquire.gpu.global.u32 v, [%5];\nsetp.ne.u32 p, u, %4;\nsetp.ne.or.u32 p, v, %6, p;\n@p bra POLL;\nfence.proxy.async.global;\n}"
                 : "+r"(n) : "n"(SPIN_LIMIT), "l"(0ull), "l"(h), "r"(th), "l"(p), "r"(target) : "memory");
}
__device__ __forceinline__ void bar_sync(int id, int n) { asm volatile("bar.sync %0, %1;" ::"r"(id), "r"(n) : "memory"); }
__device__ __forceinline__ void bar_arrive(int id, int n) { asm volatile("bar.arrive %0, %1;" ::"r"(id), "r"(n) : "memory"); }
__device__ __forceinline__ void wg_fence() { asm volatile("wgmma.fence.sync.aligned;" ::: "memory"); }
__device__ __forceinline__ void wg_commit() { asm volatile("wgmma.commit_group.sync.aligned;" ::: "memory"); }
template <int N> __device__ __forceinline__ void wg_wait() { asm volatile("wgmma.wait_group.sync.aligned %0;" ::"n"(N) : "memory"); }
template <int N> __device__ __forceinline__ void pin(float (&d)[N]) {
#pragma unroll
    for (int i = 0; i < N; i++) asm volatile("" : "+f"(d[i])::"memory");
}
__host__ __device__ constexpr uint32_t desc_hi(uint32_t sbo, uint32_t swz) { return (sbo >> 4) | (swz << 30); }
__host__ __device__ constexpr uint32_t desc_lo(uint32_t off, uint32_t lbo) { return ((SMEM0 + off) >> 4) | ((lbo >> 4) << 16); }
__device__ __forceinline__ uint32_t pack2(float lo, float hi) { uint32_t r; asm("cvt.rn.bf16x2.f32 %0, %1, %2;" : "=r"(r) : "f"(hi), "f"(lo)); return r; }
__device__ __forceinline__ float bf_lo(uint32_t v) { return __uint_as_float(v << 16); }
__device__ __forceinline__ float bf_hi(uint32_t v) { return __uint_as_float(v & 0xffff0000u); }
__device__ __forceinline__ void stsm4(uint32_t a, uint32_t r0, uint32_t r1, uint32_t r2, uint32_t r3) {
    asm volatile("stmatrix.sync.aligned.m8n8.x4.shared.b16 [%0], {%1, %2, %3, %4};" ::"r"(a), "r"(r0), "r"(r1), "r"(r2), "r"(r3) : "memory");
}
__device__ __forceinline__ void stsm2(uint32_t a, uint32_t r0, uint32_t r1) {
    asm volatile("stmatrix.sync.aligned.m8n8.x2.shared.b16 [%0], {%1, %2};" ::"r"(a), "r"(r0), "r"(r1) : "memory");
}
__device__ __forceinline__ uint4 lds4(uint32_t a) { uint4 v; asm volatile("ld.shared.v4.b32 {%0, %1, %2, %3}, [%4];" : "=r"(v.x), "=r"(v.y), "=r"(v.z), "=r"(v.w) : "r"(a) : "memory"); return v; }
__device__ __forceinline__ uint2 lds2(uint32_t a) { uint2 v; asm volatile("ld.shared.v2.b32 {%0, %1}, [%2];" : "=r"(v.x), "=r"(v.y) : "r"(a) : "memory"); return v; }
__device__ __forceinline__ float lds1f(uint32_t a) { float v; asm volatile("ld.shared.f32 %0, [%1];" : "=f"(v) : "r"(a) : "memory"); return v; }
__device__ __forceinline__ void ldsm4(uint32_t* r, uint32_t a) {
    asm volatile("ldmatrix.sync.aligned.m8n8.x4.shared.b16 {%0, %1, %2, %3}, [%4];" : "=r"(r[0]), "=r"(r[1]), "=r"(r[2]), "=r"(r[3]) : "r"(a) : "memory");
}
__device__ __forceinline__ void ldsm4t(uint32_t* r, uint32_t a) {
    asm volatile("ldmatrix.sync.aligned.m8n8.x4.trans.shared.b16 {%0, %1, %2, %3}, [%4];" : "=r"(r[0]), "=r"(r[1]), "=r"(r[2]), "=r"(r[3]) : "r"(a) : "memory");
}
__device__ __forceinline__ void ldsm2t(uint32_t* r, uint32_t a) {
    asm volatile("ldmatrix.sync.aligned.m8n8.x2.trans.shared.b16 {%0, %1}, [%2];" : "=r"(r[0]), "=r"(r[1]) : "r"(a) : "memory");
}
__device__ __forceinline__ uint32_t transpose8(uint32_t v) { uint32_t r; asm volatile("movmatrix.sync.aligned.m8n8.trans.b16 %0, %1;" : "=r"(r) : "r"(v)); return r; }
__device__ __forceinline__ void mma16(float (&c)[4], uint32_t a0, uint32_t a1, uint32_t a2, uint32_t a3, uint32_t b0, uint32_t b1) {
    asm volatile("mma.sync.aligned.m16n8k16.row.col.f32.bf16.bf16.f32 {%0, %1, %2, %3}, {%4, %5, %6, %7}, {%8, %9}, {%0, %1, %2, %3};"
                 : "+f"(c[0]), "+f"(c[1]), "+f"(c[2]), "+f"(c[3]) : "r"(a0), "r"(a1), "r"(a2), "r"(a3), "r"(b0), "r"(b1));
}
__device__ __forceinline__ void mma8(float (&c)[4], uint32_t a0, uint32_t a1, uint32_t b0) {
    asm volatile("mma.sync.aligned.m16n8k8.row.col.f32.bf16.bf16.f32 {%0, %1, %2, %3}, {%4, %5}, {%6}, {%0, %1, %2, %3};"
                 : "+f"(c[0]), "+f"(c[1]), "+f"(c[2]), "+f"(c[3]) : "r"(a0), "r"(a1), "r"(b0));
}
__device__ __forceinline__ void st_async4(uint32_t a, uint32_t bar, uint32_t v0, uint32_t v1, uint32_t v2, uint32_t v3) {
    asm volatile("st.async.weak.shared::cluster.mbarrier::complete_tx::bytes.v4.b32 [%0], {%2, %3, %4, %5}, [%1];" ::"r"(a), "r"(bar), "r"(v0), "r"(v1), "r"(v2), "r"(v3) : "memory");
}
__device__ __forceinline__ void st_async2(uint32_t a, uint32_t bar, uint32_t v0, uint32_t v1) {
    asm volatile("st.async.weak.shared::cluster.mbarrier::complete_tx::bytes.v2.b32 [%0], {%2, %3}, [%1];" ::"r"(a), "r"(bar), "r"(v0), "r"(v1) : "memory");
}
__device__ __forceinline__ float quad_max(float v) { v = fmaxf(v, __shfl_xor_sync(~0u, v, 1)); return fmaxf(v, __shfl_xor_sync(~0u, v, 2)); }
__device__ __forceinline__ float quad_sum(float v) { v += __shfl_xor_sync(~0u, v, 1); return v + __shfl_xor_sync(~0u, v, 2); }
__device__ __forceinline__ float ex2(float v) { float r; asm("ex2.approx.ftz.f32 %0, %1;" : "=f"(r) : "f"(v)); return r; }
__device__ __forceinline__ float rcp(float v) { float r; asm("rcp.approx.ftz.f32 %0, %1;" : "=f"(r) : "f"(v)); return r; }
__device__ __forceinline__ float rsq(float v) { float r; asm("rsqrt.approx.ftz.f32 %0, %1;" : "=f"(r) : "f"(v)); return r; }
__device__ __forceinline__ float gelu2(float v) {
    float z = v * fmaf(v * v, 8 * 0.044715f * 0.7978845608028654f, 2 * 0.7978845608028654f), t;
    asm("tanh.approx.f32 %0, %1;" : "=f"(t) : "f"(z));
    return fmaf(v, t, v);
}
__device__ __forceinline__ float row_sum(float v) {
    v = quad_sum(v); v += __shfl_xor_sync(~0u, v, 4);
    return v + __shfl_xor_sync(~0u, v, 24);
}

template <int TA, int TB, uint32_t HA, uint32_t HB>
__device__ __forceinline__ void wgmma_n112(float (&d)[56], uint32_t da, uint32_t db, int accumulate) {
    asm volatile("{\n.reg .pred p;\n.reg .b64 a, b;\nmov.b64 a, {%56, %61};\nmov.b64 b, {%57, %62};\nsetp.ne.b32 p, %58, 0;\n"
        "wgmma.mma_async.sync.aligned.m64n112k16.f32.bf16.bf16 {"
        "%0, %1, %2, %3, %4, %5, %6, %7, %8, %9, %10, %11, %12, %13, %14, %15, "
        "%16, %17, %18, %19, %20, %21, %22, %23, %24, %25, %26, %27, %28, %29, %30, %31, "
        "%32, %33, %34, %35, %36, %37, %38, %39, %40, %41, %42, %43, %44, %45, %46, %47, "
        "%48, %49, %50, %51, %52, %53, %54, %55"
        "}, a, b, p, 1, 1, %59, %60;\n}\n"
        : "+f"(d[0]), "+f"(d[1]), "+f"(d[2]), "+f"(d[3]), "+f"(d[4]), "+f"(d[5]), "+f"(d[6]), "+f"(d[7]),
          "+f"(d[8]), "+f"(d[9]), "+f"(d[10]), "+f"(d[11]), "+f"(d[12]), "+f"(d[13]), "+f"(d[14]), "+f"(d[15]),
          "+f"(d[16]), "+f"(d[17]), "+f"(d[18]), "+f"(d[19]), "+f"(d[20]), "+f"(d[21]), "+f"(d[22]), "+f"(d[23]),
          "+f"(d[24]), "+f"(d[25]), "+f"(d[26]), "+f"(d[27]), "+f"(d[28]), "+f"(d[29]), "+f"(d[30]), "+f"(d[31]),
          "+f"(d[32]), "+f"(d[33]), "+f"(d[34]), "+f"(d[35]), "+f"(d[36]), "+f"(d[37]), "+f"(d[38]), "+f"(d[39]),
          "+f"(d[40]), "+f"(d[41]), "+f"(d[42]), "+f"(d[43]), "+f"(d[44]), "+f"(d[45]), "+f"(d[46]), "+f"(d[47]),
          "+f"(d[48]), "+f"(d[49]), "+f"(d[50]), "+f"(d[51]), "+f"(d[52]), "+f"(d[53]), "+f"(d[54]), "+f"(d[55])
        : "r"(da), "r"(db), "r"(accumulate), "n"(TA), "n"(TB), "n"(HA), "n"(HB));
}

template <int TA, int TB, uint32_t HA, uint32_t HB>
__device__ __forceinline__ void wgmma_n168(float (&d)[84], uint32_t da, uint32_t db, int accumulate) {
    asm volatile("{\n.reg .pred p;\n.reg .b64 a, b;\nmov.b64 a, {%84, %89};\nmov.b64 b, {%85, %90};\nsetp.ne.b32 p, %86, 0;\n"
        "wgmma.mma_async.sync.aligned.m64n168k16.f32.bf16.bf16 {"
        "%0, %1, %2, %3, %4, %5, %6, %7, %8, %9, %10, %11, %12, %13, %14, %15, "
        "%16, %17, %18, %19, %20, %21, %22, %23, %24, %25, %26, %27, %28, %29, %30, %31, "
        "%32, %33, %34, %35, %36, %37, %38, %39, %40, %41, %42, %43, %44, %45, %46, %47, "
        "%48, %49, %50, %51, %52, %53, %54, %55, %56, %57, %58, %59, %60, %61, %62, %63, "
        "%64, %65, %66, %67, %68, %69, %70, %71, %72, %73, %74, %75, %76, %77, %78, %79, "
        "%80, %81, %82, %83"
        "}, a, b, p, 1, 1, %87, %88;\n}\n"
        : "+f"(d[0]), "+f"(d[1]), "+f"(d[2]), "+f"(d[3]), "+f"(d[4]), "+f"(d[5]), "+f"(d[6]), "+f"(d[7]),
          "+f"(d[8]), "+f"(d[9]), "+f"(d[10]), "+f"(d[11]), "+f"(d[12]), "+f"(d[13]), "+f"(d[14]), "+f"(d[15]),
          "+f"(d[16]), "+f"(d[17]), "+f"(d[18]), "+f"(d[19]), "+f"(d[20]), "+f"(d[21]), "+f"(d[22]), "+f"(d[23]),
          "+f"(d[24]), "+f"(d[25]), "+f"(d[26]), "+f"(d[27]), "+f"(d[28]), "+f"(d[29]), "+f"(d[30]), "+f"(d[31]),
          "+f"(d[32]), "+f"(d[33]), "+f"(d[34]), "+f"(d[35]), "+f"(d[36]), "+f"(d[37]), "+f"(d[38]), "+f"(d[39]),
          "+f"(d[40]), "+f"(d[41]), "+f"(d[42]), "+f"(d[43]), "+f"(d[44]), "+f"(d[45]), "+f"(d[46]), "+f"(d[47]),
          "+f"(d[48]), "+f"(d[49]), "+f"(d[50]), "+f"(d[51]), "+f"(d[52]), "+f"(d[53]), "+f"(d[54]), "+f"(d[55]),
          "+f"(d[56]), "+f"(d[57]), "+f"(d[58]), "+f"(d[59]), "+f"(d[60]), "+f"(d[61]), "+f"(d[62]), "+f"(d[63]),
          "+f"(d[64]), "+f"(d[65]), "+f"(d[66]), "+f"(d[67]), "+f"(d[68]), "+f"(d[69]), "+f"(d[70]), "+f"(d[71]),
          "+f"(d[72]), "+f"(d[73]), "+f"(d[74]), "+f"(d[75]), "+f"(d[76]), "+f"(d[77]), "+f"(d[78]), "+f"(d[79]),
          "+f"(d[80]), "+f"(d[81]), "+f"(d[82]), "+f"(d[83])
        : "r"(da), "r"(db), "r"(accumulate), "n"(TA), "n"(TB), "n"(HA), "n"(HB));
}

template <uint32_t HB>
__device__ __forceinline__ void wgmma_rs_n168(float (&d)[84], uint32_t a0, uint32_t a1, uint32_t db) {
    asm volatile("{\n.reg .b64 b;\nmov.b64 b, {%86, %88};\n"
        "wgmma.mma_async.sync.aligned.m64n168k16.f32.bf16.bf16 {"
        "%0, %1, %2, %3, %4, %5, %6, %7, %8, %9, %10, %11, %12, %13, %14, %15, "
        "%16, %17, %18, %19, %20, %21, %22, %23, %24, %25, %26, %27, %28, %29, %30, %31, "
        "%32, %33, %34, %35, %36, %37, %38, %39, %40, %41, %42, %43, %44, %45, %46, %47, "
        "%48, %49, %50, %51, %52, %53, %54, %55, %56, %57, %58, %59, %60, %61, %62, %63, "
        "%64, %65, %66, %67, %68, %69, %70, %71, %72, %73, %74, %75, %76, %77, %78, %79, "
        "%80, %81, %82, %83"
        "}, {%84, %85, %87, %87}, b, 1, 1, 1, 0;\n}\n"
        : "+f"(d[0]), "+f"(d[1]), "+f"(d[2]), "+f"(d[3]), "+f"(d[4]), "+f"(d[5]), "+f"(d[6]), "+f"(d[7]),
          "+f"(d[8]), "+f"(d[9]), "+f"(d[10]), "+f"(d[11]), "+f"(d[12]), "+f"(d[13]), "+f"(d[14]), "+f"(d[15]),
          "+f"(d[16]), "+f"(d[17]), "+f"(d[18]), "+f"(d[19]), "+f"(d[20]), "+f"(d[21]), "+f"(d[22]), "+f"(d[23]),
          "+f"(d[24]), "+f"(d[25]), "+f"(d[26]), "+f"(d[27]), "+f"(d[28]), "+f"(d[29]), "+f"(d[30]), "+f"(d[31]),
          "+f"(d[32]), "+f"(d[33]), "+f"(d[34]), "+f"(d[35]), "+f"(d[36]), "+f"(d[37]), "+f"(d[38]), "+f"(d[39]),
          "+f"(d[40]), "+f"(d[41]), "+f"(d[42]), "+f"(d[43]), "+f"(d[44]), "+f"(d[45]), "+f"(d[46]), "+f"(d[47]),
          "+f"(d[48]), "+f"(d[49]), "+f"(d[50]), "+f"(d[51]), "+f"(d[52]), "+f"(d[53]), "+f"(d[54]), "+f"(d[55]),
          "+f"(d[56]), "+f"(d[57]), "+f"(d[58]), "+f"(d[59]), "+f"(d[60]), "+f"(d[61]), "+f"(d[62]), "+f"(d[63]),
          "+f"(d[64]), "+f"(d[65]), "+f"(d[66]), "+f"(d[67]), "+f"(d[68]), "+f"(d[69]), "+f"(d[70]), "+f"(d[71]),
          "+f"(d[72]), "+f"(d[73]), "+f"(d[74]), "+f"(d[75]), "+f"(d[76]), "+f"(d[77]), "+f"(d[78]), "+f"(d[79]),
          "+f"(d[80]), "+f"(d[81]), "+f"(d[82]), "+f"(d[83])
        : "r"(a0), "r"(a1), "r"(db), "r"(0), "n"(HB));
}

struct Ring {
    uint32_t slot, ph;
    __device__ __forceinline__ void next() { if (++slot == NSLOT) { slot = 0; ph ^= 1; } }
    __device__ __forceinline__ void next2() { ph ^= slot == 5; slot = __byte_perm(0x06030201u, 0x00040005u, 0x7770 + slot); }
};
struct Slot {
    uint32_t dst, bar, ph;
    __device__ __forceinline__ void next(uint32_t bars) {
        dst += SLOT; bar += 8;
        if (bar == bars + 8 * NSLOT) { dst -= NSLOT * SLOT; bar = bars; ph ^= 1; }
    }
};
__device__ __forceinline__ uint32_t xslot(int i) { return __byte_perm(0x04130e0cu, 0x00130e0cu, 0x7770 + i); }
__device__ __forceinline__ uint32_t wslot(int i) { return __byte_perm(0x06001510u, 0x00151009u, 0x7770 + i); }

constexpr uint32_t HI_SW = desc_hi(1024, 1);

struct Mma {
    uint32_t bars, rel;
    bool lead;
    int wg, half, w;
    Ring r;
    uint32_t prev;
    __device__ __forceinline__ void release_pair(uint32_t s) { if (lead) mbar_arrive4_remote(rel + B_EMPTY + 8 * s); }
    __device__ __forceinline__ void release(uint32_t s) { if (lead) mbar_arrive_n<4>(bars + B_EMPTY + 8 * s); }
    template <bool G1>
    __device__ __forceinline__ void run(float (&a)[56], int n, int first, int last, int lag, int accumulate, int ts, const __nv_bfloat16* bias = nullptr) {
#pragma unroll 1
        for (int i = 0; i < n; i++) {
            if (lag && i == (wg ? n - lag : -1)) {
                if (!G1) {
                    const uint32_t c0 = ld_u16(bias), c1 = ld_u16(bias + 8);
                    wg_wait<0>(); release(prev); last = first;
                    pin(a);
#pragma unroll
                    for (int k = 0; k < 56; k++) a[k] += bf_lo((k & 2) ? c1 : c0);
                    pin(a);
                }
                bar_sync(7, 256);
            }
            const bool seen = !G1 && last == first;
            const uint32_t s = seen ? n - 1 - i : r.slot;
            if (!seen) mbar_wait(bars + B_FULL + 8 * s, r.ph);
            if (G1) r.next(); else r.next2();
            if (!TSQ || !i) TS0(G1 ? 2 : 8, ts + i + wg * 68);
            const uint32_t dB = s * (SLOT >> 4), dA = dB + half * 512;
            wg_fence();
#pragma unroll
            for (int k = 0; k < 4; k++) {
                wgmma_n112<1, 1, HI_SW, desc_hi(G1 ? 256 : 1024, 0)>(a, dA + desc_lo(k * 2048, 8192), dB + desc_lo(16384 + k * (G1 ? SLAB : 256), 128), k > 0 || accumulate || i > 0);
                if (k == 1) {
                    wg_commit(); wg_wait<1>();
                    if ((uint32_t)(i - first) < (uint32_t)(last - first)) release(prev);
                    if (G1 && lag && i == (wg ? -1 : n - 1)) bar_arrive(7, 256);
                    if (TSQ && i) TS0(G1 ? 2 : 8, ts + i + wg * 68);
                }
            }
            wg_commit();
            prev = s;
        }
    }
    __device__ __forceinline__ void run_o(float (&a)[56]) {
#pragma unroll 1
        for (int i = 0; i < 2; i++) {
            const uint32_t s = r.slot, dB = s * (SLOT >> 4), dA = dB + half * (HALF >> 4);
            mbar_wait(bars + B_FULL + 8 * s, r.ph);
            TS0(8, 48 + 2 * i + wg * 68);
            wg_fence();
#pragma unroll
            for (int k = 0; k < 7; k++) {
                if (k == 3) { mbar_wait(bars + B_FULL + 8 * s + 8, r.ph); wg_fence(); }
                wgmma_n112<0, 1, desc_hi(128, 0), desc_hi(256, 0)>(a, dA + desc_lo(k * 2048 + (k > 3) * (SLOT - HALF), k == 3 ? SLOT - 6144 : 1024),
                                                                   dB + desc_lo(16384 + k * SLAB + (k > 2) * (SLOT - 3 * SLAB), 128), k > 0 || i > 0);
                if (k & 1) wg_commit();
                if (k == 1) { wg_wait<1>(); if (i) release(prev); }
                if (k == 5) { wg_wait<1>(); release(s); }
            }
            wg_commit();
            prev = s + 1;
            r.slot++; r.next2();
        }
    }
};

__global__ void __cluster_dims__(2, 1, 1) __launch_bounds__(NTHREADS, 1)
fused_kernel(const __nv_bfloat16* __restrict__ x, const __nv_bfloat16* __restrict__ b1, const __nv_bfloat16* __restrict__ b2, const __nv_bfloat16* __restrict__ wo, __nv_bfloat16* out, Scratch* G,
             const __nv_bfloat16* __restrict__ w1,
             const __grid_constant__ Params P) {
    extern __shared__ __align__(1024) uint8_t smem[];
    const uint32_t sbase = (uint32_t)__cvta_generic_to_shared(smem);
    const uint32_t bars = sbase + OFF_BAR;
    const uint32_t rank = blockIdx.x & 1, pr = blockIdx.x >> 1;
    const uint32_t row0 = blockIdx.x * 16;
    if (threadIdx.x == 0) {
        TS(15, 0);
        mbar_init(bars + B_ROW, 1);
        asm volatile("fence.mbarrier_init.release.cluster;" ::: "memory");
        bulk_load(sbase + OFF_Y, x + row0 * D_, TILEB, bars + B_ROW);
        mbar_expect(bars + B_ROW, TILEB);
        TS(1, 97);
    }
    const int lane = threadIdx.x & 31;
    const int warp = __shfl_sync(~0u, threadIdx.x >> 5, 0), w = warp & 3;
    if (elect()) {
        const uint32_t first = bars + warp * 24, count = warp < 7 ? 1 : warp < 9 ? 18 - 2 * warp : 16;
#pragma unroll
        for (int i = 0; i < 3; i++) mbar_init(first + 8 * i, count);
        asm volatile("fence.mbarrier_init.release.cluster;" ::: "memory");
    }
    __syncwarp();
    asm volatile("barrier.cluster.arrive.relaxed.aligned;" ::: "memory");
    const uint32_t pv = pr < 4 ? pr * 8 + 36 : pr - 4 + (max((int)pr - 33, 0) * 37 >> 8);
    const uint32_t gp = (pv + 4) & 7, hp = pv >> 3;
    const uint32_t tb = gp * 2 + rank, c = hp * 16 + tb;
    const bool has_g1 = gp > 0;
    const uint32_t nt1 = hp & 3, ft = max((int)gp - 1, 0) * 2 + (hp >> 2);
    const uint32_t nt2 = (hp & 1) * 2 + rank, mt = (gp & 3) * 4 + (hp >> 1), ks = gp >> 2;
    asm volatile("barrier.cluster.wait.aligned;" ::: "memory");

    if (warp == 8) {
        uint32_t kw = (gp & 1) * 192, kx;
        if (elect()) {
            mbar_expect(bars + B_QFULL, WSLOT);
            tma3d(sbase + xslot(0) * 8192, &P.tmX, bars + B_FULL, 0, tb * 64, 0);
            tma3d_pair(sbase + wslot(0) * 8192 + rank * 12288, &P.tmWqkv, bars + B_QFULL, (hp * 56) & ~15, rank * 32, 0);
            TS(1, 23);
            uint32_t due = (uint32_t)clock() + PACE, ep = ld_relaxed(&G->epoch[c]);
            uint32_t spins = sbase == (rank << 24 | SMEM0) ? 0 : SPIN_LIMIT;
#pragma unroll 1
            for (int i = 1; i < 8; i++) {
                kx = kw; kw += 64;
                if (i >= 5) mbar_wait_bounded(bars + B_QEMPTY + 8 * (i - 5), 0, spins);
                else { while ((int)((uint32_t)clock() - due) < 0) {} due += PACE; }
                if (kw == D_) kw = 64;
                if (i < 4) kx = kw;
                const int ix = i - (i > 4);
                if (i < 7) mbar_expect(bars + B_QFULL + 8 * i, WSLOT);
                if (i != 4) tma3d(sbase + xslot(ix) * 8192, &P.tmX, bars + B_FULL + 8 * ix, kx, tb * 64, 0);
                if (i & (i >> 2)) mbar_wait_bounded(bars + B_CS - 20 + 4 * i, 0, spins);
                if (i < 7) tma3d_pair(sbase + wslot(i) * 8192 + rank * 12288, &P.tmWqkv, bars + B_QFULL + 8 * i, (hp * 56) & ~15, kw + rank * 32, 0);
            }
            ep++;
            Slot r{sbase, bars, 0};
            if (has_g1) {
                const uint8_t* src = G->H[nt1][rank * 16];
                const int row = rank * 1024;
                mbar_expect(bars + B_FULL, 16384 + TILEB);
                tma3d(sbase, &P.tmW1, bars + B_FULL, 0, row, ft * 2);
                wait_flag(G->flag[2 + rank * 2], 20 * ep, spins);
                TS(1, 16);
#pragma unroll 1
                for (int j = 64;; j += 64) {
                    bulk_load(r.dst + 16384, src, TILEB, r.bar + B_FULL);
                    src += TILEB;
                    r.next(bars);
                    if (j == 1024) break;
                    mbar_wait_bounded(r.bar + B_EMPTY, r.ph, spins);
                    if (j < 14 * 64) TS(2, 146 + j / 64);
                    mbar_expect(r.bar + B_FULL, 16384 + TILEB);
                    tma3d(r.dst, &P.tmW1, r.bar + B_FULL, 0, row + j, ft * 2);
                }
                mbar_arrive(bars + B_FULL + 48); mbar_arrive_n<16>(bars + B_EMPTY + 48);
#pragma unroll
                for (int i = 0; i < 4; i++) mbar_expect(bars + B_X + 8 * i, (i & 1) ? 3072 : 4096);
            } else {
                due = (uint32_t)clock();
#pragma unroll 1
                for (int j = PF0; j < PF1; j++) {
                    asm volatile("cp.async.bulk.prefetch.L2.global [%0], %1;" ::"l"(w1 + (rank * 1024 + j * 64 + hp * 8) * F_), "n"(16 * F_) : "memory");
                    due += PF;
                    while ((int)((uint32_t)clock() - due) < 0) {}
                }
            }
            const uint8_t *so = G->O[mt][ks * 4], *sw = G->Wo[nt2][ks * 4];
            wait_flag2(G->flag[16 + mt], 8 * ep, G->flag[0], 16 * ep, spins);
            TS(4, 18);
#pragma unroll 1
            for (int j = 0; j < 4 * TILEB; j += TILEB) {
                mbar_wait_bounded(r.bar + B_EMPTY, r.ph, spins);
                mbar_expect(r.bar + B_QFULL, TILEB);
                bulk_load(r.dst, so + j, TILEB, r.bar + B_QFULL);
                bulk_load(r.dst + 16384, sw + j, (r.bar & 8) ? TILEB : 3 * SLAB, r.bar + B_FULL);
                r.next(bars);
            }
            Ring q{has_g1 ? 2u : 6u, has_g1}, p{q.slot, !has_g1};
#pragma unroll 1
            for (int j = 0; j < 14 * 128; j += 128) {
                mbar_wait_bounded(bars + B_EMPTY + 8 * q.slot, q.ph, spins);
                if (LEADW && j >= LEADW * 128 && j < LEADN * 128) { mbar_wait_bounded(bars + B_FULL + 8 * p.slot, p.ph, spins); p.next2(); }
                TS(8, 176 + j / 128);
                tma3d(sbase + q.slot * SLOT, &P.tmW2, bars + B_FULL + 8 * q.slot, 0, ks * 896 + j - (j < 896 ? 0 : 832), mt * 2);
                q.next2();
            }
            mbar_wait_bounded(bars + B_END, 0, spins);
        }
    } else if (warp > 8) {
        const uint32_t ep = ld_relaxed(&G->epoch[c]) + 1;
        const uint8_t* src = G->U[nt2][ks * 14];
        uint32_t spins = 0, bad;
        {
            uint2* cs = G->colsum[hp][0];
            if (w == 2) {
                bar_sync(6, 288);
                TS(1, 8);
                stg1((uint32_t*)(G->stat + row0) + lane, tag(__float_as_uint(lds1f(sbase + OFF_ST + lane * 4)), ~lane & 1, ep));
                if (elect()) {
                    fence_async_shared();
#pragma unroll
                    for (int i = 0; i < 4; i++) bulk_store(G->H[i][0] + row0 * (SLAB / 16), sbase + OFF_X + i * HSTG, SLAB);
                    bulk_flush();
                    TS(1, 99);
                    signal(G->flag[2 + (row0 >> 10) * 2 + ((row0 & 1023) >= 320)]);
                }
                __syncwarp();
            } else {
                const uint32_t word = rank * 16 + (w & 2) * 4 + (lane & 7), done = mapa(bars + B_CS, rank ^ (lane & 1));
                const uint32_t from = (sbase + word * 4 + (gp >> 2) * 12288 + (gp & 2) * 1024) ^ ((lane >> 3) * 288);
                auto swz = [](uint32_t a) { return a ^ ((a >> 3) & 0x70); };
                const uint32_t lin = sbase + lane * 128 + (hp & 1) * 16, f0 = swz(lin + 80) + 8192, f1 = swz(lin + 96) + 8192, to = swz(lin + 112);
                float s[6] = {};
#pragma unroll 1
                for (int i = 0; i < 7; i++) {
                    const uint32_t o = wslot(i) * 8192, a0 = from + o, a1 = a0 ^ 144;
                    mbar_wait(bars + B_QFULL + 8 * i, 0);
                    if ((i ^ (w >> 1)) & 1) {
                        const uint4 v0 = lds4(f0 + o), v1 = lds4(f1 + o), v2 = lds4(f0 + o + 12288), v3 = lds4(f1 + o + 12288);
                        sts4(to + o, v0); sts4(to + o + 4096, v1); sts4(to + o + 12288, v2); sts4(to + o + 16384, v3);
                        fence_async_shared();
                        __syncwarp();
                        if (elect()) mbar_expect(bars + B_FULL + 8 * i, 16384);
                    }
                    if (i > 3 || i < (gp & 1)) continue;
                    if (w == 1) TS(1, 66);
                    uint32_t v[12];
#pragma unroll
                    for (int k = 0; k < 12; k++) v[k] = __float_as_uint(lds1f(((k & 1) ? a1 : a0) + (k & 2) * 512 + (k >> 2) * 4096));
#pragma unroll
                    for (int k = 0; k < 12; k++) { s[(k >> 2) * 2] += bf_lo(v[k]); s[(k >> 2) * 2 + 1] += bf_hi(v[k]); }
                    __syncwarp();
                    if ((i & 1) && lane < 2) mbar_arrive_remote(done + (i & 2) * 4);
                    if (i < 3) continue;
#pragma unroll
                    for (int k = 0; k < 6; k++) { s[k] += __shfl_xor_sync(~0u, s[k], 8); s[k] += __shfl_xor_sync(~0u, s[k], 16); }
                    const float s0 = lane < 8 ? s[0] : lane < 16 ? s[2] : s[4], s1 = lane < 8 ? s[1] : lane < 16 ? s[3] : s[5];
                    if (lane < 24) cs[gp * 96 + (lane >> 3) * 32 + word] = make_uint2(tag(__float_as_uint(s0), 1, ep), __float_as_uint(s1));
                    if (w == 1) TS(1, 24);
                }
            }
            bar_sync(1, 96);
            if (w == 1) TS(1, 98);
            const int i0 = threadIdx.x - 288, j0 = i0 - (hp & 1) * 4;
            cs += i0 + ((j0 & 92) == 28 ? (j0 & 32 ? 28 : 56) : 0);
            uint2 u[8];
            uint4 sv;
            do {
                sv = ld_relaxed4(G->stat + tb * 128 + (i0 & 63) * 2);
                bad = sv.x ^ ep;
#pragma unroll
                for (int i = 0; i < 8; i++) { u[i] = ld_relaxed2(cs + i * 96); bad = or_diff(bad, u[i].x, ep); }
                if (bad & 1) TS(1, 3);
            } while (bad & 1);
            if (w < 3) sts4(sbase + OFF_ST + i0 * 16, sv);
#pragma unroll
            for (int e = 0; e < 2; e++) {
                float f = 0.f;
#pragma unroll
                for (int i = 0; i < 8; i++) f += __uint_as_float(e ? u[i].y : u[i].x);
                const uint32_t hi = pack2(f, f);
                sts4(sbase + OFF_X + i0 * 32 + e * 16, make_uint4(hi, pack2(f - bf_hi(hi), f - bf_hi(hi)), 0, 0));
            }
            sts1(bars + 8 * NBAR, ep);
            fence_async_shared();
            __syncwarp();
            bar_arrive(8, 224); bar_arrive(9, 224);
            TS(1, 90 + w);
        }
        if (w < 3) {
            if (w == 1) {
                if (elect()) {
                    wait_flag(G->flag[3 + rank * 2], 44 * ep, spins);
                    mbar_arrive_n<16>(bars + B_EMPTY + 8 * 5);
                    TS(1, 96);
                }
                __syncwarp();
                if (!has_g1) { bar_sync(5, 288); if (elect()) signal(G->flag[0]); __syncwarp(); TS(2, 26); }
            }
            mbar_wait(bars + B_HALO, 0);
            uint32_t slot = (has_g1 ? 16 % NSLOT : 0) + w - 1, ph = ~0u;
#pragma unroll 1
            for (int i = w - 1; i < 18;) {
                const uint32_t d0 = sbase + slot * SLOT + (i < 4 ? 0 : 16384), landed = bars + B_QFULL + 8 * slot;
                mbar_wait(landed, (ph >> slot) & 1);
                ph ^= 1 << slot;
                if (i < 8) TS(4, 82 + i);
                if (i >= 4) TS(8, 156 + i);
                bad = 0;
#pragma unroll
                for (int k = 0; k < 14; k++) bad = or_diff(bad, __float_as_uint(lds1f(d0 + k * 1024 + lane * 32 + (lane >> 2) * 4)), ep);
                if (__any_sync(~0u, bad & 1)) {
                    if (elect()) {
                        const uint8_t* cur = (i < 4 ? G->O[mt][ks * 4] : src - 4 * TILEB) + i * TILEB;
                        fence_async_shared();
                        mbar_expect(landed, TILEB);
                        bulk_load(d0, cur, TILEB, landed);
                    }
                    TS(4, i < 4 ? 94 : 95);
                } else {
                    if (elect()) mbar_expect(landed + (B_FULL - B_QFULL), i < 4 ? (2 + w) * SLAB : 16384);
                    i += __byte_perm(0x03020202u, 0x00010202u, 0x7770 + slot);
                    slot = __byte_perm(0x05060302u, 0x00040100u, 0x7770 + slot);
                }
            }
        } else {
            bar_sync(3, 288);
            __nanosleep(HALO_NS);
            uint4 v[7];
            do {
                bad = 0;
#pragma unroll
                for (int i = 0; i < 7; i++) { v[i] = ld_relaxed4(G->halo[c - (tb > 0)] + i * 512 + lane * 16); bad = or_diff(bad, v[i].x, ep); }
            } while (bad & 1);
#pragma unroll
            for (int i = 0; i < 7; i++) sts4(sbase + OFF_X + i * 512 + lane * 16, v[i]);
            __syncwarp();
            if (elect()) mbar_arrive(bars + B_HALO);
            TS(2, 21);
            bar_sync(2, 288);
            if (elect()) bulk_store(out + row0 * D_, sbase + OFF_Y, TILEB);
            __syncwarp();
            bar_sync(4, 288);
            if (elect()) {
                fence_async_shared();
                bulk_store(G->O[tb][hp], sbase + OFF_X, TILEB);
                bulk_flush();
                TS(2, 7);
                mbar_arrive_remote(mapa(bars + B_FREE, rank ^ 1));
                mbar_arrive(bars + B_FREE);
                hint(G->flag[16 + tb]);
                signal(G->flag[16 + (row0 >> 7)] + 1);
                TS(2, 22);
            }
            __syncwarp();
            uint32_t late = ~0u;
            const uint32_t* hints = G->flag[8 + nt2 * 2 + ks] + (lane & 7);
            mbar_wait(bars + (has_g1 ? B_X : B_FREE), 0);
            Ring r{has_g1 ? 2u : 6u, has_g1};
#pragma unroll 1
            for (int i = 0; i < 14; i++) {
                while ((late >> i) & 1) late = __ballot_sync(~0u, ld_relaxed(hints) != 2 * ep) & 127;
                if (i == 0) TS(4, 17);
                mbar_wait(bars + B_EMPTY + 8 * r.slot, r.ph);
                TS(8, 192 + i);
                if (elect()) {
                    mbar_expect(bars + B_QFULL + 8 * r.slot, TILEB);
                    bulk_load(sbase + r.slot * SLOT + 16384, src, TILEB, bars + B_QFULL + 8 * r.slot);
                }
                src += TILEB; r.next2();
            }
            if (elect()) {
                wait_flag(G->flag[16 + mt] + 1, 8 * ep, spins);
                mbar_arrive(bars + B_ROW);
                TS(2, 27);
                G->epoch[c] = ep;
            }
        }
    } else {
        const int wg = warp >> 2;
        Mma M{bars, mapa(bars, rank ^ (lane & 1)), (threadIdx.x & 127) < 2, wg, wg, w, Ring{0, 1}, 0};
        const int r = lane >> 2, t = lane & 3;
        uint32_t ep;
        const uint32_t bias0 = ld_u16(b1 + ft * 128 + warp * 16 + r), bias1 = ld_u16(b1 + ft * 128 + warp * 16 + r + 8);
        const uint32_t kv = sbase + OFF_X + (w * 2 + wg) * KV + lane * 16;
        uint32_t q[8][2], k0[7], k1[14], v0[7];
        float f0, f1;
        {
            const int half = (lane >> 3) & 1, r16 = warp * 2 + (half ^ (lane >> 4)), nt = (lane >> 1) & 3;
            const uint32_t row = sbase + OFF_Y + r16 * (2 * D_), part = row + nt * 224 + half * 112 + (lane & 1) * 8;
            const uint32_t hb = sbase + OFF_X + nt * HSTG + r16 * 16 + (half ^ (row0 >> 10)) * (7 * 256) + (lane & 1) * 8;
            mbar_wait(bars + B_ROW, 0);
            TS0(1, 67);
            const float x0 = bf_lo(__float_as_uint(lds1f(row)));
            float d[28], m1 = 0.f, n1 = 0.f, m2 = 0.f, n2 = 0.f;
#pragma unroll
            for (int i = 0; i < 7; i++) {
                const uint2 v = lds2(part + i * 16);
#pragma unroll
                for (int k = 0; k < 2; k++) {
                    const float d0 = d[4 * i + 2 * k] = bf_lo(k ? v.y : v.x) - x0, d1 = d[4 * i + 2 * k + 1] = bf_hi(k ? v.y : v.x) - x0;
                    m1 += d0; n1 += d1; m2 = fmaf(d0, d0, m2); n2 = fmaf(d1, d1, n2);
                }
            }
            const float md = row_sum(m1 + n1) * (1.f / D_), var = fmaf(-md, md, row_sum(m2 + n2) * (1.f / D_)), nmean = -(x0 + md);
            const float rstd = rsq(var + LN_EPS);
            const float sc = rstd * rsq(fmaf(var * rstd, 4 * rstd, 4 * LN_EPS)), nb = -md * sc;
            sts2(sbase + OFF_ST + r16 * 8, __float_as_uint(rstd), pack2(nmean, nmean - bf_hi(pack2(nmean, nmean))));
#pragma unroll
            for (int i = 0; i < 7; i++) sts2(hb + i * 256, pack2(fmaf(d[4 * i], sc, nb), fmaf(d[4 * i + 1], sc, nb)), pack2(fmaf(d[4 * i + 2], sc, nb), fmaf(d[4 * i + 3], sc, nb)));
            TS0(1, 25);
            bar_arrive(6, 288);
            float acc[84];
#pragma unroll 1
            for (int kb = 0; kb < 7; kb++) {
                const bool held = kb == (wg ? 7 - HOLD : -1);
                if (held) { wg_wait<0>(); M.release_pair(4 - HOLD); TS0(1, 138); bar_sync(7, 256); }
                mbar_wait(bars + B_FULL + 8 * kb, 0);
                if (!TSQ || !kb) TS0(1, 68 + wg * 7 + kb);
                const uint32_t dA = (xslot(kb) + wg) * 512, dB = wslot(kb) * 512 + (hp & 1);
                wg_fence();
#pragma unroll
                for (int k = 0; k < 4; k++) {
                    wgmma_n168<0, 1, HI_SW, HI_SW>(acc, dA + desc_lo(k * 32, 16), dB + desc_lo((k & 1) * 2048 + (k >> 1) * 12288, 4096), k > 0 || kb > 0);
                    if (k == 0) { wg_commit(); wg_wait<1>(); if (kb > 0 && !held) M.release_pair(kb - 3); if (TSQ && kb) TS0(1, 68 + wg * 7 + kb); }
                }
                wg_commit();
            }
            if (wg == 0 && !LATEREL) bar_arrive(7, 256);
            if (wg == 0) TS0(1, 139);
            bar_sync(8 + wg, 224);
            if (wg == 0) TS0(1, 174);
            ep = __float_as_uint(lds1f(bars + 8 * NBAR));
            const uint32_t st = sbase + OFF_ST + (w * 32 + r * 2 + wg) * 8;
            const uint2 s0 = lds2(st), s1 = lds2(st + 128);
            const uint32_t a0 = t < 2 ? s0.y : 0, a1 = t < 2 ? s1.y : 0;
            wg_fence();
            wgmma_rs_n168<desc_hi(128, 0)>(acc, a0, a1, desc_lo(OFF_X, 0) + (hp & 1) * 8);
            wg_commit();
            if (wg == 0 && LATEREL) bar_arrive(7, 256);
            if (wg == 0) TS0(1, 175);
            wg_wait<1>();
            TS0(1, 190 + wg);
            M.release_pair(4);
            wg_wait<0>();
            pin(acc);
            TS0(1, 4 + 7 * wg);
            f0 = __uint_as_float(s0.x); f1 = __uint_as_float(s1.x);
#pragma unroll
            for (int g = 13; g >= 0; g--) {
                const float* a = acc + (g < 7 ? g + 8 : g < 12 ? g + 9 : g * 8 - 89) * 4;
                (g < 7 ? k0[g] : v0[g - 7]) = pack2(a[0] * f0, a[1] * f0);
                k1[g] = pack2(a[2] * f1, a[3] * f1);
            }
#pragma unroll
            for (int i = 0; i < 3; i++) stsm4(kv + 2 * KV + i * 512, k1[4 * i], k1[4 * i + 1], k1[4 * i + 2], k1[4 * i + 3]);
            stsm2(kv + 2 * KV + 1536, k1[12], k1[13]);
            if (w == 3) {
#pragma unroll
                for (int i = 0; i < 14; i++) stg1(G->halo[c] + wg * KV + lane * 4 + i * 128, tag(k1[i], t == 0, ep));
            }
            bar_arrive(3, 288);
#pragma unroll
            for (int g = 0; g < 7; g++) { q[g][0] = pack2(acc[4 * g], acc[4 * g + 1]); q[g][1] = pack2(acc[4 * g + 2], acc[4 * g + 3]); }
#pragma unroll
            for (int j = 0; j < 2; j++) { q[7][j] = t < 2 ? 0u : q[3][j]; q[3][j] = t < 2 ? q[3][j] : 0u; }
#pragma unroll
            for (int g = 0; g < 7; g++) v0[g] = transpose8(v0[g]);
        }
        TS0(1, 9 + 11 * wg);
        float a[56];
#pragma unroll
        for (int i = 0; i < 56; i++) asm volatile("" : "=f"(a[i]));
        if (__builtin_expect(!has_g1, 0)) {
            const int g = min(lane >> 1, 13), nt = rank * 2 + wg;
            const uint4* src = (const uint4*)(wo + (hp * 56 - (hp & 1) * 8 + w * 16 + (lane & 1)) * D_ + nt * 112) + g;
            uint4 v[8];
#pragma unroll
            for (int i = 0; i < 8; i++) v[i] = __ldg(src + i * (D_ / 4));
#pragma unroll
            for (int i = 0; i < 8; i++) ((uint4*)G->Wo[nt][hp])[w * (SLAB / 16) + g * 16 + (lane & 1) + 2 * i] = v[i];
            bar_arrive(5, 288);
        }
        M.run<true>(a, has_g1 ? PAUSE : 0, 1, 16, 0, 0, 32);
        {
            uint32_t kp[8], vv[14];
            TS0(2, 140 + wg);
            mbar_wait(bars + B_HALO, 0);
            TS0(2, 142 + wg);
            ldsm4(kp, kv); ldsm4(kp + 4, kv + (lane < 24 ? 512 : 0));
            const uint32_t va = kv + 896 + (lane & 8) * (2 * KV / 8 - 16) - (lane & 16) * 8;
            ldsm4t(vv, va); ldsm4t(vv + 4, va + 256); ldsm4t(vv + 8, va + 512); ldsm2t(vv + 12, va + 768);
            const bool e0 = 2 * t > r, e1 = 2 * t >= r;
            const uint32_t mk = (e0 ? 0xffffu : 0u) | (e1 ? 0xffff0000u : 0u);
            wg_wait<0>();
            pin(a);
            if (has_g1) M.release(M.prev);
            TS0(2, 144 + wg);
            bar_sync(2, 288);
            mbar_wait(bars + B_HALO, 0);
            TS0(2, 12 + 16 * wg);
            float sv[2][4];
#pragma unroll
            for (int h = 0; h < 2; h++) {
                const int ga = h * 4, gb = h * 4 + 1, gc = h * 4 + 2, gd = h * 4 + 3;
                float s[3][4] = {};
                mma16(s[0], q[ga][0], q[ga][1], q[gb][0], q[gb][1], kp[ga], kp[gb]);
                mma16(s[1], q[ga][0], q[ga][1], q[gb][0], q[gb][1], k0[ga], k0[gb]);
                mma16(s[2], q[ga][0], q[ga][1], q[gb][0], q[gb][1], k1[ga], k1[gb]);
                mma16(s[0], q[gc][0], q[gc][1], q[gd][0], q[gd][1], kp[gc], kp[gd]);
                mma16(s[1], q[gc][0], q[gc][1], q[gd][0], q[gd][1], k0[gc], k0[3]);
                mma16(s[2], q[gc][0], q[gc][1], q[gd][0], q[gd][1], k1[gc], k1[3]);
                if ((tb | w) == 0) s[0][0] = s[0][1] = -1e30f;
                sv[h][0] = e0 ? s[0][0] : s[1][0];
                sv[h][1] = e1 ? s[0][1] : s[1][1];
                sv[h][2] = e0 ? s[1][2] : s[2][2];
                sv[h][3] = e1 ? s[1][3] : s[2][3];
            }
            uint32_t pp[2][2];
#pragma unroll
            for (int i = 0; i < 4; i++) {
                float* v = &sv[i >> 1][(i & 1) * 2];
                const float f = ((i & 1) ? f1 : f0) * QK_SCALE, m = quad_max(fmaxf(v[0], v[1])) * f;
                const float p0 = ex2(fmaf(v[0], f, -m)), p1 = ex2(fmaf(v[1], f, -m));
                const float inv = rcp(quad_sum(p0 + p1));
                pp[i >> 1][i & 1] = pack2(p0 * inv, p1 * inv);
            }
            uint32_t o[8][2];
#pragma unroll
            for (int i = 0; i < 8; i++) {
                const int h = i >> 2, g = i - h;
                float d[4] = {};
                mma16(d, pp[h][0] & mk, 0u, 0u, pp[h][1] & ~mk, vv[2 * g], vv[2 * g + 1]);
                mma8(d, pp[h][0] & ~mk, pp[h][1] & mk, v0[g]);
                o[i][0] = pack2(d[0], d[1]); o[i][1] = pack2(d[2], d[3]);
            }
            if (t >= 2) { o[3][0] = o[4][0]; o[3][1] = o[4][1]; }
            const int word = wg * 4 + t - (w & 1) * 4 - (r >> 2);
#pragma unroll
            for (int i = 0; i < 8; i++) { o[i][0] = tag(o[i][0], word == 0, ep); o[i][1] = tag(o[i][1], word == 2, ep); }
            const uint32_t dst = sbase + OFF_X + (w >> 1) * HALF + ((w & 1) * 32 + (lane & 15) * 2 + wg) * 16 + (lane >> 4) * 1024;
            stsm4(dst, o[0][0], o[0][1], o[1][0], o[1][1]);
            stsm4(dst + 2048, o[2][0], o[2][1], o[3][0], o[3][1]);
            stsm4(dst + 4096, o[5][0], o[5][1], o[6][0], o[6][1]);
            stsm2(dst + 6144, o[7][0], o[7][1]);
            if (ENDBAR) bar_sync(4, 288); else bar_arrive(4, 288);
            TS0(2, 10 + 19 * wg);
        }
        if (has_g1) {
            M.run<true>(a, 16 - PAUSE, 1, 16, LAG1, 1, 32 + PAUSE);
            mbar_wait(bars + B_FREE, 0);
            const uint32_t xb = sbase + OFF_X + wg * 8192 + (threadIdx.x & 127) * 16, xbar = bars + B_X + 16 * wg;
            const uint32_t rx = mapa(xb, rank ^ 1), rbar = mapa(xbar, rank ^ 1);
            wg_wait<0>();
            pin(a);
            M.release(M.prev);
            TS0(4, 5 + wg);
#pragma unroll
            for (int i = 0; i < 3; i++)
                st_async4(rx + i * 2048, rbar + 8 * (i >> 1), pack2(a[28 + 8 * i], a[29 + 8 * i]), pack2(a[30 + 8 * i], a[31 + 8 * i]), pack2(a[32 + 8 * i], a[33 + 8 * i]), pack2(a[34 + 8 * i], a[35 + 8 * i]));
            const uint32_t tail = 6144 - (threadIdx.x & 127) * 8;
            st_async2(rx + tail, rbar + 8, pack2(a[52], a[53]), pack2(a[54], a[55]));
            uint8_t* dst = G->U[nt1][((ft >= 7) + wg) * 7 + ft] + rank * HALF + w * 256 + lane * 4;
            uint32_t u[14];
#pragma unroll
            for (int i = 0; i < 28; i++) a[i] = fmaf(bf_lo((i & 2) ? bias1 : bias0), 0.5f, a[i]);
#pragma unroll
            for (int i = 0; i < 14; i++) {
                if (i % 8 == 0) {
                    if (i) TS0(4, 134 + wg);
                    mbar_wait(xbar + i, 0);
                    TS0(4, (i ? 136 : 1) + wg);
#pragma unroll
                    for (int k = i / 4; k < i / 4 + 2; k++) {
                        if (k < 3) { const uint4 v = lds4(xb + k * 2048); u[4 * k] = v.x; u[4 * k + 1] = v.y; u[4 * k + 2] = v.z; u[4 * k + 3] = v.w; }
                        else { const uint2 v = lds2(xb + tail); u[12] = v.x; u[13] = v.y; }
                    }
                    if (i && lane < 2) mbar_arrive(bars + B_EMPTY + 48);
                }
                if (i == HINT && threadIdx.x == 0) hint(G->flag[8 + nt1 * 2] + ft + (ft >= 7) * 25);
                stg1(dst + (i >> 1) * 1024 + (i & 1) * 128, tag(pack2(gelu2(a[2 * i] + bf_lo(u[i])), gelu2(a[2 * i + 1] + bf_hi(u[i]))), (lane & 7) == w * 2 + (i & 1), ep));
            }
            TS0(4, 30 + wg);
        } else {
            mbar_wait(bars + B_FREE, 0);
            if (lane < 2) mbar_arrive(bars + B_EMPTY + 48);
        }
        M.half = wg ^ ks;
        const uint32_t orow = mt * 128 + M.half * 64 + w * 16;
        M.run_o(a);
        if (wg == 1) TS0(4, 13);
        M.run<false>(a, 14, 0, 14 - NSLOT, NSLOT + 1, 1, 52, b2 + orow + r);
        mbar_wait(bars + B_ROW, 1);
        const uint32_t stg = sbase + (4 + (w >> 1)) * SLOT + M.half * 8192 + (w & 1) * (PITCH * 16);
        const uint32_t sa = stg + (lane & 15) * PITCH + (lane >> 4) * 16;
        wg_wait<1>();
        if (wg == 0) bar_arrive(7, 256);
        wg_wait<0>();
        pin(a);
        TS0(8, 14 + wg);
#pragma unroll
        for (int i = 0; i < 7; i++)
            stsm4(sa + i * 32, pack2(a[8 * i], a[8 * i + 1]), pack2(a[8 * i + 2], a[8 * i + 3]), pack2(a[8 * i + 4], a[8 * i + 5]), pack2(a[8 * i + 6], a[8 * i + 7]));
        if (!wg) TS0(8, 206);
        fence_async_shared();
        __syncwarp();
        if (elect()) {
            asm volatile("cp.reduce.async.bulk.tensor.3d.global.shared::cta.add.tile.bulk_group [%0, {%4, %2, %3}], [%1];\ncp.async.bulk.commit_group;" ::"l"(&P.tmOut), "r"(stg), "r"(nt2), "r"(orow), "r"(0) : "memory");
            if (w == 0) mbar_arrive(bars + B_END);
            asm volatile("cp.async.bulk.wait_group.read 0;" ::: "memory");
        }
        TS0(15, wg ? 19 : 207);
        TSDUMP();
    }
}

typedef CUresult (*EncodeFn)(CUtensorMap*, CUtensorMapDataType, cuuint32_t, void*, const cuuint64_t*, const cuuint64_t*, const cuuint32_t*, const cuuint32_t*,
                             CUtensorMapInterleave, CUtensorMapSwizzle, CUtensorMapL2promotion, CUtensorMapFloatOOBfill);

void make_map(EncodeFn enc, CUtensorMap* tm, const void* base, bool swizzle, int d0, int d1, int d2, int s1, int s2, int b0, int b1, int b2) {
    const cuuint64_t dims[3] = {(cuuint64_t)d0, (cuuint64_t)d1, (cuuint64_t)d2}, strides[2] = {(cuuint64_t)s1 * 2, (cuuint64_t)s2 * 2};
    const cuuint32_t box[3] = {(cuuint32_t)b0, (cuuint32_t)b1, (cuuint32_t)b2}, es[3] = {1, 1, 1};
    enc(tm, CU_TENSOR_MAP_DATA_TYPE_BFLOAT16, d2 ? 3 : 2, (void*)base, dims, strides, box, es, CU_TENSOR_MAP_INTERLEAVE_NONE,
        swizzle ? CU_TENSOR_MAP_SWIZZLE_128B : CU_TENSOR_MAP_SWIZZLE_NONE, CU_TENSOR_MAP_L2_PROMOTION_L2_128B, CU_TENSOR_MAP_FLOAT_OOB_FILL_NONE);
}

}

extern "C" void kernel_launch(void* const* d_in, const int* in_sizes, int n_in, void* d_out, int out_size) {
    static EncodeFn enc = nullptr;
    static Scratch* scratch = nullptr;
    if (!enc) {
        void* fn = nullptr;
        cudaDriverEntryPointQueryResult qr;
        cudaGetDriverEntryPoint("cuTensorMapEncodeTiled", &fn, cudaEnableDefault, &qr);
        enc = (EncodeFn)fn;
        cudaGetSymbolAddress((void**)&scratch, g_s);
        cudaFuncSetAttribute(fused_kernel, cudaFuncAttributeMaxDynamicSharedMemorySize, SMEM_BYTES);
    }
    Params P;
    const __nv_bfloat16* x = (const __nv_bfloat16*)d_in[0];
    make_map(enc, &P.tmX, x, true, D_, S_ / 2, 2, 2 * D_, D_, 64, 64, 2);
    make_map(enc, &P.tmWqkv, d_in[1], true, D_, D_, 3, 3 * D_, D_, 64, 32, 3);
    make_map(enc, &P.tmW1, d_in[4], true, 64, S_, F_ / 64, F_, 64, 64, 64, 2);
    make_map(enc, &P.tmW2, d_in[6], true, 64, F_, S_ / 64, S_, 64, 64, 64, 2);
    make_map(enc, &P.tmOut, d_out, false, 112, 4, S_, 112, D_, PITCH / 2, 1, 16);
    fused_kernel<<<NCTA, NTHREADS, SMEM_BYTES, cudaStreamPerThread>>>(x, (const __nv_bfloat16*)d_in[5], (const __nv_bfloat16*)d_in[7], (const __nv_bfloat16*)d_in[2], (__nv_bfloat16*)d_out, scratch,
                                                                      (const __nv_bfloat16*)d_in[4], P);
}
```

```cpp
#include <cuda_runtime.h>
#include <cuda_bf16.h>
#include <cuda.h>
#include <stdint.h>

#define HALO_NS 300
#define HINT 5
#define HOLD 1
#define LATEREL 1
#define PF 400
#define PF0 2
#define PF1 8
#define LEADW 4
#define LEADN 7
#define TSQ 0
#define PACE 600
#define PAUSE 8
#define LAG1 4

namespace {

constexpr int S_ = 2048, D_ = 448, F_ = 1792;
constexpr int NCTA = 128, NTHREADS = 384;
constexpr int NSLOT = 6, SLOT = 32768, WSLOT = 24576, TILEB = 14336, SLAB = 3584, HALF = 7168;
constexpr int KV = 1792, HSTG = SLAB + 32, PITCH = 240;
constexpr int OFF_X = NSLOT * SLOT;
constexpr int OFF_Y = OFF_X + 10 * KV;
constexpr int OFF_ST = OFF_Y + TILEB;
constexpr int OFF_BAR = OFF_ST + 1024;
constexpr int SMEM_BYTES = OFF_BAR + 1280;
constexpr uint32_t SMEM0 = 1024;
constexpr int B_QFULL = 0, B_FULL = 56, B_HALO = 128, B_X = 136, B_CS = 168, B_FREE = 192, B_END = 200, B_QEMPTY = 216, B_EMPTY = 232, B_ROW = 288, NBAR = 37;
constexpr float LN_EPS = 1e-5f, QK_SCALE = 0.1889822365046136f * 1.4426950408889634f;
constexpr int SPIN_LIMIT = 1 << 22;

struct Scratch {
    uint8_t H[4][32][TILEB];
    uint8_t U[4][28][TILEB];
    uint8_t O[16][8][TILEB];
    uint8_t Wo[4][8][TILEB];
    uint8_t halo[NCTA][2 * KV];
    uint2 stat[S_];
    uint2 colsum[8][8][96];
    uint32_t flag[32][32];
    uint32_t epoch[NCTA];
};
__device__ __align__(1024) Scratch g_s;

#define TS(g, i)
#define TS0(g, i)
#define TSDUMP()

struct Params {
    CUtensorMap tmX, tmWqkv, tmW1, tmW2, tmOut;
};

__device__ __forceinline__ bool elect() {
    uint32_t p;
    asm volatile("{\n.reg .pred p;\nelect.sync _|p, 0xffffffff;\nselp.u32 %0, 1, 0, p;\n}" : "=r"(p));
    return p;
}
__device__ __forceinline__ void mbar_init(uint32_t b, uint32_t c) { asm volatile("mbarrier.init.shared::cta.b64 [%0], %1;" ::"r"(b), "r"(c) : "memory"); }
__device__ __forceinline__ void mbar_expect(uint32_t b, uint32_t tx) { asm volatile("mbarrier.arrive.expect_tx.shared::cta.b64 _, [%0], %1;" ::"r"(b), "r"(tx) : "memory"); }
__device__ __forceinline__ void mbar_arrive(uint32_t b) { asm volatile("mbarrier.arrive.shared::cta.b64 _, [%0];" ::"r"(b) : "memory"); }
template <int N> __device__ __forceinline__ void mbar_arrive_n(uint32_t b) { asm volatile("mbarrier.arrive.shared::cta.b64 _, [%0], %1;" ::"r"(b), "n"(N) : "memory"); }
__device__ __forceinline__ void mbar_arrive4_remote(uint32_t b) { asm volatile("mbarrier.arrive.shared::cluster.b64 _, [%0], 4;" ::"r"(b) : "memory"); }
__device__ __forceinline__ void mbar_arrive_remote(uint32_t b) { asm volatile("mbarrier.arrive.shared::cluster.b64 _, [%0];" ::"r"(b) : "memory"); }
#define MBAR_WAIT_ASM(SEM) \
    asm volatile("{\n.reg .pred p;\nWAIT:\nmbarrier.try_wait.parity" SEM ".shared::cta.b64 p, [%0], %1;\n@!p bra WAIT;\n}" ::"r"(b), "r"(parity) : "memory")
__device__ __forceinline__ void mbar_wait(uint32_t b, uint32_t parity) { MBAR_WAIT_ASM(""); }
__device__ __forceinline__ void mbar_wait_bounded(uint32_t b, uint32_t parity, uint32_t& n) {
    asm volatile("{\n.reg .pred p;\nWAIT:\nadd.u32 %0, %0, 1;\nsetp.gt.u32 p, %0, %3;\n@p st.global.u32 [%4], %0;\n"
                 "mbarrier.try_wait.parity.shared::cta.b64 p, [%1], %2;\n@!p bra WAIT;\n}" : "+r"(n) : "r"(b), "r"(parity), "n"(SPIN_LIMIT), "l"(0ull) : "memory");
}
__device__ __forceinline__ uint32_t mapa(uint32_t a, uint32_t rank) { uint32_t r; asm("mapa.shared::cluster.u32 %0, %1, %2;" : "=r"(r) : "r"(a), "r"(rank)); return r; }
__device__ __forceinline__ void tma3d(uint32_t dst, const CUtensorMap* tm, uint32_t bar, int c0, int c1, int c2) {
    asm volatile("cp.async.bulk.tensor.3d.shared::cluster.global.mbarrier::complete_tx::bytes [%0], [%1, {%3, %4, %5}], [%2];" ::"r"(dst), "l"(tm), "r"(bar), "r"(c0), "r"(c1), "r"(c2) : "memory");
}
__device__ __forceinline__ void tma3d_pair(uint32_t dst, const CUtensorMap* tm, uint32_t bar, int c0, int c1, int c2) {
    asm volatile("cp.async.bulk.tensor.3d.shared::cluster.global.mbarrier::complete_tx::bytes.multicast::cluster [%0], [%1, {%3, %4, %5}], [%2], %6;" ::"r"(dst), "l"(tm), "r"(bar), "r"(c0), "r"(c1), "r"(c2), "h"((uint16_t)3) : "memory");
}
__device__ __forceinline__ void bulk_load(uint32_t dst, const void* src, uint32_t bytes, uint32_t bar) {
    asm volatile("cp.async.bulk.shared::cluster.global.mbarrier::complete_tx::bytes [%0], [%1], %2, [%3];" ::"r"(dst), "l"(src), "r"(bytes), "r"(bar) : "memory");
}
__device__ __forceinline__ void bulk_store(void* dst, uint32_t src, uint32_t bytes) {
    asm volatile("cp.async.bulk.global.shared::cta.bulk_group [%0], [%1], %2;" ::"l"(dst), "r"(src), "r"(bytes) : "memory");
}
__device__ __forceinline__ uint32_t ld_u16(const void* p) { uint32_t v; asm volatile("ld.global.nc.u16 %0, [%1];" : "=r"(v) : "l"(p)); return v; }
__device__ __forceinline__ uint32_t ld_relaxed(const uint32_t* p) { uint32_t v; asm volatile("ld.relaxed.gpu.global.u32 %0, [%1];" : "=r"(v) : "l"(p) : "memory"); return v; }
__device__ __forceinline__ void bulk_flush() { asm volatile("cp.async.bulk.commit_group;\ncp.async.bulk.wait_group 0;" ::: "memory"); }
__device__ __forceinline__ void signal(uint32_t* flag) { asm volatile("fence.acq_rel.gpu;\nred.relaxed.gpu.global.add.u32 [%0], 1;" ::"l"(flag) : "memory"); }
__device__ __forceinline__ void hint(uint32_t* flag) { asm volatile("red.relaxed.gpu.global.add.u32 [%0], 1;" ::"l"(flag) : "memory"); }
__device__ __forceinline__ uint32_t tag(uint32_t v, uint32_t mask, uint32_t parity) { return (v & ~mask) | (parity & mask); }
__device__ __forceinline__ uint32_t or_diff(uint32_t acc, uint32_t v, uint32_t parity) { asm("lop3.b32 %0, %0, %1, %2, 0xf6;" : "+r"(acc) : "r"(v), "r"(parity)); return acc; }
__device__ __forceinline__ uint4 ld_relaxed4(const void* p) {
    uint4 v;
    asm volatile("ld.relaxed.gpu.global.v4.u32 {%0, %1, %2, %3}, [%4];" : "=r"(v.x), "=r"(v.y), "=r"(v.z), "=r"(v.w) : "l"(p) : "memory");
    return v;
}
__device__ __forceinline__ uint2 ld_relaxed2(const void* p) { uint2 v; asm volatile("ld.relaxed.gpu.global.v2.u32 {%0, %1}, [%2];" : "=r"(v.x), "=r"(v.y) : "l"(p) : "memory"); return v; }
__device__ __forceinline__ void sts4(uint32_t a, uint4 v) { asm volatile("st.shared.v4.b32 [%0], {%1, %2, %3, %4};" ::"r"(a), "r"(v.x), "r"(v.y), "r"(v.z), "r"(v.w) : "memory"); }
__device__ __forceinline__ void sts1(uint32_t a, uint32_t v) { asm volatile("st.shared.b32 [%0], %1;" ::"r"(a), "r"(v) : "memory"); }
__device__ __forceinline__ void sts2(uint32_t a, uint32_t v0, uint32_t v1) { asm volatile("st.shared.v2.b32 [%0], {%1, %2};" ::"r"(a), "r"(v0), "r"(v1) : "memory"); }
__device__ __forceinline__ void stg1(void* p, uint32_t v) { asm volatile("st.global.b32 [%0], %1;" ::"l"(p), "r"(v) : "memory"); }
__device__ __forceinline__ void fence_async_shared() { asm volatile("fence.proxy.async.shared::cta;" ::: "memory"); }
#define BOUND "add.u32 %0, %0, 16;\nsetp.gt.u32 p, %0, %1;\n@p st.global.u32 [%2], %0;\n"
__device__ __forceinline__ void wait_flag(const uint32_t* p, uint32_t target, uint32_t& n) {
    asm volatile("{\n.reg .pred p;\n.reg .u32 v;\nPOLL:\n" BOUND "ld.acquire.gpu.global.u32 v, [%3];\nsetp.ne.u32 p, v, %4;\n@p bra POLL;\nfence.proxy.async.global;\n}"
                 : "+r"(n) : "n"(SPIN_LIMIT), "l"(0ull), "l"(p), "r"(target) : "memory");
}
__device__ __forceinline__ void wait_flag2(const uint32_t* h, uint32_t th, const uint32_t* p, uint32_t target, uint32_t& n) {
    asm volatile("{\n.reg .pred p;\n.reg .u32 u, v;\nPOLL:\n" BOUND "ld.relaxed.gpu.global.u32 u, [%3];\nld.acquire.gpu.global.u32 v, [%5];\nsetp.ne.u32 p, u, %4;\nsetp.ne.or.u32 p, v, %6, p;\n@p bra POLL;\nfence.proxy.async.global;\n}"
                 : "+r"(n) : "n"(SPIN_LIMIT), "l"(0ull), "l"(h), "r"(th), "l"(p), "r"(target) : "memory");
}
__device__ __forceinline__ void block_end() { asm volatile("{\n.reg .pred p;\n.reg .u32 t;\nAGAIN:\nmov.u32 t, %%clock;\nsetp.eq.u32 p, t, %0;\n@p bra AGAIN;\n}" ::"n"(0) : "memory"); }
__device__ __forceinline__ void bar_sync(int id, int n) { asm volatile("bar.sync %0, %1;" ::"r"(id), "r"(n) : "memory"); }
__device__ __forceinline__ void bar_arrive(int id, int n) { asm volatile("bar.arrive %0, %1;" ::"r"(id), "r"(n) : "memory"); }
__device__ __forceinline__ void wg_fence() { asm volatile("wgmma.fence.sync.aligned;" ::: "memory"); }
__device__ __forceinline__ void wg_commit() { asm volatile("wgmma.commit_group.sync.aligned;" ::: "memory"); }
template <int N> __device__ __forceinline__ void wg_wait() { asm volatile("wgmma.wait_group.sync.aligned %0;" ::"n"(N) : "memory"); }
template <int N> __device__ __forceinline__ void pin(float (&d)[N]) {
#pragma unroll
    for (int i = 0; i < N; i++) asm volatile("" : "+f"(d[i])::"memory");
}
__host__ __device__ constexpr uint32_t desc_hi(uint32_t sbo, uint32_t swz) { return (sbo >> 4) | (swz << 30); }
__host__ __device__ constexpr uint32_t desc_lo(uint32_t off, uint32_t lbo) { return ((SMEM0 + off) >> 4) | ((lbo >> 4) << 16); }
__device__ __forceinline__ uint32_t pack2(float lo, float hi) { uint32_t r; asm("cvt.rn.bf16x2.f32 %0, %1, %2;" : "=r"(r) : "f"(hi), "f"(lo)); return r; }
__device__ __forceinline__ float bf_lo(uint32_t v) { return __uint_as_float(v << 16); }
__device__ __forceinline__ float bf_hi(uint32_t v) { return __uint_as_float(v & 0xffff0000u); }
__device__ __forceinline__ void stsm4(uint32_t a, uint32_t r0, uint32_t r1, uint32_t r2, uint32_t r3) {
    asm volatile("stmatrix.sync.aligned.m8n8.x4.shared.b16 [%0], {%1, %2, %3, %4};" ::"r"(a), "r"(r0), "r"(r1), "r"(r2), "r"(r3) : "memory");
}
__device__ __forceinline__ void stsm2(uint32_t a, uint32_t r0, uint32_t r1) {
    asm volatile("stmatrix.sync.aligned.m8n8.x2.shared.b16 [%0], {%1, %2};" ::"r"(a), "r"(r0), "r"(r1) : "memory");
}
__device__ __forceinline__ uint4 lds4(uint32_t a) { uint4 v; asm volatile("ld.shared.v4.b32 {%0, %1, %2, %3}, [%4];" : "=r"(v.x), "=r"(v.y), "=r"(v.z), "=r"(v.w) : "r"(a) : "memory"); return v; }
__device__ __forceinline__ uint2 lds2(uint32_t a) { uint2 v; asm volatile("ld.shared.v2.b32 {%0, %1}, [%2];" : "=r"(v.x), "=r"(v.y) : "r"(a) : "memory"); return v; }
__device__ __forceinline__ float lds1f(uint32_t a) { float v; asm volatile("ld.shared.f32 %0, [%1];" : "=f"(v) : "r"(a) : "memory"); return v; }
__device__ __forceinline__ void ldsm4(uint32_t* r, uint32_t a) {
    asm volatile("ldmatrix.sync.aligned.m8n8.x4.shared.b16 {%0, %1, %2, %3}, [%4];" : "=r"(r[0]), "=r"(r[1]), "=r"(r[2]), "=r"(r[3]) : "r"(a) : "memory");
}
__device__ __forceinline__ void ldsm4t(uint32_t* r, uint32_t a) {
    asm volatile("ldmatrix.sync.aligned.m8n8.x4.trans.shared.b16 {%0, %1, %2, %3}, [%4];" : "=r"(r[0]), "=r"(r[1]), "=r"(r[2]), "=r"(r[3]) : "r"(a) : "memory");
}
__device__ __forceinline__ void ldsm2t(uint32_t* r, uint32_t a) {
    asm volatile("ldmatrix.sync.aligned.m8n8.x2.trans.shared.b16 {%0, %1}, [%2];" : "=r"(r[0]), "=r"(r[1]) : "r"(a) : "memory");
}
__device__ __forceinline__ uint32_t transpose8(uint32_t v) { uint32_t r; asm volatile("movmatrix.sync.aligned.m8n8.trans.b16 %0, %1;" : "=r"(r) : "r"(v)); return r; }
__device__ __forceinline__ void mma16(float (&c)[4], uint32_t a0, uint32_t a1, uint32_t a2, uint32_t a3, uint32_t b0, uint32_t b1) {
    asm volatile("mma.sync.aligned.m16n8k16.row.col.f32.bf16.bf16.f32 {%0, %1, %2, %3}, {%4, %5, %6, %7}, {%8, %9}, {%0, %1, %2, %3};"
                 : "+f"(c[0]), "+f"(c[1]), "+f"(c[2]), "+f"(c[3]) : "r"(a0), "r"(a1), "r"(a2), "r"(a3), "r"(b0), "r"(b1));
}
__device__ __forceinline__ void mma8(float (&c)[4], uint32_t a0, uint32_t a1, uint32_t b0) {
    asm volatile("mma.sync.aligned.m16n8k8.row.col.f32.bf16.bf16.f32 {%0, %1, %2, %3}, {%4, %5}, {%6}, {%0, %1, %2, %3};"
                 : "+f"(c[0]), "+f"(c[1]), "+f"(c[2]), "+f"(c[3]) : "r"(a0), "r"(a1), "r"(b0));
}
__device__ __forceinline__ void st_async4(uint32_t a, uint32_t bar, uint32_t v0, uint32_t v1, uint32_t v2, uint32_t v3) {
    asm volatile("st.async.weak.shared::cluster.mbarrier::complete_tx::bytes.v4.b32 [%0], {%2, %3, %4, %5}, [%1];" ::"r"(a), "r"(bar), "r"(v0), "r"(v1), "r"(v2), "r"(v3) : "memory");
}
__device__ __forceinline__ void st_async2(uint32_t a, uint32_t bar, uint32_t v0, uint32_t v1) {
    asm volatile("st.async.weak.shared::cluster.mbarrier::complete_tx::bytes.v2.b32 [%0], {%2, %3}, [%1];" ::"r"(a), "r"(bar), "r"(v0), "r"(v1) : "memory");
}
__device__ __forceinline__ float quad_max(float v) { v = fmaxf(v, __shfl_xor_sync(~0u, v, 1)); return fmaxf(v, __shfl_xor_sync(~0u, v, 2)); }
__device__ __forceinline__ float quad_sum(float v) { v += __shfl_xor_sync(~0u, v, 1); return v + __shfl_xor_sync(~0u, v, 2); }
__device__ __forceinline__ float ex2(float v) { float r; asm("ex2.approx.ftz.f32 %0, %1;" : "=f"(r) : "f"(v)); return r; }
__device__ __forceinline__ float rcp(float v) { float r; asm("rcp.approx.ftz.f32 %0, %1;" : "=f"(r) : "f"(v)); return r; }
__device__ __forceinline__ float rsq(float v) { float r; asm("rsqrt.approx.ftz.f32 %0, %1;" : "=f"(r) : "f"(v)); return r; }
__device__ __forceinline__ float gelu2(float v) {
    float z = v * fmaf(v * v, 8 * 0.044715f * 0.7978845608028654f, 2 * 0.7978845608028654f), t;
    asm("tanh.approx.f32 %0, %1;" : "=f"(t) : "f"(z));
    return fmaf(v, t, v);
}
__device__ __forceinline__ float row_sum(float v) {
    v = quad_sum(v); v += __shfl_xor_sync(~0u, v, 4);
    return v + __shfl_xor_sync(~0u, v, 24);
}

template <int TA, int TB, uint32_t HA, uint32_t HB>
__device__ __forceinline__ void wgmma_n112(float (&d)[56], uint32_t da, uint32_t db, int accumulate) {
    asm volatile("{\n.reg .pred p;\n.reg .b64 a, b;\nmov.b64 a, {%56, %61};\nmov.b64 b, {%57, %62};\nsetp.ne.b32 p, %58, 0;\n"
        "wgmma.mma_async.sync.aligned.m64n112k16.f32.bf16.bf16 {"
        "%0, %1, %2, %3, %4, %5, %6, %7, %8, %9, %10, %11, %12, %13, %14, %15, "
        "%16, %17, %18, %19, %20, %21, %22, %23, %24, %25, %26, %27, %28, %29, %30, %31, "
        "%32, %33, %34, %35, %36, %37, %38, %39, %40, %41, %42, %43, %44, %45, %46, %47, "
        "%48, %49, %50, %51, %52, %53, %54, %55"
        "}, a, b, p, 1, 1, %59, %60;\n}\n"
        : "+f"(d[0]), "+f"(d[1]), "+f"(d[2]), "+f"(d[3]), "+f"(d[4]), "+f"(d[5]), "+f"(d[6]), "+f"(d[7]),
          "+f"(d[8]), "+f"(d[9]), "+f"(d[10]), "+f"(d[11]), "+f"(d[12]), "+f"(d[13]), "+f"(d[14]), "+f"(d[15]),
          "+f"(d[16]), "+f"(d[17]), "+f"(d[18]), "+f"(d[19]), "+f"(d[20]), "+f"(d[21]), "+f"(d[22]), "+f"(d[23]),
          "+f"(d[24]), "+f"(d[25]), "+f"(d[26]), "+f"(d[27]), "+f"(d[28]), "+f"(d[29]), "+f"(d[30]), "+f"(d[31]),
          "+f"(d[32]), "+f"(d[33]), "+f"(d[34]), "+f"(d[35]), "+f"(d[36]), "+f"(d[37]), "+f"(d[38]), "+f"(d[39]),
          "+f"(d[40]), "+f"(d[41]), "+f"(d[42]), "+f"(d[43]), "+f"(d[44]), "+f"(d[45]), "+f"(d[46]), "+f"(d[47]),
          "+f"(d[48]), "+f"(d[49]), "+f"(d[50]), "+f"(d[51]), "+f"(d[52]), "+f"(d[53]), "+f"(d[54]), "+f"(d[55])
        : "r"(da), "r"(db), "r"(accumulate), "n"(TA), "n"(TB), "n"(HA), "n"(HB));
}

template <int TA, int TB, uint32_t HA, uint32_t HB>
__device__ __forceinline__ void wgmma_n168(float (&d)[84], uint32_t da, uint32_t db, int accumulate) {
    asm volatile("{\n.reg .pred p;\n.reg .b64 a, b;\nmov.b64 a, {%84, %89};\nmov.b64 b, {%85, %90};\nsetp.ne.b32 p, %86, 0;\n"
        "wgmma.mma_async.sync.aligned.m64n168k16.f32.bf16.bf16 {"
        "%0, %1, %2, %3, %4, %5, %6, %7, %8, %9, %10, %11, %12, %13, %14, %15, "
        "%16, %17, %18, %19, %20, %21, %22, %23, %24, %25, %26, %27, %28, %29, %30, %31, "
        "%32, %33, %34, %35, %36, %37, %38, %39, %40, %41, %42, %43, %44, %45, %46, %47, "
        "%48, %49, %50, %51, %52, %53, %54, %55, %56, %57, %58, %59, %60, %61, %62, %63, "
        "%64, %65, %66, %67, %68, %69, %70, %71, %72, %73, %74, %75, %76, %77, %78, %79, "
        "%80, %81, %82, %83"
        "}, a, b, p, 1, 1, %87, %88;\n}\n"
        : "+f"(d[0]), "+f"(d[1]), "+f"(d[2]), "+f"(d[3]), "+f"(d[4]), "+f"(d[5]), "+f"(d[6]), "+f"(d[7]),
          "+f"(d[8]), "+f"(d[9]), "+f"(d[10]), "+f"(d[11]), "+f"(d[12]), "+f"(d[13]), "+f"(d[14]), "+f"(d[15]),
          "+f"(d[16]), "+f"(d[17]), "+f"(d[18]), "+f"(d[19]), "+f"(d[20]), "+f"(d[21]), "+f"(d[22]), "+f"(d[23]),
          "+f"(d[24]), "+f"(d[25]), "+f"(d[26]), "+f"(d[27]), "+f"(d[28]), "+f"(d[29]), "+f"(d[30]), "+f"(d[31]),
          "+f"(d[32]), "+f"(d[33]), "+f"(d[34]), "+f"(d[35]), "+f"(d[36]), "+f"(d[37]), "+f"(d[38]), "+f"(d[39]),
          "+f"(d[40]), "+f"(d[41]), "+f"(d[42]), "+f"(d[43]), "+f"(d[44]), "+f"(d[45]), "+f"(d[46]), "+f"(d[47]),
          "+f"(d[48]), "+f"(d[49]), "+f"(d[50]), "+f"(d[51]), "+f"(d[52]), "+f"(d[53]), "+f"(d[54]), "+f"(d[55]),
          "+f"(d[56]), "+f"(d[57]), "+f"(d[58]), "+f"(d[59]), "+f"(d[60]), "+f"(d[61]), "+f"(d[62]), "+f"(d[63]),
          "+f"(d[64]), "+f"(d[65]), "+f"(d[66]), "+f"(d[67]), "+f"(d[68]), "+f"(d[69]), "+f"(d[70]), "+f"(d[71]),
          "+f"(d[72]), "+f"(d[73]), "+f"(d[74]), "+f"(d[75]), "+f"(d[76]), "+f"(d[77]), "+f"(d[78]), "+f"(d[79]),
          "+f"(d[80]), "+f"(d[81]), "+f"(d[82]), "+f"(d[83])
        : "r"(da), "r"(db), "r"(accumulate), "n"(TA), "n"(TB), "n"(HA), "n"(HB));
}

template <uint32_t HB>
__device__ __forceinline__ void wgmma_rs_n168(float (&d)[84], uint32_t a0, uint32_t a1, uint32_t db) {
    asm volatile("{\n.reg .b64 b;\nmov.b64 b, {%86, %88};\n"
        "wgmma.mma_async.sync.aligned.m64n168k16.f32.bf16.bf16 {"
        "%0, %1, %2, %3, %4, %5, %6, %7, %8, %9, %10, %11, %12, %13, %14, %15, "
        "%16, %17, %18, %19, %20, %21, %22, %23, %24, %25, %26, %27, %28, %29, %30, %31, "
        "%32, %33, %34, %35, %36, %37, %38, %39, %40, %41, %42, %43, %44, %45, %46, %47, "
        "%48, %49, %50, %51, %52, %53, %54, %55, %56, %57, %58, %59, %60, %61, %62, %63, "
        "%64, %65, %66, %67, %68, %69, %70, %71, %72, %73, %74, %75, %76, %77, %78, %79, "
        "%80, %81, %82, %83"
        "}, {%84, %85, %87, %87}, b, 1, 1, 1, 0;\n}\n"
        : "+f"(d[0]), "+f"(d[1]), "+f"(d[2]), "+f"(d[3]), "+f"(d[4]), "+f"(d[5]), "+f"(d[6]), "+f"(d[7]),
          "+f"(d[8]), "+f"(d[9]), "+f"(d[10]), "+f"(d[11]), "+f"(d[12]), "+f"(d[13]), "+f"(d[14]), "+f"(d[15]),
          "+f"(d[16]), "+f"(d[17]), "+f"(d[18]), "+f"(d[19]), "+f"(d[20]), "+f"(d[21]), "+f"(d[22]), "+f"(d[23]),
          "+f"(d[24]), "+f"(d[25]), "+f"(d[26]), "+f"(d[27]), "+f"(d[28]), "+f"(d[29]), "+f"(d[30]), "+f"(d[31]),
          "+f"(d[32]), "+f"(d[33]), "+f"(d[34]), "+f"(d[35]), "+f"(d[36]), "+f"(d[37]), "+f"(d[38]), "+f"(d[39]),
          "+f"(d[40]), "+f"(d[41]), "+f"(d[42]), "+f"(d[43]), "+f"(d[44]), "+f"(d[45]), "+f"(d[46]), "+f"(d[47]),
          "+f"(d[48]), "+f"(d[49]), "+f"(d[50]), "+f"(d[51]), "+f"(d[52]), "+f"(d[53]), "+f"(d[54]), "+f"(d[55]),
          "+f"(d[56]), "+f"(d[57]), "+f"(d[58]), "+f"(d[59]), "+f"(d[60]), "+f"(d[61]), "+f"(d[62]), "+f"(d[63]),
          "+f"(d[64]), "+f"(d[65]), "+f"(d[66]), "+f"(d[67]), "+f"(d[68]), "+f"(d[69]), "+f"(d[70]), "+f"(d[71]),
          "+f"(d[72]), "+f"(d[73]), "+f"(d[74]), "+f"(d[75]), "+f"(d[76]), "+f"(d[77]), "+f"(d[78]), "+f"(d[79]),
          "+f"(d[80]), "+f"(d[81]), "+f"(d[82]), "+f"(d[83])
        : "r"(a0), "r"(a1), "r"(db), "r"(0), "n"(HB));
}

struct Ring {
    uint32_t slot, ph;
    __device__ __forceinline__ void next() { if (++slot == NSLOT) { slot = 0; ph ^= 1; } }
    __device__ __forceinline__ void next2() { ph ^= slot == 5; slot = __byte_perm(0x06030201u, 0x00040005u, 0x7770 + slot); }
};
struct Slot {
    uint32_t dst, bar, ph;
    __device__ __forceinline__ void next(uint32_t bars) {
        dst += SLOT; bar += 8;
        if (bar == bars + 8 * NSLOT) { dst -= NSLOT * SLOT; bar = bars; ph ^= 1; }
    }
};
__device__ __forceinline__ uint32_t xslot(int i) { return __byte_perm(0x04130e0cu, 0x00130e0cu, 0x7770 + i); }
__device__ __forceinline__ uint32_t wslot(int i) { return __byte_perm(0x06001510u, 0x00151009u, 0x7770 + i); }

constexpr uint32_t HI_SW = desc_hi(1024, 1);

struct Mma {
    uint32_t bars, rel;
    bool lead;
    int wg, half, w;
    Ring r;
    uint32_t prev;
    __device__ __forceinline__ void release_pair(uint32_t s) { if (lead) mbar_arrive4_remote(rel + B_EMPTY + 8 * s); }
    __device__ __forceinline__ void release(uint32_t s) { if (lead) mbar_arrive_n<4>(bars + B_EMPTY + 8 * s); }
    template <bool G1>
    __device__ __forceinline__ void run(float (&a)[56], int n, int first, int last, int lag, int accumulate, int ts, const __nv_bfloat16* bias = nullptr) {
#pragma unroll 1
        for (int i = 0; i < n; i++) {
            if (lag && i == (wg ? n - lag : -1)) {
                if (!G1) {
                    const uint32_t c0 = ld_u16(bias), c1 = ld_u16(bias + 8);
                    wg_wait<0>(); release(prev); last = first;
                    pin(a);
#pragma unroll
                    for (int k = 0; k < 56; k++) a[k] += bf_lo((k & 2) ? c1 : c0);
                    pin(a);
                }
                bar_sync(7, 256);
            }
            const bool seen = !G1 && last == first;
            const uint32_t s = seen ? n - 1 - i : r.slot;
            if (!seen) mbar_wait(bars + B_FULL + 8 * s, r.ph);
            if (G1) r.next(); else r.next2();
            if (!TSQ || !i) TS0(G1 ? 2 : 8, ts + i + wg * 68);
            const uint32_t dB = s * (SLOT >> 4), dA = dB + half * 512;
            wg_fence();
#pragma unroll
            for (int k = 0; k < 4; k++) {
                wgmma_n112<1, 1, HI_SW, desc_hi(G1 ? 256 : 1024, 0)>(a, dA + desc_lo(k * 2048, 8192), dB + desc_lo(16384 + k * (G1 ? SLAB : 256), 128), k > 0 || accumulate || i > 0);
                if (k == 1) {
                    wg_commit(); wg_wait<1>();
                    if ((uint32_t)(i - first) < (uint32_t)(last - first)) release(prev);
                    if (G1 && lag && i == (wg ? -1 : n - 1)) bar_arrive(7, 256);
                    if (TSQ && i) TS0(G1 ? 2 : 8, ts + i + wg * 68);
                }
            }
            wg_commit();
            prev = s;
        }
    }
    __device__ __forceinline__ void run_o(float (&a)[56]) {
#pragma unroll 1
        for (int i = 0; i < 2; i++) {
            const uint32_t s = r.slot, dB = s * (SLOT >> 4), dA = dB + half * (HALF >> 4);
            mbar_wait(bars + B_FULL + 8 * s, r.ph);
            TS0(8, 48 + 2 * i + wg * 68);
            wg_fence();
#pragma unroll
            for (int k = 0; k < 7; k++) {
                if (k == 3) { mbar_wait(bars + B_FULL + 8 * s + 8, r.ph); wg_fence(); }
                wgmma_n112<0, 1, desc_hi(128, 0), desc_hi(256, 0)>(a, dA + desc_lo(k * 2048 + (k > 3) * (SLOT - HALF), k == 3 ? SLOT - 6144 : 1024),
                                                                   dB + desc_lo(16384 + k * SLAB + (k > 2) * (SLOT - 3 * SLAB), 128), k > 0 || i > 0);
                if (k & 1) wg_commit();
                if (k == 1) { wg_wait<1>(); if (i) release(prev); }
                if (k == 5) { wg_wait<1>(); release(s); }
            }
            wg_commit();
            prev = s + 1;
            r.slot++; r.next2();
        }
    }
};

__global__ void __cluster_dims__(2, 1, 1) __launch_bounds__(NTHREADS, 1)
fused_kernel(const __nv_bfloat16* __restrict__ x, const __nv_bfloat16* __restrict__ b1, const __nv_bfloat16* __restrict__ b2, const __nv_bfloat16* __restrict__ wo, __nv_bfloat16* out, Scratch* G,
             const __nv_bfloat16* __restrict__ w1,
             const __grid_constant__ Params P) {
    extern __shared__ __align__(1024) uint8_t smem[];
    const uint32_t sbase = (uint32_t)__cvta_generic_to_shared(smem);
    const uint32_t bars = sbase + OFF_BAR;
    const uint32_t rank = blockIdx.x & 1, pr = blockIdx.x >> 1;
    const uint32_t row0 = blockIdx.x * 16;
    if (threadIdx.x == 0) {
        TS(15, 0);
        mbar_init(bars + B_ROW, 1);
        asm volatile("fence.mbarrier_init.release.cluster;" ::: "memory");
        bulk_load(sbase + OFF_Y, x + row0 * D_, TILEB, bars + B_ROW);
        mbar_expect(bars + B_ROW, TILEB);
        TS(1, 97);
    }
    const int lane = threadIdx.x & 31;
    const int warp = __shfl_sync(~0u, threadIdx.x >> 5, 0), w = warp & 3;
    if (elect()) {
        const uint32_t first = bars + warp * 24, count = warp < 7 ? 1 : warp < 9 ? 18 - 2 * warp : 16;
#pragma unroll
        for (int i = 0; i < 3; i++) mbar_init(first + 8 * i, count);
        asm volatile("fence.mbarrier_init.release.cluster;" ::: "memory");
    }
    __syncwarp();
    asm volatile("barrier.cluster.arrive.relaxed.aligned;" ::: "memory");
    const uint32_t pv = pr < 4 ? pr * 8 + 36 : pr - 4 + (max((int)pr - 33, 0) * 37 >> 8);
    const uint32_t gp = (pv + 4) & 7, hp = pv >> 3;
    const uint32_t tb = gp * 2 + rank, c = hp * 16 + tb;
    const bool has_g1 = gp > 0;
    const uint32_t nt1 = hp & 3, ft = max((int)gp - 1, 0) * 2 + (hp >> 2);
    const uint32_t nt2 = (hp & 1) * 2 + rank, mt = (gp & 3) * 4 + (hp >> 1), ks = gp >> 2;
    asm volatile("barrier.cluster.wait.aligned;" ::: "memory");

    if (warp == 8) {
        uint32_t kw = (gp & 1) * 192, kx;
        if (elect()) {
            mbar_expect(bars + B_QFULL, WSLOT);
            tma3d(sbase + xslot(0) * 8192, &P.tmX, bars + B_FULL, 0, tb * 64, 0);
            tma3d_pair(sbase + wslot(0) * 8192 + rank * 12288, &P.tmWqkv, bars + B_QFULL, (hp * 56) & ~15, rank * 32, 0);
            TS(1, 23);
            uint32_t due = (uint32_t)clock() + PACE, ep = ld_relaxed(&G->epoch[c]);
            uint32_t spins = sbase == (rank << 24 | SMEM0) ? 0 : SPIN_LIMIT;
#pragma unroll 1
            for (int i = 1; i < 8; i++) {
                kx = kw; kw += 64;
                if (i >= 5) mbar_wait_bounded(bars + B_QEMPTY + 8 * (i - 5), 0, spins);
                else { while ((int)((uint32_t)clock() - due) < 0) {} due += PACE; }
                if (kw == D_) kw = 64;
                if (i < 4) kx = kw;
                const int ix = i - (i > 4);
                if (i < 7) mbar_expect(bars + B_QFULL + 8 * i, WSLOT);
                if (i != 4) tma3d(sbase + xslot(ix) * 8192, &P.tmX, bars + B_FULL + 8 * ix, kx, tb * 64, 0);
                if (i & (i >> 2)) mbar_wait_bounded(bars + B_CS - 20 + 4 * i, 0, spins);
                if (i < 7) tma3d_pair(sbase + wslot(i) * 8192 + rank * 12288, &P.tmWqkv, bars + B_QFULL + 8 * i, (hp * 56) & ~15, kw + rank * 32, 0);
            }
            ep++;
            Slot r{sbase, bars, 0};
            if (has_g1) {
                const uint8_t* src = G->H[nt1][rank * 16];
                const int row = rank * 1024;
                mbar_expect(bars + B_FULL, 16384 + TILEB);
                tma3d(sbase, &P.tmW1, bars + B_FULL, 0, row, ft * 2);
                wait_flag(G->flag[2 + rank * 2], 20 * ep, spins);
                TS(1, 16);
#pragma unroll 1
                for (int j = 64;; j += 64) {
                    bulk_load(r.dst + 16384, src, TILEB, r.bar + B_FULL);
                    src += TILEB;
                    r.next(bars);
                    if (j == 1024) break;
                    mbar_wait_bounded(r.bar + B_EMPTY, r.ph, spins);
                    if (j < 14 * 64) TS(2, 146 + j / 64);
                    mbar_expect(r.bar + B_FULL, 16384 + TILEB);
                    tma3d(r.dst, &P.tmW1, r.bar + B_FULL, 0, row + j, ft * 2);
                }
                mbar_arrive(bars + B_FULL + 48); mbar_arrive_n<16>(bars + B_EMPTY + 48);
#pragma unroll
                for (int i = 0; i < 4; i++) mbar_expect(bars + B_X + 8 * i, (i & 1) ? 3072 : 4096);
            } else {
                due = (uint32_t)clock();
#pragma unroll 1
                for (int j = PF0; j < PF1; j++) {
                    asm volatile("cp.async.bulk.prefetch.L2.global [%0], %1;" ::"l"(w1 + (rank * 1024 + j * 64 + hp * 8) * F_), "n"(16 * F_) : "memory");
                    due += PF;
                    while ((int)((uint32_t)clock() - due) < 0) {}
                }
            }
            const uint8_t *so = G->O[mt][ks * 4], *sw = G->Wo[nt2][ks * 4];
            wait_flag2(G->flag[16 + mt], 8 * ep, G->flag[0], 16 * ep, spins);
            TS(4, 18);
#pragma unroll 1
            for (int j = 0; j < 4 * TILEB; j += TILEB) {
                mbar_wait_bounded(r.bar + B_EMPTY, r.ph, spins);
                mbar_expect(r.bar + B_QFULL, TILEB);
                bulk_load(r.dst, so + j, TILEB, r.bar + B_QFULL);
                bulk_load(r.dst + 16384, sw + j, (r.bar & 8) ? TILEB : 3 * SLAB, r.bar + B_FULL);
                r.next(bars);
            }
            Ring q{has_g1 ? 2u : 6u, has_g1}, p{q.slot, !has_g1};
#pragma unroll 1
            for (int j = 0; j < 14 * 128; j += 128) {
                mbar_wait_bounded(bars + B_EMPTY + 8 * q.slot, q.ph, spins);
                if (LEADW && j >= LEADW * 128 && j < LEADN * 128) { mbar_wait_bounded(bars + B_FULL + 8 * p.slot, p.ph, spins); p.next2(); }
                TS(8, 176 + j / 128);
                tma3d(sbase + q.slot * SLOT, &P.tmW2, bars + B_FULL + 8 * q.slot, 0, ks * 896 + j - (j < 896 ? 0 : 832), mt * 2);
                q.next2();
            }
            mbar_wait_bounded(bars + B_END, 0, spins);
        }
    } else if (warp > 8) {
        const uint32_t ep = ld_relaxed(&G->epoch[c]) + 1;
        const uint8_t* src = G->U[nt2][ks * 14];
        uint32_t spins = 0, bad;
        {
            uint2* cs = G->colsum[hp][0];
            if (w == 2) {
                bar_sync(6, 288);
                TS(1, 8);
                stg1((uint32_t*)(G->stat + row0) + lane, tag(__float_as_uint(lds1f(sbase + OFF_ST + lane * 4)), ~lane & 1, ep));
                if (elect()) {
                    fence_async_shared();
#pragma unroll
                    for (int i = 0; i < 4; i++) bulk_store(G->H[i][0] + row0 * (SLAB / 16), sbase + OFF_X + i * HSTG, SLAB);
                    bulk_flush();
                    TS(1, 99);
                    signal(G->flag[2 + (row0 >> 10) * 2 + ((row0 & 1023) >= 320)]);
                }
                __syncwarp();
            } else {
                const uint32_t word = rank * 16 + (w & 2) * 4 + (lane & 7), done = mapa(bars + B_CS, rank ^ (lane & 1));
                const uint32_t from = (sbase + word * 4 + (gp >> 2) * 12288 + (gp & 2) * 1024) ^ ((lane >> 3) * 288);
                auto swz = [](uint32_t a) { return a ^ ((a >> 3) & 0x70); };
                const uint32_t lin = sbase + lane * 128 + (hp & 1) * 16, f0 = swz(lin + 80) + 8192, f1 = swz(lin + 96) + 8192, to = swz(lin + 112);
                float s[6] = {};
#pragma unroll 1
                for (int i = 0; i < 7; i++) {
                    const uint32_t o = wslot(i) * 8192, a0 = from + o, a1 = a0 ^ 144;
                    mbar_wait(bars + B_QFULL + 8 * i, 0);
                    if ((i ^ (w >> 1)) & 1) {
                        const uint4 v0 = lds4(f0 + o), v1 = lds4(f1 + o), v2 = lds4(f0 + o + 12288), v3 = lds4(f1 + o + 12288);
                        sts4(to + o, v0); sts4(to + o + 4096, v1); sts4(to + o + 12288, v2); sts4(to + o + 16384, v3);
                        fence_async_shared();
                        __syncwarp();
                        if (elect()) mbar_expect(bars + B_FULL + 8 * i, 16384);
                    }
                    if (i > 3 || i < (gp & 1)) continue;
                    if (w == 1) TS(1, 66);
                    uint32_t v[12];
#pragma unroll
                    for (int k = 0; k < 12; k++) v[k] = __float_as_uint(lds1f(((k & 1) ? a1 : a0) + (k & 2) * 512 + (k >> 2) * 4096));
#pragma unroll
                    for (int k = 0; k < 12; k++) { s[(k >> 2) * 2] += bf_lo(v[k]); s[(k >> 2) * 2 + 1] += bf_hi(v[k]); }
                    __syncwarp();
                    if ((i & 1) && lane < 2) mbar_arrive_remote(done + (i & 2) * 4);
                    if (i < 3) continue;
#pragma unroll
                    for (int k = 0; k < 6; k++) { s[k] += __shfl_xor_sync(~0u, s[k], 8); s[k] += __shfl_xor_sync(~0u, s[k], 16); }
                    const float s0 = lane < 8 ? s[0] : lane < 16 ? s[2] : s[4], s1 = lane < 8 ? s[1] : lane < 16 ? s[3] : s[5];
                    if (lane < 24) cs[gp * 96 + (lane >> 3) * 32 + word] = make_uint2(tag(__float_as_uint(s0), 1, ep), __float_as_uint(s1));
                    if (w == 1) TS(1, 24);
                }
            }
            bar_sync(1, 96);
            if (w == 1) TS(1, 98);
            const int i0 = threadIdx.x - 288, j0 = i0 - (hp & 1) * 4;
            cs += i0 + ((j0 & 92) == 28 ? (j0 & 32 ? 28 : 56) : 0);
            uint2 u[8];
            uint4 sv;
            do {
                sv = ld_relaxed4(G->stat + tb * 128 + (i0 & 63) * 2);
                bad = sv.x ^ ep;
#pragma unroll
                for (int i = 0; i < 8; i++) { u[i] = ld_relaxed2(cs + i * 96); bad = or_diff(bad, u[i].x, ep); }
                if (bad & 1) TS(1, 3);
            } while (bad & 1);
            if (w < 3) sts4(sbase + OFF_ST + i0 * 16, sv);
#pragma unroll
            for (int e = 0; e < 2; e++) {
                float f = 0.f;
#pragma unroll
                for (int i = 0; i < 8; i++) f += __uint_as_float(e ? u[i].y : u[i].x);
                const uint32_t hi = pack2(f, f);
                sts4(sbase + OFF_X + i0 * 32 + e * 16, make_uint4(hi, pack2(f - bf_hi(hi), f - bf_hi(hi)), 0, 0));
            }
            sts1(bars + 8 * NBAR, ep);
            fence_async_shared();
            __syncwarp();
            bar_arrive(8, 224); bar_arrive(9, 224);
            TS(1, 90 + w);
        }
        if (w < 3) {
            if (w == 1) {
                if (elect()) {
                    wait_flag(G->flag[3 + rank * 2], 44 * ep, spins);
                    mbar_arrive_n<16>(bars + B_EMPTY + 8 * 5);
                    TS(1, 96);
                }
                __syncwarp();
                if (!has_g1) { bar_sync(5, 288); if (elect()) signal(G->flag[0]); __syncwarp(); TS(2, 26); }
            }
            mbar_wait(bars + B_HALO, 0);
            uint32_t slot = (has_g1 ? 16 % NSLOT : 0) + w - 1, ph = ~0u;
#pragma unroll 1
            for (int i = w - 1; i < 18;) {
                const uint32_t d0 = sbase + slot * SLOT + (i < 4 ? 0 : 16384), landed = bars + B_QFULL + 8 * slot;
                mbar_wait(landed, (ph >> slot) & 1);
                ph ^= 1 << slot;
                if (i < 8) TS(4, 82 + i);
                if (i >= 4) TS(8, 156 + i);
                bad = 0;
#pragma unroll
                for (int k = 0; k < 14; k++) bad = or_diff(bad, __float_as_uint(lds1f(d0 + k * 1024 + lane * 32 + (lane >> 2) * 4)), ep);
                if (__any_sync(~0u, bad & 1)) {
                    if (elect()) {
                        const uint8_t* cur = (i < 4 ? G->O[mt][ks * 4] : src - 4 * TILEB) + i * TILEB;
                        fence_async_shared();
                        mbar_expect(landed, TILEB);
                        bulk_load(d0, cur, TILEB, landed);
                    }
                    TS(4, i < 4 ? 94 : 95);
                } else {
                    if (elect()) mbar_expect(landed + (B_FULL - B_QFULL), i < 4 ? (2 + w) * SLAB : 16384);
                    i += __byte_perm(0x03020202u, 0x00010202u, 0x7770 + slot);
                    slot = __byte_perm(0x05060302u, 0x00040100u, 0x7770 + slot);
                }
            }
        } else {
            bar_sync(3, 288);
            __nanosleep(HALO_NS);
            uint4 v[7];
            do {
                bad = 0;
#pragma unroll
                for (int i = 0; i < 7; i++) { v[i] = ld_relaxed4(G->halo[c - (tb > 0)] + i * 512 + lane * 16); bad = or_diff(bad, v[i].x, ep); }
            } while (bad & 1);
#pragma unroll
            for (int i = 0; i < 7; i++) sts4(sbase + OFF_X + i * 512 + lane * 16, v[i]);
            __syncwarp();
            if (elect()) mbar_arrive(bars + B_HALO);
            TS(2, 21);
            bar_sync(2, 160);
            if (elect()) bulk_store(out + row0 * D_, sbase + OFF_Y, TILEB);
            __syncwarp();
            bar_sync(4, 288);
            if (elect()) {
                fence_async_shared();
                bulk_store(G->O[tb][hp], sbase + OFF_X, TILEB);
                bulk_flush();
                TS(2, 7);
                mbar_arrive_remote(mapa(bars + B_FREE, rank ^ 1));
                mbar_arrive(bars + B_FREE);
                hint(G->flag[16 + tb]);
                signal(G->flag[16 + (row0 >> 7)] + 1);
                TS(2, 22);
            }
            __syncwarp();
            uint32_t late = ~0u;
            const uint32_t* hints = G->flag[8 + nt2 * 2 + ks] + (lane & 7);
            mbar_wait(bars + (has_g1 ? B_X : B_FREE), 0);
            Ring r{has_g1 ? 2u : 6u, has_g1};
#pragma unroll 1
            for (int i = 0; i < 14; i++) {
                while ((late >> i) & 1) late = __ballot_sync(~0u, ld_relaxed(hints) != 2 * ep) & 127;
                if (i == 0) TS(4, 17);
                mbar_wait(bars + B_EMPTY + 8 * r.slot, r.ph);
                TS(8, 192 + i);
                if (elect()) {
                    mbar_expect(bars + B_QFULL + 8 * r.slot, TILEB);
                    bulk_load(sbase + r.slot * SLOT + 16384, src, TILEB, bars + B_QFULL + 8 * r.slot);
                }
                src += TILEB; r.next2();
            }
            if (elect()) {
                wait_flag(G->flag[16 + mt] + 1, 8 * ep, spins);
                mbar_arrive(bars + B_ROW);
                TS(2, 27);
                G->epoch[c] = ep;
            }
        }
    } else {
        const int wg = warp >> 2;
        Mma M{bars, mapa(bars, rank ^ (lane & 1)), (threadIdx.x & 127) < 2, wg, wg, w, Ring{0, 1}, 0};
        const int r = lane >> 2, t = lane & 3;
        uint32_t ep;
        const uint32_t bias0 = ld_u16(b1 + ft * 128 + warp * 16 + r), bias1 = ld_u16(b1 + ft * 128 + warp * 16 + r + 8);
        const uint32_t kv = sbase + OFF_X + (w * 2 + wg) * KV + lane * 16;
        uint32_t q[8][2], k0[7], k1[14], v0[7];
        float f0, f1;
        {
            const int half = (lane >> 3) & 1, r16 = warp * 2 + (half ^ (lane >> 4)), nt = (lane >> 1) & 3;
            const uint32_t row = sbase + OFF_Y + r16 * (2 * D_), part = row + nt * 224 + half * 112 + (lane & 1) * 8;
            const uint32_t hb = sbase + OFF_X + nt * HSTG + r16 * 16 + (half ^ (row0 >> 10)) * (7 * 256) + (lane & 1) * 8;
            mbar_wait(bars + B_ROW, 0);
            TS0(1, 67);
            const float x0 = bf_lo(__float_as_uint(lds1f(row)));
            float d[28], m1 = 0.f, n1 = 0.f, m2 = 0.f, n2 = 0.f;
#pragma unroll
            for (int i = 0; i < 7; i++) {
                const uint2 v = lds2(part + i * 16);
#pragma unroll
                for (int k = 0; k < 2; k++) {
                    const float d0 = d[4 * i + 2 * k] = bf_lo(k ? v.y : v.x) - x0, d1 = d[4 * i + 2 * k + 1] = bf_hi(k ? v.y : v.x) - x0;
                    m1 += d0; n1 += d1; m2 = fmaf(d0, d0, m2); n2 = fmaf(d1, d1, n2);
                }
            }
            const float md = row_sum(m1 + n1) * (1.f / D_), var = fmaf(-md, md, row_sum(m2 + n2) * (1.f / D_)), nmean = -(x0 + md);
            const float rstd = rsq(var + LN_EPS);
            const float sc = rstd * rsq(fmaf(var * rstd, 4 * rstd, 4 * LN_EPS)), nb = -md * sc;
            sts2(sbase + OFF_ST + r16 * 8, __float_as_uint(rstd), pack2(nmean, nmean - bf_hi(pack2(nmean, nmean))));
#pragma unroll
            for (int i = 0; i < 7; i++) sts2(hb + i * 256, pack2(fmaf(d[4 * i], sc, nb), fmaf(d[4 * i + 1], sc, nb)), pack2(fmaf(d[4 * i + 2], sc, nb), fmaf(d[4 * i + 3], sc, nb)));
            TS0(1, 25);
            bar_arrive(6, 288);
            float acc[84];
#pragma unroll 1
            for (int kb = 0; kb < 7; kb++) {
                const bool held = kb == (wg ? 7 - HOLD : -1);
                if (held) { wg_wait<0>(); M.release_pair(4 - HOLD); TS0(1, 138); bar_sync(7, 256); }
                mbar_wait(bars + B_FULL + 8 * kb, 0);
                if (!TSQ || !kb) TS0(1, 68 + wg * 7 + kb);
                const uint32_t dA = (xslot(kb) + wg) * 512, dB = wslot(kb) * 512 + (hp & 1);
                wg_fence();
#pragma unroll
                for (int k = 0; k < 4; k++) {
                    wgmma_n168<0, 1, HI_SW, HI_SW>(acc, dA + desc_lo(k * 32, 16), dB + desc_lo((k & 1) * 2048 + (k >> 1) * 12288, 4096), k > 0 || kb > 0);
                    if (k == 0) { wg_commit(); wg_wait<1>(); if (kb > 0 && !held) M.release_pair(kb - 3); if (TSQ && kb) TS0(1, 68 + wg * 7 + kb); }
                }
                wg_commit();
            }
            if (wg == 0 && !LATEREL) bar_arrive(7, 256);
            if (wg == 0) TS0(1, 139);
            bar_sync(8 + wg, 224);
            if (wg == 0) TS0(1, 174);
            ep = __float_as_uint(lds1f(bars + 8 * NBAR));
            const uint32_t st = sbase + OFF_ST + (w * 32 + r * 2 + wg) * 8;
            const uint2 s0 = lds2(st), s1 = lds2(st + 128);
            const uint32_t a0 = t < 2 ? s0.y : 0, a1 = t < 2 ? s1.y : 0;
            wg_fence();
            wgmma_rs_n168<desc_hi(128, 0)>(acc, a0, a1, desc_lo(OFF_X, 0) + (hp & 1) * 8);
            wg_commit();
            if (wg == 0 && LATEREL) bar_arrive(7, 256);
            if (wg == 0) TS0(1, 175);
            wg_wait<1>();
            TS0(1, 190 + wg);
            M.release_pair(4);
            wg_wait<0>();
            pin(acc);
            TS0(1, 4 + 7 * wg);
            f0 = __uint_as_float(s0.x); f1 = __uint_as_float(s1.x);
#pragma unroll
            for (int g = 13; g >= 0; g--) {
                const float* a = acc + (g < 7 ? g + 8 : g < 12 ? g + 9 : g * 8 - 89) * 4;
                (g < 7 ? k0[g] : v0[g - 7]) = pack2(a[0] * f0, a[1] * f0);
                k1[g] = pack2(a[2] * f1, a[3] * f1);
            }
#pragma unroll
            for (int i = 0; i < 3; i++) stsm4(kv + 2 * KV + i * 512, k1[4 * i], k1[4 * i + 1], k1[4 * i + 2], k1[4 * i + 3]);
            stsm2(kv + 2 * KV + 1536, k1[12], k1[13]);
            if (w == 3) {
#pragma unroll
                for (int i = 0; i < 14; i++) stg1(G->halo[c] + wg * KV + lane * 4 + i * 128, tag(k1[i], t == 0, ep));
            }
            bar_arrive(3, 288);
#pragma unroll
            for (int g = 0; g < 7; g++) { q[g][0] = pack2(acc[4 * g], acc[4 * g + 1]); q[g][1] = pack2(acc[4 * g + 2], acc[4 * g + 3]); }
#pragma unroll
            for (int j = 0; j < 2; j++) { q[7][j] = t < 2 ? 0u : q[3][j]; q[3][j] = t < 2 ? q[3][j] : 0u; }
#pragma unroll
            for (int g = 0; g < 7; g++) v0[g] = transpose8(v0[g]);
        }
        TS0(1, 9 + 11 * wg);
        float a[56];
#pragma unroll
        for (int i = 0; i < 56; i++) asm volatile("" : "=f"(a[i]));
        if (__builtin_expect(!has_g1, 0)) {
            const int g = min(lane >> 1, 13), nt = rank * 2 + wg;
            const uint4* src = (const uint4*)(wo + (hp * 56 - (hp & 1) * 8 + w * 16 + (lane & 1)) * D_ + nt * 112) + g;
            uint4 v[8];
#pragma unroll
            for (int i = 0; i < 8; i++) v[i] = __ldg(src + i * (D_ / 4));
#pragma unroll
            for (int i = 0; i < 8; i++) ((uint4*)G->Wo[nt][hp])[w * (SLAB / 16) + g * 16 + (lane & 1) + 2 * i] = v[i];
            bar_arrive(5, 288);
        }
        M.run<true>(a, has_g1 ? PAUSE : 0, 1, 16, 0, 0, 32);
        {
            uint32_t kp[8], vv[14];
            mbar_wait(bars + B_HALO, 0);
            ldsm4(kp, kv); ldsm4(kp + 4, kv + (lane < 24 ? 512 : 0));
            const uint32_t va = kv + 896 + (lane & 8) * (2 * KV / 8 - 16) - (lane & 16) * 8;
            ldsm4t(vv, va); ldsm4t(vv + 4, va + 256); ldsm4t(vv + 8, va + 512); ldsm2t(vv + 12, va + 768);
            const bool e0 = 2 * t > r, e1 = 2 * t >= r;
            const uint32_t mk = (e0 ? 0xffffu : 0u) | (e1 ? 0xffff0000u : 0u);
            wg_wait<0>();
            pin(a);
            if (has_g1) M.release(M.prev);
            TS0(2, 144 + wg);
            bar_arrive(10 + wg, 256);
            if (wg) bar_arrive(2, 160);
            block_end();
            TS0(2, 12 + 16 * wg);
            float sv[2][4];
#pragma unroll
            for (int h = 0; h < 2; h++) {
                const int ga = h * 4, gb = h * 4 + 1, gc = h * 4 + 2, gd = h * 4 + 3;
                float s[3][4] = {};
                mma16(s[0], q[ga][0], q[ga][1], q[gb][0], q[gb][1], kp[ga], kp[gb]);
                mma16(s[1], q[ga][0], q[ga][1], q[gb][0], q[gb][1], k0[ga], k0[gb]);
                mma16(s[2], q[ga][0], q[ga][1], q[gb][0], q[gb][1], k1[ga], k1[gb]);
                mma16(s[0], q[gc][0], q[gc][1], q[gd][0], q[gd][1], kp[gc], kp[gd]);
                mma16(s[1], q[gc][0], q[gc][1], q[gd][0], q[gd][1], k0[gc], k0[3]);
                mma16(s[2], q[gc][0], q[gc][1], q[gd][0], q[gd][1], k1[gc], k1[3]);
                if ((tb | w) == 0) s[0][0] = s[0][1] = -1e30f;
                sv[h][0] = e0 ? s[0][0] : s[1][0];
                sv[h][1] = e1 ? s[0][1] : s[1][1];
                sv[h][2] = e0 ? s[1][2] : s[2][2];
                sv[h][3] = e1 ? s[1][3] : s[2][3];
            }
            uint32_t pp[2][2];
#pragma unroll
            for (int i = 0; i < 4; i++) {
                float* v = &sv[i >> 1][(i & 1) * 2];
                const float f = ((i & 1) ? f1 : f0) * QK_SCALE, m = quad_max(fmaxf(v[0], v[1])) * f;
                const float p0 = ex2(fmaf(v[0], f, -m)), p1 = ex2(fmaf(v[1], f, -m));
                const float inv = rcp(quad_sum(p0 + p1));
                pp[i >> 1][i & 1] = pack2(p0 * inv, p1 * inv);
            }
            uint32_t o[8][2];
#pragma unroll
            for (int i = 0; i < 8; i++) {
                const int h = i >> 2, g = i - h;
                float d[4] = {};
                mma16(d, pp[h][0] & mk, 0u, 0u, pp[h][1] & ~mk, vv[2 * g], vv[2 * g + 1]);
                mma8(d, pp[h][0] & ~mk, pp[h][1] & mk, v0[g]);
                o[i][0] = pack2(d[0], d[1]); o[i][1] = pack2(d[2], d[3]);
            }
            if (t >= 2) { o[3][0] = o[4][0]; o[3][1] = o[4][1]; }
            const int word = wg * 4 + t - (w & 1) * 4 - (r >> 2);
#pragma unroll
            for (int i = 0; i < 8; i++) { o[i][0] = tag(o[i][0], word == 0, ep); o[i][1] = tag(o[i][1], word == 2, ep); }
            const uint32_t dst = sbase + OFF_X + (w >> 1) * HALF + ((w & 1) * 32 + (lane & 15) * 2 + wg) * 16 + (lane >> 4) * 1024;
            bar_sync(11 - wg, 256);
            stsm4(dst, o[0][0], o[0][1], o[1][0], o[1][1]);
            stsm4(dst + 2048, o[2][0], o[2][1], o[3][0], o[3][1]);
            stsm4(dst + 4096, o[5][0], o[5][1], o[6][0], o[6][1]);
            stsm2(dst + 6144, o[7][0], o[7][1]);
            bar_arrive(4, 288);
            TS0(2, 10 + 19 * wg);
        }
        if (has_g1) {
            M.run<true>(a, 16 - PAUSE, 1, 16, LAG1, 1, 32 + PAUSE);
            mbar_wait(bars + B_FREE, 0);
            const uint32_t xb = sbase + OFF_X + wg * 8192 + (threadIdx.x & 127) * 16, xbar = bars + B_X + 16 * wg;
            const uint32_t rx = mapa(xb, rank ^ 1), rbar = mapa(xbar, rank ^ 1);
            wg_wait<0>();
            pin(a);
            M.release(M.prev);
            TS0(4, 5 + wg);
#pragma unroll
            for (int i = 0; i < 3; i++)
                st_async4(rx + i * 2048, rbar + 8 * (i >> 1), pack2(a[28 + 8 * i], a[29 + 8 * i]), pack2(a[30 + 8 * i], a[31 + 8 * i]), pack2(a[32 + 8 * i], a[33 + 8 * i]), pack2(a[34 + 8 * i], a[35 + 8 * i]));
            const uint32_t tail = 6144 - (threadIdx.x & 127) * 8;
            st_async2(rx + tail, rbar + 8, pack2(a[52], a[53]), pack2(a[54], a[55]));
            uint8_t* dst = G->U[nt1][((ft >= 7) + wg) * 7 + ft] + rank * HALF + w * 256 + lane * 4;
            uint32_t u[14];
#pragma unroll
            for (int i = 0; i < 28; i++) a[i] = fmaf(bf_lo((i & 2) ? bias1 : bias0), 0.5f, a[i]);
#pragma unroll
            for (int i = 0; i < 14; i++) {
                if (i % 8 == 0) {
                    if (i) TS0(4, 134 + wg);
                    mbar_wait(xbar + i, 0);
                    TS0(4, (i ? 136 : 1) + wg);
#pragma unroll
                    for (int k = i / 4; k < i / 4 + 2; k++) {
                        if (k < 3) { const uint4 v = lds4(xb + k * 2048); u[4 * k] = v.x; u[4 * k + 1] = v.y; u[4 * k + 2] = v.z; u[4 * k + 3] = v.w; }
                        else { const uint2 v = lds2(xb + tail); u[12] = v.x; u[13] = v.y; }
                    }
                    if (i && lane < 2) mbar_arrive(bars + B_EMPTY + 48);
                }
                if (i == HINT && threadIdx.x == 0) hint(G->flag[8 + nt1 * 2] + ft + (ft >= 7) * 25);
                stg1(dst + (i >> 1) * 1024 + (i & 1) * 128, tag(pack2(gelu2(a[2 * i] + bf_lo(u[i])), gelu2(a[2 * i + 1] + bf_hi(u[i]))), (lane & 7) == w * 2 + (i & 1), ep));
            }
            TS0(4, 30 + wg);
        } else {
            mbar_wait(bars + B_FREE, 0);
            if (lane < 2) mbar_arrive(bars + B_EMPTY + 48);
        }
        M.half = wg ^ ks;
        const uint32_t orow = mt * 128 + M.half * 64 + w * 16;
        M.run_o(a);
        if (wg == 1) TS0(4, 13);
        M.run<false>(a, 14, 0, 14 - NSLOT, NSLOT + 1, 1, 52, b2 + orow + r);
        mbar_wait(bars + B_ROW, 1);
        const uint32_t stg = sbase + (4 + (w >> 1)) * SLOT + M.half * 8192 + (w & 1) * (PITCH * 16);
        const uint32_t sa = stg + (lane & 15) * PITCH + (lane >> 4) * 16;
        wg_wait<1>();
        if (wg == 0) bar_arrive(7, 256);
        wg_wait<0>();
        pin(a);
        TS0(8, 14 + wg);
#pragma unroll
        for (int i = 0; i < 7; i++)
            stsm4(sa + i * 32, pack2(a[8 * i], a[8 * i + 1]), pack2(a[8 * i + 2], a[8 * i + 3]), pack2(a[8 * i + 4], a[8 * i + 5]), pack2(a[8 * i + 6], a[8 * i + 7]));
        if (!wg) TS0(8, 206);
        fence_async_shared();
        __syncwarp();
        if (elect()) {
            asm volatile("cp.reduce.async.bulk.tensor.3d.global.shared::cta.add.tile.bulk_group [%0, {%4, %2, %3}], [%1];\ncp.async.bulk.commit_group;" ::"l"(&P.tmOut), "r"(stg), "r"(nt2), "r"(orow), "r"(0) : "memory");
            if (w == 0) mbar_arrive(bars + B_END);
            asm volatile("cp.async.bulk.wait_group.read 0;" ::: "memory");
        }
        TS0(15, wg ? 19 : 207);
        TSDUMP();
    }
}

typedef CUresult (*EncodeFn)(CUtensorMap*, CUtensorMapDataType, cuuint32_t, void*, const cuuint64_t*, const cuuint64_t*, const cuuint32_t*, const cuuint32_t*,
                             CUtensorMapInterleave, CUtensorMapSwizzle, CUtensorMapL2promotion, CUtensorMapFloatOOBfill);

void make_map(EncodeFn enc, CUtensorMap* tm, const void* base, bool swizzle, int d0, int d1, int d2, int s1, int s2, int b0, int b1, int b2) {
    const cuuint64_t dims[3] = {(cuuint64_t)d0, (cuuint64_t)d1, (cuuint64_t)d2}, strides[2] = {(cuuint64_t)s1 * 2, (cuuint64_t)s2 * 2};
    const cuuint32_t box[3] = {(cuuint32_t)b0, (cuuint32_t)b1, (cuuint32_t)b2}, es[3] = {1, 1, 1};
    enc(tm, CU_TENSOR_MAP_DATA_TYPE_BFLOAT16, d2 ? 3 : 2, (void*)base, dims, strides, box, es, CU_TENSOR_MAP_INTERLEAVE_NONE,
        swizzle ? CU_TENSOR_MAP_SWIZZLE_128B : CU_TENSOR_MAP_SWIZZLE_NONE, CU_TENSOR_MAP_L2_PROMOTION_L2_128B, CU_TENSOR_MAP_FLOAT_OOB_FILL_NONE);
}

}

extern "C" void kernel_launch(void* const* d_in, const int* in_sizes, int n_in, void* d_out, int out_size) {
    static EncodeFn enc = nullptr;
    static Scratch* scratch = nullptr;
    if (!enc) {
        void* fn = nullptr;
        cudaDriverEntryPointQueryResult qr;
        cudaGetDriverEntryPoint("cuTensorMapEncodeTiled", &fn, cudaEnableDefault, &qr);
        enc = (EncodeFn)fn;
        cudaGetSymbolAddress((void**)&scratch, g_s);
        cudaFuncSetAttribute(fused_kernel, cudaFuncAttributeMaxDynamicSharedMemorySize, SMEM_BYTES);
    }
    Params P;
    const __nv_bfloat16* x = (const __nv_bfloat16*)d_in[0];
    make_map(enc, &P.tmX, x, true, D_, S_ / 2, 2, 2 * D_, D_, 64, 64, 2);
    make_map(enc, &P.tmWqkv, d_in[1], true, D_, D_, 3, 3 * D_, D_, 64, 32, 3);
    make_map(enc, &P.tmW1, d_in[4], true, 64, S_, F_ / 64, F_, 64, 64, 64, 2);
    make_map(enc, &P.tmW2, d_in[6], true, 64, F_, S_ / 64, S_, 64, 64, 64, 2);
    make_map(enc, &P.tmOut, d_out, false, 112, 4, S_, 112, D_, PITCH / 2, 1, 16);
    fused_kernel<<<NCTA, NTHREADS, SMEM_BYTES, cudaStreamPerThread>>>(x, (const __nv_bfloat16*)d_in[5], (const __nv_bfloat16*)d_in[7], (const __nv_bfloat16*)d_in[2], (__nv_bfloat16*)d_out, scratch,
                                                                      (const __nv_bfloat16*)d_in[4], P);
}
```

```cpp
#include <cuda_runtime.h>
#include <cuda_bf16.h>
#include <cuda.h>
#include <stdint.h>

#define HALO_NS 300
#define HINT 5
#define HOLD 1
#define LATEREL 1
#define PF 400
#define PF0 2
#define PF1 8
#define LEADW 4
#define LEADN 7
#define TSQ 0
#define PF2 14
#define PFD 1500
#define PACE 600
#define PAUSE 8
#define LAG1 4

namespace {

constexpr int S_ = 2048, D_ = 448, F_ = 1792;
constexpr int NCTA = 128, NTHREADS = 384;
constexpr int NSLOT = 6, SLOT = 32768, WSLOT = 24576, TILEB = 14336, SLAB = 3584, HALF = 7168;
constexpr int KV = 1792, HSTG = SLAB + 32, PITCH = 240;
constexpr int OFF_X = NSLOT * SLOT;
constexpr int OFF_Y = OFF_X + 10 * KV;
constexpr int OFF_ST = OFF_Y + TILEB;
constexpr int OFF_BAR = OFF_ST + 1024;
constexpr int SMEM_BYTES = OFF_BAR + 1280;
constexpr uint32_t SMEM0 = 1024;
constexpr int B_QFULL = 0, B_FULL = 56, B_HALO = 128, B_X = 136, B_CS = 168, B_FREE = 192, B_END = 200, B_QEMPTY = 216, B_EMPTY = 232, B_ROW = 288, NBAR = 37;
constexpr float LN_EPS = 1e-5f, QK_SCALE = 0.1889822365046136f * 1.4426950408889634f;
constexpr int SPIN_LIMIT = 1 << 22;

struct Scratch {
    uint8_t H[4][32][TILEB];
    uint8_t U[4][28][TILEB];
    uint8_t O[16][8][TILEB];
    uint8_t Wo[4][8][TILEB];
    uint8_t halo[NCTA][2 * KV];
    uint2 stat[S_];
    uint2 colsum[8][8][96];
    uint32_t flag[32][32];
    uint32_t epoch[NCTA];
};
__device__ __align__(1024) Scratch g_s;

#define TS(g, i)
#define TS0(g, i)
#define TSDUMP()

struct Params {
    CUtensorMap tmX, tmWqkv, tmW1, tmW2, tmOut;
};

__device__ __forceinline__ bool elect() {
    uint32_t p;
    asm volatile("{\n.reg .pred p;\nelect.sync _|p, 0xffffffff;\nselp.u32 %0, 1, 0, p;\n}" : "=r"(p));
    return p;
}
__device__ __forceinline__ void mbar_init(uint32_t b, uint32_t c) { asm volatile("mbarrier.init.shared::cta.b64 [%0], %1;" ::"r"(b), "r"(c) : "memory"); }
__device__ __forceinline__ void mbar_expect(uint32_t b, uint32_t tx) { asm volatile("mbarrier.arrive.expect_tx.shared::cta.b64 _, [%0], %1;" ::"r"(b), "r"(tx) : "memory"); }
__device__ __forceinline__ void mbar_arrive(uint32_t b) { asm volatile("mbarrier.arrive.shared::cta.b64 _, [%0];" ::"r"(b) : "memory"); }
template <int N> __device__ __forceinline__ void mbar_arrive_n(uint32_t b) { asm volatile("mbarrier.arrive.shared::cta.b64 _, [%0], %1;" ::"r"(b), "n"(N) : "memory"); }
__device__ __forceinline__ void mbar_arrive4_remote(uint32_t b) { asm volatile("mbarrier.arrive.shared::cluster.b64 _, [%0], 4;" ::"r"(b) : "memory"); }
__device__ __forceinline__ void mbar_arrive_remote(uint32_t b) { asm volatile("mbarrier.arrive.shared::cluster.b64 _, [%0];" ::"r"(b) : "memory"); }
#define MBAR_WAIT_ASM(SEM) \
    asm volatile("{\n.reg .pred p;\nWAIT:\nmbarrier.try_wait.parity" SEM ".shared::cta.b64 p, [%0], %1;\n@!p bra WAIT;\n}" ::"r"(b), "r"(parity) : "memory")
__device__ __forceinline__ void mbar_wait(uint32_t b, uint32_t parity) { MBAR_WAIT_ASM(""); }
__device__ __forceinline__ void mbar_wait_bounded(uint32_t b, uint32_t parity, uint32_t& n) {
    asm volatile("{\n.reg .pred p;\nWAIT:\nadd.u32 %0, %0, 1;\nsetp.gt.u32 p, %0, %3;\n@p st.global.u32 [%4], %0;\n"
                 "mbarrier.try_wait.parity.shared::cta.b64 p, [%1], %2;\n@!p bra WAIT;\n}" : "+r"(n) : "r"(b), "r"(parity), "n"(SPIN_LIMIT), "l"(0ull) : "memory");
}
__device__ __forceinline__ uint32_t mapa(uint32_t a, uint32_t rank) { uint32_t r; asm("mapa.shared::cluster.u32 %0, %1, %2;" : "=r"(r) : "r"(a), "r"(rank)); return r; }
__device__ __forceinline__ void tma3d(uint32_t dst, const CUtensorMap* tm, uint32_t bar, int c0, int c1, int c2) {
    asm volatile("cp.async.bulk.tensor.3d.shared::cluster.global.mbarrier::complete_tx::bytes [%0], [%1, {%3, %4, %5}], [%2];" ::"r"(dst), "l"(tm), "r"(bar), "r"(c0), "r"(c1), "r"(c2) : "memory");
}
__device__ __forceinline__ void tma3d_pair(uint32_t dst, const CUtensorMap* tm, uint32_t bar, int c0, int c1, int c2) {
    asm volatile("cp.async.bulk.tensor.3d.shared::cluster.global.mbarrier::complete_tx::bytes.multicast::cluster [%0], [%1, {%3, %4, %5}], [%2], %6;" ::"r"(dst), "l"(tm), "r"(bar), "r"(c0), "r"(c1), "r"(c2), "h"((uint16_t)3) : "memory");
}
__device__ __forceinline__ void bulk_load(uint32_t dst, const void* src, uint32_t bytes, uint32_t bar) {
    asm volatile("cp.async.bulk.shared::cluster.global.mbarrier::complete_tx::bytes [%0], [%1], %2, [%3];" ::"r"(dst), "l"(src), "r"(bytes), "r"(bar) : "memory");
}
template <int BYTES> __device__ __forceinline__ void prefetch_l2(const void* p) { asm volatile("cp.async.bulk.prefetch.L2.global [%0], %1;" ::"l"(p), "n"(BYTES) : "memory"); }
__device__ __forceinline__ void bulk_store(void* dst, uint32_t src, uint32_t bytes) {
    asm volatile("cp.async.bulk.global.shared::cta.bulk_group [%0], [%1], %2;" ::"l"(dst), "r"(src), "r"(bytes) : "memory");
}
__device__ __forceinline__ uint32_t ld_u16(const void* p) { uint32_t v; asm volatile("ld.global.nc.u16 %0, [%1];" : "=r"(v) : "l"(p)); return v; }
__device__ __forceinline__ uint32_t ld_relaxed(const uint32_t* p) { uint32_t v; asm volatile("ld.relaxed.gpu.global.u32 %0, [%1];" : "=r"(v) : "l"(p) : "memory"); return v; }
__device__ __forceinline__ void bulk_flush() { asm volatile("cp.async.bulk.commit_group;\ncp.async.bulk.wait_group 0;" ::: "memory"); }
__device__ __forceinline__ void signal(uint32_t* flag) { asm volatile("fence.acq_rel.gpu;\nred.relaxed.gpu.global.add.u32 [%0], 1;" ::"l"(flag) : "memory"); }
__device__ __forceinline__ void hint(uint32_t* flag) { asm volatile("red.relaxed.gpu.global.add.u32 [%0], 1;" ::"l"(flag) : "memory"); }
__device__ __forceinline__ uint32_t tag(uint32_t v, uint32_t mask, uint32_t parity) { return (v & ~mask) | (parity & mask); }
__device__ __forceinline__ uint32_t or_diff(uint32_t acc, uint32_t v, uint32_t parity) { asm("lop3.b32 %0, %0, %1, %2, 0xf6;" : "+r"(acc) : "r"(v), "r"(parity)); return acc; }
__device__ __forceinline__ uint4 ld_relaxed4(const void* p) {
    uint4 v;
    asm volatile("ld.relaxed.gpu.global.v4.u32 {%0, %1, %2, %3}, [%4];" : "=r"(v.x), "=r"(v.y), "=r"(v.z), "=r"(v.w) : "l"(p) : "memory");
    return v;
}
__device__ __forceinline__ uint2 ld_relaxed2(const void* p) { uint2 v; asm volatile("ld.relaxed.gpu.global.v2.u32 {%0, %1}, [%2];" : "=r"(v.x), "=r"(v.y) : "l"(p) : "memory"); return v; }
__device__ __forceinline__ void sts4(uint32_t a, uint4 v) { asm volatile("st.shared.v4.b32 [%0], {%1, %2, %3, %4};" ::"r"(a), "r"(v.x), "r"(v.y), "r"(v.z), "r"(v.w) : "memory"); }
__device__ __forceinline__ void sts1(uint32_t a, uint32_t v) { asm volatile("st.shared.b32 [%0], %1;" ::"r"(a), "r"(v) : "memory"); }
__device__ __forceinline__ void sts2(uint32_t a, uint32_t v0, uint32_t v1) { asm volatile("st.shared.v2.b32 [%0], {%1, %2};" ::"r"(a), "r"(v0), "r"(v1) : "memory"); }
__device__ __forceinline__ void stg1(void* p, uint32_t v) { asm volatile("st.global.b32 [%0], %1;" ::"l"(p), "r"(v) : "memory"); }
__device__ __forceinline__ void fence_async_shared() { asm volatile("fence.proxy.async.shared::cta;" ::: "memory"); }
#define BOUND "add.u32 %0, %0, 16;\nsetp.gt.u32 p, %0, %1;\n@p st.global.u32 [%2], %0;\n"
__device__ __forceinline__ void wait_flag(const uint32_t* p, uint32_t target, uint32_t& n) {
    asm volatile("{\n.reg .pred p;\n.reg .u32 v;\nPOLL:\n" BOUND "ld.acquire.gpu.global.u32 v, [%3];\nsetp.ne.u32 p, v, %4;\n@p bra POLL;\nfence.proxy.async.global;\n}"
                 : "+r"(n) : "n"(SPIN_LIMIT), "l"(0ull), "l"(p), "r"(target) : "memory");
}
__device__ __forceinline__ void wait_flag2(const uint32_t* h, uint32_t th, const uint32_t* p, uint32_t target, uint32_t& n) {
    asm volatile("{\n.reg .pred p;\n.reg .u32 u, v;\nPOLL:\n" BOUND "ld.relaxed.gpu.global.u32 u, [%3];\nld.acquire.gpu.global.u32 v, [%5];\nsetp.ne.u32 p, u, %4;\nsetp.ne.or.u32 p, v, %6, p;\n@p bra POLL;\nfence.proxy.async.global;\n}"
                 : "+r"(n) : "n"(SPIN_LIMIT), "l"(0ull), "l"(h), "r"(th), "l"(p), "r"(target) : "memory");
}
__device__ __forceinline__ void block_end() { asm volatile("{\n.reg .pred p;\n.reg .u32 t;\nAGAIN:\nmov.u32 t, %%clock;\nsetp.eq.u32 p, t, %0;\n@p bra AGAIN;\n}" ::"n"(0) : "memory"); }
__device__ __forceinline__ void bar_sync(int id, int n) { asm volatile("bar.sync %0, %1;" ::"r"(id), "r"(n) : "memory"); }
__device__ __forceinline__ void bar_arrive(int id, int n) { asm volatile("bar.arrive %0, %1;" ::"r"(id), "r"(n) : "memory"); }
__device__ __forceinline__ void wg_fence() { asm volatile("wgmma.fence.sync.aligned;" ::: "memory"); }
__device__ __forceinline__ void wg_commit() { asm volatile("wgmma.commit_group.sync.aligned;" ::: "memory"); }
template <int N> __device__ __forceinline__ void wg_wait() { asm volatile("wgmma.wait_group.sync.aligned %0;" ::"n"(N) : "memory"); }
template <int N> __device__ __forceinline__ void pin(float (&d)[N]) {
#pragma unroll
    for (int i = 0; i < N; i++) asm volatile("" : "+f"(d[i])::"memory");
}
__host__ __device__ constexpr uint32_t desc_hi(uint32_t sbo, uint32_t swz) { return (sbo >> 4) | (swz << 30); }
__host__ __device__ constexpr uint32_t desc_lo(uint32_t off, uint32_t lbo) { return ((SMEM0 + off) >> 4) | ((lbo >> 4) << 16); }
__device__ __forceinline__ uint32_t pack2(float lo, float hi) { uint32_t r; asm("cvt.rn.bf16x2.f32 %0, %1, %2;" : "=r"(r) : "f"(hi), "f"(lo)); return r; }
__device__ __forceinline__ float bf_lo(uint32_t v) { return __uint_as_float(v << 16); }
__device__ __forceinline__ float bf_hi(uint32_t v) { return __uint_as_float(v & 0xffff0000u); }
__device__ __forceinline__ void stsm4(uint32_t a, uint32_t r0, uint32_t r1, uint32_t r2, uint32_t r3) {
    asm volatile("stmatrix.sync.aligned.m8n8.x4.shared.b16 [%0], {%1, %2, %3, %4};" ::"r"(a), "r"(r0), "r"(r1), "r"(r2), "r"(r3) : "memory");
}
__device__ __forceinline__ void stsm2(uint32_t a, uint32_t r0, uint32_t r1) {
    asm volatile("stmatrix.sync.aligned.m8n8.x2.shared.b16 [%0], {%1, %2};" ::"r"(a), "r"(r0), "r"(r1) : "memory");
}
__device__ __forceinline__ uint4 lds4(uint32_t a) { uint4 v; asm volatile("ld.shared.v4.b32 {%0, %1, %2, %3}, [%4];" : "=r"(v.x), "=r"(v.y), "=r"(v.z), "=r"(v.w) : "r"(a) : "memory"); return v; }
__device__ __forceinline__ uint2 lds2(uint32_t a) { uint2 v; asm volatile("ld.shared.v2.b32 {%0, %1}, [%2];" : "=r"(v.x), "=r"(v.y) : "r"(a) : "memory"); return v; }
__device__ __forceinline__ float lds1f(uint32_t a) { float v; asm volatile("ld.shared.f32 %0, [%1];" : "=f"(v) : "r"(a) : "memory"); return v; }
__device__ __forceinline__ void ldsm4(uint32_t* r, uint32_t a) {
    asm volatile("ldmatrix.sync.aligned.m8n8.x4.shared.b16 {%0, %1, %2, %3}, [%4];" : "=r"(r[0]), "=r"(r[1]), "=r"(r[2]), "=r"(r[3]) : "r"(a) : "memory");
}
__device__ __forceinline__ void ldsm4t(uint32_t* r, uint32_t a) {
    asm volatile("ldmatrix.sync.aligned.m8n8.x4.trans.shared.b16 {%0, %1, %2, %3}, [%4];" : "=r"(r[0]), "=r"(r[1]), "=r"(r[2]), "=r"(r[3]) : "r"(a) : "memory");
}
__device__ __forceinline__ void ldsm2t(uint32_t* r, uint32_t a) {
    asm volatile("ldmatrix.sync.aligned.m8n8.x2.trans.shared.b16 {%0, %1}, [%2];" : "=r"(r[0]), "=r"(r[1]) : "r"(a) : "memory");
}
__device__ __forceinline__ uint32_t transpose8(uint32_t v) { uint32_t r; asm volatile("movmatrix.sync.aligned.m8n8.trans.b16 %0, %1;" : "=r"(r) : "r"(v)); return r; }
__device__ __forceinline__ void mma16(float (&c)[4], uint32_t a0, uint32_t a1, uint32_t a2, uint32_t a3, uint32_t b0, uint32_t b1) {
    asm volatile("mma.sync.aligned.m16n8k16.row.col.f32.bf16.bf16.f32 {%0, %1, %2, %3}, {%4, %5, %6, %7}, {%8, %9}, {%0, %1, %2, %3};"
                 : "+f"(c[0]), "+f"(c[1]), "+f"(c[2]), "+f"(c[3]) : "r"(a0), "r"(a1), "r"(a2), "r"(a3), "r"(b0), "r"(b1));
}
__device__ __forceinline__ void mma8(float (&c)[4], uint32_t a0, uint32_t a1, uint32_t b0) {
    asm volatile("mma.sync.aligned.m16n8k8.row.col.f32.bf16.bf16.f32 {%0, %1, %2, %3}, {%4, %5}, {%6}, {%0, %1, %2, %3};"
                 : "+f"(c[0]), "+f"(c[1]), "+f"(c[2]), "+f"(c[3]) : "r"(a0), "r"(a1), "r"(b0));
}
__device__ __forceinline__ void st_async4(uint32_t a, uint32_t bar, uint32_t v0, uint32_t v1, uint32_t v2, uint32_t v3) {
    asm volatile("st.async.weak.shared::cluster.mbarrier::complete_tx::bytes.v4.b32 [%0], {%2, %3, %4, %5}, [%1];" ::"r"(a), "r"(bar), "r"(v0), "r"(v1), "r"(v2), "r"(v3) : "memory");
}
__device__ __forceinline__ void st_async2(uint32_t a, uint32_t bar, uint32_t v0, uint32_t v1) {
    asm volatile("st.async.weak.shared::cluster.mbarrier::complete_tx::bytes.v2.b32 [%0], {%2, %3}, [%1];" ::"r"(a), "r"(bar), "r"(v0), "r"(v1) : "memory");
}
__device__ __forceinline__ float quad_max(float v) { v = fmaxf(v, __shfl_xor_sync(~0u, v, 1)); return fmaxf(v, __shfl_xor_sync(~0u, v, 2)); }
__device__ __forceinline__ float quad_sum(float v) { v += __shfl_xor_sync(~0u, v, 1); return v + __shfl_xor_sync(~0u, v, 2); }
__device__ __forceinline__ float ex2(float v) { float r; asm("ex2.approx.ftz.f32 %0, %1;" : "=f"(r) : "f"(v)); return r; }
__device__ __forceinline__ float rcp(float v) { float r; asm("rcp.approx.ftz.f32 %0, %1;" : "=f"(r) : "f"(v)); return r; }
__device__ __forceinline__ float rsq(float v) { float r; asm("rsqrt.approx.ftz.f32 %0, %1;" : "=f"(r) : "f"(v)); return r; }
__device__ __forceinline__ float gelu2(float v) {
    float z = v * fmaf(v * v, 8 * 0.044715f * 0.7978845608028654f, 2 * 0.7978845608028654f), t;
    asm("tanh.approx.f32 %0, %1;" : "=f"(t) : "f"(z));
    return fmaf(v, t, v);
}
__device__ __forceinline__ float row_sum(float v) {
    v = quad_sum(v); v += __shfl_xor_sync(~0u, v, 4);
    return v + __shfl_xor_sync(~0u, v, 24);
}

template <int TA, int TB, uint32_t HA, uint32_t HB>
__device__ __forceinline__ void wgmma_n112(float (&d)[56], uint32_t da, uint32_t db, int accumulate) {
    asm volatile("{\n.reg .pred p;\n.reg .b64 a, b;\nmov.b64 a, {%56, %61};\nmov.b64 b, {%57, %62};\nsetp.ne.b32 p, %58, 0;\n"
        "wgmma.mma_async.sync.aligned.m64n112k16.f32.bf16.bf16 {"
        "%0, %1, %2, %3, %4, %5, %6, %7, %8, %9, %10, %11, %12, %13, %14, %15, "
        "%16, %17, %18, %19, %20, %21, %22, %23, %24, %25, %26, %27, %28, %29, %30, %31, "
        "%32, %33, %34, %35, %36, %37, %38, %39, %40, %41, %42, %43, %44, %45, %46, %47, "
        "%48, %49, %50, %51, %52, %53, %54, %55"
        "}, a, b, p, 1, 1, %59, %60;\n}\n"
        : "+f"(d[0]), "+f"(d[1]), "+f"(d[2]), "+f"(d[3]), "+f"(d[4]), "+f"(d[5]), "+f"(d[6]), "+f"(d[7]),
          "+f"(d[8]), "+f"(d[9]), "+f"(d[10]), "+f"(d[11]), "+f"(d[12]), "+f"(d[13]), "+f"(d[14]), "+f"(d[15]),
          "+f"(d[16]), "+f"(d[17]), "+f"(d[18]), "+f"(d[19]), "+f"(d[20]), "+f"(d[21]), "+f"(d[22]), "+f"(d[23]),
          "+f"(d[24]), "+f"(d[25]), "+f"(d[26]), "+f"(d[27]), "+f"(d[28]), "+f"(d[29]), "+f"(d[30]), "+f"(d[31]),
          "+f"(d[32]), "+f"(d[33]), "+f"(d[34]), "+f"(d[35]), "+f"(d[36]), "+f"(d[37]), "+f"(d[38]), "+f"(d[39]),
          "+f"(d[40]), "+f"(d[41]), "+f"(d[42]), "+f"(d[43]), "+f"(d[44]), "+f"(d[45]), "+f"(d[46]), "+f"(d[47]),
          "+f"(d[48]), "+f"(d[49]), "+f"(d[50]), "+f"(d[51]), "+f"(d[52]), "+f"(d[53]), "+f"(d[54]), "+f"(d[55])
        : "r"(da), "r"(db), "r"(accumulate), "n"(TA), "n"(TB), "n"(HA), "n"(HB));
}

template <int TA, int TB, uint32_t HA, uint32_t HB>
__device__ __forceinline__ void wgmma_n168(float (&d)[84], uint32_t da, uint32_t db, int accumulate) {
    asm volatile("{\n.reg .pred p;\n.reg .b64 a, b;\nmov.b64 a, {%84, %89};\nmov.b64 b, {%85, %90};\nsetp.ne.b32 p, %86, 0;\n"
        "wgmma.mma_async.sync.aligned.m64n168k16.f32.bf16.bf16 {"
        "%0, %1, %2, %3, %4, %5, %6, %7, %8, %9, %10, %11, %12, %13, %14, %15, "
        "%16, %17, %18, %19, %20, %21, %22, %23, %24, %25, %26, %27, %28, %29, %30, %31, "
        "%32, %33, %34, %35, %36, %37, %38, %39, %40, %41, %42, %43, %44, %45, %46, %47, "
        "%48, %49, %50, %51, %52, %53, %54, %55, %56, %57, %58, %59, %60, %61, %62, %63, "
        "%64, %65, %66, %67, %68, %69, %70, %71, %72, %73, %74, %75, %76, %77, %78, %79, "
        "%80, %81, %82, %83"
        "}, a, b, p, 1, 1, %87, %88;\n}\n"
        : "+f"(d[0]), "+f"(d[1]), "+f"(d[2]), "+f"(d[3]), "+f"(d[4]), "+f"(d[5]), "+f"(d[6]), "+f"(d[7]),
          "+f"(d[8]), "+f"(d[9]), "+f"(d[10]), "+f"(d[11]), "+f"(d[12]), "+f"(d[13]), "+f"(d[14]), "+f"(d[15]),
          "+f"(d[16]), "+f"(d[17]), "+f"(d[18]), "+f"(d[19]), "+f"(d[20]), "+f"(d[21]), "+f"(d[22]), "+f"(d[23]),
          "+f"(d[24]), "+f"(d[25]), "+f"(d[26]), "+f"(d[27]), "+f"(d[28]), "+f"(d[29]), "+f"(d[30]), "+f"(d[31]),
          "+f"(d[32]), "+f"(d[33]), "+f"(d[34]), "+f"(d[35]), "+f"(d[36]), "+f"(d[37]), "+f"(d[38]), "+f"(d[39]),
          "+f"(d[40]), "+f"(d[41]), "+f"(d[42]), "+f"(d[43]), "+f"(d[44]), "+f"(d[45]), "+f"(d[46]), "+f"(d[47]),
          "+f"(d[48]), "+f"(d[49]), "+f"(d[50]), "+f"(d[51]), "+f"(d[52]), "+f"(d[53]), "+f"(d[54]), "+f"(d[55]),
          "+f"(d[56]), "+f"(d[57]), "+f"(d[58]), "+f"(d[59]), "+f"(d[60]), "+f"(d[61]), "+f"(d[62]), "+f"(d[63]),
          "+f"(d[64]), "+f"(d[65]), "+f"(d[66]), "+f"(d[67]), "+f"(d[68]), "+f"(d[69]), "+f"(d[70]), "+f"(d[71]),
          "+f"(d[72]), "+f"(d[73]), "+f"(d[74]), "+f"(d[75]), "+f"(d[76]), "+f"(d[77]), "+f"(d[78]), "+f"(d[79]),
          "+f"(d[80]), "+f"(d[81]), "+f"(d[82]), "+f"(d[83])
        : "r"(da), "r"(db), "r"(accumulate), "n"(TA), "n"(TB), "n"(HA), "n"(HB));
}

template <uint32_t HB>
__device__ __forceinline__ void wgmma_rs_n168(float (&d)[84], uint32_t a0, uint32_t a1, uint32_t db) {
    asm volatile("{\n.reg .b64 b;\nmov.b64 b, {%86, %88};\n"
        "wgmma.mma_async.sync.aligned.m64n168k16.f32.bf16.bf16 {"
        "%0, %1, %2, %3, %4, %5, %6, %7, %8, %9, %10, %11, %12, %13, %14, %15, "
        "%16, %17, %18, %19, %20, %21, %22, %23, %24, %25, %26, %27, %28, %29, %30, %31, "
        "%32, %33, %34, %35, %36, %37, %38, %39, %40, %41, %42, %43, %44, %45, %46, %47, "
        "%48, %49, %50, %51, %52, %53, %54, %55, %56, %57, %58, %59, %60, %61, %62, %63, "
        "%64, %65, %66, %67, %68, %69, %70, %71, %72, %73, %74, %75, %76, %77, %78, %79, "
        "%80, %81, %82, %83"
        "}, {%84, %85, %87, %87}, b, 1, 1, 1, 0;\n}\n"
        : "+f"(d[0]), "+f"(d[1]), "+f"(d[2]), "+f"(d[3]), "+f"(d[4]), "+f"(d[5]), "+f"(d[6]), "+f"(d[7]),
          "+f"(d[8]), "+f"(d[9]), "+f"(d[10]), "+f"(d[11]), "+f"(d[12]), "+f"(d[13]), "+f"(d[14]), "+f"(d[15]),
          "+f"(d[16]), "+f"(d[17]), "+f"(d[18]), "+f"(d[19]), "+f"(d[20]), "+f"(d[21]), "+f"(d[22]), "+f"(d[23]),
          "+f"(d[24]), "+f"(d[25]), "+f"(d[26]), "+f"(d[27]), "+f"(d[28]), "+f"(d[29]), "+f"(d[30]), "+f"(d[31]),
          "+f"(d[32]), "+f"(d[33]), "+f"(d[34]), "+f"(d[35]), "+f"(d[36]), "+f"(d[37]), "+f"(d[38]), "+f"(d[39]),
          "+f"(d[40]), "+f"(d[41]), "+f"(d[42]), "+f"(d[43]), "+f"(d[44]), "+f"(d[45]), "+f"(d[46]), "+f"(d[47]),
          "+f"(d[48]), "+f"(d[49]), "+f"(d[50]), "+f"(d[51]), "+f"(d[52]), "+f"(d[53]), "+f"(d[54]), "+f"(d[55]),
          "+f"(d[56]), "+f"(d[57]), "+f"(d[58]), "+f"(d[59]), "+f"(d[60]), "+f"(d[61]), "+f"(d[62]), "+f"(d[63]),
          "+f"(d[64]), "+f"(d[65]), "+f"(d[66]), "+f"(d[67]), "+f"(d[68]), "+f"(d[69]), "+f"(d[70]), "+f"(d[71]),
          "+f"(d[72]), "+f"(d[73]), "+f"(d[74]), "+f"(d[75]), "+f"(d[76]), "+f"(d[77]), "+f"(d[78]), "+f"(d[79]),
          "+f"(d[80]), "+f"(d[81]), "+f"(d[82]), "+f"(d[83])
        : "r"(a0), "r"(a1), "r"(db), "r"(0), "n"(HB));
}

struct Ring {
    uint32_t slot, ph;
    __device__ __forceinline__ void next() { if (++slot == NSLOT) { slot = 0; ph ^= 1; } }
    __device__ __forceinline__ void next2() { ph ^= slot == 5; slot = __byte_perm(0x06030201u, 0x00040005u, 0x7770 + slot); }
};
struct Slot {
    uint32_t dst, bar, ph;
    __device__ __forceinline__ void next(uint32_t bars) {
        dst += SLOT; bar += 8;
        if (bar == bars + 8 * NSLOT) { dst -= NSLOT * SLOT; bar = bars; ph ^= 1; }
    }
};
__device__ __forceinline__ uint32_t xslot(int i) { return __byte_perm(0x04130e0cu, 0x00130e0cu, 0x7770 + i); }
__device__ __forceinline__ uint32_t wslot(int i) { return __byte_perm(0x06001510u, 0x00151009u, 0x7770 + i); }

constexpr uint32_t HI_SW = desc_hi(1024, 1);

struct Mma {
    uint32_t bars, rel;
    bool lead;
    int wg, half, w;
    Ring r;
    uint32_t prev;
    __device__ __forceinline__ void release_pair(uint32_t s) { if (lead) mbar_arrive4_remote(rel + B_EMPTY + 8 * s); }
    __device__ __forceinline__ void release(uint32_t s) { if (lead) mbar_arrive_n<4>(bars + B_EMPTY + 8 * s); }
    template <bool G1>
    __device__ __forceinline__ void run(float (&a)[56], int n, int first, int last, int lag, int accumulate, int ts, const __nv_bfloat16* bias = nullptr) {
#pragma unroll 1
        for (int i = 0; i < n; i++) {
            if (lag && i == (wg ? n - lag : -1)) {
                if (!G1) {
                    const uint32_t c0 = ld_u16(bias), c1 = ld_u16(bias + 8);
                    wg_wait<0>(); release(prev); last = first;
                    pin(a);
#pragma unroll
                    for (int k = 0; k < 56; k++) a[k] += bf_lo((k & 2) ? c1 : c0);
                    pin(a);
                }
                bar_sync(7, 256);
            }
            const bool seen = !G1 && last == first;
            const uint32_t s = seen ? n - 1 - i : r.slot;
            if (!seen) mbar_wait(bars + B_FULL + 8 * s, r.ph);
            if (G1) r.next(); else r.next2();
            if (!TSQ || !i) TS0(G1 ? 2 : 8, ts + i + wg * 68);
            const uint32_t dB = s * (SLOT >> 4), dA = dB + half * 512;
            wg_fence();
#pragma unroll
            for (int k = 0; k < 4; k++) {
                wgmma_n112<1, 1, HI_SW, desc_hi(G1 ? 256 : 1024, 0)>(a, dA + desc_lo(k * 2048, 8192), dB + desc_lo(16384 + k * (G1 ? SLAB : 256), 128), k > 0 || accumulate || i > 0);
                if (k == 1) {
                    wg_commit(); wg_wait<1>();
                    if ((uint32_t)(i - first) < (uint32_t)(last - first)) release(prev);
                    if (G1 && lag && i == (wg ? -1 : n - 1)) bar_arrive(7, 256);
                    if (TSQ && i) TS0(G1 ? 2 : 8, ts + i + wg * 68);
                }
            }
            wg_commit();
            prev = s;
        }
    }
    __device__ __forceinline__ void run_o(float (&a)[56]) {
#pragma unroll 1
        for (int i = 0; i < 2; i++) {
            const uint32_t s = r.slot, dB = s * (SLOT >> 4), dA = dB + half * (HALF >> 4);
            mbar_wait(bars + B_FULL + 8 * s, r.ph);
            TS0(8, 48 + 2 * i + wg * 68);
            wg_fence();
#pragma unroll
            for (int k = 0; k < 7; k++) {
                if (k == 3) { mbar_wait(bars + B_FULL + 8 * s + 8, r.ph); wg_fence(); }
                wgmma_n112<0, 1, desc_hi(128, 0), desc_hi(256, 0)>(a, dA + desc_lo(k * 2048 + (k > 3) * (SLOT - HALF), k == 3 ? SLOT - 6144 : 1024),
                                                                   dB + desc_lo(16384 + k * SLAB + (k > 2) * (SLOT - 3 * SLAB), 128), k > 0 || i > 0);
                if (k & 1) wg_commit();
                if (k == 1) { wg_wait<1>(); if (i) release(prev); }
                if (k == 5) { wg_wait<1>(); release(s); }
            }
            wg_commit();
            prev = s + 1;
            r.slot++; r.next2();
        }
    }
};

__global__ void __cluster_dims__(2, 1, 1) __launch_bounds__(NTHREADS, 1)
fused_kernel(const __nv_bfloat16* __restrict__ x, const __nv_bfloat16* __restrict__ b1, const __nv_bfloat16* __restrict__ b2, const __nv_bfloat16* __restrict__ wo, __nv_bfloat16* out, Scratch* G,
             const __nv_bfloat16* __restrict__ w1,
             const __grid_constant__ Params P) {
    extern __shared__ __align__(1024) uint8_t smem[];
    const uint32_t sbase = (uint32_t)__cvta_generic_to_shared(smem);
    const uint32_t bars = sbase + OFF_BAR;
    const uint32_t rank = blockIdx.x & 1, pr = blockIdx.x >> 1;
    const uint32_t row0 = blockIdx.x * 16;
    if (threadIdx.x == 32) prefetch_l2<TILEB>(x + row0 * D_);
    if (threadIdx.x == 0) {
        TS(15, 0);
        mbar_init(bars + B_ROW, 1);
        asm volatile("fence.mbarrier_init.release.cluster;" ::: "memory");
        bulk_load(sbase + OFF_Y, x + row0 * D_, TILEB, bars + B_ROW);
        mbar_expect(bars + B_ROW, TILEB);
        TS(1, 97);
    }
    const int lane = threadIdx.x & 31;
    const int warp = __shfl_sync(~0u, threadIdx.x >> 5, 0), w = warp & 3;
    if (elect()) {
        const uint32_t first = bars + warp * 24, count = warp < 7 ? 1 : warp < 9 ? 18 - 2 * warp : 16;
#pragma unroll
        for (int i = 0; i < 3; i++) mbar_init(first + 8 * i, count);
        asm volatile("fence.mbarrier_init.release.cluster;" ::: "memory");
    }
    __syncwarp();
    asm volatile("barrier.cluster.arrive.relaxed.aligned;" ::: "memory");
    const uint32_t pv = pr < 4 ? pr * 8 + 36 : pr - 4 + (max((int)pr - 33, 0) * 37 >> 8);
    const uint32_t gp = (pv + 4) & 7, hp = pv >> 3;
    const uint32_t tb = gp * 2 + rank, c = hp * 16 + tb;
    const bool has_g1 = gp > 0;
    const uint32_t nt1 = hp & 3, ft = max((int)gp - 1, 0) * 2 + (hp >> 2);
    const uint32_t nt2 = (hp & 1) * 2 + rank, mt = (gp & 3) * 4 + (hp >> 1), ks = gp >> 2;
    asm volatile("barrier.cluster.wait.aligned;" ::: "memory");

    if (warp == 8) {
        uint32_t kw = (gp & 1) * 192, kx;
        if (elect()) {
            mbar_expect(bars + B_QFULL, WSLOT);
            tma3d(sbase + xslot(0) * 8192, &P.tmX, bars + B_FULL, 0, tb * 64, 0);
            tma3d_pair(sbase + wslot(0) * 8192 + rank * 12288, &P.tmWqkv, bars + B_QFULL, (hp * 56) & ~15, rank * 32, 0);
            TS(1, 23);
            asm volatile("prefetch.tensormap [%0];\nprefetch.tensormap [%1];\nprefetch.tensormap [%2];" ::"l"(&P.tmW1), "l"(&P.tmW2), "l"(&P.tmOut) : "memory");
            uint32_t due = (uint32_t)clock() + PACE, ep = ld_relaxed(&G->epoch[c]);
            uint32_t spins = sbase == (rank << 24 | SMEM0) ? 0 : SPIN_LIMIT;
#pragma unroll 1
            for (int i = 1; i < 8; i++) {
                kx = kw; kw += 64;
                if (i >= 5) mbar_wait_bounded(bars + B_QEMPTY + 8 * (i - 5), 0, spins);
                else { while ((int)((uint32_t)clock() - due) < 0) {} due += PACE; }
                if (kw == D_) kw = 64;
                if (i < 4) kx = kw;
                const int ix = i - (i > 4);
                if (i < 7) mbar_expect(bars + B_QFULL + 8 * i, WSLOT);
                if (i != 4) tma3d(sbase + xslot(ix) * 8192, &P.tmX, bars + B_FULL + 8 * ix, kx, tb * 64, 0);
                if (i & (i >> 2)) mbar_wait_bounded(bars + B_CS - 20 + 4 * i, 0, spins);
                if (i < 7) tma3d_pair(sbase + wslot(i) * 8192 + rank * 12288, &P.tmWqkv, bars + B_QFULL + 8 * i, (hp * 56) & ~15, kw + rank * 32, 0);
            }
            ep++;
            Slot r{sbase, bars, 0};
            if (has_g1) {
                const uint8_t* src = G->H[nt1][rank * 16];
                const int row = rank * 1024;
                mbar_expect(bars + B_FULL, 16384 + TILEB);
                tma3d(sbase, &P.tmW1, bars + B_FULL, 0, row, ft * 2);
                wait_flag(G->flag[2 + rank * 2], 20 * ep, spins);
                TS(1, 16);
#pragma unroll 1
                for (int j = 64;; j += 64) {
                    bulk_load(r.dst + 16384, src, TILEB, r.bar + B_FULL);
                    src += TILEB;
                    r.next(bars);
                    if (j == 1024) break;
                    mbar_wait_bounded(r.bar + B_EMPTY, r.ph, spins);
                    if (j < 14 * 64) TS(2, 146 + j / 64);
                    mbar_expect(r.bar + B_FULL, 16384 + TILEB);
                    tma3d(r.dst, &P.tmW1, r.bar + B_FULL, 0, row + j, ft * 2);
                }
                mbar_arrive(bars + B_FULL + 48); mbar_arrive_n<16>(bars + B_EMPTY + 48);
#pragma unroll
                for (int i = 0; i < 4; i++) mbar_expect(bars + B_X + 8 * i, (i & 1) ? 3072 : 4096);
            } else {
                due = (uint32_t)clock();
                const __nv_bfloat16* at = w1 + (rank * 1024 + PF0 * 64 + hp * 8) * F_;
#pragma unroll 1
                for (int j = PF0; j < PF1 + 16 - PF2; j++) {
                    while ((int)((uint32_t)clock() - due) < 0) {}
                    prefetch_l2<16 * F_>(at);
                    due += j == PF1 - 1 ? PF + PFD : PF;
                    at += j == PF1 - 1 ? (PF2 - PF1 + 1) * 64 * F_ : 64 * F_;
                }
            }
            const uint8_t *so = G->O[mt][ks * 4], *sw = G->Wo[nt2][ks * 4];
            wait_flag2(G->flag[16 + mt], 8 * ep, G->flag[0], 16 * ep, spins);
            TS(4, 18);
#pragma unroll 1
            for (int j = 0; j < 4 * TILEB; j += TILEB) {
                mbar_wait_bounded(r.bar + B_EMPTY, r.ph, spins);
                mbar_expect(r.bar + B_QFULL, TILEB);
                bulk_load(r.dst, so + j, TILEB, r.bar + B_QFULL);
                bulk_load(r.dst + 16384, sw + j, (r.bar & 8) ? TILEB : 3 * SLAB, r.bar + B_FULL);
                r.next(bars);
            }
            Ring q{has_g1 ? 2u : 6u, has_g1}, p{q.slot, !has_g1};
#pragma unroll 1
            for (int j = 0; j < 14 * 128; j += 128) {
                mbar_wait_bounded(bars + B_EMPTY + 8 * q.slot, q.ph, spins);
                if (LEADW && j >= LEADW * 128 && j < LEADN * 128) { mbar_wait_bounded(bars + B_FULL + 8 * p.slot, p.ph, spins); p.next2(); }
                TS(8, 176 + j / 128);
                tma3d(sbase + q.slot * SLOT, &P.tmW2, bars + B_FULL + 8 * q.slot, 0, ks * 896 + j - (j < 896 ? 0 : 832), mt * 2);
                q.next2();
            }
            mbar_wait_bounded(bars + B_END, 0, spins);
        }
    } else if (warp > 8) {
        const uint32_t ep = ld_relaxed(&G->epoch[c]) + 1;
        const uint8_t* src = G->U[nt2][ks * 14];
        uint32_t spins = 0, bad;
        {
            uint2* cs = G->colsum[hp][0];
            if (w == 2) {
                bar_sync(6, 288);
                TS(1, 8);
                stg1((uint32_t*)(G->stat + row0) + lane, tag(__float_as_uint(lds1f(sbase + OFF_ST + lane * 4)), ~lane & 1, ep));
                if (elect()) {
                    fence_async_shared();
#pragma unroll
                    for (int i = 0; i < 4; i++) bulk_store(G->H[i][0] + row0 * (SLAB / 16), sbase + OFF_X + i * HSTG, SLAB);
                    bulk_flush();
                    TS(1, 99);
                    signal(G->flag[2 + (row0 >> 10) * 2 + ((row0 & 1023) >= 320)]);
                }
                __syncwarp();
            } else {
                const uint32_t word = rank * 16 + (w & 2) * 4 + (lane & 7), done = mapa(bars + B_CS, rank ^ (lane & 1));
                const uint32_t from = (sbase + word * 4 + (gp >> 2) * 12288 + (gp & 2) * 1024) ^ ((lane >> 3) * 288);
                auto swz = [](uint32_t a) { return a ^ ((a >> 3) & 0x70); };
                const uint32_t lin = sbase + lane * 128 + (hp & 1) * 16, f0 = swz(lin + 80) + 8192, f1 = swz(lin + 96) + 8192, to = swz(lin + 112);
                float s[6] = {};
#pragma unroll 1
                for (int i = 0; i < 7; i++) {
                    const uint32_t o = wslot(i) * 8192, a0 = from + o, a1 = a0 ^ 144;
                    mbar_wait(bars + B_QFULL + 8 * i, 0);
                    if (i < 2 && w == 1) TS(1, 140 + i);
                    if ((i ^ (w >> 1)) & 1) {
                        const uint4 v0 = lds4(f0 + o), v1 = lds4(f1 + o), v2 = lds4(f0 + o + 12288), v3 = lds4(f1 + o + 12288);
                        sts4(to + o, v0); sts4(to + o + 4096, v1); sts4(to + o + 12288, v2); sts4(to + o + 16384, v3);
                        fence_async_shared();
                        __syncwarp();
                        if (elect()) mbar_expect(bars + B_FULL + 8 * i, 16384);
                    }
                    if (i > 3 || i < (gp & 1)) continue;
                    if (w == 1) TS(1, 66);
                    uint32_t v[12];
#pragma unroll
                    for (int k = 0; k < 12; k++) v[k] = __float_as_uint(lds1f(((k & 1) ? a1 : a0) + (k & 2) * 512 + (k >> 2) * 4096));
#pragma unroll
                    for (int k = 0; k < 12; k++) { s[(k >> 2) * 2] += bf_lo(v[k]); s[(k >> 2) * 2 + 1] += bf_hi(v[k]); }
                    __syncwarp();
                    if ((i & 1) && lane < 2) mbar_arrive_remote(done + (i & 2) * 4);
                    if (i < 3) continue;
#pragma unroll
                    for (int k = 0; k < 6; k++) { s[k] += __shfl_xor_sync(~0u, s[k], 8); s[k] += __shfl_xor_sync(~0u, s[k], 16); }
                    const float s0 = lane < 8 ? s[0] : lane < 16 ? s[2] : s[4], s1 = lane < 8 ? s[1] : lane < 16 ? s[3] : s[5];
                    if (lane < 24) cs[gp * 96 + (lane >> 3) * 32 + word] = make_uint2(tag(__float_as_uint(s0), 1, ep), __float_as_uint(s1));
                    if (w == 1) TS(1, 24);
                }
            }
            bar_sync(1, 96);
            if (w == 1) TS(1, 98);
            const int i0 = threadIdx.x - 288, j0 = i0 - (hp & 1) * 4;
            cs += i0 + ((j0 & 92) == 28 ? (j0 & 32 ? 28 : 56) : 0);
            uint2 u[8];
            uint4 sv;
            do {
                sv = ld_relaxed4(G->stat + tb * 128 + (i0 & 63) * 2);
                bad = sv.x ^ ep;
#pragma unroll
                for (int i = 0; i < 8; i++) { u[i] = ld_relaxed2(cs + i * 96); bad = or_diff(bad, u[i].x, ep); }
                if (bad & 1) TS(1, 3);
            } while (bad & 1);
            if (w < 3) sts4(sbase + OFF_ST + i0 * 16, sv);
#pragma unroll
            for (int e = 0; e < 2; e++) {
                float f = 0.f;
#pragma unroll
                for (int i = 0; i < 8; i++) f += __uint_as_float(e ? u[i].y : u[i].x);
                const uint32_t hi = pack2(f, f);
                sts4(sbase + OFF_X + i0 * 32 + e * 16, make_uint4(hi, pack2(f - bf_hi(hi), f - bf_hi(hi)), 0, 0));
            }
            sts1(bars + 8 * NBAR, ep);
            fence_async_shared();
            __syncwarp();
            bar_arrive(8, 224); bar_arrive(9, 224);
            TS(1, 90 + w);
        }
        if (w < 3) {
            if (w == 1) {
                if (elect()) {
                    wait_flag(G->flag[3 + rank * 2], 44 * ep, spins);
                    mbar_arrive_n<16>(bars + B_EMPTY + 8 * 5);
                    TS(1, 96);
                }
                __syncwarp();
                if (!has_g1) { bar_sync(5, 288); if (elect()) signal(G->flag[0]); __syncwarp(); TS(2, 26); }
            }
            mbar_wait(bars + B_HALO, 0);
            uint32_t slot = (has_g1 ? 16 % NSLOT : 0) + w - 1, ph = ~0u;
#pragma unroll 1
            for (int i = w - 1; i < 18;) {
                const uint32_t d0 = sbase + slot * SLOT + (i < 4 ? 0 : 16384), landed = bars + B_QFULL + 8 * slot;
                mbar_wait(landed, (ph >> slot) & 1);
                ph ^= 1 << slot;
                if (i < 8) TS(4, 82 + i);
                if (i >= 4) TS(8, 156 + i);
                bad = 0;
#pragma unroll
                for (int k = 0; k < 14; k++) bad = or_diff(bad, __float_as_uint(lds1f(d0 + k * 1024 + lane * 32 + (lane >> 2) * 4)), ep);
                if (__any_sync(~0u, bad & 1)) {
                    if (elect()) {
                        const uint8_t* cur = (i < 4 ? G->O[mt][ks * 4] : src - 4 * TILEB) + i * TILEB;
                        fence_async_shared();
                        mbar_expect(landed, TILEB);
                        bulk_load(d0, cur, TILEB, landed);
                    }
                    TS(4, i < 4 ? 94 : 95);
                } else {
                    if (elect()) mbar_expect(landed + (B_FULL - B_QFULL), i < 4 ? (2 + w) * SLAB : 16384);
                    i += __byte_perm(0x03020202u, 0x00010202u, 0x7770 + slot);
                    slot = __byte_perm(0x05060302u, 0x00040100u, 0x7770 + slot);
                }
            }
        } else {
            bar_sync(3, 288);
            __nanosleep(HALO_NS);
            uint4 v[7];
            do {
                bad = 0;
#pragma unroll
                for (int i = 0; i < 7; i++) { v[i] = ld_relaxed4(G->halo[c - (tb > 0)] + i * 512 + lane * 16); bad = or_diff(bad, v[i].x, ep); }
            } while (bad & 1);
#pragma unroll
            for (int i = 0; i < 7; i++) sts4(sbase + OFF_X + i * 512 + lane * 16, v[i]);
            __syncwarp();
            if (elect()) mbar_arrive(bars + B_HALO);
            TS(2, 21);
            bar_sync(2, 160);
            if (elect()) bulk_store(out + row0 * D_, sbase + OFF_Y, TILEB);
            __syncwarp();
            bar_sync(4, 288);
            if (elect()) {
                fence_async_shared();
                bulk_store(G->O[tb][hp], sbase + OFF_X, TILEB);
                bulk_flush();
                TS(2, 7);
                mbar_arrive_remote(mapa(bars + B_FREE, rank ^ 1));
                mbar_arrive(bars + B_FREE);
                hint(G->flag[16 + tb]);
                signal(G->flag[16 + (row0 >> 7)] + 1);
                TS(2, 22);
            }
            __syncwarp();
            uint32_t late = ~0u;
            const uint32_t* hints = G->flag[8 + nt2 * 2 + ks] + (lane & 7);
            mbar_wait(bars + (has_g1 ? B_X : B_FREE), 0);
            Ring r{has_g1 ? 2u : 6u, has_g1};
#pragma unroll 1
            for (int i = 0; i < 14; i++) {
                while ((late >> i) & 1) late = __ballot_sync(~0u, ld_relaxed(hints) != 2 * ep) & 127;
                if (i == 0) TS(4, 17);
                mbar_wait(bars + B_EMPTY + 8 * r.slot, r.ph);
                TS(8, 192 + i);
                if (elect()) {
                    mbar_expect(bars + B_QFULL + 8 * r.slot, TILEB);
                    bulk_load(sbase + r.slot * SLOT + 16384, src, TILEB, bars + B_QFULL + 8 * r.slot);
                }
                src += TILEB; r.next2();
            }
            if (elect()) {
                wait_flag(G->flag[16 + mt] + 1, 8 * ep, spins);
                mbar_arrive(bars + B_ROW);
                TS(2, 27);
                G->epoch[c] = ep;
            }
        }
    } else {
        const int wg = warp >> 2;
        Mma M{bars, mapa(bars, rank ^ (lane & 1)), (threadIdx.x & 127) < 2, wg, wg, w, Ring{0, 1}, 0};
        const int r = lane >> 2, t = lane & 3;
        uint32_t ep;
        const uint32_t kv = sbase + OFF_X + (w * 2 + wg) * KV + lane * 16;
        uint32_t q[8][2], k0[7], k1[14], v0[7];
        float f0, f1;
        {
            const int half = (lane >> 3) & 1, r16 = warp * 2 + (half ^ (lane >> 4)), nt = (lane >> 1) & 3;
            const uint32_t row = sbase + OFF_Y + r16 * (2 * D_), part = row + nt * 224 + half * 112 + (lane & 1) * 8;
            const uint32_t hb = sbase + OFF_X + nt * HSTG + r16 * 16 + (half ^ (row0 >> 10)) * (7 * 256) + (lane & 1) * 8;
            mbar_wait(bars + B_ROW, 0);
            TS0(1, 67);
            const float x0 = bf_lo(__float_as_uint(lds1f(row)));
            float d[28], m1 = 0.f, n1 = 0.f, m2 = 0.f, n2 = 0.f;
#pragma unroll
            for (int i = 0; i < 7; i++) {
                const uint2 v = lds2(part + i * 16);
#pragma unroll
                for (int k = 0; k < 2; k++) {
                    const float d0 = d[4 * i + 2 * k] = bf_lo(k ? v.y : v.x) - x0, d1 = d[4 * i + 2 * k + 1] = bf_hi(k ? v.y : v.x) - x0;
                    m1 += d0; n1 += d1; m2 = fmaf(d0, d0, m2); n2 = fmaf(d1, d1, n2);
                }
            }
            const float md = row_sum(m1 + n1) * (1.f / D_), var = fmaf(-md, md, row_sum(m2 + n2) * (1.f / D_)), nmean = -(x0 + md);
            const float rstd = rsq(var + LN_EPS);
            const float sc = rstd * rsq(fmaf(var * rstd, 4 * rstd, 4 * LN_EPS)), nb = -md * sc;
            sts2(sbase + OFF_ST + r16 * 8, __float_as_uint(rstd), pack2(nmean, nmean - bf_hi(pack2(nmean, nmean))));
#pragma unroll
            for (int i = 0; i < 7; i++) sts2(hb + i * 256, pack2(fmaf(d[4 * i], sc, nb), fmaf(d[4 * i + 1], sc, nb)), pack2(fmaf(d[4 * i + 2], sc, nb), fmaf(d[4 * i + 3], sc, nb)));
            TS0(1, 25);
            bar_arrive(6, 288);
            float acc[84];
#pragma unroll 1
            for (int kb = 0; kb < 7; kb++) {
                const bool held = kb == (wg ? 7 - HOLD : -1);
                if (held) { wg_wait<0>(); M.release_pair(4 - HOLD); TS0(1, 138); bar_sync(7, 256); }
                mbar_wait(bars + B_FULL + 8 * kb, 0);
                if (!TSQ || !kb) TS0(1, 68 + wg * 7 + kb);
                const uint32_t dA = (xslot(kb) + wg) * 512, dB = wslot(kb) * 512 + (hp & 1);
                wg_fence();
#pragma unroll
                for (int k = 0; k < 4; k++) {
                    wgmma_n168<0, 1, HI_SW, HI_SW>(acc, dA + desc_lo(k * 32, 16), dB + desc_lo((k & 1) * 2048 + (k >> 1) * 12288, 4096), k > 0 || kb > 0);
                    if (k == 0) { wg_commit(); wg_wait<1>(); if (kb > 0 && !held) M.release_pair(kb - 3); if (TSQ && kb) TS0(1, 68 + wg * 7 + kb); }
                }
                wg_commit();
            }
            if (wg == 0 && !LATEREL) bar_arrive(7, 256);
            if (wg == 0) TS0(1, 139);
            bar_sync(8 + wg, 224);
            if (wg == 0) TS0(1, 174);
            ep = __float_as_uint(lds1f(bars + 8 * NBAR));
            const uint32_t st = sbase + OFF_ST + (w * 32 + r * 2 + wg) * 8;
            const uint2 s0 = lds2(st), s1 = lds2(st + 128);
            const uint32_t a0 = t < 2 ? s0.y : 0, a1 = t < 2 ? s1.y : 0;
            wg_fence();
            wgmma_rs_n168<desc_hi(128, 0)>(acc, a0, a1, desc_lo(OFF_X, 0) + (hp & 1) * 8);
            wg_commit();
            if (wg == 0 && LATEREL) bar_arrive(7, 256);
            if (wg == 0) TS0(1, 175);
            wg_wait<1>();
            TS0(1, 190 + wg);
            M.release_pair(4);
            wg_wait<0>();
            pin(acc);
            TS0(1, 4 + 7 * wg);
            f0 = __uint_as_float(s0.x); f1 = __uint_as_float(s1.x);
#pragma unroll
            for (int g = 13; g >= 0; g--) {
                const float* a = acc + (g < 7 ? g + 8 : g < 12 ? g + 9 : g * 8 - 89) * 4;
                (g < 7 ? k0[g] : v0[g - 7]) = pack2(a[0] * f0, a[1] * f0);
                k1[g] = pack2(a[2] * f1, a[3] * f1);
            }
#pragma unroll
            for (int i = 0; i < 3; i++) stsm4(kv + 2 * KV + i * 512, k1[4 * i], k1[4 * i + 1], k1[4 * i + 2], k1[4 * i + 3]);
            stsm2(kv + 2 * KV + 1536, k1[12], k1[13]);
            if (w == 3) {
#pragma unroll
                for (int i = 0; i < 14; i++) stg1(G->halo[c] + wg * KV + lane * 4 + i * 128, tag(k1[i], t == 0, ep));
            }
            bar_arrive(3, 288);
#pragma unroll
            for (int g = 0; g < 7; g++) { q[g][0] = pack2(acc[4 * g], acc[4 * g + 1]); q[g][1] = pack2(acc[4 * g + 2], acc[4 * g + 3]); }
#pragma unroll
            for (int j = 0; j < 2; j++) { q[7][j] = t < 2 ? 0u : q[3][j]; q[3][j] = t < 2 ? q[3][j] : 0u; }
#pragma unroll
            for (int g = 0; g < 7; g++) v0[g] = transpose8(v0[g]);
        }
        TS0(1, 9 + 11 * wg);
        float a[56];
#pragma unroll
        for (int i = 0; i < 56; i++) asm volatile("" : "=f"(a[i]));
        if (__builtin_expect(!has_g1, 0)) {
            const int g = min(lane >> 1, 13), nt = rank * 2 + wg;
            const uint4* src = (const uint4*)(wo + (hp * 56 - (hp & 1) * 8 + w * 16 + (lane & 1)) * D_ + nt * 112) + g;
            uint4 v[8];
#pragma unroll
            for (int i = 0; i < 8; i++) v[i] = __ldg(src + i * (D_ / 4));
#pragma unroll
            for (int i = 0; i < 8; i++) ((uint4*)G->Wo[nt][hp])[w * (SLAB / 16) + g * 16 + (lane & 1) + 2 * i] = v[i];
            bar_arrive(5, 288);
        }
        M.run<true>(a, has_g1 ? PAUSE : 0, 1, 16, 0, 0, 32);
        const uint32_t bias0 = ld_u16(b1 + ft * 128 + warp * 16 + r), bias1 = ld_u16(b1 + ft * 128 + warp * 16 + r + 8);
        {
            uint32_t kp[8], vv[14];
            mbar_wait(bars + B_HALO, 0);
            ldsm4(kp, kv); ldsm4(kp + 4, kv + (lane < 24 ? 512 : 0));
            const uint32_t va = kv + 896 + (lane & 8) * (2 * KV / 8 - 16) - (lane & 16) * 8;
            ldsm4t(vv, va); ldsm4t(vv + 4, va + 256); ldsm4t(vv + 8, va + 512); ldsm2t(vv + 12, va + 768);
            const bool e0 = 2 * t > r, e1 = 2 * t >= r;
            const uint32_t mk = (e0 ? 0xffffu : 0u) | (e1 ? 0xffff0000u : 0u);
            wg_wait<0>();
            pin(a);
            if (has_g1) M.release(M.prev);
            TS0(2, 144 + wg);
            bar_arrive(10 + wg, 256);
            if (wg) bar_arrive(2, 160);
            block_end();
            TS0(2, 12 + 16 * wg);
            float sv[2][4];
#pragma unroll
            for (int h = 0; h < 2; h++) {
                const int ga = h * 4, gb = h * 4 + 1, gc = h * 4 + 2, gd = h * 4 + 3;
                float s[3][4] = {};
                mma16(s[0], q[ga][0], q[ga][1], q[gb][0], q[gb][1], kp[ga], kp[gb]);
                mma16(s[1], q[ga][0], q[ga][1], q[gb][0], q[gb][1], k0[ga], k0[gb]);
                mma16(s[2], q[ga][0], q[ga][1], q[gb][0], q[gb][1], k1[ga], k1[gb]);
                mma16(s[0], q[gc][0], q[gc][1], q[gd][0], q[gd][1], kp[gc], kp[gd]);
                mma16(s[1], q[gc][0], q[gc][1], q[gd][0], q[gd][1], k0[gc], k0[3]);
                mma16(s[2], q[gc][0], q[gc][1], q[gd][0], q[gd][1], k1[gc], k1[3]);
                if ((tb | w) == 0) s[0][0] = s[0][1] = -1e30f;
                sv[h][0] = e0 ? s[0][0] : s[1][0];
                sv[h][1] = e1 ? s[0][1] : s[1][1];
                sv[h][2] = e0 ? s[1][2] : s[2][2];
                sv[h][3] = e1 ? s[1][3] : s[2][3];
            }
            uint32_t pp[2][2];
#pragma unroll
            for (int i = 0; i < 4; i++) {
                float* v = &sv[i >> 1][(i & 1) * 2];
                const float f = ((i & 1) ? f1 : f0) * QK_SCALE, m = quad_max(fmaxf(v[0], v[1])) * f;
                const float p0 = ex2(fmaf(v[0], f, -m)), p1 = ex2(fmaf(v[1], f, -m));
                const float inv = rcp(quad_sum(p0 + p1));
                pp[i >> 1][i & 1] = pack2(p0 * inv, p1 * inv);
            }
            uint32_t o[8][2];
#pragma unroll
            for (int i = 0; i < 8; i++) {
                const int h = i >> 2, g = i - h;
                float d[4] = {};
                mma16(d, pp[h][0] & mk, 0u, 0u, pp[h][1] & ~mk, vv[2 * g], vv[2 * g + 1]);
                mma8(d, pp[h][0] & ~mk, pp[h][1] & mk, v0[g]);
                o[i][0] = pack2(d[0], d[1]); o[i][1] = pack2(d[2], d[3]);
            }
            if (t >= 2) { o[3][0] = o[4][0]; o[3][1] = o[4][1]; }
            const int word = wg * 4 + t - (w & 1) * 4 - (r >> 2);
#pragma unroll
            for (int i = 0; i < 8; i++) { o[i][0] = tag(o[i][0], word == 0, ep); o[i][1] = tag(o[i][1], word == 2, ep); }
            const uint32_t dst = sbase + OFF_X + (w >> 1) * HALF + ((w & 1) * 32 + (lane & 15) * 2 + wg) * 16 + (lane >> 4) * 1024;
            bar_sync(11 - wg, 256);
            stsm4(dst, o[0][0], o[0][1], o[1][0], o[1][1]);
            stsm4(dst + 2048, o[2][0], o[2][1], o[3][0], o[3][1]);
            stsm4(dst + 4096, o[5][0], o[5][1], o[6][0], o[6][1]);
            stsm2(dst + 6144, o[7][0], o[7][1]);
            bar_arrive(4, 288);
            TS0(2, 10 + 19 * wg);
        }
        if (has_g1) {
            M.run<true>(a, 16 - PAUSE, 1, 16, LAG1, 1, 32 + PAUSE);
            mbar_wait(bars + B_FREE, 0);
            const uint32_t xb = sbase + OFF_X + wg * 8192 + (threadIdx.x & 127) * 16, xbar = bars + B_X + 16 * wg;
            const uint32_t rx = mapa(xb, rank ^ 1), rbar = mapa(xbar, rank ^ 1);
            wg_wait<0>();
            pin(a);
            M.release(M.prev);
            TS0(4, 5 + wg);
#pragma unroll
            for (int i = 0; i < 3; i++)
                st_async4(rx + i * 2048, rbar + 8 * (i >> 1), pack2(a[28 + 8 * i], a[29 + 8 * i]), pack2(a[30 + 8 * i], a[31 + 8 * i]), pack2(a[32 + 8 * i], a[33 + 8 * i]), pack2(a[34 + 8 * i], a[35 + 8 * i]));
            const uint32_t tail = 6144 - (threadIdx.x & 127) * 8;
            st_async2(rx + tail, rbar + 8, pack2(a[52], a[53]), pack2(a[54], a[55]));
            uint8_t* dst = G->U[nt1][((ft >= 7) + wg) * 7 + ft] + rank * HALF + w * 256 + lane * 4;
            uint32_t u[14];
#pragma unroll
            for (int i = 0; i < 28; i++) a[i] = fmaf(bf_lo((i & 2) ? bias1 : bias0), 0.5f, a[i]);
#pragma unroll
            for (int i = 0; i < 14; i++) {
                if (i % 8 == 0) {
                    if (i) TS0(4, 134 + wg);
                    mbar_wait(xbar + i, 0);
                    TS0(4, (i ? 136 : 1) + wg);
#pragma unroll
                    for (int k = i / 4; k < i / 4 + 2; k++) {
                        if (k < 3) { const uint4 v = lds4(xb + k * 2048); u[4 * k] = v.x; u[4 * k + 1] = v.y; u[4 * k + 2] = v.z; u[4 * k + 3] = v.w; }
                        else { const uint2 v = lds2(xb + tail); u[12] = v.x; u[13] = v.y; }
                    }
                    if (i && lane < 2) mbar_arrive(bars + B_EMPTY + 48);
                }
                if (i == HINT && threadIdx.x == 0) hint(G->flag[8 + nt1 * 2] + ft + (ft >= 7) * 25);
                stg1(dst + (i >> 1) * 1024 + (i & 1) * 128, tag(pack2(gelu2(a[2 * i] + bf_lo(u[i])), gelu2(a[2 * i + 1] + bf_hi(u[i]))), (lane & 7) == w * 2 + (i & 1), ep));
            }
            TS0(4, 30 + wg);
        } else {
            mbar_wait(bars + B_FREE, 0);
            if (lane < 2) mbar_arrive(bars + B_EMPTY + 48);
        }
        M.half = wg ^ ks;
        const uint32_t orow = mt * 128 + M.half * 64 + w * 16;
        M.run_o(a);
        if (wg == 1) TS0(4, 13);
        M.run<false>(a, 14, 0, 14 - NSLOT, NSLOT + 1, 1, 52, b2 + orow + r);
        mbar_wait(bars + B_ROW, 1);
        const uint32_t stg = sbase + (4 + (w >> 1)) * SLOT + M.half * 8192 + (w & 1) * (PITCH * 16);
        const uint32_t sa = stg + (lane & 15) * PITCH + (lane >> 4) * 16;
        wg_wait<1>();
        if (wg == 0) bar_arrive(7, 256);
        wg_wait<0>();
        pin(a);
        TS0(8, 14 + wg);
#pragma unroll
        for (int i = 0; i < 7; i++)
            stsm4(sa + i * 32, pack2(a[8 * i], a[8 * i + 1]), pack2(a[8 * i + 2], a[8 * i + 3]), pack2(a[8 * i + 4], a[8 * i + 5]), pack2(a[8 * i + 6], a[8 * i + 7]));
        if (!wg) TS0(8, 206);
        fence_async_shared();
        __syncwarp();
        if (elect()) {
            asm volatile("cp.reduce.async.bulk.tensor.3d.global.shared::cta.add.tile.bulk_group [%0, {%4, %2, %3}], [%1];\ncp.async.bulk.commit_group;" ::"l"(&P.tmOut), "r"(stg), "r"(nt2), "r"(orow), "r"(0) : "memory");
            if (w == 0) mbar_arrive(bars + B_END);
            asm volatile("cp.async.bulk.wait_group.read 0;" ::: "memory");
        }
        TS0(15, wg ? 19 : 207);
        TSDUMP();
    }
}

typedef CUresult (*EncodeFn)(CUtensorMap*, CUtensorMapDataType, cuuint32_t, void*, const cuuint64_t*, const cuuint64_t*, const cuuint32_t*, const cuuint32_t*,
                             CUtensorMapInterleave, CUtensorMapSwizzle, CUtensorMapL2promotion, CUtensorMapFloatOOBfill);

void make_map(EncodeFn enc, CUtensorMap* tm, const void* base, bool swizzle, int d0, int d1, int d2, int s1, int s2, int b0, int b1, int b2) {
    const cuuint64_t dims[3] = {(cuuint64_t)d0, (cuuint64_t)d1, (cuuint64_t)d2}, strides[2] = {(cuuint64_t)s1 * 2, (cuuint64_t)s2 * 2};
    const cuuint32_t box[3] = {(cuuint32_t)b0, (cuuint32_t)b1, (cuuint32_t)b2}, es[3] = {1, 1, 1};
    enc(tm, CU_TENSOR_MAP_DATA_TYPE_BFLOAT16, d2 ? 3 : 2, (void*)base, dims, strides, box, es, CU_TENSOR_MAP_INTERLEAVE_NONE,
        swizzle ? CU_TENSOR_MAP_SWIZZLE_128B : CU_TENSOR_MAP_SWIZZLE_NONE, CU_TENSOR_MAP_L2_PROMOTION_L2_128B, CU_TENSOR_MAP_FLOAT_OOB_FILL_NONE);
}

}

extern "C" void kernel_launch(void* const* d_in, const int* in_sizes, int n_in, void* d_out, int out_size) {
    static EncodeFn enc = nullptr;
    static Scratch* scratch = nullptr;
    if (!enc) {
        void* fn = nullptr;
        cudaDriverEntryPointQueryResult qr;
        cudaGetDriverEntryPoint("cuTensorMapEncodeTiled", &fn, cudaEnableDefault, &qr);
        enc = (EncodeFn)fn;
        cudaGetSymbolAddress((void**)&scratch, g_s);
        cudaFuncSetAttribute(fused_kernel, cudaFuncAttributeMaxDynamicSharedMemorySize, SMEM_BYTES);
    }
    Params P;
    const __nv_bfloat16* x = (const __nv_bfloat16*)d_in[0];
    make_map(enc, &P.tmX, x, true, D_, S_ / 2, 2, 2 * D_, D_, 64, 64, 2);
    make_map(enc, &P.tmWqkv, d_in[1], true, D_, D_, 3, 3 * D_, D_, 64, 32, 3);
    make_map(enc, &P.tmW1, d_in[4], true, 64, S_, F_ / 64, F_, 64, 64, 64, 2);
    make_map(enc, &P.tmW2, d_in[6], true, 64, F_, S_ / 64, S_, 64, 64, 64, 2);
    make_map(enc, &P.tmOut, d_out, false, 112, 4, S_, 112, D_, PITCH / 2, 1, 16);
    fused_kernel<<<NCTA, NTHREADS, SMEM_BYTES, cudaStreamPerThread>>>(x, (const __nv_bfloat16*)d_in[5], (const __nv_bfloat16*)d_in[7], (const __nv_bfloat16*)d_in[2], (__nv_bfloat16*)d_out, scratch,
                                                                      (const __nv_bfloat16*)d_in[4], P);
}
```

```cpp
#include <cuda_runtime.h>
#include <cuda_bf16.h>
#include <cuda.h>
#include <stdint.h>

#define HALO_NS 300
#define HINT 5
#define HOLD 1
#define LATEREL 1
#define PF 400
#define PF0 2
#define PF1 8
#define LEADW 4
#define LEADN 7
#define TSQ 0
#define PF2 14
#define PFD 1500
#define PACE 580
#define PAUSE 8
#define LAG1 4

namespace {

constexpr int S_ = 2048, D_ = 448, F_ = 1792;
constexpr int NCTA = 128, NTHREADS = 384;
constexpr int NSLOT = 6, SLOT = 32768, WSLOT = 24576, TILEB = 14336, SLAB = 3584, HALF = 7168;
constexpr int KV = 1792, HSTG = SLAB + 32, PITCH = 240;
constexpr int OFF_X = NSLOT * SLOT;
constexpr int OFF_Y = OFF_X + 10 * KV;
constexpr int OFF_ST = OFF_Y + TILEB;
constexpr int OFF_BAR = OFF_ST + 1024;
constexpr int SMEM_BYTES = OFF_BAR + 1280;
constexpr uint32_t SMEM0 = 1024;
constexpr int B_QFULL = 0, B_FULL = 56, B_HALO = 128, B_X = 136, B_CS = 168, B_FREE = 192, B_END = 200, B_QEMPTY = 216, B_EMPTY = 232, B_ROW = 288, NBAR = 37;
constexpr float LN_EPS = 1e-5f, QK_SCALE = 0.1889822365046136f * 1.4426950408889634f;
constexpr int SPIN_LIMIT = 1 << 22;

struct Scratch {
    uint8_t H[4][32][TILEB];
    uint8_t U[4][28][TILEB];
    uint8_t O[16][8][TILEB];
    uint8_t Wo[4][8][TILEB];
    uint8_t halo[NCTA][2 * KV];
    uint2 stat[S_];
    uint2 colsum[8][8][96];
    uint32_t flag[32][32];
    uint32_t epoch[NCTA];
};
__device__ __align__(1024) Scratch g_s;

#define TS(g, i)
#define TS0(g, i)
#define TSDUMP()

struct Params {
    CUtensorMap tmX, tmWqkv, tmW1, tmW2, tmOut;
};

__device__ __forceinline__ bool elect() {
    uint32_t p;
    asm volatile("{\n.reg .pred p;\nelect.sync _|p, 0xffffffff;\nselp.u32 %0, 1, 0, p;\n}" : "=r"(p));
    return p;
}
__device__ __forceinline__ void mbar_init(uint32_t b, uint32_t c) { asm volatile("mbarrier.init.shared::cta.b64 [%0], %1;" ::"r"(b), "r"(c) : "memory"); }
__device__ __forceinline__ void mbar_expect(uint32_t b, uint32_t tx) { asm volatile("mbarrier.arrive.expect_tx.shared::cta.b64 _, [%0], %1;" ::"r"(b), "r"(tx) : "memory"); }
__device__ __forceinline__ void mbar_arrive(uint32_t b) { asm volatile("mbarrier.arrive.shared::cta.b64 _, [%0];" ::"r"(b) : "memory"); }
template <int N> __device__ __forceinline__ void mbar_arrive_n(uint32_t b) { asm volatile("mbarrier.arrive.shared::cta.b64 _, [%0], %1;" ::"r"(b), "n"(N) : "memory"); }
__device__ __forceinline__ void mbar_arrive4_remote(uint32_t b) { asm volatile("mbarrier.arrive.shared::cluster.b64 _, [%0], 4;" ::"r"(b) : "memory"); }
__device__ __forceinline__ void mbar_arrive_remote(uint32_t b) { asm volatile("mbarrier.arrive.shared::cluster.b64 _, [%0];" ::"r"(b) : "memory"); }
#define MBAR_WAIT_ASM(SEM) \
    asm volatile("{\n.reg .pred p;\nWAIT:\nmbarrier.try_wait.parity" SEM ".shared::cta.b64 p, [%0], %1;\n@!p bra WAIT;\n}" ::"r"(b), "r"(parity) : "memory")
__device__ __forceinline__ void mbar_wait(uint32_t b, uint32_t parity) { MBAR_WAIT_ASM(""); }
__device__ __forceinline__ void mbar_wait_bounded(uint32_t b, uint32_t parity, uint32_t& n) {
    asm volatile("{\n.reg .pred p;\nWAIT:\nadd.u32 %0, %0, 1;\nsetp.gt.u32 p, %0, %3;\n@p st.global.u32 [%4], %0;\n"
                 "mbarrier.try_wait.parity.shared::cta.b64 p, [%1], %2;\n@!p bra WAIT;\n}" : "+r"(n) : "r"(b), "r"(parity), "n"(SPIN_LIMIT), "l"(0ull) : "memory");
}
__device__ __forceinline__ uint32_t mapa(uint32_t a, uint32_t rank) { uint32_t r; asm("mapa.shared::cluster.u32 %0, %1, %2;" : "=r"(r) : "r"(a), "r"(rank)); return r; }
__device__ __forceinline__ void tma3d(uint32_t dst, const CUtensorMap* tm, uint32_t bar, int c0, int c1, int c2) {
    asm volatile("cp.async.bulk.tensor.3d.shared::cluster.global.mbarrier::complete_tx::bytes [%0], [%1, {%3, %4, %5}], [%2];" ::"r"(dst), "l"(tm), "r"(bar), "r"(c0), "r"(c1), "r"(c2) : "memory");
}
__device__ __forceinline__ void tma3d_pair(uint32_t dst, const CUtensorMap* tm, uint32_t bar, int c0, int c1, int c2) {
    asm volatile("cp.async.bulk.tensor.3d.shared::cluster.global.mbarrier::complete_tx::bytes.multicast::cluster [%0], [%1, {%3, %4, %5}], [%2], %6;" ::"r"(dst), "l"(tm), "r"(bar), "r"(c0), "r"(c1), "r"(c2), "h"((uint16_t)3) : "memory");
}
__device__ __forceinline__ void bulk_load(uint32_t dst, const void* src, uint32_t bytes, uint32_t bar) {
    asm volatile("cp.async.bulk.shared::cluster.global.mbarrier::complete_tx::bytes [%0], [%1], %2, [%3];" ::"r"(dst), "l"(src), "r"(bytes), "r"(bar) : "memory");
}
template <int BYTES> __device__ __forceinline__ void prefetch_l2(const void* p) { asm volatile("cp.async.bulk.prefetch.L2.global [%0], %1;" ::"l"(p), "n"(BYTES) : "memory"); }
__device__ __forceinline__ void bulk_store(void* dst, uint32_t src, uint32_t bytes) {
    asm volatile("cp.async.bulk.global.shared::cta.bulk_group [%0], [%1], %2;" ::"l"(dst), "r"(src), "r"(bytes) : "memory");
}
__device__ __forceinline__ uint32_t ld_u16(const void* p) { uint32_t v; asm volatile("ld.global.nc.u16 %0, [%1];" : "=r"(v) : "l"(p)); return v; }
__device__ __forceinline__ uint32_t ld_relaxed(const uint32_t* p) { uint32_t v; asm volatile("ld.relaxed.gpu.global.u32 %0, [%1];" : "=r"(v) : "l"(p) : "memory"); return v; }
__device__ __forceinline__ void bulk_flush() { asm volatile("cp.async.bulk.commit_group;\ncp.async.bulk.wait_group 0;" ::: "memory"); }
__device__ __forceinline__ void signal(uint32_t* flag) { asm volatile("fence.acq_rel.gpu;\nred.relaxed.gpu.global.add.u32 [%0], 1;" ::"l"(flag) : "memory"); }
__device__ __forceinline__ void hint(uint32_t* flag) { asm volatile("red.relaxed.gpu.global.add.u32 [%0], 1;" ::"l"(flag) : "memory"); }
__device__ __forceinline__ uint32_t tag(uint32_t v, uint32_t mask, uint32_t parity) { return (v & ~mask) | (parity & mask); }
__device__ __forceinline__ uint32_t or_diff(uint32_t acc, uint32_t v, uint32_t parity) { asm("lop3.b32 %0, %0, %1, %2, 0xf6;" : "+r"(acc) : "r"(v), "r"(parity)); return acc; }
__device__ __forceinline__ uint4 ld_relaxed4(const void* p) {
    uint4 v;
    asm volatile("ld.relaxed.gpu.global.v4.u32 {%0, %1, %2, %3}, [%4];" : "=r"(v.x), "=r"(v.y), "=r"(v.z), "=r"(v.w) : "l"(p) : "memory");
    return v;
}
__device__ __forceinline__ uint2 ld_relaxed2(const void* p) { uint2 v; asm volatile("ld.relaxed.gpu.global.v2.u32 {%0, %1}, [%2];" : "=r"(v.x), "=r"(v.y) : "l"(p) : "memory"); return v; }
__device__ __forceinline__ void sts4(uint32_t a, uint4 v) { asm volatile("st.shared.v4.b32 [%0], {%1, %2, %3, %4};" ::"r"(a), "r"(v.x), "r"(v.y), "r"(v.z), "r"(v.w) : "memory"); }
__device__ __forceinline__ void sts1(uint32_t a, uint32_t v) { asm volatile("st.shared.b32 [%0], %1;" ::"r"(a), "r"(v) : "memory"); }
__device__ __forceinline__ void sts2(uint32_t a, uint32_t v0, uint32_t v1) { asm volatile("st.shared.v2.b32 [%0], {%1, %2};" ::"r"(a), "r"(v0), "r"(v1) : "memory"); }
__device__ __forceinline__ void stg1(void* p, uint32_t v) { asm volatile("st.global.b32 [%0], %1;" ::"l"(p), "r"(v) : "memory"); }
__device__ __forceinline__ void fence_async_shared() { asm volatile("fence.proxy.async.shared::cta;" ::: "memory"); }
#define BOUND "add.u32 %0, %0, 16;\nsetp.gt.u32 p, %0, %1;\n@p st.global.u32 [%2], %0;\n"
__device__ __forceinline__ void wait_flag(const uint32_t* p, uint32_t target, uint32_t& n) {
    asm volatile("{\n.reg .pred p;\n.reg .u32 v;\nPOLL:\n" BOUND "ld.acquire.gpu.global.u32 v, [%3];\nsetp.ne.u32 p, v, %4;\n@p bra POLL;\nfence.proxy.async.global;\n}"
                 : "+r"(n) : "n"(SPIN_LIMIT), "l"(0ull), "l"(p), "r"(target) : "memory");
}
__device__ __forceinline__ void wait_flag2(const uint32_t* h, uint32_t th, const uint32_t* p, uint32_t target, uint32_t& n) {
    asm volatile("{\n.reg .pred p;\n.reg .u32 u, v;\nPOLL:\n" BOUND "ld.relaxed.gpu.global.u32 u, [%3];\nld.acquire.gpu.global.u32 v, [%5];\nsetp.ne.u32 p, u, %4;\nsetp.ne.or.u32 p, v, %6, p;\n@p bra POLL;\nfence.proxy.async.global;\n}"
                 : "+r"(n) : "n"(SPIN_LIMIT), "l"(0ull), "l"(h), "r"(th), "l"(p), "r"(target) : "memory");
}
__device__ __forceinline__ void block_end() { asm volatile("{\n.reg .pred p;\n.reg .u32 t;\nAGAIN:\nmov.u32 t, %%clock;\nsetp.eq.u32 p, t, %0;\n@p bra AGAIN;\n}" ::"n"(0) : "memory"); }
__device__ __forceinline__ void bar_sync(int id, int n) { asm volatile("bar.sync %0, %1;" ::"r"(id), "r"(n) : "memory"); }
__device__ __forceinline__ void bar_arrive(int id, int n) { asm volatile("bar.arrive %0, %1;" ::"r"(id), "r"(n) : "memory"); }
__device__ __forceinline__ void wg_fence() { asm volatile("wgmma.fence.sync.aligned;" ::: "memory"); }
__device__ __forceinline__ void wg_commit() { asm volatile("wgmma.commit_group.sync.aligned;" ::: "memory"); }
template <int N> __device__ __forceinline__ void wg_wait() { asm volatile("wgmma.wait_group.sync.aligned %0;" ::"n"(N) : "memory"); }
template <int N> __device__ __forceinline__ void pin(float (&d)[N]) {
#pragma unroll
    for (int i = 0; i < N; i++) asm volatile("" : "+f"(d[i])::"memory");
}
__host__ __device__ constexpr uint32_t desc_hi(uint32_t sbo, uint32_t swz) { return (sbo >> 4) | (swz << 30); }
__host__ __device__ constexpr uint32_t desc_lo(uint32_t off, uint32_t lbo) { return ((SMEM0 + off) >> 4) | ((lbo >> 4) << 16); }
__device__ __forceinline__ uint32_t pack2(float lo, float hi) { uint32_t r; asm("cvt.rn.bf16x2.f32 %0, %1, %2;" : "=r"(r) : "f"(hi), "f"(lo)); return r; }
__device__ __forceinline__ float bf_lo(uint32_t v) { return __uint_as_float(v << 16); }
__device__ __forceinline__ float bf_hi(uint32_t v) { return __uint_as_float(v & 0xffff0000u); }
__device__ __forceinline__ void stsm4(uint32_t a, uint32_t r0, uint32_t r1, uint32_t r2, uint32_t r3) {
    asm volatile("stmatrix.sync.aligned.m8n8.x4.shared.b16 [%0], {%1, %2, %3, %4};" ::"r"(a), "r"(r0), "r"(r1), "r"(r2), "r"(r3) : "memory");
}
__device__ __forceinline__ void stsm2(uint32_t a, uint32_t r0, uint32_t r1) {
    asm volatile("stmatrix.sync.aligned.m8n8.x2.shared.b16 [%0], {%1, %2};" ::"r"(a), "r"(r0), "r"(r1) : "memory");
}
__device__ __forceinline__ uint4 lds4(uint32_t a) { uint4 v; asm volatile("ld.shared.v4.b32 {%0, %1, %2, %3}, [%4];" : "=r"(v.x), "=r"(v.y), "=r"(v.z), "=r"(v.w) : "r"(a) : "memory"); return v; }
__device__ __forceinline__ uint2 lds2(uint32_t a) { uint2 v; asm volatile("ld.shared.v2.b32 {%0, %1}, [%2];" : "=r"(v.x), "=r"(v.y) : "r"(a) : "memory"); return v; }
__device__ __forceinline__ float lds1f(uint32_t a) { float v; asm volatile("ld.shared.f32 %0, [%1];" : "=f"(v) : "r"(a) : "memory"); return v; }
__device__ __forceinline__ void ldsm4(uint32_t* r, uint32_t a) {
    asm volatile("ldmatrix.sync.aligned.m8n8.x4.shared.b16 {%0, %1, %2, %3}, [%4];" : "=r"(r[0]), "=r"(r[1]), "=r"(r[2]), "=r"(r[3]) : "r"(a) : "memory");
}
__device__ __forceinline__ void ldsm4t(uint32_t* r, uint32_t a) {
    asm volatile("ldmatrix.sync.aligned.m8n8.x4.trans.shared.b16 {%0, %1, %2, %3}, [%4];" : "=r"(r[0]), "=r"(r[1]), "=r"(r[2]), "=r"(r[3]) : "r"(a) : "memory");
}
__device__ __forceinline__ void ldsm2t(uint32_t* r, uint32_t a) {
    asm volatile("ldmatrix.sync.aligned.m8n8.x2.trans.shared.b16 {%0, %1}, [%2];" : "=r"(r[0]), "=r"(r[1]) : "r"(a) : "memory");
}
__device__ __forceinline__ uint32_t transpose8(uint32_t v) { uint32_t r; asm volatile("movmatrix.sync.aligned.m8n8.trans.b16 %0, %1;" : "=r"(r) : "r"(v)); return r; }
__device__ __forceinline__ void mma16(float (&c)[4], uint32_t a0, uint32_t a1, uint32_t a2, uint32_t a3, uint32_t b0, uint32_t b1) {
    asm volatile("mma.sync.aligned.m16n8k16.row.col.f32.bf16.bf16.f32 {%0, %1, %2, %3}, {%4, %5, %6, %7}, {%8, %9}, {%0, %1, %2, %3};"
                 : "+f"(c[0]), "+f"(c[1]), "+f"(c[2]), "+f"(c[3]) : "r"(a0), "r"(a1), "r"(a2), "r"(a3), "r"(b0), "r"(b1));
}
__device__ __forceinline__ void mma8(float (&c)[4], uint32_t a0, uint32_t a1, uint32_t b0) {
    asm volatile("mma.sync.aligned.m16n8k8.row.col.f32.bf16.bf16.f32 {%0, %1, %2, %3}, {%4, %5}, {%6}, {%0, %1, %2, %3};"
                 : "+f"(c[0]), "+f"(c[1]), "+f"(c[2]), "+f"(c[3]) : "r"(a0), "r"(a1), "r"(b0));
}
__device__ __forceinline__ void st_async4(uint32_t a, uint32_t bar, uint32_t v0, uint32_t v1, uint32_t v2, uint32_t v3) {
    asm volatile("st.async.weak.shared::cluster.mbarrier::complete_tx::bytes.v4.b32 [%0], {%2, %3, %4, %5}, [%1];" ::"r"(a), "r"(bar), "r"(v0), "r"(v1), "r"(v2), "r"(v3) : "memory");
}
__device__ __forceinline__ void st_async2(uint32_t a, uint32_t bar, uint32_t v0, uint32_t v1) {
    asm volatile("st.async.weak.shared::cluster.mbarrier::complete_tx::bytes.v2.b32 [%0], {%2, %3}, [%1];" ::"r"(a), "r"(bar), "r"(v0), "r"(v1) : "memory");
}
__device__ __forceinline__ float quad_max(float v) { v = fmaxf(v, __shfl_xor_sync(~0u, v, 1)); return fmaxf(v, __shfl_xor_sync(~0u, v, 2)); }
__device__ __forceinline__ float quad_sum(float v) { v += __shfl_xor_sync(~0u, v, 1); return v + __shfl_xor_sync(~0u, v, 2); }
__device__ __forceinline__ float ex2(float v) { float r; asm("ex2.approx.ftz.f32 %0, %1;" : "=f"(r) : "f"(v)); return r; }
__device__ __forceinline__ float rcp(float v) { float r; asm("rcp.approx.ftz.f32 %0, %1;" : "=f"(r) : "f"(v)); return r; }
__device__ __forceinline__ float rsq(float v) { float r; asm("rsqrt.approx.ftz.f32 %0, %1;" : "=f"(r) : "f"(v)); return r; }
__device__ __forceinline__ float gelu2(float v) {
    float z = v * fmaf(v * v, 8 * 0.044715f * 0.7978845608028654f, 2 * 0.7978845608028654f), t;
    asm("tanh.approx.f32 %0, %1;" : "=f"(t) : "f"(z));
    return fmaf(v, t, v);
}
__device__ __forceinline__ float row_sum(float v) {
    v = quad_sum(v); v += __shfl_xor_sync(~0u, v, 4);
    return v + __shfl_xor_sync(~0u, v, 24);
}

template <int TA, int TB, uint32_t HA, uint32_t HB>
__device__ __forceinline__ void wgmma_n112(float (&d)[56], uint32_t da, uint32_t db, int accumulate) {
    asm volatile("{\n.reg .pred p;\n.reg .b64 a, b;\nmov.b64 a, {%56, %61};\nmov.b64 b, {%57, %62};\nsetp.ne.b32 p, %58, 0;\n"
        "wgmma.mma_async.sync.aligned.m64n112k16.f32.bf16.bf16 {"
        "%0, %1, %2, %3, %4, %5, %6, %7, %8, %9, %10, %11, %12, %13, %14, %15, "
        "%16, %17, %18, %19, %20, %21, %22, %23, %24, %25, %26, %27, %28, %29, %30, %31, "
        "%32, %33, %34, %35, %36, %37, %38, %39, %40, %41, %42, %43, %44, %45, %46, %47, "
        "%48, %49, %50, %51, %52, %53, %54, %55"
        "}, a, b, p, 1, 1, %59, %60;\n}\n"
        : "+f"(d[0]), "+f"(d[1]), "+f"(d[2]), "+f"(d[3]), "+f"(d[4]), "+f"(d[5]), "+f"(d[6]), "+f"(d[7]),
          "+f"(d[8]), "+f"(d[9]), "+f"(d[10]), "+f"(d[11]), "+f"(d[12]), "+f"(d[13]), "+f"(d[14]), "+f"(d[15]),
          "+f"(d[16]), "+f"(d[17]), "+f"(d[18]), "+f"(d[19]), "+f"(d[20]), "+f"(d[21]), "+f"(d[22]), "+f"(d[23]),
          "+f"(d[24]), "+f"(d[25]), "+f"(d[26]), "+f"(d[27]), "+f"(d[28]), "+f"(d[29]), "+f"(d[30]), "+f"(d[31]),
          "+f"(d[32]), "+f"(d[33]), "+f"(d[34]), "+f"(d[35]), "+f"(d[36]), "+f"(d[37]), "+f"(d[38]), "+f"(d[39]),
          "+f"(d[40]), "+f"(d[41]), "+f"(d[42]), "+f"(d[43]), "+f"(d[44]), "+f"(d[45]), "+f"(d[46]), "+f"(d[47]),
          "+f"(d[48]), "+f"(d[49]), "+f"(d[50]), "+f"(d[51]), "+f"(d[52]), "+f"(d[53]), "+f"(d[54]), "+f"(d[55])
        : "r"(da), "r"(db), "r"(accumulate), "n"(TA), "n"(TB), "n"(HA), "n"(HB));
}

template <int TA, int TB, uint32_t HA, uint32_t HB>
__device__ __forceinline__ void wgmma_n168(float (&d)[84], uint32_t da, uint32_t db, int accumulate) {
    asm volatile("{\n.reg .pred p;\n.reg .b64 a, b;\nmov.b64 a, {%84, %89};\nmov.b64 b, {%85, %90};\nsetp.ne.b32 p, %86, 0;\n"
        "wgmma.mma_async.sync.aligned.m64n168k16.f32.bf16.bf16 {"
        "%0, %1, %2, %3, %4, %5, %6, %7, %8, %9, %10, %11, %12, %13, %14, %15, "
        "%16, %17, %18, %19, %20, %21, %22, %23, %24, %25, %26, %27, %28, %29, %30, %31, "
        "%32, %33, %34, %35, %36, %37, %38, %39, %40, %41, %42, %43, %44, %45, %46, %47, "
        "%48, %49, %50, %51, %52, %53, %54, %55, %56, %57, %58, %59, %60, %61, %62, %63, "
        "%64, %65, %66, %67, %68, %69, %70, %71, %72, %73, %74, %75, %76, %77, %78, %79, "
        "%80, %81, %82, %83"
        "}, a, b, p, 1, 1, %87, %88;\n}\n"
        : "+f"(d[0]), "+f"(d[1]), "+f"(d[2]), "+f"(d[3]), "+f"(d[4]), "+f"(d[5]), "+f"(d[6]), "+f"(d[7]),
          "+f"(d[8]), "+f"(d[9]), "+f"(d[10]), "+f"(d[11]), "+f"(d[12]), "+f"(d[13]), "+f"(d[14]), "+f"(d[15]),
          "+f"(d[16]), "+f"(d[17]), "+f"(d[18]), "+f"(d[19]), "+f"(d[20]), "+f"(d[21]), "+f"(d[22]), "+f"(d[23]),
          "+f"(d[24]), "+f"(d[25]), "+f"(d[26]), "+f"(d[27]), "+f"(d[28]), "+f"(d[29]), "+f"(d[30]), "+f"(d[31]),
          "+f"(d[32]), "+f"(d[33]), "+f"(d[34]), "+f"(d[35]), "+f"(d[36]), "+f"(d[37]), "+f"(d[38]), "+f"(d[39]),
          "+f"(d[40]), "+f"(d[41]), "+f"(d[42]), "+f"(d[43]), "+f"(d[44]), "+f"(d[45]), "+f"(d[46]), "+f"(d[47]),
          "+f"(d[48]), "+f"(d[49]), "+f"(d[50]), "+f"(d[51]), "+f"(d[52]), "+f"(d[53]), "+f"(d[54]), "+f"(d[55]),
          "+f"(d[56]), "+f"(d[57]), "+f"(d[58]), "+f"(d[59]), "+f"(d[60]), "+f"(d[61]), "+f"(d[62]), "+f"(d[63]),
          "+f"(d[64]), "+f"(d[65]), "+f"(d[66]), "+f"(d[67]), "+f"(d[68]), "+f"(d[69]), "+f"(d[70]), "+f"(d[71]),
          "+f"(d[72]), "+f"(d[73]), "+f"(d[74]), "+f"(d[75]), "+f"(d[76]), "+f"(d[77]), "+f"(d[78]), "+f"(d[79]),
          "+f"(d[80]), "+f"(d[81]), "+f"(d[82]), "+f"(d[83])
        : "r"(da), "r"(db), "r"(accumulate), "n"(TA), "n"(TB), "n"(HA), "n"(HB));
}

template <uint32_t HB>
__device__ __forceinline__ void wgmma_rs_n168(float (&d)[84], uint32_t a0, uint32_t a1, uint32_t db) {
    asm volatile("{\n.reg .b64 b;\nmov.b64 b, {%86, %88};\n"
        "wgmma.mma_async.sync.aligned.m64n168k16.f32.bf16.bf16 {"
        "%0, %1, %2, %3, %4, %5, %6, %7, %8, %9, %10, %11, %12, %13, %14, %15, "
        "%16, %17, %18, %19, %20, %21, %22, %23, %24, %25, %26, %27, %28, %29, %30, %31, "
        "%32, %33, %34, %35, %36, %37, %38, %39, %40, %41, %42, %43, %44, %45, %46, %47, "
        "%48, %49, %50, %51, %52, %53, %54, %55, %56, %57, %58, %59, %60, %61, %62, %63, "
        "%64, %65, %66, %67, %68, %69, %70, %71, %72, %73, %74, %75, %76, %77, %78, %79, "
        "%80, %81, %82, %83"
        "}, {%84, %85, %87, %87}, b, 1, 1, 1, 0;\n}\n"
        : "+f"(d[0]), "+f"(d[1]), "+f"(d[2]), "+f"(d[3]), "+f"(d[4]), "+f"(d[5]), "+f"(d[6]), "+f"(d[7]),
          "+f"(d[8]), "+f"(d[9]), "+f"(d[10]), "+f"(d[11]), "+f"(d[12]), "+f"(d[13]), "+f"(d[14]), "+f"(d[15]),
          "+f"(d[16]), "+f"(d[17]), "+f"(d[18]), "+f"(d[19]), "+f"(d[20]), "+f"(d[21]), "+f"(d[22]), "+f"(d[23]),
          "+f"(d[24]), "+f"(d[25]), "+f"(d[26]), "+f"(d[27]), "+f"(d[28]), "+f"(d[29]), "+f"(d[30]), "+f"(d[31]),
          "+f"(d[32]), "+f"(d[33]), "+f"(d[34]), "+f"(d[35]), "+f"(d[36]), "+f"(d[37]), "+f"(d[38]), "+f"(d[39]),
          "+f"(d[40]), "+f"(d[41]), "+f"(d[42]), "+f"(d[43]), "+f"(d[44]), "+f"(d[45]), "+f"(d[46]), "+f"(d[47]),
          "+f"(d[48]), "+f"(d[49]), "+f"(d[50]), "+f"(d[51]), "+f"(d[52]), "+f"(d[53]), "+f"(d[54]), "+f"(d[55]),
          "+f"(d[56]), "+f"(d[57]), "+f"(d[58]), "+f"(d[59]), "+f"(d[60]), "+f"(d[61]), "+f"(d[62]), "+f"(d[63]),
          "+f"(d[64]), "+f"(d[65]), "+f"(d[66]), "+f"(d[67]), "+f"(d[68]), "+f"(d[69]), "+f"(d[70]), "+f"(d[71]),
          "+f"(d[72]), "+f"(d[73]), "+f"(d[74]), "+f"(d[75]), "+f"(d[76]), "+f"(d[77]), "+f"(d[78]), "+f"(d[79]),
          "+f"(d[80]), "+f"(d[81]), "+f"(d[82]), "+f"(d[83])
        : "r"(a0), "r"(a1), "r"(db), "r"(0), "n"(HB));
}

struct Ring {
    uint32_t slot, ph;
    __device__ __forceinline__ void next() { if (++slot == NSLOT) { slot = 0; ph ^= 1; } }
    __device__ __forceinline__ void next2() { ph ^= slot == 5; slot = __byte_perm(0x06030201u, 0x00040005u, 0x7770 + slot); }
};
struct Slot {
    uint32_t dst, bar, ph;
    __device__ __forceinline__ void next(uint32_t bars) {
        dst += SLOT; bar += 8;
        if (bar == bars + 8 * NSLOT) { dst -= NSLOT * SLOT; bar = bars; ph ^= 1; }
    }
};
__device__ __forceinline__ uint32_t xslot(int i) { return __byte_perm(0x04130e0cu, 0x00130e0cu, 0x7770 + i); }
__device__ __forceinline__ uint32_t wslot(int i) { return __byte_perm(0x06001510u, 0x00151009u, 0x7770 + i); }

constexpr uint32_t HI_SW = desc_hi(1024, 1);

struct Mma {
    uint32_t bars, rel;
    bool lead;
    int wg, half, w;
    Ring r;
    uint32_t prev;
    __device__ __forceinline__ void release_pair(uint32_t s) { if (lead) mbar_arrive4_remote(rel + B_EMPTY + 8 * s); }
    __device__ __forceinline__ void release(uint32_t s) { if (lead) mbar_arrive_n<4>(bars + B_EMPTY + 8 * s); }
    template <bool G1>
    __device__ __forceinline__ void run(float (&a)[56], int n, int first, int last, int lag, int accumulate, int ts, const __nv_bfloat16* bias = nullptr) {
#pragma unroll 1
        for (int i = 0; i < n; i++) {
            if (lag && i == (wg ? n - lag : -1)) {
                if (!G1) {
                    const uint32_t c0 = ld_u16(bias), c1 = ld_u16(bias + 8);
                    wg_wait<0>(); release(prev); last = first;
                    pin(a);
#pragma unroll
                    for (int k = 0; k < 56; k++) a[k] += bf_lo((k & 2) ? c1 : c0);
                    pin(a);
                }
                bar_sync(7, 256);
            }
            const bool seen = !G1 && last == first;
            const uint32_t s = seen ? n - 1 - i : r.slot;
            if (!seen) mbar_wait(bars + B_FULL + 8 * s, r.ph);
            if (G1) r.next(); else r.next2();
            if (!TSQ || !i) TS0(G1 ? 2 : 8, ts + i + wg * 68);
            const uint32_t dB = s * (SLOT >> 4), dA = dB + half * 512;
            wg_fence();
#pragma unroll
            for (int k = 0; k < 4; k++) {
                wgmma_n112<1, 1, HI_SW, desc_hi(G1 ? 256 : 1024, 0)>(a, dA + desc_lo(k * 2048, 8192), dB + desc_lo(16384 + k * (G1 ? SLAB : 256), 128), k > 0 || accumulate || i > 0);
                if (k == 1) {
                    wg_commit(); wg_wait<1>();
                    if ((uint32_t)(i - first) < (uint32_t)(last - first)) release(prev);
                    if (G1 && lag && i == (wg ? -1 : n - 1)) bar_arrive(7, 256);
                    if (TSQ && i) TS0(G1 ? 2 : 8, ts + i + wg * 68);
                }
            }
            wg_commit();
            prev = s;
        }
    }
    __device__ __forceinline__ void run_o(float (&a)[56]) {
#pragma unroll 1
        for (int i = 0; i < 2; i++) {
            const uint32_t s = r.slot, dB = s * (SLOT >> 4), dA = dB + half * (HALF >> 4);
            mbar_wait(bars + B_FULL + 8 * s, r.ph);
            TS0(8, 48 + 2 * i + wg * 68);
            wg_fence();
#pragma unroll
            for (int k = 0; k < 7; k++) {
                if (k == 3) { mbar_wait(bars + B_FULL + 8 * s + 8, r.ph); wg_fence(); }
                wgmma_n112<0, 1, desc_hi(128, 0), desc_hi(256, 0)>(a, dA + desc_lo(k * 2048 + (k > 3) * (SLOT - HALF), k == 3 ? SLOT - 6144 : 1024),
                                                                   dB + desc_lo(16384 + k * SLAB + (k > 2) * (SLOT - 3 * SLAB), 128), k > 0 || i > 0);
                if (k & 1) wg_commit();
                if (k == 1) { wg_wait<1>(); if (i) release(prev); }
                if (k == 5) { wg_wait<1>(); release(s); }
            }
            wg_commit();
            prev = s + 1;
            r.slot++; r.next2();
        }
    }
};

__global__ void __cluster_dims__(2, 1, 1) __launch_bounds__(NTHREADS, 1)
fused_kernel(const __nv_bfloat16* __restrict__ x, const __nv_bfloat16* __restrict__ b1, const __nv_bfloat16* __restrict__ b2, const __nv_bfloat16* __restrict__ wo, __nv_bfloat16* out, Scratch* G,
             const __nv_bfloat16* __restrict__ w1,
             const __grid_constant__ Params P) {
    extern __shared__ __align__(1024) uint8_t smem[];
    const uint32_t sbase = (uint32_t)__cvta_generic_to_shared(smem);
    const uint32_t bars = sbase + OFF_BAR;
    const uint32_t rank = blockIdx.x & 1, pr = blockIdx.x >> 1;
    const uint32_t row0 = blockIdx.x * 16;
    if (threadIdx.x == 32) prefetch_l2<TILEB>(x + row0 * D_);
    if (threadIdx.x == 0) {
        TS(15, 0);
        mbar_init(bars + B_ROW, 1);
        asm volatile("fence.mbarrier_init.release.cluster;" ::: "memory");
        bulk_load(sbase + OFF_Y, x + row0 * D_, TILEB, bars + B_ROW);
        mbar_expect(bars + B_ROW, TILEB);
        TS(1, 97);
    }
    const int lane = threadIdx.x & 31;
    const int warp = __shfl_sync(~0u, threadIdx.x >> 5, 0), w = warp & 3;
    if (elect()) {
        const uint32_t first = bars + warp * 24, count = warp < 7 ? 1 : warp < 9 ? 18 - 2 * warp : 16;
#pragma unroll
        for (int i = 0; i < 3; i++) mbar_init(first + 8 * i, count);
        asm volatile("fence.mbarrier_init.release.cluster;" ::: "memory");
    }
    __syncwarp();
    asm volatile("barrier.cluster.arrive.relaxed.aligned;" ::: "memory");
    const uint32_t pv = pr < 4 ? pr * 8 + 36 : pr - 4 + (max((int)pr - 33, 0) * 37 >> 8);
    const uint32_t gp = (pv + 4) & 7, hp = pv >> 3;
    const uint32_t tb = gp * 2 + rank, c = hp * 16 + tb;
    const bool has_g1 = gp > 0;
    const uint32_t nt1 = hp & 3, ft = max((int)gp - 1, 0) * 2 + (hp >> 2);
    const uint32_t nt2 = (hp & 1) * 2 + rank, mt = (gp & 3) * 4 + (hp >> 1), ks = gp >> 2;
    asm volatile("barrier.cluster.wait.aligned;" ::: "memory");

    if (warp == 8) {
        uint32_t kw = (gp & 1) * 192, kx;
        if (elect()) {
            mbar_expect(bars + B_QFULL, WSLOT);
            tma3d(sbase + xslot(0) * 8192, &P.tmX, bars + B_FULL, 0, tb * 64, 0);
            tma3d_pair(sbase + wslot(0) * 8192 + rank * 12288, &P.tmWqkv, bars + B_QFULL, (hp * 56) & ~15, rank * 32, 0);
            TS(1, 23);
            asm volatile("prefetch.tensormap [%0];\nprefetch.tensormap [%1];\nprefetch.tensormap [%2];" ::"l"(&P.tmW1), "l"(&P.tmW2), "l"(&P.tmOut) : "memory");
            uint32_t due = (uint32_t)clock() + PACE, ep = ld_relaxed(&G->epoch[c]);
            uint32_t spins = sbase == (rank << 24 | SMEM0) ? 0 : SPIN_LIMIT;
#pragma unroll 1
            for (int i = 1; i < 8; i++) {
                kx = kw; kw += 64;
                if (i >= 5) mbar_wait_bounded(bars + B_QEMPTY + 8 * (i - 5), 0, spins);
                else { while ((int)((uint32_t)clock() - due) < 0) {} due += PACE; }
                if (kw == D_) kw = 64;
                if (i < 4) kx = kw;
                const int ix = i - (i > 4);
                if (i < 7) mbar_expect(bars + B_QFULL + 8 * i, WSLOT);
                if (i != 4) tma3d(sbase + xslot(ix) * 8192, &P.tmX, bars + B_FULL + 8 * ix, kx, tb * 64, 0);
                if (i & (i >> 2)) mbar_wait_bounded(bars + B_CS - 20 + 4 * i, 0, spins);
                if (i < 7) tma3d_pair(sbase + wslot(i) * 8192 + rank * 12288, &P.tmWqkv, bars + B_QFULL + 8 * i, (hp * 56) & ~15, kw + rank * 32, 0);
            }
            ep++;
            Slot r{sbase, bars, 0};
            if (has_g1) {
                const uint8_t* src = G->H[nt1][rank * 16];
                const int row = rank * 1024;
                mbar_expect(bars + B_FULL, 16384 + TILEB);
                tma3d(sbase, &P.tmW1, bars + B_FULL, 0, row, ft * 2);
                wait_flag(G->flag[2 + rank * 2], 20 * ep, spins);
                TS(1, 16);
#pragma unroll 1
                for (int j = 64;; j += 64) {
                    bulk_load(r.dst + 16384, src, TILEB, r.bar + B_FULL);
                    src += TILEB;
                    r.next(bars);
                    if (j == 1024) break;
                    mbar_wait_bounded(r.bar + B_EMPTY, r.ph, spins);
                    if (j < 14 * 64) TS(2, 146 + j / 64);
                    mbar_expect(r.bar + B_FULL, 16384 + TILEB);
                    tma3d(r.dst, &P.tmW1, r.bar + B_FULL, 0, row + j, ft * 2);
                }
                mbar_arrive(bars + B_FULL + 48); mbar_arrive_n<16>(bars + B_EMPTY + 48);
#pragma unroll
                for (int i = 0; i < 4; i++) mbar_expect(bars + B_X + 8 * i, (i & 1) ? 3072 : 4096);
            } else {
                due = (uint32_t)clock();
                const __nv_bfloat16* at = w1 + (rank * 1024 + PF0 * 64 + hp * 8) * F_;
#pragma unroll 1
                for (int j = PF0; j < PF1 + 16 - PF2; j++) {
                    while ((int)((uint32_t)clock() - due) < 0) {}
                    prefetch_l2<16 * F_>(at);
                    due += j == PF1 - 1 ? PF + PFD : PF;
                    at += j == PF1 - 1 ? (PF2 - PF1 + 1) * 64 * F_ : 64 * F_;
                }
            }
            const uint8_t *so = G->O[mt][ks * 4], *sw = G->Wo[nt2][ks * 4];
            wait_flag2(G->flag[16 + mt], 8 * ep, G->flag[0], 16 * ep, spins);
            TS(4, 18);
#pragma unroll 1
            for (int j = 0; j < 4 * TILEB; j += TILEB) {
                mbar_wait_bounded(r.bar + B_EMPTY, r.ph, spins);
                mbar_expect(r.bar + B_QFULL, TILEB);
                bulk_load(r.dst, so + j, TILEB, r.bar + B_QFULL);
                bulk_load(r.dst + 16384, sw + j, (r.bar & 8) ? TILEB : 3 * SLAB, r.bar + B_FULL);
                r.next(bars);
            }
            Ring q{has_g1 ? 2u : 6u, has_g1}, p{q.slot, !has_g1};
#pragma unroll 1
            for (int j = 0; j < 14 * 128; j += 128) {
                mbar_wait_bounded(bars + B_EMPTY + 8 * q.slot, q.ph, spins);
                if (LEADW && j >= LEADW * 128 && j < LEADN * 128) { mbar_wait_bounded(bars + B_FULL + 8 * p.slot, p.ph, spins); p.next2(); }
                TS(8, 176 + j / 128);
                tma3d(sbase + q.slot * SLOT, &P.tmW2, bars + B_FULL + 8 * q.slot, 0, ks * 896 + j - (j < 896 ? 0 : 832), mt * 2);
                q.next2();
            }
            mbar_wait_bounded(bars + B_END, 0, spins);
        }
    } else if (warp > 8) {
        const uint32_t ep = ld_relaxed(&G->epoch[c]) + 1;
        const uint8_t* src = G->U[nt2][ks * 14];
        uint32_t spins = 0, bad;
        {
            uint2* cs = G->colsum[hp][0];
            if (w == 2) {
                bar_sync(6, 288);
                TS(1, 8);
                stg1((uint32_t*)(G->stat + row0) + lane, tag(__float_as_uint(lds1f(sbase + OFF_ST + lane * 4)), ~lane & 1, ep));
                if (elect()) {
                    fence_async_shared();
#pragma unroll
                    for (int i = 0; i < 4; i++) bulk_store(G->H[i][0] + row0 * (SLAB / 16), sbase + OFF_X + i * HSTG, SLAB);
                    bulk_flush();
                    TS(1, 99);
                    signal(G->flag[2 + (row0 >> 10) * 2 + ((row0 & 1023) >= 320)]);
                }
                __syncwarp();
            } else {
                const uint32_t word = rank * 16 + (w & 2) * 4 + (lane & 7), done = mapa(bars + B_CS, rank ^ (lane & 1));
                const uint32_t from = (sbase + word * 4 + (gp >> 2) * 12288 + (gp & 2) * 1024) ^ ((lane >> 3) * 288);
                auto swz = [](uint32_t a) { return a ^ ((a >> 3) & 0x70); };
                const uint32_t lin = sbase + lane * 128 + (hp & 1) * 16, f0 = swz(lin + 80) + 8192, f1 = swz(lin + 96) + 8192, to = swz(lin + 112);
                float s[6] = {};
#pragma unroll 1
                for (int i = 0; i < 7; i++) {
                    const uint32_t o = wslot(i) * 8192, a0 = from + o, a1 = a0 ^ 144;
                    mbar_wait(bars + B_QFULL + 8 * i, 0);
                    if (i < 2 && w == 1) TS(1, 140 + i);
                    if ((i ^ (w >> 1)) & 1) {
                        const uint4 v0 = lds4(f0 + o), v1 = lds4(f1 + o), v2 = lds4(f0 + o + 12288), v3 = lds4(f1 + o + 12288);
                        sts4(to + o, v0); sts4(to + o + 4096, v1); sts4(to + o + 12288, v2); sts4(to + o + 16384, v3);
                        fence_async_shared();
                        __syncwarp();
                        if (elect()) mbar_expect(bars + B_FULL + 8 * i, 16384);
                    }
                    if (i > 3 || i < (gp & 1)) continue;
                    if (w == 1) TS(1, 66);
                    uint32_t v[12];
#pragma unroll
                    for (int k = 0; k < 12; k++) v[k] = __float_as_uint(lds1f(((k & 1) ? a1 : a0) + (k & 2) * 512 + (k >> 2) * 4096));
#pragma unroll
                    for (int k = 0; k < 12; k++) { s[(k >> 2) * 2] += bf_lo(v[k]); s[(k >> 2) * 2 + 1] += bf_hi(v[k]); }
                    __syncwarp();
                    if ((i & 1) && lane < 2) mbar_arrive_remote(done + (i & 2) * 4);
                    if (i < 3) continue;
#pragma unroll
                    for (int k = 0; k < 6; k++) { s[k] += __shfl_xor_sync(~0u, s[k], 8); s[k] += __shfl_xor_sync(~0u, s[k], 16); }
                    const float s0 = lane < 8 ? s[0] : lane < 16 ? s[2] : s[4], s1 = lane < 8 ? s[1] : lane < 16 ? s[3] : s[5];
                    if (lane < 24) cs[gp * 96 + (lane >> 3) * 32 + word] = make_uint2(tag(__float_as_uint(s0), 1, ep), __float_as_uint(s1));
                    if (w == 1) TS(1, 24);
                }
            }
            bar_sync(1, 96);
            if (w == 1) TS(1, 98);
            const int i0 = threadIdx.x - 288, j0 = i0 - (hp & 1) * 4;
            cs += i0 + ((j0 & 92) == 28 ? (j0 & 32 ? 28 : 56) : 0);
            uint2 u[8];
            uint4 sv;
            do {
                sv = ld_relaxed4(G->stat + tb * 128 + (i0 & 63) * 2);
                bad = sv.x ^ ep;
#pragma unroll
                for (int i = 0; i < 8; i++) { u[i] = ld_relaxed2(cs + i * 96); bad = or_diff(bad, u[i].x, ep); }
                if (bad & 1) TS(1, 3);
            } while (bad & 1);
            if (w < 3) sts4(sbase + OFF_ST + i0 * 16, sv);
#pragma unroll
            for (int e = 0; e < 2; e++) {
                float f = 0.f;
#pragma unroll
                for (int i = 0; i < 8; i++) f += __uint_as_float(e ? u[i].y : u[i].x);
                const uint32_t hi = pack2(f, f);
                sts4(sbase + OFF_X + i0 * 32 + e * 16, make_uint4(hi, pack2(f - bf_hi(hi), f - bf_hi(hi)), 0, 0));
            }
            sts1(bars + 8 * NBAR, ep);
            fence_async_shared();
            __syncwarp();
            bar_arrive(8, 224); bar_arrive(9, 224);
            TS(1, 90 + w);
        }
        if (w < 3) {
            if (w == 1) {
                if (elect()) {
                    wait_flag(G->flag[3 + rank * 2], 44 * ep, spins);
                    mbar_arrive_n<16>(bars + B_EMPTY + 8 * 5);
                    TS(1, 96);
                }
                __syncwarp();
                if (!has_g1) { bar_sync(5, 288); if (elect()) signal(G->flag[0]); __syncwarp(); TS(2, 26); }
            }
            mbar_wait(bars + B_HALO, 0);
            uint32_t slot = (has_g1 ? 16 % NSLOT : 0) + w - 1, ph = ~0u;
#pragma unroll 1
            for (int i = w - 1; i < 18;) {
                const uint32_t d0 = sbase + slot * SLOT + (i < 4 ? 0 : 16384), landed = bars + B_QFULL + 8 * slot;
                mbar_wait(landed, (ph >> slot) & 1);
                ph ^= 1 << slot;
                if (i < 8) TS(4, 82 + i);
                if (i >= 4) TS(8, 156 + i);
                bad = 0;
#pragma unroll
                for (int k = 0; k < 14; k++) bad = or_diff(bad, __float_as_uint(lds1f(d0 + k * 1024 + lane * 32 + (lane >> 2) * 4)), ep);
                if (__any_sync(~0u, bad & 1)) {
                    if (elect()) {
                        const uint8_t* cur = (i < 4 ? G->O[mt][ks * 4] : src - 4 * TILEB) + i * TILEB;
                        fence_async_shared();
                        mbar_expect(landed, TILEB);
                        bulk_load(d0, cur, TILEB, landed);
                    }
                    TS(4, i < 4 ? 94 : 95);
                } else {
                    if (elect()) mbar_expect(landed + (B_FULL - B_QFULL), i < 4 ? (2 + w) * SLAB : 16384);
                    i += __byte_perm(0x03020202u, 0x00010202u, 0x7770 + slot);
                    slot = __byte_perm(0x05060302u, 0x00040100u, 0x7770 + slot);
                }
            }
        } else {
            bar_sync(3, 288);
            __nanosleep(HALO_NS);
            uint4 v[7];
            do {
                bad = 0;
#pragma unroll
                for (int i = 0; i < 7; i++) { v[i] = ld_relaxed4(G->halo[c - (tb > 0)] + i * 512 + lane * 16); bad = or_diff(bad, v[i].x, ep); }
            } while (bad & 1);
#pragma unroll
            for (int i = 0; i < 7; i++) sts4(sbase + OFF_X + i * 512 + lane * 16, v[i]);
            __syncwarp();
            if (elect()) mbar_arrive(bars + B_HALO);
            TS(2, 21);
            bar_sync(2, 160);
            if (elect()) bulk_store(out + row0 * D_, sbase + OFF_Y, TILEB);
            __syncwarp();
            bar_sync(4, 288);
            if (elect()) {
                fence_async_shared();
                bulk_store(G->O[tb][hp], sbase + OFF_X, TILEB);
                bulk_flush();
                TS(2, 7);
                mbar_arrive_remote(mapa(bars + B_FREE, rank ^ 1));
                mbar_arrive(bars + B_FREE);
                hint(G->flag[16 + tb]);
                signal(G->flag[16 + (row0 >> 7)] + 1);
                TS(2, 22);
            }
            __syncwarp();
            uint32_t late = ~0u;
            const uint32_t* hints = G->flag[8 + nt2 * 2 + ks] + (lane & 7);
            mbar_wait(bars + (has_g1 ? B_X : B_FREE), 0);
            Ring r{has_g1 ? 2u : 6u, has_g1};
#pragma unroll 1
            for (int i = 0; i < 14; i++) {
                while ((late >> i) & 1) late = __ballot_sync(~0u, ld_relaxed(hints) != 2 * ep) & 127;
                if (i == 0) TS(4, 17);
                mbar_wait(bars + B_EMPTY + 8 * r.slot, r.ph);
                TS(8, 192 + i);
                if (elect()) {
                    mbar_expect(bars + B_QFULL + 8 * r.slot, TILEB);
                    bulk_load(sbase + r.slot * SLOT + 16384, src, TILEB, bars + B_QFULL + 8 * r.slot);
                }
                src += TILEB; r.next2();
            }
            if (elect()) {
                wait_flag(G->flag[16 + mt] + 1, 8 * ep, spins);
                mbar_arrive(bars + B_ROW);
                TS(2, 27);
                G->epoch[c] = ep;
            }
        }
    } else {
        const int wg = warp >> 2;
        Mma M{bars, mapa(bars, rank ^ (lane & 1)), (threadIdx.x & 127) < 2, wg, wg, w, Ring{0, 1}, 0};
        const int r = lane >> 2, t = lane & 3;
        uint32_t ep;
        const uint32_t kv = sbase + OFF_X + (w * 2 + wg) * KV + lane * 16;
        uint32_t q[8][2], k0[7], k1[14], v0[7];
        float f0, f1;
        {
            const int half = (lane >> 3) & 1, r16 = warp * 2 + (half ^ (lane >> 4)), nt = (lane >> 1) & 3;
            const uint32_t row = sbase + OFF_Y + r16 * (2 * D_), part = row + nt * 224 + half * 112 + (lane & 1) * 8;
            const uint32_t hb = sbase + OFF_X + nt * HSTG + r16 * 16 + (half ^ (row0 >> 10)) * (7 * 256) + (lane & 1) * 8;
            mbar_wait(bars + B_ROW, 0);
            TS0(1, 67);
            const float x0 = bf_lo(__float_as_uint(lds1f(row)));
            float d[28], m1 = 0.f, n1 = 0.f, m2 = 0.f, n2 = 0.f;
#pragma unroll
            for (int i = 0; i < 7; i++) {
                const uint2 v = lds2(part + i * 16);
#pragma unroll
                for (int k = 0; k < 2; k++) {
                    const float d0 = d[4 * i + 2 * k] = bf_lo(k ? v.y : v.x) - x0, d1 = d[4 * i + 2 * k + 1] = bf_hi(k ? v.y : v.x) - x0;
                    m1 += d0; n1 += d1; m2 = fmaf(d0, d0, m2); n2 = fmaf(d1, d1, n2);
                }
            }
            const float md = row_sum(m1 + n1) * (1.f / D_), var = fmaf(-md, md, row_sum(m2 + n2) * (1.f / D_)), nmean = -(x0 + md);
            const float rstd = rsq(var + LN_EPS);
            const float sc = rstd * rsq(fmaf(var * rstd, 4 * rstd, 4 * LN_EPS)), nb = -md * sc;
            sts2(sbase + OFF_ST + r16 * 8, __float_as_uint(rstd), pack2(nmean, nmean - bf_hi(pack2(nmean, nmean))));
#pragma unroll
            for (int i = 0; i < 7; i++) sts2(hb + i * 256, pack2(fmaf(d[4 * i], sc, nb), fmaf(d[4 * i + 1], sc, nb)), pack2(fmaf(d[4 * i + 2], sc, nb), fmaf(d[4 * i + 3], sc, nb)));
            TS0(1, 25);
            bar_arrive(6, 288);
            float acc[84];
#pragma unroll 1
            for (int kb = 0; kb < 7; kb++) {
                const bool held = kb == (wg ? 7 - HOLD : -1);
                if (held) { wg_wait<0>(); M.release_pair(4 - HOLD); TS0(1, 138); bar_sync(7, 256); }
                mbar_wait(bars + B_FULL + 8 * kb, 0);
                if (!TSQ || !kb) TS0(1, 68 + wg * 7 + kb);
                const uint32_t dA = (xslot(kb) + wg) * 512, dB = wslot(kb) * 512 + (hp & 1);
                wg_fence();
#pragma unroll
                for (int k = 0; k < 4; k++) {
                    wgmma_n168<0, 1, HI_SW, HI_SW>(acc, dA + desc_lo(k * 32, 16), dB + desc_lo((k & 1) * 2048 + (k >> 1) * 12288, 4096), k > 0 || kb > 0);
                    if (k == 0) { wg_commit(); wg_wait<1>(); if (kb > 0 && !held) M.release_pair(kb - 3); if (TSQ && kb) TS0(1, 68 + wg * 7 + kb); }
                }
                wg_commit();
            }
            if (wg == 0 && !LATEREL) bar_arrive(7, 256);
            if (wg == 0) TS0(1, 139);
            bar_sync(8 + wg, 224);
            if (wg == 0) TS0(1, 174);
            ep = __float_as_uint(lds1f(bars + 8 * NBAR));
            const uint32_t st = sbase + OFF_ST + (w * 32 + r * 2 + wg) * 8;
            const uint2 s0 = lds2(st), s1 = lds2(st + 128);
            const uint32_t a0 = t < 2 ? s0.y : 0, a1 = t < 2 ? s1.y : 0;
            wg_fence();
            wgmma_rs_n168<desc_hi(128, 0)>(acc, a0, a1, desc_lo(OFF_X, 0) + (hp & 1) * 8);
            wg_commit();
            if (wg == 0 && LATEREL) bar_arrive(7, 256);
            if (wg == 0) TS0(1, 175);
            wg_wait<1>();
            TS0(1, 190 + wg);
            M.release_pair(4);
            wg_wait<0>();
            pin(acc);
            TS0(1, 4 + 7 * wg);
            f0 = __uint_as_float(s0.x); f1 = __uint_as_float(s1.x);
#pragma unroll
            for (int g = 13; g >= 0; g--) {
                const float* a = acc + (g < 7 ? g + 8 : g < 12 ? g + 9 : g * 8 - 89) * 4;
                (g < 7 ? k0[g] : v0[g - 7]) = pack2(a[0] * f0, a[1] * f0);
                k1[g] = pack2(a[2] * f1, a[3] * f1);
            }
#pragma unroll
            for (int i = 0; i < 3; i++) stsm4(kv + 2 * KV + i * 512, k1[4 * i], k1[4 * i + 1], k1[4 * i + 2], k1[4 * i + 3]);
            stsm2(kv + 2 * KV + 1536, k1[12], k1[13]);
            if (w == 3) {
#pragma unroll
                for (int i = 0; i < 14; i++) stg1(G->halo[c] + wg * KV + lane * 4 + i * 128, tag(k1[i], t == 0, ep));
            }
            bar_arrive(3, 288);
#pragma unroll
            for (int g = 0; g < 7; g++) { q[g][0] = pack2(acc[4 * g], acc[4 * g + 1]); q[g][1] = pack2(acc[4 * g + 2], acc[4 * g + 3]); }
#pragma unroll
            for (int j = 0; j < 2; j++) { q[7][j] = t < 2 ? 0u : q[3][j]; q[3][j] = t < 2 ? q[3][j] : 0u; }
#pragma unroll
            for (int g = 0; g < 7; g++) v0[g] = transpose8(v0[g]);
        }
        TS0(1, 9 + 11 * wg);
        float a[56];
#pragma unroll
        for (int i = 0; i < 56; i++) asm volatile("" : "=f"(a[i]));
        if (__builtin_expect(!has_g1, 0)) {
            const int g = min(lane >> 1, 13), nt = rank * 2 + wg;
            const uint4* src = (const uint4*)(wo + (hp * 56 - (hp & 1) * 8 + w * 16 + (lane & 1)) * D_ + nt * 112) + g;
            uint4 v[8];
#pragma unroll
            for (int i = 0; i < 8; i++) v[i] = __ldg(src + i * (D_ / 4));
#pragma unroll
            for (int i = 0; i < 8; i++) ((uint4*)G->Wo[nt][hp])[w * (SLAB / 16) + g * 16 + (lane & 1) + 2 * i] = v[i];
            bar_arrive(5, 288);
        }
        M.run<true>(a, has_g1 ? PAUSE : 0, 1, 16, 0, 0, 32);
        const uint32_t bias0 = ld_u16(b1 + ft * 128 + warp * 16 + r), bias1 = ld_u16(b1 + ft * 128 + warp * 16 + r + 8);
        {
            uint32_t kp[8], vv[14];
            mbar_wait(bars + B_HALO, 0);
            ldsm4(kp, kv); ldsm4(kp + 4, kv + (lane < 24 ? 512 : 0));
            const uint32_t va = kv + 896 + (lane & 8) * (2 * KV / 8 - 16) - (lane & 16) * 8;
            ldsm4t(vv, va); ldsm4t(vv + 4, va + 256); ldsm4t(vv + 8, va + 512); ldsm2t(vv + 12, va + 768);
            const bool e0 = 2 * t > r, e1 = 2 * t >= r;
            const uint32_t mk = (e0 ? 0xffffu : 0u) | (e1 ? 0xffff0000u : 0u);
            wg_wait<0>();
            pin(a);
            if (has_g1) M.release(M.prev);
            TS0(2, 144 + wg);
            bar_arrive(10 + wg, 256);
            if (wg) bar_arrive(2, 160);
            block_end();
            TS0(2, 12 + 16 * wg);
            float sv[2][4];
#pragma unroll
            for (int h = 0; h < 2; h++) {
                const int ga = h * 4, gb = h * 4 + 1, gc = h * 4 + 2, gd = h * 4 + 3;
                float s[3][4] = {};
                mma16(s[0], q[ga][0], q[ga][1], q[gb][0], q[gb][1], kp[ga], kp[gb]);
                mma16(s[1], q[ga][0], q[ga][1], q[gb][0], q[gb][1], k0[ga], k0[gb]);
                mma16(s[2], q[ga][0], q[ga][1], q[gb][0], q[gb][1], k1[ga], k1[gb]);
                mma16(s[0], q[gc][0], q[gc][1], q[gd][0], q[gd][1], kp[gc], kp[gd]);
                mma16(s[1], q[gc][0], q[gc][1], q[gd][0], q[gd][1], k0[gc], k0[3]);
                mma16(s[2], q[gc][0], q[gc][1], q[gd][0], q[gd][1], k1[gc], k1[3]);
                if ((tb | w) == 0) s[0][0] = s[0][1] = -1e30f;
                sv[h][0] = e0 ? s[0][0] : s[1][0];
                sv[h][1] = e1 ? s[0][1] : s[1][1];
                sv[h][2] = e0 ? s[1][2] : s[2][2];
                sv[h][3] = e1 ? s[1][3] : s[2][3];
            }
            uint32_t pp[2][2];
#pragma unroll
            for (int i = 0; i < 4; i++) {
                float* v = &sv[i >> 1][(i & 1) * 2];
                const float f = ((i & 1) ? f1 : f0) * QK_SCALE, m = quad_max(fmaxf(v[0], v[1])) * f;
                const float p0 = ex2(fmaf(v[0], f, -m)), p1 = ex2(fmaf(v[1], f, -m));
                const float inv = rcp(quad_sum(p0 + p1));
                pp[i >> 1][i & 1] = pack2(p0 * inv, p1 * inv);
            }
            uint32_t o[8][2];
#pragma unroll
            for (int i = 0; i < 8; i++) {
                const int h = i >> 2, g = i - h;
                float d[4] = {};
                mma16(d, pp[h][0] & mk, 0u, 0u, pp[h][1] & ~mk, vv[2 * g], vv[2 * g + 1]);
                mma8(d, pp[h][0] & ~mk, pp[h][1] & mk, v0[g]);
                o[i][0] = pack2(d[0], d[1]); o[i][1] = pack2(d[2], d[3]);
            }
            if (t >= 2) { o[3][0] = o[4][0]; o[3][1] = o[4][1]; }
            const int word = wg * 4 + t - (w & 1) * 4 - (r >> 2);
#pragma unroll
            for (int i = 0; i < 8; i++) { o[i][0] = tag(o[i][0], word == 0, ep); o[i][1] = tag(o[i][1], word == 2, ep); }
            const uint32_t dst = sbase + OFF_X + (w >> 1) * HALF + ((w & 1) * 32 + (lane & 15) * 2 + wg) * 16 + (lane >> 4) * 1024;
            bar_sync(11 - wg, 256);
            stsm4(dst, o[0][0], o[0][1], o[1][0], o[1][1]);
            stsm4(dst + 2048, o[2][0], o[2][1], o[3][0], o[3][1]);
            stsm4(dst + 4096, o[5][0], o[5][1], o[6][0], o[6][1]);
            stsm2(dst + 6144, o[7][0], o[7][1]);
            bar_arrive(4, 288);
            TS0(2, 10 + 19 * wg);
        }
        if (has_g1) {
            M.run<true>(a, 16 - PAUSE, 1, 16, LAG1, 1, 32 + PAUSE);
            mbar_wait(bars + B_FREE, 0);
            const uint32_t xb = sbase + OFF_X + wg * 8192 + (threadIdx.x & 127) * 16, xbar = bars + B_X + 16 * wg;
            const uint32_t rx = mapa(xb, rank ^ 1), rbar = mapa(xbar, rank ^ 1);
            wg_wait<0>();
            pin(a);
            M.release(M.prev);
            TS0(4, 5 + wg);
#pragma unroll
            for (int i = 0; i < 3; i++)
                st_async4(rx + i * 2048, rbar + 8 * (i >> 1), pack2(a[28 + 8 * i], a[29 + 8 * i]), pack2(a[30 + 8 * i], a[31 + 8 * i]), pack2(a[32 + 8 * i], a[33 + 8 * i]), pack2(a[34 + 8 * i], a[35 + 8 * i]));
            const uint32_t tail = 6144 - (threadIdx.x & 127) * 8;
            st_async2(rx + tail, rbar + 8, pack2(a[52], a[53]), pack2(a[54], a[55]));
            uint8_t* dst = G->U[nt1][((ft >= 7) + wg) * 7 + ft] + rank * HALF + w * 256 + lane * 4;
            uint32_t u[14];
#pragma unroll
            for (int i = 0; i < 28; i++) a[i] = fmaf(bf_lo((i & 2) ? bias1 : bias0), 0.5f, a[i]);
#pragma unroll
            for (int i = 0; i < 14; i++) {
                if (i % 8 == 0) {
                    if (i) TS0(4, 134 + wg);
                    mbar_wait(xbar + i, 0);
                    TS0(4, (i ? 136 : 1) + wg);
#pragma unroll
                    for (int k = i / 4; k < i / 4 + 2; k++) {
                        if (k < 3) { const uint4 v = lds4(xb + k * 2048); u[4 * k] = v.x; u[4 * k + 1] = v.y; u[4 * k + 2] = v.z; u[4 * k + 3] = v.w; }
                        else { const uint2 v = lds2(xb + tail); u[12] = v.x; u[13] = v.y; }
                    }
                    if (i && lane < 2) mbar_arrive(bars + B_EMPTY + 48);
                }
                if (i == HINT && threadIdx.x == 0) hint(G->flag[8 + nt1 * 2] + ft + (ft >= 7) * 25);
                stg1(dst + (i >> 1) * 1024 + (i & 1) * 128, tag(pack2(gelu2(a[2 * i] + bf_lo(u[i])), gelu2(a[2 * i + 1] + bf_hi(u[i]))), (lane & 7) == w * 2 + (i & 1), ep));
            }
            TS0(4, 30 + wg);
        } else {
            mbar_wait(bars + B_FREE, 0);
            if (lane < 2) mbar_arrive(bars + B_EMPTY + 48);
        }
        M.half = wg ^ ks;
        const uint32_t orow = mt * 128 + M.half * 64 + w * 16;
        M.run_o(a);
        if (wg == 1) TS0(4, 13);
        M.run<false>(a, 14, 0, 14 - NSLOT, NSLOT + 1, 1, 52, b2 + orow + r);
        mbar_wait(bars + B_ROW, 1);
        const uint32_t stg = sbase + (4 + (w >> 1)) * SLOT + M.half * 8192 + (w & 1) * (PITCH * 16);
        const uint32_t sa = stg + (lane & 7) * PITCH + (lane >> 3) * 16;
        const bool one = elect();
        wg_wait<1>();
        if (wg == 0) bar_arrive(7, 256);
        wg_wait<0>();
        pin(a);
        TS0(8, 14 + wg);
#pragma unroll
        for (int h = 0; h < 2; h++) {
            const float* e = a + 2 * h;
#pragma unroll
            for (int i = 0; i < 3; i++)
                stsm4(sa + h * 8 * PITCH + i * 64, pack2(e[16 * i], e[16 * i + 1]), pack2(e[16 * i + 4], e[16 * i + 5]), pack2(e[16 * i + 8], e[16 * i + 9]), pack2(e[16 * i + 12], e[16 * i + 13]));
            stsm2(sa + h * 8 * PITCH + 192, pack2(e[48], e[49]), pack2(e[52], e[53]));
            fence_async_shared();
            __syncwarp();
            if (one) asm volatile("cp.reduce.async.bulk.tensor.3d.global.shared::cta.add.tile.bulk_group [%0, {%4, %2, %3}], [%1];" ::"l"(&P.tmOut), "r"(stg + h * 8 * PITCH), "r"(nt2), "r"(orow + 8 * h), "r"(0) : "memory");
        }
        if (one) {
            asm volatile("cp.async.bulk.commit_group;" ::: "memory");
            if (w == 0) mbar_arrive(bars + B_END);
            asm volatile("cp.async.bulk.wait_group.read 0;" ::: "memory");
        }
        TS0(15, wg ? 19 : 207);
        TSDUMP();
    }
}

typedef CUresult (*EncodeFn)(CUtensorMap*, CUtensorMapDataType, cuuint32_t, void*, const cuuint64_t*, const cuuint64_t*, const cuuint32_t*, const cuuint32_t*,
                             CUtensorMapInterleave, CUtensorMapSwizzle, CUtensorMapL2promotion, CUtensorMapFloatOOBfill);

void make_map(EncodeFn enc, CUtensorMap* tm, const void* base, bool swizzle, int d0, int d1, int d2, int s1, int s2, int b0, int b1, int b2) {
    const cuuint64_t dims[3] = {(cuuint64_t)d0, (cuuint64_t)d1, (cuuint64_t)d2}, strides[2] = {(cuuint64_t)s1 * 2, (cuuint64_t)s2 * 2};
    const cuuint32_t box[3] = {(cuuint32_t)b0, (cuuint32_t)b1, (cuuint32_t)b2}, es[3] = {1, 1, 1};
    enc(tm, CU_TENSOR_MAP_DATA_TYPE_BFLOAT16, d2 ? 3 : 2, (void*)base, dims, strides, box, es, CU_TENSOR_MAP_INTERLEAVE_NONE,
        swizzle ? CU_TENSOR_MAP_SWIZZLE_128B : CU_TENSOR_MAP_SWIZZLE_NONE, CU_TENSOR_MAP_L2_PROMOTION_L2_128B, CU_TENSOR_MAP_FLOAT_OOB_FILL_NONE);
}

}

extern "C" void kernel_launch(void* const* d_in, const int* in_sizes, int n_in, void* d_out, int out_size) {
    static EncodeFn enc = nullptr;
    static Scratch* scratch = nullptr;
    if (!enc) {
        void* fn = nullptr;
        cudaDriverEntryPointQueryResult qr;
        cudaGetDriverEntryPoint("cuTensorMapEncodeTiled", &fn, cudaEnableDefault, &qr);
        enc = (EncodeFn)fn;
        cudaGetSymbolAddress((void**)&scratch, g_s);
        cudaFuncSetAttribute(fused_kernel, cudaFuncAttributeMaxDynamicSharedMemorySize, SMEM_BYTES);
    }
    Params P;
    const __nv_bfloat16* x = (const __nv_bfloat16*)d_in[0];
    make_map(enc, &P.tmX, x, true, D_, S_ / 2, 2, 2 * D_, D_, 64, 64, 2);
    make_map(enc, &P.tmWqkv, d_in[1], true, D_, D_, 3, 3 * D_, D_, 64, 32, 3);
    make_map(enc, &P.tmW1, d_in[4], true, 64, S_, F_ / 64, F_, 64, 64, 64, 2);
    make_map(enc, &P.tmW2, d_in[6], true, 64, F_, S_ / 64, S_, 64, 64, 64, 2);
    make_map(enc, &P.tmOut, d_out, false, 112, 4, S_, 112, D_, PITCH / 2, 1, 8);
    fused_kernel<<<NCTA, NTHREADS, SMEM_BYTES, cudaStreamPerThread>>>(x, (const __nv_bfloat16*)d_in[5], (const __nv_bfloat16*)d_in[7], (const __nv_bfloat16*)d_in[2], (__nv_bfloat16*)d_out, scratch,
                                                                      (const __nv_bfloat16*)d_in[4], P);
}
```

```cpp
#include <cuda_runtime.h>
#include <cuda_bf16.h>
#include <cuda.h>
#include <stdint.h>

#define HALO_NS 300
#define HINT 5
#define HOLD 1
#define LATEREL 1
#define PF 400
#define PF0 2
#define PF1 8
#define LEADW 4
#define LEADN 7
#define TSQ 0
#define PF2 14
#define PFD 1500
#define PACE 580
#define PAUSE 8
#define LAG1 4

namespace {

constexpr int S_ = 2048, D_ = 448, F_ = 1792;
constexpr int NCTA = 128, NTHREADS = 384;
constexpr int NSLOT = 6, SLOT = 32768, WSLOT = 24576, TILEB = 14336, SLAB = 3584, HALF = 7168;
constexpr int KV = 1792, HSTG = SLAB + 32, PITCH = 240;
constexpr int OFF_X = NSLOT * SLOT;
constexpr int OFF_Y = OFF_X + 10 * KV;
constexpr int OFF_ST = OFF_Y + TILEB;
constexpr int OFF_BAR = OFF_ST + 1024;
constexpr int SMEM_BYTES = OFF_BAR + 1280;
constexpr uint32_t SMEM0 = 1024;
constexpr int B_QFULL = 0, B_FULL = 56, B_HALO = 128, B_X = 136, B_CS = 168, B_FREE = 192, B_END = 200, B_QEMPTY = 216, B_EMPTY = 232, B_ROW = 288, NBAR = 37;
constexpr float LN_EPS = 1e-5f, QK_SCALE = 0.1889822365046136f * 1.4426950408889634f;
constexpr int SPIN_LIMIT = 1 << 22;

struct Scratch {
    uint8_t H[4][32][TILEB];
    uint8_t U[4][28][TILEB];
    uint8_t O[16][8][TILEB];
    uint8_t Wo[4][8][TILEB];
    uint8_t halo[NCTA][2 * KV];
    uint2 stat[S_];
    uint2 colsum[8][8][96];
    uint32_t flag[32][32];
    uint32_t epoch[NCTA][32];
};
__device__ __align__(1024) Scratch g_s;

#define TS(g, i)
#define TS0(g, i)
#define TSDUMP()

struct Params {
    CUtensorMap tmX, tmWqkv, tmW1, tmW2, tmOut;
};

__device__ __forceinline__ bool elect() {
    uint32_t p;
    asm volatile("{\n.reg .pred p;\nelect.sync _|p, 0xffffffff;\nselp.u32 %0, 1, 0, p;\n}" : "=r"(p));
    return p;
}
__device__ __forceinline__ void mbar_init(uint32_t b, uint32_t c) { asm volatile("mbarrier.init.shared::cta.b64 [%0], %1;" ::"r"(b), "r"(c) : "memory"); }
__device__ __forceinline__ void mbar_expect(uint32_t b, uint32_t tx) { asm volatile("mbarrier.arrive.expect_tx.shared::cta.b64 _, [%0], %1;" ::"r"(b), "r"(tx) : "memory"); }
__device__ __forceinline__ void mbar_arrive(uint32_t b) { asm volatile("mbarrier.arrive.shared::cta.b64 _, [%0];" ::"r"(b) : "memory"); }
template <int N> __device__ __forceinline__ void mbar_arrive_n(uint32_t b) { asm volatile("mbarrier.arrive.shared::cta.b64 _, [%0], %1;" ::"r"(b), "n"(N) : "memory"); }
__device__ __forceinline__ void mbar_arrive4_remote(uint32_t b) { asm volatile("mbarrier.arrive.shared::cluster.b64 _, [%0], 4;" ::"r"(b) : "memory"); }
__device__ __forceinline__ void mbar_arrive_remote(uint32_t b) { asm volatile("mbarrier.arrive.shared::cluster.b64 _, [%0];" ::"r"(b) : "memory"); }
#define MBAR_WAIT_ASM(SEM) \
    asm volatile("{\n.reg .pred p;\nWAIT:\nmbarrier.try_wait.parity" SEM ".shared::cta.b64 p, [%0], %1;\n@!p bra WAIT;\n}" ::"r"(b), "r"(parity) : "memory")
__device__ __forceinline__ void mbar_wait(uint32_t b, uint32_t parity) { MBAR_WAIT_ASM(""); }
__device__ __forceinline__ void mbar_wait_bounded(uint32_t b, uint32_t parity, uint32_t& n) {
    asm volatile("{\n.reg .pred p;\nWAIT:\nadd.u32 %0, %0, 1;\nsetp.gt.u32 p, %0, %3;\n@p st.global.u32 [%4], %0;\n"
                 "mbarrier.try_wait.parity.shared::cta.b64 p, [%1], %2;\n@!p bra WAIT;\n}" : "+r"(n) : "r"(b), "r"(parity), "n"(SPIN_LIMIT), "l"(0ull) : "memory");
}
__device__ __forceinline__ uint32_t mapa(uint32_t a, uint32_t rank) { uint32_t r; asm("mapa.shared::cluster.u32 %0, %1, %2;" : "=r"(r) : "r"(a), "r"(rank)); return r; }
__device__ __forceinline__ void tma3d(uint32_t dst, const CUtensorMap* tm, uint32_t bar, int c0, int c1, int c2) {
    asm volatile("cp.async.bulk.tensor.3d.shared::cluster.global.mbarrier::complete_tx::bytes [%0], [%1, {%3, %4, %5}], [%2];" ::"r"(dst), "l"(tm), "r"(bar), "r"(c0), "r"(c1), "r"(c2) : "memory");
}
__device__ __forceinline__ void tma3d_pair(uint32_t dst, const CUtensorMap* tm, uint32_t bar, int c0, int c1, int c2) {
    asm volatile("cp.async.bulk.tensor.3d.shared::cluster.global.mbarrier::complete_tx::bytes.multicast::cluster [%0], [%1, {%3, %4, %5}], [%2], %6;" ::"r"(dst), "l"(tm), "r"(bar), "r"(c0), "r"(c1), "r"(c2), "h"((uint16_t)3) : "memory");
}
__device__ __forceinline__ void bulk_load(uint32_t dst, const void* src, uint32_t bytes, uint32_t bar) {
    asm volatile("cp.async.bulk.shared::cluster.global.mbarrier::complete_tx::bytes [%0], [%1], %2, [%3];" ::"r"(dst), "l"(src), "r"(bytes), "r"(bar) : "memory");
}
template <int BYTES> __device__ __forceinline__ void prefetch_l2(const void* p) { asm volatile("cp.async.bulk.prefetch.L2.global [%0], %1;" ::"l"(p), "n"(BYTES) : "memory"); }
__device__ __forceinline__ void bulk_store(void* dst, uint32_t src, uint32_t bytes) {
    asm volatile("cp.async.bulk.global.shared::cta.bulk_group [%0], [%1], %2;" ::"l"(dst), "r"(src), "r"(bytes) : "memory");
}
__device__ __forceinline__ uint32_t ld_u16(const void* p) { uint32_t v; asm volatile("ld.global.nc.u16 %0, [%1];" : "=r"(v) : "l"(p)); return v; }
__device__ __forceinline__ uint32_t ld_relaxed(const uint32_t* p) { uint32_t v; asm volatile("ld.relaxed.gpu.global.u32 %0, [%1];" : "=r"(v) : "l"(p) : "memory"); return v; }
__device__ __forceinline__ void bulk_flush() { asm volatile("cp.async.bulk.commit_group;\ncp.async.bulk.wait_group 0;" ::: "memory"); }
__device__ __forceinline__ void signal(uint32_t* flag) { asm volatile("fence.acq_rel.gpu;\nred.relaxed.gpu.global.add.u32 [%0], 1;" ::"l"(flag) : "memory"); }
__device__ __forceinline__ void hint(uint32_t* flag) { asm volatile("red.relaxed.gpu.global.add.u32 [%0], 1;" ::"l"(flag) : "memory"); }
__device__ __forceinline__ uint32_t tag(uint32_t v, uint32_t mask, uint32_t parity) { return (v & ~mask) | (parity & mask); }
__device__ __forceinline__ uint32_t or_diff(uint32_t acc, uint32_t v, uint32_t parity) { asm("lop3.b32 %0, %0, %1, %2, 0xf6;" : "+r"(acc) : "r"(v), "r"(parity)); return acc; }
__device__ __forceinline__ uint4 ld_relaxed4(const void* p) {
    uint4 v;
    asm volatile("ld.relaxed.gpu.global.v4.u32 {%0, %1, %2, %3}, [%4];" : "=r"(v.x), "=r"(v.y), "=r"(v.z), "=r"(v.w) : "l"(p) : "memory");
    return v;
}
__device__ __forceinline__ uint2 ld_relaxed2(const void* p) { uint2 v; asm volatile("ld.relaxed.gpu.global.v2.u32 {%0, %1}, [%2];" : "=r"(v.x), "=r"(v.y) : "l"(p) : "memory"); return v; }
__device__ __forceinline__ void sts4(uint32_t a, uint4 v) { asm volatile("st.shared.v4.b32 [%0], {%1, %2, %3, %4};" ::"r"(a), "r"(v.x), "r"(v.y), "r"(v.z), "r"(v.w) : "memory"); }
__device__ __forceinline__ void sts1(uint32_t a, uint32_t v) { asm volatile("st.shared.b32 [%0], %1;" ::"r"(a), "r"(v) : "memory"); }
__device__ __forceinline__ void sts2(uint32_t a, uint32_t v0, uint32_t v1) { asm volatile("st.shared.v2.b32 [%0], {%1, %2};" ::"r"(a), "r"(v0), "r"(v1) : "memory"); }
__device__ __forceinline__ void stg1(void* p, uint32_t v) { asm volatile("st.global.b32 [%0], %1;" ::"l"(p), "r"(v) : "memory"); }
__device__ __forceinline__ void fence_async_shared() { asm volatile("fence.proxy.async.shared::cta;" ::: "memory"); }
#define BOUND "add.u32 %0, %0, 16;\nsetp.gt.u32 p, %0, %1;\n@p st.global.u32 [%2], %0;\n"
__device__ __forceinline__ void wait_flag(const uint32_t* p, uint32_t target, uint32_t& n) {
    asm volatile("{\n.reg .pred p;\n.reg .u32 v;\nPOLL:\n" BOUND "ld.acquire.gpu.global.u32 v, [%3];\nsetp.ne.u32 p, v, %4;\n@p bra POLL;\nfence.proxy.async.global;\n}"
                 : "+r"(n) : "n"(SPIN_LIMIT), "l"(0ull), "l"(p), "r"(target) : "memory");
}
__device__ __forceinline__ void wait_flag2(const uint32_t* h, uint32_t th, const uint32_t* p, uint32_t target, uint32_t& n) {
    asm volatile("{\n.reg .pred p;\n.reg .u32 u, v;\nPOLL:\n" BOUND "ld.relaxed.gpu.global.u32 u, [%3];\nld.acquire.gpu.global.u32 v, [%5];\nsetp.ne.u32 p, u, %4;\nsetp.ne.or.u32 p, v, %6, p;\n@p bra POLL;\nfence.proxy.async.global;\n}"
                 : "+r"(n) : "n"(SPIN_LIMIT), "l"(0ull), "l"(h), "r"(th), "l"(p), "r"(target) : "memory");
}
__device__ __forceinline__ void block_end() { asm volatile("{\n.reg .pred p;\n.reg .u32 t;\nAGAIN:\nmov.u32 t, %%clock;\nsetp.eq.u32 p, t, %0;\n@p bra AGAIN;\n}" ::"n"(0) : "memory"); }
__device__ __forceinline__ void bar_sync(int id, int n) { asm volatile("bar.sync %0, %1;" ::"r"(id), "r"(n) : "memory"); }
__device__ __forceinline__ void bar_arrive(int id, int n) { asm volatile("bar.arrive %0, %1;" ::"r"(id), "r"(n) : "memory"); }
__device__ __forceinline__ void wg_fence() { asm volatile("wgmma.fence.sync.aligned;" ::: "memory"); }
__device__ __forceinline__ void wg_commit() { asm volatile("wgmma.commit_group.sync.aligned;" ::: "memory"); }
template <int N> __device__ __forceinline__ void wg_wait() { asm volatile("wgmma.wait_group.sync.aligned %0;" ::"n"(N) : "memory"); }
template <int N> __device__ __forceinline__ void pin(float (&d)[N]) {
#pragma unroll
    for (int i = 0; i < N; i++) asm volatile("" : "+f"(d[i])::"memory");
}
__host__ __device__ constexpr uint32_t desc_hi(uint32_t sbo, uint32_t swz) { return (sbo >> 4) | (swz << 30); }
__host__ __device__ constexpr uint32_t desc_lo(uint32_t off, uint32_t lbo) { return ((SMEM0 + off) >> 4) | ((lbo >> 4) << 16); }
__device__ __forceinline__ uint32_t pack2(float lo, float hi) { uint32_t r; asm("cvt.rn.bf16x2.f32 %0, %1, %2;" : "=r"(r) : "f"(hi), "f"(lo)); return r; }
__device__ __forceinline__ float bf_lo(uint32_t v) { return __uint_as_float(v << 16); }
__device__ __forceinline__ float bf_hi(uint32_t v) { return __uint_as_float(v & 0xffff0000u); }
__device__ __forceinline__ void stsm4(uint32_t a, uint32_t r0, uint32_t r1, uint32_t r2, uint32_t r3) {
    asm volatile("stmatrix.sync.aligned.m8n8.x4.shared.b16 [%0], {%1, %2, %3, %4};" ::"r"(a), "r"(r0), "r"(r1), "r"(r2), "r"(r3) : "memory");
}
__device__ __forceinline__ void stsm2(uint32_t a, uint32_t r0, uint32_t r1) {
    asm volatile("stmatrix.sync.aligned.m8n8.x2.shared.b16 [%0], {%1, %2};" ::"r"(a), "r"(r0), "r"(r1) : "memory");
}
__device__ __forceinline__ uint4 lds4(uint32_t a) { uint4 v; asm volatile("ld.shared.v4.b32 {%0, %1, %2, %3}, [%4];" : "=r"(v.x), "=r"(v.y), "=r"(v.z), "=r"(v.w) : "r"(a) : "memory"); return v; }
__device__ __forceinline__ uint2 lds2(uint32_t a) { uint2 v; asm volatile("ld.shared.v2.b32 {%0, %1}, [%2];" : "=r"(v.x), "=r"(v.y) : "r"(a) : "memory"); return v; }
__device__ __forceinline__ float lds1f(uint32_t a) { float v; asm volatile("ld.shared.f32 %0, [%1];" : "=f"(v) : "r"(a) : "memory"); return v; }
__device__ __forceinline__ void ldsm4(uint32_t* r, uint32_t a) {
    asm volatile("ldmatrix.sync.aligned.m8n8.x4.shared.b16 {%0, %1, %2, %3}, [%4];" : "=r"(r[0]), "=r"(r[1]), "=r"(r[2]), "=r"(r[3]) : "r"(a) : "memory");
}
__device__ __forceinline__ void ldsm4t(uint32_t* r, uint32_t a) {
    asm volatile("ldmatrix.sync.aligned.m8n8.x4.trans.shared.b16 {%0, %1, %2, %3}, [%4];" : "=r"(r[0]), "=r"(r[1]), "=r"(r[2]), "=r"(r[3]) : "r"(a) : "memory");
}
__device__ __forceinline__ void ldsm2t(uint32_t* r, uint32_t a) {
    asm volatile("ldmatrix.sync.aligned.m8n8.x2.trans.shared.b16 {%0, %1}, [%2];" : "=r"(r[0]), "=r"(r[1]) : "r"(a) : "memory");
}
__device__ __forceinline__ uint32_t transpose8(uint32_t v) { uint32_t r; asm volatile("movmatrix.sync.aligned.m8n8.trans.b16 %0, %1;" : "=r"(r) : "r"(v)); return r; }
__device__ __forceinline__ void mma16(float (&c)[4], uint32_t a0, uint32_t a1, uint32_t a2, uint32_t a3, uint32_t b0, uint32_t b1) {
    asm volatile("mma.sync.aligned.m16n8k16.row.col.f32.bf16.bf16.f32 {%0, %1, %2, %3}, {%4, %5, %6, %7}, {%8, %9}, {%0, %1, %2, %3};"
                 : "+f"(c[0]), "+f"(c[1]), "+f"(c[2]), "+f"(c[3]) : "r"(a0), "r"(a1), "r"(a2), "r"(a3), "r"(b0), "r"(b1));
}
__device__ __forceinline__ void mma8(float (&c)[4], uint32_t a0, uint32_t a1, uint32_t b0) {
    asm volatile("mma.sync.aligned.m16n8k8.row.col.f32.bf16.bf16.f32 {%0, %1, %2, %3}, {%4, %5}, {%6}, {%0, %1, %2, %3};"
                 : "+f"(c[0]), "+f"(c[1]), "+f"(c[2]), "+f"(c[3]) : "r"(a0), "r"(a1), "r"(b0));
}
__device__ __forceinline__ void st_async4(uint32_t a, uint32_t bar, uint32_t v0, uint32_t v1, uint32_t v2, uint32_t v3) {
    asm volatile("st.async.weak.shared::cluster.mbarrier::complete_tx::bytes.v4.b32 [%0], {%2, %3, %4, %5}, [%1];" ::"r"(a), "r"(bar), "r"(v0), "r"(v1), "r"(v2), "r"(v3) : "memory");
}
__device__ __forceinline__ void st_async2(uint32_t a, uint32_t bar, uint32_t v0, uint32_t v1) {
    asm volatile("st.async.weak.shared::cluster.mbarrier::complete_tx::bytes.v2.b32 [%0], {%2, %3}, [%1];" ::"r"(a), "r"(bar), "r"(v0), "r"(v1) : "memory");
}
__device__ __forceinline__ float quad_max(float v) { v = fmaxf(v, __shfl_xor_sync(~0u, v, 1)); return fmaxf(v, __shfl_xor_sync(~0u, v, 2)); }
__device__ __forceinline__ float quad_sum(float v) { v += __shfl_xor_sync(~0u, v, 1); return v + __shfl_xor_sync(~0u, v, 2); }
__device__ __forceinline__ float ex2(float v) { float r; asm("ex2.approx.ftz.f32 %0, %1;" : "=f"(r) : "f"(v)); return r; }
__device__ __forceinline__ float rcp(float v) { float r; asm("rcp.approx.ftz.f32 %0, %1;" : "=f"(r) : "f"(v)); return r; }
__device__ __forceinline__ float rsq(float v) { float r; asm("rsqrt.approx.ftz.f32 %0, %1;" : "=f"(r) : "f"(v)); return r; }
__device__ __forceinline__ float gelu2(float v) {
    float z = v * fmaf(v * v, 8 * 0.044715f * 0.7978845608028654f, 2 * 0.7978845608028654f), t;
    asm("tanh.approx.f32 %0, %1;" : "=f"(t) : "f"(z));
    return fmaf(v, t, v);
}
__device__ __forceinline__ float row_sum(float v) {
    v = quad_sum(v); v += __shfl_xor_sync(~0u, v, 4);
    return v + __shfl_xor_sync(~0u, v, 24);
}

template <int TA, int TB, uint32_t HA, uint32_t HB>
__device__ __forceinline__ void wgmma_n112(float (&d)[56], uint32_t da, uint32_t db, int accumulate) {
    asm volatile("{\n.reg .pred p;\n.reg .b64 a, b;\nmov.b64 a, {%56, %61};\nmov.b64 b, {%57, %62};\nsetp.ne.b32 p, %58, 0;\n"
        "wgmma.mma_async.sync.aligned.m64n112k16.f32.bf16.bf16 {"
        "%0, %1, %2, %3, %4, %5, %6, %7, %8, %9, %10, %11, %12, %13, %14, %15, "
        "%16, %17, %18, %19, %20, %21, %22, %23, %24, %25, %26, %27, %28, %29, %30, %31, "
        "%32, %33, %34, %35, %36, %37, %38, %39, %40, %41, %42, %43, %44, %45, %46, %47, "
        "%48, %49, %50, %51, %52, %53, %54, %55"
        "}, a, b, p, 1, 1, %59, %60;\n}\n"
        : "+f"(d[0]), "+f"(d[1]), "+f"(d[2]), "+f"(d[3]), "+f"(d[4]), "+f"(d[5]), "+f"(d[6]), "+f"(d[7]),
          "+f"(d[8]), "+f"(d[9]), "+f"(d[10]), "+f"(d[11]), "+f"(d[12]), "+f"(d[13]), "+f"(d[14]), "+f"(d[15]),
          "+f"(d[16]), "+f"(d[17]), "+f"(d[18]), "+f"(d[19]), "+f"(d[20]), "+f"(d[21]), "+f"(d[22]), "+f"(d[23]),
          "+f"(d[24]), "+f"(d[25]), "+f"(d[26]), "+f"(d[27]), "+f"(d[28]), "+f"(d[29]), "+f"(d[30]), "+f"(d[31]),
          "+f"(d[32]), "+f"(d[33]), "+f"(d[34]), "+f"(d[35]), "+f"(d[36]), "+f"(d[37]), "+f"(d[38]), "+f"(d[39]),
          "+f"(d[40]), "+f"(d[41]), "+f"(d[42]), "+f"(d[43]), "+f"(d[44]), "+f"(d[45]), "+f"(d[46]), "+f"(d[47]),
          "+f"(d[48]), "+f"(d[49]), "+f"(d[50]), "+f"(d[51]), "+f"(d[52]), "+f"(d[53]), "+f"(d[54]), "+f"(d[55])
        : "r"(da), "r"(db), "r"(accumulate), "n"(TA), "n"(TB), "n"(HA), "n"(HB));
}

template <int TA, int TB, uint32_t HA, uint32_t HB>
__device__ __forceinline__ void wgmma_n168(float (&d)[84], uint32_t da, uint32_t db, int accumulate) {
    asm volatile("{\n.reg .pred p;\n.reg .b64 a, b;\nmov.b64 a, {%84, %89};\nmov.b64 b, {%85, %90};\nsetp.ne.b32 p, %86, 0;\n"
        "wgmma.mma_async.sync.aligned.m64n168k16.f32.bf16.bf16 {"
        "%0, %1, %2, %3, %4, %5, %6, %7, %8, %9, %10, %11, %12, %13, %14, %15, "
        "%16, %17, %18, %19, %20, %21, %22, %23, %24, %25, %26, %27, %28, %29, %30, %31, "
        "%32, %33, %34, %35, %36, %37, %38, %39, %40, %41, %42, %43, %44, %45, %46, %47, "
        "%48, %49, %50, %51, %52, %53, %54, %55, %56, %57, %58, %59, %60, %61, %62, %63, "
        "%64, %65, %66, %67, %68, %69, %70, %71, %72, %73, %74, %75, %76, %77, %78, %79, "
        "%80, %81, %82, %83"
        "}, a, b, p, 1, 1, %87, %88;\n}\n"
        : "+f"(d[0]), "+f"(d[1]), "+f"(d[2]), "+f"(d[3]), "+f"(d[4]), "+f"(d[5]), "+f"(d[6]), "+f"(d[7]),
          "+f"(d[8]), "+f"(d[9]), "+f"(d[10]), "+f"(d[11]), "+f"(d[12]), "+f"(d[13]), "+f"(d[14]), "+f"(d[15]),
          "+f"(d[16]), "+f"(d[17]), "+f"(d[18]), "+f"(d[19]), "+f"(d[20]), "+f"(d[21]), "+f"(d[22]), "+f"(d[23]),
          "+f"(d[24]), "+f"(d[25]), "+f"(d[26]), "+f"(d[27]), "+f"(d[28]), "+f"(d[29]), "+f"(d[30]), "+f"(d[31]),
          "+f"(d[32]), "+f"(d[33]), "+f"(d[34]), "+f"(d[35]), "+f"(d[36]), "+f"(d[37]), "+f"(d[38]), "+f"(d[39]),
          "+f"(d[40]), "+f"(d[41]), "+f"(d[42]), "+f"(d[43]), "+f"(d[44]), "+f"(d[45]), "+f"(d[46]), "+f"(d[47]),
          "+f"(d[48]), "+f"(d[49]), "+f"(d[50]), "+f"(d[51]), "+f"(d[52]), "+f"(d[53]), "+f"(d[54]), "+f"(d[55]),
          "+f"(d[56]), "+f"(d[57]), "+f"(d[58]), "+f"(d[59]), "+f"(d[60]), "+f"(d[61]), "+f"(d[62]), "+f"(d[63]),
          "+f"(d[64]), "+f"(d[65]), "+f"(d[66]), "+f"(d[67]), "+f"(d[68]), "+f"(d[69]), "+f"(d[70]), "+f"(d[71]),
          "+f"(d[72]), "+f"(d[73]), "+f"(d[74]), "+f"(d[75]), "+f"(d[76]), "+f"(d[77]), "+f"(d[78]), "+f"(d[79]),
          "+f"(d[80]), "+f"(d[81]), "+f"(d[82]), "+f"(d[83])
        : "r"(da), "r"(db), "r"(accumulate), "n"(TA), "n"(TB), "n"(HA), "n"(HB));
}

template <uint32_t HB>
__device__ __forceinline__ void wgmma_rs_n168(float (&d)[84], uint32_t a0, uint32_t a1, uint32_t db) {
    asm volatile("{\n.reg .b64 b;\nmov.b64 b, {%86, %88};\n"
        "wgmma.mma_async.sync.aligned.m64n168k16.f32.bf16.bf16 {"
        "%0, %1, %2, %3, %4, %5, %6, %7, %8, %9, %10, %11, %12, %13, %14, %15, "
        "%16, %17, %18, %19, %20, %21, %22, %23, %24, %25, %26, %27, %28, %29, %30, %31, "
        "%32, %33, %34, %35, %36, %37, %38, %39, %40, %41, %42, %43, %44, %45, %46, %47, "
        "%48, %49, %50, %51, %52, %53, %54, %55, %56, %57, %58, %59, %60, %61, %62, %63, "
        "%64, %65, %66, %67, %68, %69, %70, %71, %72, %73, %74, %75, %76, %77, %78, %79, "
        "%80, %81, %82, %83"
        "}, {%84, %85, %87, %87}, b, 1, 1, 1, 0;\n}\n"
        : "+f"(d[0]), "+f"(d[1]), "+f"(d[2]), "+f"(d[3]), "+f"(d[4]), "+f"(d[5]), "+f"(d[6]), "+f"(d[7]),
          "+f"(d[8]), "+f"(d[9]), "+f"(d[10]), "+f"(d[11]), "+f"(d[12]), "+f"(d[13]), "+f"(d[14]), "+f"(d[15]),
          "+f"(d[16]), "+f"(d[17]), "+f"(d[18]), "+f"(d[19]), "+f"(d[20]), "+f"(d[21]), "+f"(d[22]), "+f"(d[23]),
          "+f"(d[24]), "+f"(d[25]), "+f"(d[26]), "+f"(d[27]), "+f"(d[28]), "+f"(d[29]), "+f"(d[30]), "+f"(d[31]),
          "+f"(d[32]), "+f"(d[33]), "+f"(d[34]), "+f"(d[35]), "+f"(d[36]), "+f"(d[37]), "+f"(d[38]), "+f"(d[39]),
          "+f"(d[40]), "+f"(d[41]), "+f"(d[42]), "+f"(d[43]), "+f"(d[44]), "+f"(d[45]), "+f"(d[46]), "+f"(d[47]),
          "+f"(d[48]), "+f"(d[49]), "+f"(d[50]), "+f"(d[51]), "+f"(d[52]), "+f"(d[53]), "+f"(d[54]), "+f"(d[55]),
          "+f"(d[56]), "+f"(d[57]), "+f"(d[58]), "+f"(d[59]), "+f"(d[60]), "+f"(d[61]), "+f"(d[62]), "+f"(d[63]),
          "+f"(d[64]), "+f"(d[65]), "+f"(d[66]), "+f"(d[67]), "+f"(d[68]), "+f"(d[69]), "+f"(d[70]), "+f"(d[71]),
          "+f"(d[72]), "+f"(d[73]), "+f"(d[74]), "+f"(d[75]), "+f"(d[76]), "+f"(d[77]), "+f"(d[78]), "+f"(d[79]),
          "+f"(d[80]), "+f"(d[81]), "+f"(d[82]), "+f"(d[83])
        : "r"(a0), "r"(a1), "r"(db), "r"(0), "n"(HB));
}

struct Ring {
    uint32_t slot, ph;
    __device__ __forceinline__ void next() { if (++slot == NSLOT) { slot = 0; ph ^= 1; } }
    __device__ __forceinline__ void next2() { ph ^= slot == 5; slot = __byte_perm(0x06030201u, 0x00040005u, 0x7770 + slot); }
};
struct Slot {
    uint32_t dst, bar, ph;
    __device__ __forceinline__ void next(uint32_t bars) {
        dst += SLOT; bar += 8;
        if (bar == bars + 8 * NSLOT) { dst -= NSLOT * SLOT; bar = bars; ph ^= 1; }
    }
};
__device__ __forceinline__ uint32_t xslot(int i) { return __byte_perm(0x04130e0cu, 0x00130e0cu, 0x7770 + i); }
__device__ __forceinline__ uint32_t wslot(int i) { return __byte_perm(0x06001510u, 0x00151009u, 0x7770 + i); }

constexpr uint32_t HI_SW = desc_hi(1024, 1);

struct Mma {
    uint32_t bars, rel;
    bool lead;
    int wg, half, w;
    Ring r;
    uint32_t prev;
    __device__ __forceinline__ void release_pair(uint32_t s) { if (lead) mbar_arrive4_remote(rel + B_EMPTY + 8 * s); }
    __device__ __forceinline__ void release(uint32_t s) { if (lead) mbar_arrive_n<4>(bars + B_EMPTY + 8 * s); }
    template <bool G1>
    __device__ __forceinline__ void run(float (&a)[56], int n, int first, int last, int lag, int accumulate, int ts, const __nv_bfloat16* bias = nullptr) {
#pragma unroll 1
        for (int i = 0; i < n; i++) {
            if (lag && i == (wg ? n - lag : -1)) {
                if (!G1) {
                    const uint32_t c0 = ld_u16(bias), c1 = ld_u16(bias + 8);
                    wg_wait<0>(); release(prev); last = first;
                    pin(a);
#pragma unroll
                    for (int k = 0; k < 56; k++) a[k] += bf_lo((k & 2) ? c1 : c0);
                    pin(a);
                }
                bar_sync(7, 256);
            }
            const bool seen = !G1 && last == first;
            const uint32_t s = seen ? n - 1 - i : r.slot;
            if (!seen) mbar_wait(bars + B_FULL + 8 * s, r.ph);
            if (G1) r.next(); else r.next2();
            if (!TSQ || !i) TS0(G1 ? 2 : 8, ts + i + wg * 68);
            const uint32_t dB = s * (SLOT >> 4), dA = dB + half * 512;
            wg_fence();
#pragma unroll
            for (int k = 0; k < 4; k++) {
                wgmma_n112<1, 1, HI_SW, desc_hi(G1 ? 256 : 1024, 0)>(a, dA + desc_lo(k * 2048, 8192), dB + desc_lo(16384 + k * (G1 ? SLAB : 256), 128), k > 0 || accumulate || i > 0);
                if (k == 1) {
                    wg_commit(); wg_wait<1>();
                    if ((uint32_t)(i - first) < (uint32_t)(last - first)) release(prev);
                    if (G1 && lag && i == (wg ? -1 : n - 1)) bar_arrive(7, 256);
                    if (TSQ && i) TS0(G1 ? 2 : 8, ts + i + wg * 68);
                }
            }
            wg_commit();
            prev = s;
        }
    }
    __device__ __forceinline__ void run_o(float (&a)[56]) {
#pragma unroll 1
        for (int i = 0; i < 2; i++) {
            const uint32_t s = r.slot, dB = s * (SLOT >> 4), dA = dB + half * (HALF >> 4);
            mbar_wait(bars + B_FULL + 8 * s, r.ph);
            TS0(8, 48 + 2 * i + wg * 68);
            wg_fence();
#pragma unroll
            for (int k = 0; k < 7; k++) {
                if (k == 3) { mbar_wait(bars + B_FULL + 8 * s + 8, r.ph); wg_fence(); }
                wgmma_n112<0, 1, desc_hi(128, 0), desc_hi(256, 0)>(a, dA + desc_lo(k * 2048 + (k > 3) * (SLOT - HALF), k == 3 ? SLOT - 6144 : 1024),
                                                                   dB + desc_lo(16384 + k * SLAB + (k > 2) * (SLOT - 3 * SLAB), 128), k > 0 || i > 0);
                if (k & 1) wg_commit();
                if (k == 1) { wg_wait<1>(); if (i) release(prev); }
                if (k == 5) { wg_wait<1>(); release(s); }
            }
            wg_commit();
            prev = s + 1;
            r.slot++; r.next2();
        }
    }
};

__global__ void __cluster_dims__(2, 1, 1) __launch_bounds__(NTHREADS, 1)
fused_kernel(const __nv_bfloat16* __restrict__ x, const __nv_bfloat16* __restrict__ b1, const __nv_bfloat16* __restrict__ b2, const __nv_bfloat16* __restrict__ wo, __nv_bfloat16* out, Scratch* G,
             const __nv_bfloat16* __restrict__ w1,
             const __grid_constant__ Params P) {
    extern __shared__ __align__(1024) uint8_t smem[];
    const uint32_t sbase = (uint32_t)__cvta_generic_to_shared(smem);
    const uint32_t bars = sbase + OFF_BAR;
    const uint32_t rank = blockIdx.x & 1, pr = blockIdx.x >> 1;
    const uint32_t row0 = blockIdx.x * 16;
    if (threadIdx.x == 32) prefetch_l2<TILEB>(x + row0 * D_);
    if (threadIdx.x == 0) {
        TS(15, 0);
        mbar_init(bars + B_ROW, 1);
        asm volatile("fence.mbarrier_init.release.cluster;" ::: "memory");
        bulk_load(sbase + OFF_Y, x + row0 * D_, TILEB, bars + B_ROW);
        mbar_expect(bars + B_ROW, TILEB);
        TS(1, 97);
    }
    const int lane = threadIdx.x & 31;
    const int warp = __shfl_sync(~0u, threadIdx.x >> 5, 0), w = warp & 3;
    if (elect()) {
        const uint32_t first = bars + warp * 24, count = warp < 7 ? 1 : warp < 9 ? 18 - 2 * warp : 16;
#pragma unroll
        for (int i = 0; i < 3; i++) mbar_init(first + 8 * i, count);
        asm volatile("fence.mbarrier_init.release.cluster;" ::: "memory");
    }
    __syncwarp();
    asm volatile("barrier.cluster.arrive.relaxed.aligned;" ::: "memory");
    const uint32_t pv = pr < 4 ? pr * 8 + 36 : pr - 4 + (max((int)pr - 33, 0) * 37 >> 8);
    const uint32_t gp = (pv + 4) & 7, hp = pv >> 3;
    const uint32_t tb = gp * 2 + rank, c = hp * 16 + tb;
    const bool has_g1 = gp > 0;
    const uint32_t nt1 = hp & 3, ft = max((int)gp - 1, 0) * 2 + (hp >> 2);
    const uint32_t nt2 = (hp & 1) * 2 + rank, mt = (gp & 3) * 4 + (hp >> 1), ks = gp >> 2;
    asm volatile("barrier.cluster.wait.aligned;" ::: "memory");

    if (warp == 8) {
        uint32_t kw = (gp & 1) * 192, kx;
        if (elect()) {
            mbar_expect(bars + B_QFULL, WSLOT);
            tma3d(sbase + xslot(0) * 8192, &P.tmX, bars + B_FULL, 0, tb * 64, 0);
            tma3d_pair(sbase + wslot(0) * 8192 + rank * 12288, &P.tmWqkv, bars + B_QFULL, (hp * 56) & ~15, rank * 32, 0);
            TS(1, 23);
            asm volatile("prefetch.tensormap [%0];\nprefetch.tensormap [%1];\nprefetch.tensormap [%2];" ::"l"(&P.tmW1), "l"(&P.tmW2), "l"(&P.tmOut) : "memory");
            uint32_t due = (uint32_t)clock() + PACE, ep = ld_relaxed(G->epoch[c]);
            uint32_t spins = sbase == (rank << 24 | SMEM0) ? 0 : SPIN_LIMIT;
#pragma unroll 1
            for (int i = 1; i < 8; i++) {
                kx = kw; kw += 64;
                if (i >= 5) mbar_wait_bounded(bars + B_QEMPTY + 8 * (i - 5), 0, spins);
                else { while ((int)((uint32_t)clock() - due) < 0) {} due += PACE; }
                if (kw == D_) kw = 64;
                if (i < 4) kx = kw;
                const int ix = i - (i > 4);
                if (i < 7) mbar_expect(bars + B_QFULL + 8 * i, WSLOT);
                if (i != 4) tma3d(sbase + xslot(ix) * 8192, &P.tmX, bars + B_FULL + 8 * ix, kx, tb * 64, 0);
                if (i & (i >> 2)) mbar_wait_bounded(bars + B_CS - 20 + 4 * i, 0, spins);
                if (i < 7) tma3d_pair(sbase + wslot(i) * 8192 + rank * 12288, &P.tmWqkv, bars + B_QFULL + 8 * i, (hp * 56) & ~15, kw + rank * 32, 0);
            }
            ep++;
            Slot r{sbase, bars, 0};
            if (has_g1) {
                const uint8_t* src = G->H[nt1][rank * 16];
                const int row = rank * 1024;
                mbar_expect(bars + B_FULL, 16384 + TILEB);
                tma3d(sbase, &P.tmW1, bars + B_FULL, 0, row, ft * 2);
                wait_flag(G->flag[2 + rank * 2], 20 * ep, spins);
                TS(1, 16);
#pragma unroll 1
                for (int j = 64;; j += 64) {
                    bulk_load(r.dst + 16384, src, TILEB, r.bar + B_FULL);
                    src += TILEB;
                    r.next(bars);
                    if (j == 1024) break;
                    mbar_wait_bounded(r.bar + B_EMPTY, r.ph, spins);
                    if (j < 14 * 64) TS(2, 146 + j / 64);
                    mbar_expect(r.bar + B_FULL, 16384 + TILEB);
                    tma3d(r.dst, &P.tmW1, r.bar + B_FULL, 0, row + j, ft * 2);
                }
                mbar_arrive(bars + B_FULL + 48); mbar_arrive_n<16>(bars + B_EMPTY + 48);
#pragma unroll
                for (int i = 0; i < 4; i++) mbar_expect(bars + B_X + 8 * i, (i & 1) ? 3072 : 4096);
            } else {
                due = (uint32_t)clock();
                const __nv_bfloat16* at = w1 + (rank * 1024 + PF0 * 64 + hp * 8) * F_;
#pragma unroll 1
                for (int j = PF0; j < PF1 + 16 - PF2; j++) {
                    while ((int)((uint32_t)clock() - due) < 0) {}
                    prefetch_l2<16 * F_>(at);
                    due += j == PF1 - 1 ? PF + PFD : PF;
                    at += j == PF1 - 1 ? (PF2 - PF1 + 1) * 64 * F_ : 64 * F_;
                }
            }
            const uint8_t *so = G->O[mt][ks * 4], *sw = G->Wo[nt2][ks * 4];
            wait_flag2(G->flag[16 + mt], 8 * ep, G->flag[0], 16 * ep, spins);
            TS(4, 18);
#pragma unroll 1
            for (int j = 0; j < 4 * TILEB; j += TILEB) {
                mbar_wait_bounded(r.bar + B_EMPTY, r.ph, spins);
                mbar_expect(r.bar + B_QFULL, TILEB);
                bulk_load(r.dst, so + j, TILEB, r.bar + B_QFULL);
                bulk_load(r.dst + 16384, sw + j, (r.bar & 8) ? TILEB : 3 * SLAB, r.bar + B_FULL);
                r.next(bars);
            }
            Ring q{has_g1 ? 2u : 6u, has_g1}, p{q.slot, !has_g1};
#pragma unroll 1
            for (int j = 0; j < 14 * 128; j += 128) {
                mbar_wait_bounded(bars + B_EMPTY + 8 * q.slot, q.ph, spins);
                if (LEADW && j >= LEADW * 128 && j < LEADN * 128) { mbar_wait_bounded(bars + B_FULL + 8 * p.slot, p.ph, spins); p.next2(); }
                TS(8, 176 + j / 128);
                tma3d(sbase + q.slot * SLOT, &P.tmW2, bars + B_FULL + 8 * q.slot, 0, ks * 896 + j - (j < 896 ? 0 : 832), mt * 2);
                q.next2();
            }
            mbar_wait_bounded(bars + B_END, 0, spins);
        }
    } else if (warp > 8) {
        const uint32_t ep = ld_relaxed(G->epoch[c]) + 1;
        const uint8_t* src = G->U[nt2][ks * 14];
        uint32_t spins = 0, bad;
        {
            uint2* cs = G->colsum[hp][0];
            if (w == 2) {
                bar_sync(6, 288);
                TS(1, 8);
                stg1((uint32_t*)(G->stat + row0) + lane, tag(__float_as_uint(lds1f(sbase + OFF_ST + lane * 4)), ~lane & 1, ep));
                if (elect()) {
                    fence_async_shared();
#pragma unroll
                    for (int i = 0; i < 4; i++) bulk_store(G->H[i][0] + row0 * (SLAB / 16), sbase + OFF_X + i * HSTG, SLAB);
                    bulk_flush();
                    TS(1, 99);
                    signal(G->flag[2 + (row0 >> 10) * 2 + ((row0 & 1023) >= 320)]);
                }
                __syncwarp();
            } else {
                const uint32_t word = rank * 16 + (w & 2) * 4 + (lane & 7), done = mapa(bars + B_CS, rank ^ (lane & 1));
                const uint32_t from = (sbase + word * 4 + (gp >> 2) * 12288 + (gp & 2) * 1024) ^ ((lane >> 3) * 288);
                auto swz = [](uint32_t a) { return a ^ ((a >> 3) & 0x70); };
                const uint32_t lin = sbase + lane * 128 + (hp & 1) * 16, f0 = swz(lin + 80) + 8192, f1 = swz(lin + 96) + 8192, to = swz(lin + 112);
                float s[6] = {};
#pragma unroll 1
                for (int i = 0; i < 7; i++) {
                    const uint32_t o = wslot(i) * 8192, a0 = from + o, a1 = a0 ^ 144;
                    mbar_wait(bars + B_QFULL + 8 * i, 0);
                    if (i < 2 && w == 1) TS(1, 140 + i);
                    if ((i ^ (w >> 1)) & 1) {
                        const uint4 v0 = lds4(f0 + o), v1 = lds4(f1 + o), v2 = lds4(f0 + o + 12288), v3 = lds4(f1 + o + 12288);
                        sts4(to + o, v0); sts4(to + o + 4096, v1); sts4(to + o + 12288, v2); sts4(to + o + 16384, v3);
                        fence_async_shared();
                        __syncwarp();
                        if (elect()) mbar_expect(bars + B_FULL + 8 * i, 16384);
                    }
                    if (i > 3 || i < (gp & 1)) continue;
                    if (w == 1) TS(1, 66);
                    uint32_t v[12];
#pragma unroll
                    for (int k = 0; k < 12; k++) v[k] = __float_as_uint(lds1f(((k & 1) ? a1 : a0) + (k & 2) * 512 + (k >> 2) * 4096));
#pragma unroll
                    for (int k = 0; k < 12; k++) { s[(k >> 2) * 2] += bf_lo(v[k]); s[(k >> 2) * 2 + 1] += bf_hi(v[k]); }
                    __syncwarp();
                    if ((i & 1) && lane < 2) mbar_arrive_remote(done + (i & 2) * 4);
                    if (i < 3) continue;
#pragma unroll
                    for (int k = 0; k < 6; k++) { s[k] += __shfl_xor_sync(~0u, s[k], 8); s[k] += __shfl_xor_sync(~0u, s[k], 16); }
                    const float s0 = lane < 8 ? s[0] : lane < 16 ? s[2] : s[4], s1 = lane < 8 ? s[1] : lane < 16 ? s[3] : s[5];
                    if (lane < 24) cs[gp * 96 + (lane >> 3) * 32 + word] = make_uint2(tag(__float_as_uint(s0), 1, ep), __float_as_uint(s1));
                    if (w == 1) TS(1, 24);
                }
            }
            bar_sync(1, 96);
            if (w == 1) TS(1, 98);
            const int i0 = threadIdx.x - 288, j0 = i0 - (hp & 1) * 4;
            cs += i0 + ((j0 & 92) == 28 ? (j0 & 32 ? 28 : 56) : 0);
            uint2 u[8];
            uint4 sv;
            do {
                sv = ld_relaxed4(G->stat + tb * 128 + (i0 & 63) * 2);
                bad = sv.x ^ ep;
#pragma unroll
                for (int i = 0; i < 8; i++) { u[i] = ld_relaxed2(cs + i * 96); bad = or_diff(bad, u[i].x, ep); }
                if (bad & 1) TS(1, 3);
            } while (bad & 1);
            if (w < 3) sts4(sbase + OFF_ST + i0 * 16, sv);
#pragma unroll
            for (int e = 0; e < 2; e++) {
                float f = 0.f;
#pragma unroll
                for (int i = 0; i < 8; i++) f += __uint_as_float(e ? u[i].y : u[i].x);
                const uint32_t hi = pack2(f, f);
                sts4(sbase + OFF_X + i0 * 32 + e * 16, make_uint4(hi, pack2(f - bf_hi(hi), f - bf_hi(hi)), 0, 0));
            }
            sts1(bars + 8 * NBAR, ep);
            fence_async_shared();
            __syncwarp();
            bar_arrive(8, 224); bar_arrive(9, 224);
            TS(1, 90 + w);
        }
        if (w < 3) {
            if (w == 1) {
                if (elect()) {
                    wait_flag(G->flag[3 + rank * 2], 44 * ep, spins);
                    mbar_arrive_n<16>(bars + B_EMPTY + 8 * 5);
                    TS(1, 96);
                }
                __syncwarp();
                if (!has_g1) { bar_sync(5, 288); if (elect()) signal(G->flag[0]); __syncwarp(); TS(2, 26); }
            }
            mbar_wait(bars + B_HALO, 0);
            uint32_t slot = (has_g1 ? 16 % NSLOT : 0) + w - 1, ph = ~0u;
#pragma unroll 1
            for (int i = w - 1; i < 18;) {
                const uint32_t d0 = sbase + slot * SLOT + (i < 4 ? 0 : 16384), landed = bars + B_QFULL + 8 * slot;
                mbar_wait(landed, (ph >> slot) & 1);
                ph ^= 1 << slot;
                if (i < 8) TS(4, 82 + i);
                if (i >= 4) TS(8, 156 + i);
                bad = 0;
#pragma unroll
                for (int k = 0; k < 14; k++) bad = or_diff(bad, __float_as_uint(lds1f(d0 + k * 1024 + lane * 32 + (lane >> 2) * 4)), ep);
                if (__any_sync(~0u, bad & 1)) {
                    if (elect()) {
                        const uint8_t* cur = (i < 4 ? G->O[mt][ks * 4] : src - 4 * TILEB) + i * TILEB;
                        fence_async_shared();
                        mbar_expect(landed, TILEB);
                        bulk_load(d0, cur, TILEB, landed);
                    }
                    TS(4, i < 4 ? 94 : 95);
                } else {
                    if (elect()) mbar_expect(landed + (B_FULL - B_QFULL), i < 4 ? (2 + w) * SLAB : 16384);
                    i += __byte_perm(0x03020202u, 0x00010202u, 0x7770 + slot);
                    slot = __byte_perm(0x05060302u, 0x00040100u, 0x7770 + slot);
                }
            }
        } else {
            bar_sync(3, 288);
            __nanosleep(HALO_NS);
            uint4 v[7];
            do {
                bad = 0;
#pragma unroll
                for (int i = 0; i < 7; i++) { v[i] = ld_relaxed4(G->halo[c - (tb > 0)] + i * 512 + lane * 16); bad = or_diff(bad, v[i].x, ep); }
            } while (bad & 1);
#pragma unroll
            for (int i = 0; i < 7; i++) sts4(sbase + OFF_X + i * 512 + lane * 16, v[i]);
            __syncwarp();
            if (elect()) mbar_arrive(bars + B_HALO);
            TS(2, 21);
            bar_sync(2, 160);
            if (elect()) bulk_store(out + row0 * D_, sbase + OFF_Y, TILEB);
            __syncwarp();
            bar_sync(4, 288);
            if (elect()) {
                fence_async_shared();
                bulk_store(G->O[tb][hp], sbase + OFF_X, TILEB);
                bulk_flush();
                TS(2, 7);
                mbar_arrive_remote(mapa(bars + B_FREE, rank ^ 1));
                mbar_arrive(bars + B_FREE);
                hint(G->flag[16 + tb]);
                signal(G->flag[16 + (row0 >> 7)] + 1);
                TS(2, 22);
            }
            __syncwarp();
            uint32_t late = ~0u;
            const uint32_t* hints = G->flag[8 + nt2 * 2 + ks] + (lane & 7);
            mbar_wait(bars + (has_g1 ? B_X : B_FREE), 0);
            Ring r{has_g1 ? 2u : 6u, has_g1};
#pragma unroll 1
            for (int i = 0; i < 14; i++) {
                while ((late >> i) & 1) late = __ballot_sync(~0u, ld_relaxed(hints) != 2 * ep) & 127;
                if (i == 0) TS(4, 17);
                mbar_wait(bars + B_EMPTY + 8 * r.slot, r.ph);
                TS(8, 192 + i);
                if (elect()) {
                    mbar_expect(bars + B_QFULL + 8 * r.slot, TILEB);
                    bulk_load(sbase + r.slot * SLOT + 16384, src, TILEB, bars + B_QFULL + 8 * r.slot);
                }
                src += TILEB; r.next2();
            }
            if (elect()) {
                wait_flag(G->flag[16 + mt] + 1, 8 * ep, spins);
                mbar_arrive(bars + B_ROW);
                TS(2, 27);
                G->epoch[c][0] = ep;
            }
        }
    } else {
        const int wg = warp >> 2;
        Mma M{bars, mapa(bars, rank ^ (lane & 1)), (threadIdx.x & 127) < 2, wg, wg, w, Ring{0, 1}, 0};
        const int r = lane >> 2, t = lane & 3;
        uint32_t ep;
        const uint32_t kv = sbase + OFF_X + (w * 2 + wg) * KV + lane * 16;
        uint32_t q[8][2], k0[7], k1[14], v0[7];
        float f0, f1;
        {
            const int half = (lane >> 3) & 1, r16 = warp * 2 + (half ^ (lane >> 4)), nt = (lane >> 1) & 3;
            const uint32_t row = sbase + OFF_Y + r16 * (2 * D_), part = row + nt * 224 + half * 112 + (lane & 1) * 8;
            const uint32_t hb = sbase + OFF_X + nt * HSTG + r16 * 16 + (half ^ (row0 >> 10)) * (7 * 256) + (lane & 1) * 8;
            mbar_wait(bars + B_ROW, 0);
            TS0(1, 67);
            const float x0 = bf_lo(__float_as_uint(lds1f(row)));
            float d[28], m1 = 0.f, n1 = 0.f, m2 = 0.f, n2 = 0.f;
#pragma unroll
            for (int i = 0; i < 7; i++) {
                const uint2 v = lds2(part + i * 16);
#pragma unroll
                for (int k = 0; k < 2; k++) {
                    const float d0 = d[4 * i + 2 * k] = bf_lo(k ? v.y : v.x) - x0, d1 = d[4 * i + 2 * k + 1] = bf_hi(k ? v.y : v.x) - x0;
                    m1 += d0; n1 += d1; m2 = fmaf(d0, d0, m2); n2 = fmaf(d1, d1, n2);
                }
            }
            const float md = row_sum(m1 + n1) * (1.f / D_), var = fmaf(-md, md, row_sum(m2 + n2) * (1.f / D_)), nmean = -(x0 + md);
            const float rstd = rsq(var + LN_EPS);
            const float sc = rstd * rsq(fmaf(var * rstd, 4 * rstd, 4 * LN_EPS)), nb = -md * sc;
            sts2(sbase + OFF_ST + r16 * 8, __float_as_uint(rstd), pack2(nmean, nmean - bf_hi(pack2(nmean, nmean))));
#pragma unroll
            for (int i = 0; i < 7; i++) sts2(hb + i * 256, pack2(fmaf(d[4 * i], sc, nb), fmaf(d[4 * i + 1], sc, nb)), pack2(fmaf(d[4 * i + 2], sc, nb), fmaf(d[4 * i + 3], sc, nb)));
            TS0(1, 25);
            bar_arrive(6, 288);
            float acc[84];
#pragma unroll 1
            for (int kb = 0; kb < 7; kb++) {
                const bool held = kb == (wg ? 7 - HOLD : -1);
                if (held) { wg_wait<0>(); M.release_pair(4 - HOLD); TS0(1, 138); bar_sync(7, 256); }
                mbar_wait(bars + B_FULL + 8 * kb, 0);
                if (!TSQ || !kb) TS0(1, 68 + wg * 7 + kb);
                const uint32_t dA = (xslot(kb) + wg) * 512, dB = wslot(kb) * 512 + (hp & 1);
                wg_fence();
#pragma unroll
                for (int k = 0; k < 4; k++) {
                    wgmma_n168<0, 1, HI_SW, HI_SW>(acc, dA + desc_lo(k * 32, 16), dB + desc_lo((k & 1) * 2048 + (k >> 1) * 12288, 4096), k > 0 || kb > 0);
                    if (k == 0) { wg_commit(); wg_wait<1>(); if (kb > 0 && !held) M.release_pair(kb - 3); if (TSQ && kb) TS0(1, 68 + wg * 7 + kb); }
                }
                wg_commit();
            }
            if (wg == 0 && !LATEREL) bar_arrive(7, 256);
            if (wg == 0) TS0(1, 139);
            bar_sync(8 + wg, 224);
            if (wg == 0) TS0(1, 174);
            ep = __float_as_uint(lds1f(bars + 8 * NBAR));
            const uint32_t st = sbase + OFF_ST + (w * 32 + r * 2 + wg) * 8;
            const uint2 s0 = lds2(st), s1 = lds2(st + 128);
            const uint32_t a0 = t < 2 ? s0.y : 0, a1 = t < 2 ? s1.y : 0;
            wg_fence();
            wgmma_rs_n168<desc_hi(128, 0)>(acc, a0, a1, desc_lo(OFF_X, 0) + (hp & 1) * 8);
            wg_commit();
            if (wg == 0 && LATEREL) bar_arrive(7, 256);
            if (wg == 0) TS0(1, 175);
            wg_wait<1>();
            TS0(1, 190 + wg);
            M.release_pair(4);
            wg_wait<0>();
            pin(acc);
            TS0(1, 4 + 7 * wg);
            f0 = __uint_as_float(s0.x); f1 = __uint_as_float(s1.x);
#pragma unroll
            for (int g = 13; g >= 0; g--) {
                const float* a = acc + (g < 7 ? g + 8 : g < 12 ? g + 9 : g * 8 - 89) * 4;
                (g < 7 ? k0[g] : v0[g - 7]) = pack2(a[0] * f0, a[1] * f0);
                k1[g] = pack2(a[2] * f1, a[3] * f1);
            }
#pragma unroll
            for (int i = 0; i < 3; i++) stsm4(kv + 2 * KV + i * 512, k1[4 * i], k1[4 * i + 1], k1[4 * i + 2], k1[4 * i + 3]);
            stsm2(kv + 2 * KV + 1536, k1[12], k1[13]);
            if (w == 3) {
#pragma unroll
                for (int i = 0; i < 14; i++) stg1(G->halo[c] + wg * KV + lane * 4 + i * 128, tag(k1[i], t == 0, ep));
            }
            bar_arrive(3, 288);
#pragma unroll
            for (int g = 0; g < 7; g++) { q[g][0] = pack2(acc[4 * g], acc[4 * g + 1]); q[g][1] = pack2(acc[4 * g + 2], acc[4 * g + 3]); }
#pragma unroll
            for (int j = 0; j < 2; j++) { q[7][j] = t < 2 ? 0u : q[3][j]; q[3][j] = t < 2 ? q[3][j] : 0u; }
#pragma unroll
            for (int g = 0; g < 7; g++) v0[g] = transpose8(v0[g]);
        }
        TS0(1, 9 + 11 * wg);
        float a[56];
#pragma unroll
        for (int i = 0; i < 56; i++) asm volatile("" : "=f"(a[i]));
        if (__builtin_expect(!has_g1, 0)) {
            const int g = min(lane >> 1, 13), nt = rank * 2 + wg;
            const uint4* src = (const uint4*)(wo + (hp * 56 - (hp & 1) * 8 + w * 16 + (lane & 1)) * D_ + nt * 112) + g;
            uint4 v[8];
#pragma unroll
            for (int i = 0; i < 8; i++) v[i] = __ldg(src + i * (D_ / 4));
#pragma unroll
            for (int i = 0; i < 8; i++) ((uint4*)G->Wo[nt][hp])[w * (SLAB / 16) + g * 16 + (lane & 1) + 2 * i] = v[i];
            bar_arrive(5, 288);
        }
        M.run<true>(a, has_g1 ? PAUSE : 0, 1, 16, 0, 0, 32);
        const uint32_t bias0 = ld_u16(b1 + ft * 128 + warp * 16 + r), bias1 = ld_u16(b1 + ft * 128 + warp * 16 + r + 8);
        {
            uint32_t kp[8], vv[14];
            mbar_wait(bars + B_HALO, 0);
            ldsm4(kp, kv); ldsm4(kp + 4, kv + (lane < 24 ? 512 : 0));
            const uint32_t va = kv + 896 + (lane & 8) * (2 * KV / 8 - 16) - (lane & 16) * 8;
            ldsm4t(vv, va); ldsm4t(vv + 4, va + 256); ldsm4t(vv + 8, va + 512); ldsm2t(vv + 12, va + 768);
            const bool e0 = 2 * t > r, e1 = 2 * t >= r;
            const uint32_t mk = (e0 ? 0xffffu : 0u) | (e1 ? 0xffff0000u : 0u);
            wg_wait<0>();
            pin(a);
            if (has_g1) M.release(M.prev);
            TS0(2, 144 + wg);
            bar_arrive(10 + wg, 256);
            if (wg) bar_arrive(2, 160);
            block_end();
            TS0(2, 12 + 16 * wg);
            float sv[2][4];
#pragma unroll
            for (int h = 0; h < 2; h++) {
                const int ga = h * 4, gb = h * 4 + 1, gc = h * 4 + 2, gd = h * 4 + 3;
                float s[3][4] = {};
                mma16(s[0], q[ga][0], q[ga][1], q[gb][0], q[gb][1], kp[ga], kp[gb]);
                mma16(s[1], q[ga][0], q[ga][1], q[gb][0], q[gb][1], k0[ga], k0[gb]);
                mma16(s[2], q[ga][0], q[ga][1], q[gb][0], q[gb][1], k1[ga], k1[gb]);
                mma16(s[0], q[gc][0], q[gc][1], q[gd][0], q[gd][1], kp[gc], kp[gd]);
                mma16(s[1], q[gc][0], q[gc][1], q[gd][0], q[gd][1], k0[gc], k0[3]);
                mma16(s[2], q[gc][0], q[gc][1], q[gd][0], q[gd][1], k1[gc], k1[3]);
                if ((tb | w) == 0) s[0][0] = s[0][1] = -1e30f;
                sv[h][0] = e0 ? s[0][0] : s[1][0];
                sv[h][1] = e1 ? s[0][1] : s[1][1];
                sv[h][2] = e0 ? s[1][2] : s[2][2];
                sv[h][3] = e1 ? s[1][3] : s[2][3];
            }
            uint32_t pp[2][2];
#pragma unroll
            for (int i = 0; i < 4; i++) {
                float* v = &sv[i >> 1][(i & 1) * 2];
                const float f = ((i & 1) ? f1 : f0) * QK_SCALE, m = quad_max(fmaxf(v[0], v[1])) * f;
                const float p0 = ex2(fmaf(v[0], f, -m)), p1 = ex2(fmaf(v[1], f, -m));
                const float inv = rcp(quad_sum(p0 + p1));
                pp[i >> 1][i & 1] = pack2(p0 * inv, p1 * inv);
            }
            uint32_t o[8][2];
#pragma unroll
            for (int i = 0; i < 8; i++) {
                const int h = i >> 2, g = i - h;
                float d[4] = {};
                mma16(d, pp[h][0] & mk, 0u, 0u, pp[h][1] & ~mk, vv[2 * g], vv[2 * g + 1]);
                mma8(d, pp[h][0] & ~mk, pp[h][1] & mk, v0[g]);
                o[i][0] = pack2(d[0], d[1]); o[i][1] = pack2(d[2], d[3]);
            }
            if (t >= 2) { o[3][0] = o[4][0]; o[3][1] = o[4][1]; }
            const int word = wg * 4 + t - (w & 1) * 4 - (r >> 2);
#pragma unroll
            for (int i = 0; i < 8; i++) { o[i][0] = tag(o[i][0], word == 0, ep); o[i][1] = tag(o[i][1], word == 2, ep); }
            const uint32_t dst = sbase + OFF_X + (w >> 1) * HALF + ((w & 1) * 32 + (lane & 15) * 2 + wg) * 16 + (lane >> 4) * 1024;
            bar_sync(11 - wg, 256);
            stsm4(dst, o[0][0], o[0][1], o[1][0], o[1][1]);
            stsm4(dst + 2048, o[2][0], o[2][1], o[3][0], o[3][1]);
            stsm4(dst + 4096, o[5][0], o[5][1], o[6][0], o[6][1]);
            stsm2(dst + 6144, o[7][0], o[7][1]);
            bar_arrive(4, 288);
            TS0(2, 10 + 19 * wg);
        }
        if (has_g1) {
            M.run<true>(a, 16 - PAUSE, 1, 16, LAG1, 1, 32 + PAUSE);
            mbar_wait(bars + B_FREE, 0);
            const uint32_t xb = sbase + OFF_X + wg * 8192 + (threadIdx.x & 127) * 16, xbar = bars + B_X + 16 * wg;
            const uint32_t rx = mapa(xb, rank ^ 1), rbar = mapa(xbar, rank ^ 1);
            wg_wait<0>();
            pin(a);
            M.release(M.prev);
            TS0(4, 5 + wg);
#pragma unroll
            for (int i = 0; i < 3; i++)
                st_async4(rx + i * 2048, rbar + 8 * (i >> 1), pack2(a[28 + 8 * i], a[29 + 8 * i]), pack2(a[30 + 8 * i], a[31 + 8 * i]), pack2(a[32 + 8 * i], a[33 + 8 * i]), pack2(a[34 + 8 * i], a[35 + 8 * i]));
            const uint32_t tail = 6144 - (threadIdx.x & 127) * 8;
            st_async2(rx + tail, rbar + 8, pack2(a[52], a[53]), pack2(a[54], a[55]));
            uint8_t* dst = G->U[nt1][((ft >= 7) + wg) * 7 + ft] + rank * HALF + w * 256 + lane * 4;
            uint32_t u[14];
#pragma unroll
            for (int i = 0; i < 28; i++) a[i] = fmaf(bf_lo((i & 2) ? bias1 : bias0), 0.5f, a[i]);
#pragma unroll
            for (int i = 0; i < 14; i++) {
                if (i % 8 == 0) {
                    if (i) TS0(4, 134 + wg);
                    mbar_wait(xbar + i, 0);
                    TS0(4, (i ? 136 : 1) + wg);
#pragma unroll
                    for (int k = i / 4; k < i / 4 + 2; k++) {
                        if (k < 3) { const uint4 v = lds4(xb + k * 2048); u[4 * k] = v.x; u[4 * k + 1] = v.y; u[4 * k + 2] = v.z; u[4 * k + 3] = v.w; }
                        else { const uint2 v = lds2(xb + tail); u[12] = v.x; u[13] = v.y; }
                    }
                    if (i && lane < 2) mbar_arrive(bars + B_EMPTY + 48);
                }
                if (i == HINT && threadIdx.x == 0) hint(G->flag[8 + nt1 * 2] + ft + (ft >= 7) * 25);
                stg1(dst + (i >> 1) * 1024 + (i & 1) * 128, tag(pack2(gelu2(a[2 * i] + bf_lo(u[i])), gelu2(a[2 * i + 1] + bf_hi(u[i]))), (lane & 7) == w * 2 + (i & 1), ep));
            }
            TS0(4, 30 + wg);
        } else {
            mbar_wait(bars + B_FREE, 0);
            if (lane < 2) mbar_arrive(bars + B_EMPTY + 48);
        }
        M.half = wg ^ ks;
        const uint32_t orow = mt * 128 + M.half * 64 + w * 16;
        M.run_o(a);
        if (wg == 1) TS0(4, 13);
        M.run<false>(a, 14, 0, 14 - NSLOT, NSLOT + 1, 1, 52, b2 + orow + r);
        mbar_wait(bars + B_ROW, 1);
        const uint32_t stg = sbase + (4 + (w >> 1)) * SLOT + M.half * 8192 + (w & 1) * (PITCH * 16);
        const uint32_t sa = stg + (lane & 7) * PITCH + (lane >> 3) * 16;
        const bool one = elect();
        wg_wait<1>();
        if (wg == 0) bar_arrive(7, 256);
        wg_wait<0>();
        pin(a);
        TS0(8, 14 + wg);
#pragma unroll
        for (int h = 0; h < 2; h++) {
            const float* e = a + 2 * h;
#pragma unroll
            for (int i = 0; i < 3; i++)
                stsm4(sa + h * 8 * PITCH + i * 64, pack2(e[16 * i], e[16 * i + 1]), pack2(e[16 * i + 4], e[16 * i + 5]), pack2(e[16 * i + 8], e[16 * i + 9]), pack2(e[16 * i + 12], e[16 * i + 13]));
            stsm2(sa + h * 8 * PITCH + 192, pack2(e[48], e[49]), pack2(e[52], e[53]));
            fence_async_shared();
            __syncwarp();
            if (one) asm volatile("cp.reduce.async.bulk.tensor.3d.global.shared::cta.add.tile.bulk_group [%0, {%4, %2, %3}], [%1];" ::"l"(&P.tmOut), "r"(stg + h * 8 * PITCH), "r"(nt2), "r"(orow + 8 * h), "r"(0) : "memory");
        }
        if (one) {
            asm volatile("cp.async.bulk.commit_group;" ::: "memory");
            if (w == 0) mbar_arrive(bars + B_END);
            asm volatile("cp.async.bulk.wait_group.read 0;" ::: "memory");
        }
        TS0(15, wg ? 19 : 207);
        TSDUMP();
    }
}

typedef CUresult (*EncodeFn)(CUtensorMap*, CUtensorMapDataType, cuuint32_t, void*, const cuuint64_t*, const cuuint64_t*, const cuuint32_t*, const cuuint32_t*,
                             CUtensorMapInterleave, CUtensorMapSwizzle, CUtensorMapL2promotion, CUtensorMapFloatOOBfill);

void make_map(EncodeFn enc, CUtensorMap* tm, const void* base, bool swizzle, int d0, int d1, int d2, int s1, int s2, int b0, int b1, int b2) {
    const cuuint64_t dims[3] = {(cuuint64_t)d0, (cuuint64_t)d1, (cuuint64_t)d2}, strides[2] = {(cuuint64_t)s1 * 2, (cuuint64_t)s2 * 2};
    const cuuint32_t box[3] = {(cuuint32_t)b0, (cuuint32_t)b1, (cuuint32_t)b2}, es[3] = {1, 1, 1};
    enc(tm, CU_TENSOR_MAP_DATA_TYPE_BFLOAT16, d2 ? 3 : 2, (void*)base, dims, strides, box, es, CU_TENSOR_MAP_INTERLEAVE_NONE,
        swizzle ? CU_TENSOR_MAP_SWIZZLE_128B : CU_TENSOR_MAP_SWIZZLE_NONE, CU_TENSOR_MAP_L2_PROMOTION_L2_128B, CU_TENSOR_MAP_FLOAT_OOB_FILL_NONE);
}

}

extern "C" void kernel_launch(void* const* d_in, const int* in_sizes, int n_in, void* d_out, int out_size) {
    static EncodeFn enc = nullptr;
    static Scratch* scratch = nullptr;
    if (!enc) {
        void* fn = nullptr;
        cudaDriverEntryPointQueryResult qr;
        cudaGetDriverEntryPoint("cuTensorMapEncodeTiled", &fn, cudaEnableDefault, &qr);
        enc = (EncodeFn)fn;
        cudaGetSymbolAddress((void**)&scratch, g_s);
        cudaFuncSetAttribute(fused_kernel, cudaFuncAttributeMaxDynamicSharedMemorySize, SMEM_BYTES);
    }
    Params P;
    const __nv_bfloat16* x = (const __nv_bfloat16*)d_in[0];
    make_map(enc, &P.tmX, x, true, D_, S_ / 2, 2, 2 * D_, D_, 64, 64, 2);
    make_map(enc, &P.tmWqkv, d_in[1], true, D_, D_, 3, 3 * D_, D_, 64, 32, 3);
    make_map(enc, &P.tmW1, d_in[4], true, 64, S_, F_ / 64, F_, 64, 64, 64, 2);
    make_map(enc, &P.tmW2, d_in[6], true, 64, F_, S_ / 64, S_, 64, 64, 64, 2);
    make_map(enc, &P.tmOut, d_out, false, 112, 4, S_, 112, D_, PITCH / 2, 1, 8);
    fused_kernel<<<NCTA, NTHREADS, SMEM_BYTES, cudaStreamPerThread>>>(x, (const __nv_bfloat16*)d_in[5], (const __nv_bfloat16*)d_in[7], (const __nv_bfloat16*)d_in[2], (__nv_bfloat16*)d_out, scratch,
                                                                      (const __nv_bfloat16*)d_in[4], P);
}
```

```cpp
#include <cuda_runtime.h>
#include <cuda_bf16.h>
#include <cuda.h>
#include <stdint.h>

#define HALO_NS 300
#define HINT 5
#define HOLD 1
#define LATEREL 1
#define PF 400
#define PF0 2
#define PF1 8
#define LEADW 4
#define LEADN 7
#define TSQ 0
#define PF2 14
#define PFD 1500
#define PACE 580
#define PAUSE 8
#define LAG1 4

namespace {

constexpr int S_ = 2048, D_ = 448, F_ = 1792;
constexpr int NCTA = 128, NTHREADS = 384;
constexpr int NSLOT = 6, SLOT = 32768, WSLOT = 24576, TILEB = 14336, SLAB = 3584, HALF = 7168;
constexpr int KV = 1792, HSTG = SLAB + 32, PITCH = 240;
constexpr int OFF_X = NSLOT * SLOT;
constexpr int OFF_Y = OFF_X + 10 * KV;
constexpr int OFF_ST = OFF_Y + TILEB;
constexpr int OFF_BAR = OFF_ST + 1024;
constexpr int SMEM_BYTES = OFF_BAR + 1280;
constexpr uint32_t SMEM0 = 1024;
constexpr int B_QFULL = 0, B_FULL = 56, B_HALO = 128, B_X = 136, B_CS = 168, B_FREE = 192, B_END = 200, B_QEMPTY = 216, B_EMPTY = 232, B_ROW = 288, NBAR = 37;
constexpr float LN_EPS = 1e-5f, QK_SCALE = 0.1889822365046136f * 1.4426950408889634f;
constexpr int SPIN_LIMIT = 1 << 22;

struct Scratch {
    uint8_t H[4][32][TILEB];
    uint8_t U[4][28][TILEB];
    uint8_t O[16][8][TILEB];
    uint8_t Wo[4][8][TILEB];
    uint8_t halo[NCTA][2 * KV];
    uint2 stat[S_];
    uint2 colsum[8][8][96];
    uint32_t flag[32][32];
    uint32_t epoch[NCTA][32];
};
__device__ __align__(1024) Scratch g_s;

#define TS(g, i)
#define TS0(g, i)
#define TSDUMP()

struct Params {
    CUtensorMap tmX, tmWqkv, tmW1, tmW2, tmOut;
};

__device__ __forceinline__ bool elect() {
    uint32_t p;
    asm volatile("{\n.reg .pred p;\nelect.sync _|p, 0xffffffff;\nselp.u32 %0, 1, 0, p;\n}" : "=r"(p));
    return p;
}
__device__ __forceinline__ void mbar_init(uint32_t b, uint32_t c) { asm volatile("mbarrier.init.shared::cta.b64 [%0], %1;" ::"r"(b), "r"(c) : "memory"); }
__device__ __forceinline__ void mbar_expect(uint32_t b, uint32_t tx) { asm volatile("mbarrier.arrive.expect_tx.shared::cta.b64 _, [%0], %1;" ::"r"(b), "r"(tx) : "memory"); }
__device__ __forceinline__ void mbar_arrive(uint32_t b) { asm volatile("mbarrier.arrive.shared::cta.b64 _, [%0];" ::"r"(b) : "memory"); }
template <int N> __device__ __forceinline__ void mbar_arrive_n(uint32_t b) { asm volatile("mbarrier.arrive.shared::cta.b64 _, [%0], %1;" ::"r"(b), "n"(N) : "memory"); }
__device__ __forceinline__ void mbar_arrive4_remote(uint32_t b) { asm volatile("mbarrier.arrive.shared::cluster.b64 _, [%0], 4;" ::"r"(b) : "memory"); }
__device__ __forceinline__ void mbar_arrive_remote(uint32_t b) { asm volatile("mbarrier.arrive.shared::cluster.b64 _, [%0];" ::"r"(b) : "memory"); }
#define MBAR_WAIT_ASM(SEM) \
    asm volatile("{\n.reg .pred p;\nWAIT:\nmbarrier.try_wait.parity" SEM ".shared::cta.b64 p, [%0], %1;\n@!p bra WAIT;\n}" ::"r"(b), "r"(parity) : "memory")
__device__ __forceinline__ void mbar_wait(uint32_t b, uint32_t parity) { MBAR_WAIT_ASM(""); }
__device__ __forceinline__ void mbar_wait_bounded(uint32_t b, uint32_t parity, uint32_t& n) {
    asm volatile("{\n.reg .pred p;\nWAIT:\nadd.u32 %0, %0, 1;\nsetp.gt.u32 p, %0, %3;\n@p st.global.u32 [%4], %0;\n"
                 "mbarrier.try_wait.parity.shared::cta.b64 p, [%1], %2;\n@!p bra WAIT;\n}" : "+r"(n) : "r"(b), "r"(parity), "n"(SPIN_LIMIT), "l"(0ull) : "memory");
}
__device__ __forceinline__ uint32_t mapa(uint32_t a, uint32_t rank) { uint32_t r; asm("mapa.shared::cluster.u32 %0, %1, %2;" : "=r"(r) : "r"(a), "r"(rank)); return r; }
__device__ __forceinline__ void tma3d(uint32_t dst, const CUtensorMap* tm, uint32_t bar, int c0, int c1, int c2) {
    asm volatile("cp.async.bulk.tensor.3d.shared::cluster.global.mbarrier::complete_tx::bytes [%0], [%1, {%3, %4, %5}], [%2];" ::"r"(dst), "l"(tm), "r"(bar), "r"(c0), "r"(c1), "r"(c2) : "memory");
}
__device__ __forceinline__ void tma3d_pair(uint32_t dst, const CUtensorMap* tm, uint32_t bar, int c0, int c1, int c2) {
    asm volatile("cp.async.bulk.tensor.3d.shared::cluster.global.mbarrier::complete_tx::bytes.multicast::cluster [%0], [%1, {%3, %4, %5}], [%2], %6;" ::"r"(dst), "l"(tm), "r"(bar), "r"(c0), "r"(c1), "r"(c2), "h"((uint16_t)3) : "memory");
}
__device__ __forceinline__ void bulk_load(uint32_t dst, const void* src, uint32_t bytes, uint32_t bar) {
    asm volatile("cp.async.bulk.shared::cluster.global.mbarrier::complete_tx::bytes [%0], [%1], %2, [%3];" ::"r"(dst), "l"(src), "r"(bytes), "r"(bar) : "memory");
}
template <int BYTES> __device__ __forceinline__ void prefetch_l2(const void* p) { asm volatile("cp.async.bulk.prefetch.L2.global [%0], %1;" ::"l"(p), "n"(BYTES) : "memory"); }
__device__ __forceinline__ void bulk_store(void* dst, uint32_t src, uint32_t bytes) {
    asm volatile("cp.async.bulk.global.shared::cta.bulk_group [%0], [%1], %2;" ::"l"(dst), "r"(src), "r"(bytes) : "memory");
}
__device__ __forceinline__ uint32_t ld_u16(const void* p) { uint32_t v; asm volatile("ld.global.nc.u16 %0, [%1];" : "=r"(v) : "l"(p)); return v; }
__device__ __forceinline__ uint32_t ld_relaxed(const uint32_t* p) { uint32_t v; asm volatile("ld.relaxed.gpu.global.u32 %0, [%1];" : "=r"(v) : "l"(p) : "memory"); return v; }
__device__ __forceinline__ void bulk_flush() { asm volatile("cp.async.bulk.commit_group;\ncp.async.bulk.wait_group 0;" ::: "memory"); }
__device__ __forceinline__ void signal(uint32_t* flag) { asm volatile("fence.acq_rel.gpu;\nred.relaxed.gpu.global.add.u32 [%0], 1;" ::"l"(flag) : "memory"); }
__device__ __forceinline__ void hint(uint32_t* flag) { asm volatile("red.relaxed.gpu.global.add.u32 [%0], 1;" ::"l"(flag) : "memory"); }
__device__ __forceinline__ uint32_t tag(uint32_t v, uint32_t mask, uint32_t parity) { return (v & ~mask) | (parity & mask); }
__device__ __forceinline__ uint32_t or_diff(uint32_t acc, uint32_t v, uint32_t parity) { asm("lop3.b32 %0, %0, %1, %2, 0xf6;" : "+r"(acc) : "r"(v), "r"(parity)); return acc; }
__device__ __forceinline__ uint4 ld_relaxed4(const void* p) {
    uint4 v;
    asm volatile("ld.relaxed.gpu.global.v4.u32 {%0, %1, %2, %3}, [%4];" : "=r"(v.x), "=r"(v.y), "=r"(v.z), "=r"(v.w) : "l"(p) : "memory");
    return v;
}
__device__ __forceinline__ uint2 ld_relaxed2(const void* p) { uint2 v; asm volatile("ld.relaxed.gpu.global.v2.u32 {%0, %1}, [%2];" : "=r"(v.x), "=r"(v.y) : "l"(p) : "memory"); return v; }
__device__ __forceinline__ void sts4(uint32_t a, uint4 v) { asm volatile("st.shared.v4.b32 [%0], {%1, %2, %3, %4};" ::"r"(a), "r"(v.x), "r"(v.y), "r"(v.z), "r"(v.w) : "memory"); }
__device__ __forceinline__ void sts1(uint32_t a, uint32_t v) { asm volatile("st.shared.b32 [%0], %1;" ::"r"(a), "r"(v) : "memory"); }
__device__ __forceinline__ void sts2(uint32_t a, uint32_t v0, uint32_t v1) { asm volatile("st.shared.v2.b32 [%0], {%1, %2};" ::"r"(a), "r"(v0), "r"(v1) : "memory"); }
__device__ __forceinline__ void stg1(void* p, uint32_t v) { asm volatile("st.global.b32 [%0], %1;" ::"l"(p), "r"(v) : "memory"); }
__device__ __forceinline__ void fence_async_shared() { asm volatile("fence.proxy.async.shared::cta;" ::: "memory"); }
#define BOUND "add.u32 %0, %0, 16;\nsetp.gt.u32 p, %0, %1;\n@p st.global.u32 [%2], %0;\n"
__device__ __forceinline__ void wait_flag(const uint32_t* p, uint32_t target, uint32_t& n) {
    asm volatile("{\n.reg .pred p;\n.reg .u32 v;\nPOLL:\n" BOUND "ld.acquire.gpu.global.u32 v, [%3];\nsetp.ne.u32 p, v, %4;\n@p bra POLL;\nfence.proxy.async.global;\n}"
                 : "+r"(n) : "n"(SPIN_LIMIT), "l"(0ull), "l"(p), "r"(target) : "memory");
}
__device__ __forceinline__ void wait_flag2(const uint32_t* h, uint32_t th, const uint32_t* p, uint32_t target, uint32_t& n) {
    asm volatile("{\n.reg .pred p;\n.reg .u32 u, v;\nPOLL:\n" BOUND "ld.relaxed.gpu.global.u32 u, [%3];\nld.acquire.gpu.global.u32 v, [%5];\nsetp.ne.u32 p, u, %4;\nsetp.ne.or.u32 p, v, %6, p;\n@p bra POLL;\nfence.proxy.async.global;\n}"
                 : "+r"(n) : "n"(SPIN_LIMIT), "l"(0ull), "l"(h), "r"(th), "l"(p), "r"(target) : "memory");
}
__device__ __forceinline__ void block_end() { asm volatile("{\n.reg .pred p;\n.reg .u32 t;\nAGAIN:\nmov.u32 t, %%clock;\nsetp.eq.u32 p, t, %0;\n@p bra AGAIN;\n}" ::"n"(0) : "memory"); }
__device__ __forceinline__ void bar_sync(int id, int n) { asm volatile("bar.sync %0, %1;" ::"r"(id), "r"(n) : "memory"); }
__device__ __forceinline__ void bar_arrive(int id, int n) { asm volatile("bar.arrive %0, %1;" ::"r"(id), "r"(n) : "memory"); }
__device__ __forceinline__ void wg_fence() { asm volatile("wgmma.fence.sync.aligned;" ::: "memory"); }
__device__ __forceinline__ void wg_commit() { asm volatile("wgmma.commit_group.sync.aligned;" ::: "memory"); }
template <int N> __device__ __forceinline__ void wg_wait() { asm volatile("wgmma.wait_group.sync.aligned %0;" ::"n"(N) : "memory"); }
template <int N> __device__ __forceinline__ void pin(float (&d)[N]) {
#pragma unroll
    for (int i = 0; i < N; i++) asm volatile("" : "+f"(d[i])::"memory");
}
__host__ __device__ constexpr uint32_t desc_hi(uint32_t sbo, uint32_t swz) { return (sbo >> 4) | (swz << 30); }
__host__ __device__ constexpr uint32_t desc_lo(uint32_t off, uint32_t lbo) { return ((SMEM0 + off) >> 4) | ((lbo >> 4) << 16); }
__device__ __forceinline__ uint32_t pack2(float lo, float hi) { uint32_t r; asm("cvt.rn.bf16x2.f32 %0, %1, %2;" : "=r"(r) : "f"(hi), "f"(lo)); return r; }
__device__ __forceinline__ float bf_lo(uint32_t v) { return __uint_as_float(v << 16); }
__device__ __forceinline__ float bf_hi(uint32_t v) { return __uint_as_float(v & 0xffff0000u); }
__device__ __forceinline__ void stsm4(uint32_t a, uint32_t r0, uint32_t r1, uint32_t r2, uint32_t r3) {
    asm volatile("stmatrix.sync.aligned.m8n8.x4.shared.b16 [%0], {%1, %2, %3, %4};" ::"r"(a), "r"(r0), "r"(r1), "r"(r2), "r"(r3) : "memory");
}
__device__ __forceinline__ void stsm2(uint32_t a, uint32_t r0, uint32_t r1) {
    asm volatile("stmatrix.sync.aligned.m8n8.x2.shared.b16 [%0], {%1, %2};" ::"r"(a), "r"(r0), "r"(r1) : "memory");
}
__device__ __forceinline__ uint4 lds4(uint32_t a) { uint4 v; asm volatile("ld.shared.v4.b32 {%0, %1, %2, %3}, [%4];" : "=r"(v.x), "=r"(v.y), "=r"(v.z), "=r"(v.w) : "r"(a) : "memory"); return v; }
__device__ __forceinline__ uint2 lds2(uint32_t a) { uint2 v; asm volatile("ld.shared.v2.b32 {%0, %1}, [%2];" : "=r"(v.x), "=r"(v.y) : "r"(a) : "memory"); return v; }
__device__ __forceinline__ float lds1f(uint32_t a) { float v; asm volatile("ld.shared.f32 %0, [%1];" : "=f"(v) : "r"(a) : "memory"); return v; }
__device__ __forceinline__ void ldsm4(uint32_t* r, uint32_t a) {
    asm volatile("ldmatrix.sync.aligned.m8n8.x4.shared.b16 {%0, %1, %2, %3}, [%4];" : "=r"(r[0]), "=r"(r[1]), "=r"(r[2]), "=r"(r[3]) : "r"(a) : "memory");
}
__device__ __forceinline__ void ldsm4t(uint32_t* r, uint32_t a) {
    asm volatile("ldmatrix.sync.aligned.m8n8.x4.trans.shared.b16 {%0, %1, %2, %3}, [%4];" : "=r"(r[0]), "=r"(r[1]), "=r"(r[2]), "=r"(r[3]) : "r"(a) : "memory");
}
__device__ __forceinline__ void ldsm2t(uint32_t* r, uint32_t a) {
    asm volatile("ldmatrix.sync.aligned.m8n8.x2.trans.shared.b16 {%0, %1}, [%2];" : "=r"(r[0]), "=r"(r[1]) : "r"(a) : "memory");
}
__device__ __forceinline__ uint32_t transpose8(uint32_t v) { uint32_t r; asm volatile("movmatrix.sync.aligned.m8n8.trans.b16 %0, %1;" : "=r"(r) : "r"(v)); return r; }
__device__ __forceinline__ void mma16(float (&c)[4], uint32_t a0, uint32_t a1, uint32_t a2, uint32_t a3, uint32_t b0, uint32_t b1) {
    asm volatile("mma.sync.aligned.m16n8k16.row.col.f32.bf16.bf16.f32 {%0, %1, %2, %3}, {%4, %5, %6, %7}, {%8, %9}, {%0, %1, %2, %3};"
                 : "+f"(c[0]), "+f"(c[1]), "+f"(c[2]), "+f"(c[3]) : "r"(a0), "r"(a1), "r"(a2), "r"(a3), "r"(b0), "r"(b1));
}
__device__ __forceinline__ void mma8(float (&c)[4], uint32_t a0, uint32_t a1, uint32_t b0) {
    asm volatile("mma.sync.aligned.m16n8k8.row.col.f32.bf16.bf16.f32 {%0, %1, %2, %3}, {%4, %5}, {%6}, {%0, %1, %2, %3};"
                 : "+f"(c[0]), "+f"(c[1]), "+f"(c[2]), "+f"(c[3]) : "r"(a0), "r"(a1), "r"(b0));
}
__device__ __forceinline__ void st_async4(uint32_t a, uint32_t bar, uint32_t v0, uint32_t v1, uint32_t v2, uint32_t v3) {
    asm volatile("st.async.weak.shared::cluster.mbarrier::complete_tx::bytes.v4.b32 [%0], {%2, %3, %4, %5}, [%1];" ::"r"(a), "r"(bar), "r"(v0), "r"(v1), "r"(v2), "r"(v3) : "memory");
}
__device__ __forceinline__ void st_async2(uint32_t a, uint32_t bar, uint32_t v0, uint32_t v1) {
    asm volatile("st.async.weak.shared::cluster.mbarrier::complete_tx::bytes.v2.b32 [%0], {%2, %3}, [%1];" ::"r"(a), "r"(bar), "r"(v0), "r"(v1) : "memory");
}
__device__ __forceinline__ float quad_max(float v) { v = fmaxf(v, __shfl_xor_sync(~0u, v, 1)); return fmaxf(v, __shfl_xor_sync(~0u, v, 2)); }
__device__ __forceinline__ float quad_sum(float v) { v += __shfl_xor_sync(~0u, v, 1); return v + __shfl_xor_sync(~0u, v, 2); }
__device__ __forceinline__ float ex2(float v) { float r; asm("ex2.approx.ftz.f32 %0, %1;" : "=f"(r) : "f"(v)); return r; }
__device__ __forceinline__ float rcp(float v) { float r; asm("rcp.approx.ftz.f32 %0, %1;" : "=f"(r) : "f"(v)); return r; }
__device__ __forceinline__ float rsq(float v) { float r; asm("rsqrt.approx.ftz.f32 %0, %1;" : "=f"(r) : "f"(v)); return r; }
__device__ __forceinline__ float gelu2(float v) {
    float z = v * fmaf(v * v, 8 * 0.044715f * 0.7978845608028654f, 2 * 0.7978845608028654f), t;
    asm("tanh.approx.f32 %0, %1;" : "=f"(t) : "f"(z));
    return fmaf(v, t, v);
}
__device__ __forceinline__ float row_sum(float v) {
    v = quad_sum(v); v += __shfl_xor_sync(~0u, v, 4);
    return v + __shfl_xor_sync(~0u, v, 24);
}

template <int TA, int TB, uint32_t HA, uint32_t HB>
__device__ __forceinline__ void wgmma_n112(float (&d)[56], uint32_t da, uint32_t db, int accumulate) {
    asm volatile("{\n.reg .pred p;\n.reg .b64 a, b;\nmov.b64 a, {%56, %61};\nmov.b64 b, {%57, %62};\nsetp.ne.b32 p, %58, 0;\n"
        "wgmma.mma_async.sync.aligned.m64n112k16.f32.bf16.bf16 {"
        "%0, %1, %2, %3, %4, %5, %6, %7, %8, %9, %10, %11, %12, %13, %14, %15, "
        "%16, %17, %18, %19, %20, %21, %22, %23, %24, %25, %26, %27, %28, %29, %30, %31, "
        "%32, %33, %34, %35, %36, %37, %38, %39, %40, %41, %42, %43, %44, %45, %46, %47, "
        "%48, %49, %50, %51, %52, %53, %54, %55"
        "}, a, b, p, 1, 1, %59, %60;\n}\n"
        : "+f"(d[0]), "+f"(d[1]), "+f"(d[2]), "+f"(d[3]), "+f"(d[4]), "+f"(d[5]), "+f"(d[6]), "+f"(d[7]),
          "+f"(d[8]), "+f"(d[9]), "+f"(d[10]), "+f"(d[11]), "+f"(d[12]), "+f"(d[13]), "+f"(d[14]), "+f"(d[15]),
          "+f"(d[16]), "+f"(d[17]), "+f"(d[18]), "+f"(d[19]), "+f"(d[20]), "+f"(d[21]), "+f"(d[22]), "+f"(d[23]),
          "+f"(d[24]), "+f"(d[25]), "+f"(d[26]), "+f"(d[27]), "+f"(d[28]), "+f"(d[29]), "+f"(d[30]), "+f"(d[31]),
          "+f"(d[32]), "+f"(d[33]), "+f"(d[34]), "+f"(d[35]), "+f"(d[36]), "+f"(d[37]), "+f"(d[38]), "+f"(d[39]),
          "+f"(d[40]), "+f"(d[41]), "+f"(d[42]), "+f"(d[43]), "+f"(d[44]), "+f"(d[45]), "+f"(d[46]), "+f"(d[47]),
          "+f"(d[48]), "+f"(d[49]), "+f"(d[50]), "+f"(d[51]), "+f"(d[52]), "+f"(d[53]), "+f"(d[54]), "+f"(d[55])
        : "r"(da), "r"(db), "r"(accumulate), "n"(TA), "n"(TB), "n"(HA), "n"(HB));
}

template <int TA, int TB, uint32_t HA, uint32_t HB>
__device__ __forceinline__ void wgmma_n168(float (&d)[84], uint32_t da, uint32_t db, int accumulate) {
    asm volatile("{\n.reg .pred p;\n.reg .b64 a, b;\nmov.b64 a, {%84, %89};\nmov.b64 b, {%85, %90};\nsetp.ne.b32 p, %86, 0;\n"
        "wgmma.mma_async.sync.aligned.m64n168k16.f32.bf16.bf16 {"
        "%0, %1, %2, %3, %4, %5, %6, %7, %8, %9, %10, %11, %12, %13, %14, %15, "
        "%16, %17, %18, %19, %20, %21, %22, %23, %24, %25, %26, %27, %28, %29, %30, %31, "
        "%32, %33, %34, %35, %36, %37, %38, %39, %40, %41, %42, %43, %44, %45, %46, %47, "
        "%48, %49, %50, %51, %52, %53, %54, %55, %56, %57, %58, %59, %60, %61, %62, %63, "
        "%64, %65, %66, %67, %68, %69, %70, %71, %72, %73, %74, %75, %76, %77, %78, %79, "
        "%80, %81, %82, %83"
        "}, a, b, p, 1, 1, %87, %88;\n}\n"
        : "+f"(d[0]), "+f"(d[1]), "+f"(d[2]), "+f"(d[3]), "+f"(d[4]), "+f"(d[5]), "+f"(d[6]), "+f"(d[7]),
          "+f"(d[8]), "+f"(d[9]), "+f"(d[10]), "+f"(d[11]), "+f"(d[12]), "+f"(d[13]), "+f"(d[14]), "+f"(d[15]),
          "+f"(d[16]), "+f"(d[17]), "+f"(d[18]), "+f"(d[19]), "+f"(d[20]), "+f"(d[21]), "+f"(d[22]), "+f"(d[23]),
          "+f"(d[24]), "+f"(d[25]), "+f"(d[26]), "+f"(d[27]), "+f"(d[28]), "+f"(d[29]), "+f"(d[30]), "+f"(d[31]),
          "+f"(d[32]), "+f"(d[33]), "+f"(d[34]), "+f"(d[35]), "+f"(d[36]), "+f"(d[37]), "+f"(d[38]), "+f"(d[39]),
          "+f"(d[40]), "+f"(d[41]), "+f"(d[42]), "+f"(d[43]), "+f"(d[44]), "+f"(d[45]), "+f"(d[46]), "+f"(d[47]),
          "+f"(d[48]), "+f"(d[49]), "+f"(d[50]), "+f"(d[51]), "+f"(d[52]), "+f"(d[53]), "+f"(d[54]), "+f"(d[55]),
          "+f"(d[56]), "+f"(d[57]), "+f"(d[58]), "+f"(d[59]), "+f"(d[60]), "+f"(d[61]), "+f"(d[62]), "+f"(d[63]),
          "+f"(d[64]), "+f"(d[65]), "+f"(d[66]), "+f"(d[67]), "+f"(d[68]), "+f"(d[69]), "+f"(d[70]), "+f"(d[71]),
          "+f"(d[72]), "+f"(d[73]), "+f"(d[74]), "+f"(d[75]), "+f"(d[76]), "+f"(d[77]), "+f"(d[78]), "+f"(d[79]),
          "+f"(d[80]), "+f"(d[81]), "+f"(d[82]), "+f"(d[83])
        : "r"(da), "r"(db), "r"(accumulate), "n"(TA), "n"(TB), "n"(HA), "n"(HB));
}

template <uint32_t HB>
__device__ __forceinline__ void wgmma_rs_n168(float (&d)[84], uint32_t a0, uint32_t a1, uint32_t db) {
    asm volatile("{\n.reg .b64 b;\nmov.b64 b, {%86, %88};\n"
        "wgmma.mma_async.sync.aligned.m64n168k16.f32.bf16.bf16 {"
        "%0, %1, %2, %3, %4, %5, %6, %7, %8, %9, %10, %11, %12, %13, %14, %15, "
        "%16, %17, %18, %19, %20, %21, %22, %23, %24, %25, %26, %27, %28, %29, %30, %31, "
        "%32, %33, %34, %35, %36, %37, %38, %39, %40, %41, %42, %43, %44, %45, %46, %47, "
        "%48, %49, %50, %51, %52, %53, %54, %55, %56, %57, %58, %59, %60, %61, %62, %63, "
        "%64, %65, %66, %67, %68, %69, %70, %71, %72, %73, %74, %75, %76, %77, %78, %79, "
        "%80, %81, %82, %83"
        "}, {%84, %85, %87, %87}, b, 1, 1, 1, 0;\n}\n"
        : "+f"(d[0]), "+f"(d[1]), "+f"(d[2]), "+f"(d[3]), "+f"(d[4]), "+f"(d[5]), "+f"(d[6]), "+f"(d[7]),
          "+f"(d[8]), "+f"(d[9]), "+f"(d[10]), "+f"(d[11]), "+f"(d[12]), "+f"(d[13]), "+f"(d[14]), "+f"(d[15]),
          "+f"(d[16]), "+f"(d[17]), "+f"(d[18]), "+f"(d[19]), "+f"(d[20]), "+f"(d[21]), "+f"(d[22]), "+f"(d[23]),
          "+f"(d[24]), "+f"(d[25]), "+f"(d[26]), "+f"(d[27]), "+f"(d[28]), "+f"(d[29]), "+f"(d[30]), "+f"(d[31]),
          "+f"(d[32]), "+f"(d[33]), "+f"(d[34]), "+f"(d[35]), "+f"(d[36]), "+f"(d[37]), "+f"(d[38]), "+f"(d[39]),
          "+f"(d[40]), "+f"(d[41]), "+f"(d[42]), "+f"(d[43]), "+f"(d[44]), "+f"(d[45]), "+f"(d[46]), "+f"(d[47]),
          "+f"(d[48]), "+f"(d[49]), "+f"(d[50]), "+f"(d[51]), "+f"(d[52]), "+f"(d[53]), "+f"(d[54]), "+f"(d[55]),
          "+f"(d[56]), "+f"(d[57]), "+f"(d[58]), "+f"(d[59]), "+f"(d[60]), "+f"(d[61]), "+f"(d[62]), "+f"(d[63]),
          "+f"(d[64]), "+f"(d[65]), "+f"(d[66]), "+f"(d[67]), "+f"(d[68]), "+f"(d[69]), "+f"(d[70]), "+f"(d[71]),
          "+f"(d[72]), "+f"(d[73]), "+f"(d[74]), "+f"(d[75]), "+f"(d[76]), "+f"(d[77]), "+f"(d[78]), "+f"(d[79]),
          "+f"(d[80]), "+f"(d[81]), "+f"(d[82]), "+f"(d[83])
        : "r"(a0), "r"(a1), "r"(db), "r"(0), "n"(HB));
}

struct Ring {
    uint32_t slot, ph;
    __device__ __forceinline__ void next() { if (++slot == NSLOT) { slot = 0; ph ^= 1; } }
    __device__ __forceinline__ void next2() { ph ^= slot == 5; slot = __byte_perm(0x06030201u, 0x00040005u, 0x7770 + slot); }
};
struct Slot {
    uint32_t dst, bar, ph;
    __device__ __forceinline__ void next(uint32_t bars) {
        dst += SLOT; bar += 8;
        if (bar == bars + 8 * NSLOT) { dst -= NSLOT * SLOT; bar = bars; ph ^= 1; }
    }
};
__device__ __forceinline__ uint32_t xslot(int i) { return __byte_perm(0x04130e0cu, 0x00130e0cu, 0x7770 + i); }
__device__ __forceinline__ uint32_t wslot(int i) { return __byte_perm(0x06001510u, 0x00151009u, 0x7770 + i); }

constexpr uint32_t HI_SW = desc_hi(1024, 1);

struct Mma {
    uint32_t bars, rel;
    bool lead;
    int wg, half, w;
    Ring r;
    uint32_t prev;
    __device__ __forceinline__ void release_pair(uint32_t s) { if (lead) mbar_arrive4_remote(rel + B_EMPTY + 8 * s); }
    __device__ __forceinline__ void release(uint32_t s) { if (lead) mbar_arrive_n<4>(bars + B_EMPTY + 8 * s); }
    template <bool G1>
    __device__ __forceinline__ void run(float (&a)[56], int n, int first, int last, int lag, int accumulate, int ts, const __nv_bfloat16* bias = nullptr) {
#pragma unroll 1
        for (int i = 0; i < n; i++) {
            if (lag && i == (wg ? n - lag : -1)) {
                if (!G1) {
                    const uint32_t c0 = ld_u16(bias), c1 = ld_u16(bias + 8);
                    wg_wait<0>(); release(prev); last = first;
                    pin(a);
#pragma unroll
                    for (int k = 0; k < 56; k++) a[k] += bf_lo((k & 2) ? c1 : c0);
                    pin(a);
                }
                bar_sync(7, 256);
            }
            const bool seen = !G1 && last == first;
            const uint32_t s = seen ? n - 1 - i : r.slot;
            if (!seen) mbar_wait(bars + B_FULL + 8 * s, r.ph);
            if (G1) r.next(); else r.next2();
            if (!TSQ || !i) TS0(G1 ? 2 : 8, ts + i + wg * 68);
            const uint32_t dB = s * (SLOT >> 4), dA = dB + half * 512;
            wg_fence();
#pragma unroll
            for (int k = 0; k < 4; k++) {
                wgmma_n112<1, 1, HI_SW, desc_hi(G1 ? 256 : 1024, 0)>(a, dA + desc_lo(k * 2048, 8192), dB + desc_lo(16384 + k * (G1 ? SLAB : 256), 128), k > 0 || accumulate || i > 0);
                if (k == 1) {
                    wg_commit(); wg_wait<1>();
                    if ((uint32_t)(i - first) < (uint32_t)(last - first)) release(prev);
                    if (G1 && lag && i == (wg ? -1 : n - 1)) bar_arrive(7, 256);
                    if (TSQ && i) TS0(G1 ? 2 : 8, ts + i + wg * 68);
                }
            }
            wg_commit();
            prev = s;
        }
    }
    __device__ __forceinline__ void run_o(float (&a)[56]) {
#pragma unroll 1
        for (int i = 0; i < 2; i++) {
            const uint32_t s = r.slot, dB = s * (SLOT >> 4), dA = dB + half * (HALF >> 4);
            mbar_wait(bars + B_FULL + 8 * s, r.ph);
            TS0(8, 48 + 2 * i + wg * 68);
            wg_fence();
#pragma unroll
            for (int k = 0; k < 7; k++) {
                if (k == 3) { mbar_wait(bars + B_FULL + 8 * s + 8, r.ph); wg_fence(); }
                wgmma_n112<0, 1, desc_hi(128, 0), desc_hi(256, 0)>(a, dA + desc_lo(k * 2048 + (k > 3) * (SLOT - HALF), k == 3 ? SLOT - 6144 : 1024),
                                                                   dB + desc_lo(16384 + k * SLAB + (k > 2) * (SLOT - 3 * SLAB), 128), k > 0 || i > 0);
                if (k & 1) wg_commit();
                if (k == 1) { wg_wait<1>(); if (i) release(prev); }
                if (k == 5) { wg_wait<1>(); release(s); }
            }
            wg_commit();
            prev = s + 1;
            r.slot++; r.next2();
        }
    }
};

__global__ void __cluster_dims__(2, 1, 1) __launch_bounds__(NTHREADS, 1)
fused_kernel(const __nv_bfloat16* __restrict__ x, const __nv_bfloat16* __restrict__ b1, const __nv_bfloat16* __restrict__ b2, const __nv_bfloat16* __restrict__ wo, __nv_bfloat16* out, Scratch* G,
             const __nv_bfloat16* __restrict__ w1,
             const __grid_constant__ Params P) {
    extern __shared__ __align__(1024) uint8_t smem[];
    const uint32_t sbase = (uint32_t)__cvta_generic_to_shared(smem);
    const uint32_t bars = sbase + OFF_BAR;
    const uint32_t rank = blockIdx.x & 1, pr = blockIdx.x >> 1;
    const uint32_t row0 = blockIdx.x * 16;
    if (threadIdx.x == 32) prefetch_l2<TILEB>(x + row0 * D_);
    if (threadIdx.x == 0) {
        TS(15, 0);
        mbar_init(bars + B_ROW, 1);
        asm volatile("fence.mbarrier_init.release.cluster;" ::: "memory");
        bulk_load(sbase + OFF_Y, x + row0 * D_, TILEB, bars + B_ROW);
        mbar_expect(bars + B_ROW, TILEB);
        TS(1, 97);
    }
    const int lane = threadIdx.x & 31;
    const int warp = __shfl_sync(~0u, threadIdx.x >> 5, 0), w = warp & 3;
    if (elect()) {
        const uint32_t first = bars + warp * 24, count = warp < 7 ? 1 : warp < 9 ? 18 - 2 * warp : 16;
#pragma unroll
        for (int i = 0; i < 3; i++) mbar_init(first + 8 * i, count);
        asm volatile("fence.mbarrier_init.release.cluster;" ::: "memory");
    }
    __syncwarp();
    asm volatile("barrier.cluster.arrive.relaxed.aligned;" ::: "memory");
    const uint32_t pv = pr < 4 ? pr * 8 + 36 : pr - 4 + (max((int)pr - 33, 0) * 37 >> 8);
    const uint32_t gp = (pv + 4) & 7, hp = pv >> 3;
    const uint32_t tb = gp * 2 + rank, c = hp * 16 + tb;
    const bool has_g1 = gp > 0;
    const uint32_t nt1 = hp & 3, ft = max((int)gp - 1, 0) * 2 + (hp >> 2);
    const uint32_t nt2 = (hp & 1) * 2 + rank, mt = (gp & 3) * 4 + (hp >> 1), ks = gp >> 2;
    asm volatile("barrier.cluster.wait.aligned;" ::: "memory");

    if (warp == 8) {
        uint32_t kw = (gp & 1) * 192, kx;
        if (elect()) {
            mbar_expect(bars + B_QFULL, WSLOT);
            tma3d(sbase + xslot(0) * 8192, &P.tmX, bars + B_FULL, 0, tb * 64, 0);
            tma3d_pair(sbase + wslot(0) * 8192 + rank * 12288, &P.tmWqkv, bars + B_QFULL, (hp * 56) & ~15, rank * 32, 0);
            TS(1, 23);
            asm volatile("prefetch.tensormap [%0];\nprefetch.tensormap [%1];\nprefetch.tensormap [%2];" ::"l"(&P.tmW1), "l"(&P.tmW2), "l"(&P.tmOut) : "memory");
            uint32_t due = (uint32_t)clock() + PACE, ep = ld_relaxed(G->epoch[c]);
            uint32_t spins = sbase == (rank << 24 | SMEM0) ? 0 : SPIN_LIMIT;
#pragma unroll 1
            for (int i = 1; i < 8; i++) {
                kx = kw; kw += 64;
                if (i >= 5) mbar_wait_bounded(bars + B_QEMPTY + 8 * (i - 5), 0, spins);
                else { while ((int)((uint32_t)clock() - due) < 0) {} due += PACE; }
                if (kw == D_) kw = 64;
                if (i < 4) kx = kw;
                const int ix = i - (i > 4);
                if (i < 7) mbar_expect(bars + B_QFULL + 8 * i, WSLOT);
                if (i != 4) tma3d(sbase + xslot(ix) * 8192, &P.tmX, bars + B_FULL + 8 * ix, kx, tb * 64, 0);
                if (i & (i >> 2)) mbar_wait_bounded(bars + B_CS - 20 + 4 * i, 0, spins);
                if (i < 7) tma3d_pair(sbase + wslot(i) * 8192 + rank * 12288, &P.tmWqkv, bars + B_QFULL + 8 * i, (hp * 56) & ~15, kw + rank * 32, 0);
            }
            ep++;
            Slot r{sbase, bars, 0};
            if (has_g1) {
                const uint8_t* src = G->H[nt1][rank * 16];
                const int row = rank * 1024;
                mbar_expect(bars + B_FULL, 16384 + TILEB);
                tma3d(sbase, &P.tmW1, bars + B_FULL, 0, row, ft * 2);
                wait_flag(G->flag[2 + rank * 2], 20 * ep, spins);
                TS(1, 16);
#pragma unroll 1
                for (int j = 64;; j += 64) {
                    bulk_load(r.dst + 16384, src, TILEB, r.bar + B_FULL);
                    src += TILEB;
                    r.next(bars);
                    if (j == 1024) break;
                    mbar_wait_bounded(r.bar + B_EMPTY, r.ph, spins);
                    if (j < 14 * 64) TS(2, 146 + j / 64);
                    mbar_expect(r.bar + B_FULL, 16384 + TILEB);
                    tma3d(r.dst, &P.tmW1, r.bar + B_FULL, 0, row + j, ft * 2);
                }
                mbar_arrive(bars + B_FULL + 48); mbar_arrive_n<16>(bars + B_EMPTY + 48);
#pragma unroll
                for (int i = 0; i < 4; i++) mbar_expect(bars + B_X + 8 * i, (i & 1) ? 3072 : 4096);
            } else {
                due = (uint32_t)clock();
                const __nv_bfloat16* at = w1 + (rank * 1024 + PF0 * 64 + hp * 8) * F_;
#pragma unroll 1
                for (int j = PF0; j < PF1 + 16 - PF2; j++) {
                    while ((int)((uint32_t)clock() - due) < 0) {}
                    prefetch_l2<16 * F_>(at);
                    due += j == PF1 - 1 ? PF + PFD : PF;
                    at += j == PF1 - 1 ? (PF2 - PF1 + 1) * 64 * F_ : 64 * F_;
                }
            }
            const uint8_t *so = G->O[mt][ks * 4], *sw = G->Wo[nt2][ks * 4];
            wait_flag2(G->flag[16 + mt], 8 * ep, G->flag[0], 16 * ep, spins);
            TS(4, 18);
#pragma unroll 1
            for (int j = 0; j < 4 * TILEB; j += TILEB) {
                mbar_wait_bounded(r.bar + B_EMPTY, r.ph, spins);
                mbar_expect(r.bar + B_QFULL, TILEB);
                bulk_load(r.dst, so + j, TILEB, r.bar + B_QFULL);
                bulk_load(r.dst + 16384, sw + j, (r.bar & 8) ? TILEB : 3 * SLAB, r.bar + B_FULL);
                r.next(bars);
            }
            Ring q{has_g1 ? 2u : 6u, has_g1}, p{q.slot, !has_g1};
#pragma unroll 1
            for (int j = 0; j < 14 * 128; j += 128) {
                mbar_wait_bounded(bars + B_EMPTY + 8 * q.slot, q.ph, spins);
                if (LEADW && j >= LEADW * 128 && j < LEADN * 128) { mbar_wait_bounded(bars + B_FULL + 8 * p.slot, p.ph, spins); p.next2(); }
                TS(8, 176 + j / 128);
                tma3d(sbase + q.slot * SLOT, &P.tmW2, bars + B_FULL + 8 * q.slot, 0, ks * 896 + j - (j < 896 ? 0 : 832), mt * 2);
                q.next2();
            }
            mbar_wait_bounded(bars + B_END, 0, spins);
        }
    } else if (warp > 8) {
        const uint32_t ep = ld_relaxed(G->epoch[c]) + 1;
        uint32_t spins = 0, bad;
        {
            uint2* cs = G->colsum[hp][0];
            const int i0 = threadIdx.x - 288, j0 = i0 - (hp & 1) * 4;
            const uint32_t at_cs = __shfl_sync(~0u, (hp * 768 + i0 + ((j0 & 92) == 28 ? (j0 & 32 ? 28 : 56) : 0)) * 8, lane);
            const uint32_t at_st = __shfl_sync(~0u, (tb * 64 + (i0 & 63)) * 16, lane), to_st = __shfl_sync(~0u, sbase + i0 * 16, lane);
            if (w == 2) {
                bar_sync(6, 288);
                TS(1, 8);
                stg1((uint32_t*)(G->stat + row0) + lane, tag(__float_as_uint(lds1f(sbase + OFF_ST + lane * 4)), ~lane & 1, ep));
                if (elect()) {
                    fence_async_shared();
#pragma unroll
                    for (int i = 0; i < 4; i++) bulk_store(G->H[i][0] + row0 * (SLAB / 16), sbase + OFF_X + i * HSTG, SLAB);
                    bulk_flush();
                    TS(1, 99);
                    signal(G->flag[2 + (row0 >> 10) * 2 + ((row0 & 1023) >= 320)]);
                }
                __syncwarp();
            } else {
                const uint32_t word = rank * 16 + (w & 2) * 4 + (lane & 7), done = mapa(bars + B_CS, rank ^ (lane & 1));
                const uint32_t from = (sbase + word * 4 + (gp >> 2) * 12288 + (gp & 2) * 1024) ^ ((lane >> 3) * 288);
                auto swz = [](uint32_t a) { return a ^ ((a >> 3) & 0x70); };
                const uint32_t lin = sbase + lane * 128 + (hp & 1) * 16, f0 = swz(lin + 80) + 8192, f1 = swz(lin + 96) + 8192, to = swz(lin + 112);
                float s[6] = {};
#pragma unroll 1
                for (int i = 0; i < 7; i++) {
                    const uint32_t o = wslot(i) * 8192, a0 = from + o, a1 = a0 ^ 144;
                    mbar_wait(bars + B_QFULL + 8 * i, 0);
                    if (i < 2 && w == 1) TS(1, 140 + i);
                    if ((i ^ (w >> 1)) & 1) {
                        const uint4 v0 = lds4(f0 + o), v1 = lds4(f1 + o), v2 = lds4(f0 + o + 12288), v3 = lds4(f1 + o + 12288);
                        sts4(to + o, v0); sts4(to + o + 4096, v1); sts4(to + o + 12288, v2); sts4(to + o + 16384, v3);
                        fence_async_shared();
                        __syncwarp();
                        if (elect()) mbar_expect(bars + B_FULL + 8 * i, 16384);
                    }
                    if (i > 3 || i < (gp & 1)) continue;
                    if (w == 1) TS(1, 66);
                    uint32_t v[12];
#pragma unroll
                    for (int k = 0; k < 12; k++) v[k] = __float_as_uint(lds1f(((k & 1) ? a1 : a0) + (k & 2) * 512 + (k >> 2) * 4096));
#pragma unroll
                    for (int k = 0; k < 12; k++) { s[(k >> 2) * 2] += bf_lo(v[k]); s[(k >> 2) * 2 + 1] += bf_hi(v[k]); }
                    __syncwarp();
                    if ((i & 1) && lane < 2) mbar_arrive_remote(done + (i & 2) * 4);
                    if (i < 3) continue;
#pragma unroll
                    for (int k = 0; k < 6; k++) { s[k] += __shfl_xor_sync(~0u, s[k], 8); s[k] += __shfl_xor_sync(~0u, s[k], 16); }
                    const float s0 = lane < 8 ? s[0] : lane < 16 ? s[2] : s[4], s1 = lane < 8 ? s[1] : lane < 16 ? s[3] : s[5];
                    if (lane < 24) cs[gp * 96 + (lane >> 3) * 32 + word] = make_uint2(tag(__float_as_uint(s0), 1, ep), __float_as_uint(s1));
                    if (w == 1) TS(1, 24);
                }
            }
            bar_sync(1, 96);
            if (w == 1) TS(1, 98);
            uint4 sv;
            float f[2];
            do {
                uint2 u[8];
#pragma unroll
                for (int i = 0; i < 8; i++) u[i] = ld_relaxed2((const uint8_t*)G->colsum + at_cs + i * 768);
                sv = ld_relaxed4((const uint8_t*)G->stat + at_st);
#pragma unroll
                for (int e = 0; e < 2; e++) {
                    float g[4];
#pragma unroll
                    for (int i = 0; i < 4; i++) g[i] = __uint_as_float(e ? u[2 * i].y : u[2 * i].x) + __uint_as_float(e ? u[2 * i + 1].y : u[2 * i + 1].x);
                    f[e] = (g[0] + g[1]) + (g[2] + g[3]);
                }
                bad = or_diff(or_diff(u[0].x ^ ep, u[1].x, ep), u[2].x, ep) | or_diff(or_diff(u[3].x ^ ep, u[4].x, ep), u[5].x, ep) | or_diff(or_diff(u[6].x ^ ep, u[7].x, ep), sv.x, ep);
                if (bad & 1) TS(1, 3);
            } while (bad & 1);
            if (w < 3) sts4(to_st + OFF_ST, sv);
#pragma unroll
            for (int e = 0; e < 2; e++) {
                const uint32_t hi = pack2(f[e], f[e]);
                sts4(to_st + i0 * 16 + OFF_X + e * 16, make_uint4(hi, pack2(f[e] - bf_hi(hi), f[e] - bf_hi(hi)), 0, 0));
            }
            sts1(bars + 8 * NBAR, ep);
            fence_async_shared();
            __syncwarp();
            bar_arrive(8, 224); bar_arrive(9, 224);
            TS(1, 90 + w);
        }
        block_end();
        const uint8_t* src = G->U[nt2][ks * 14];
        if (w < 3) {
            if (w == 1) {
                if (elect()) {
                    wait_flag(G->flag[3 + rank * 2], 44 * ep, spins);
                    mbar_arrive_n<16>(bars + B_EMPTY + 8 * 5);
                    TS(1, 96);
                }
                __syncwarp();
                if (!has_g1) { bar_sync(5, 288); if (elect()) signal(G->flag[0]); __syncwarp(); TS(2, 26); }
            }
            mbar_wait(bars + B_HALO, 0);
            uint32_t slot = (has_g1 ? 16 % NSLOT : 0) + w - 1, ph = ~0u;
#pragma unroll 1
            for (int i = w - 1; i < 18;) {
                const uint32_t d0 = sbase + slot * SLOT + (i < 4 ? 0 : 16384), landed = bars + B_QFULL + 8 * slot;
                mbar_wait(landed, (ph >> slot) & 1);
                ph ^= 1 << slot;
                if (i < 8) TS(4, 82 + i);
                if (i >= 4) TS(8, 156 + i);
                bad = 0;
#pragma unroll
                for (int k = 0; k < 14; k++) bad = or_diff(bad, __float_as_uint(lds1f(d0 + k * 1024 + lane * 32 + (lane >> 2) * 4)), ep);
                if (__any_sync(~0u, bad & 1)) {
                    if (elect()) {
                        const uint8_t* cur = (i < 4 ? G->O[mt][ks * 4] : src - 4 * TILEB) + i * TILEB;
                        fence_async_shared();
                        mbar_expect(landed, TILEB);
                        bulk_load(d0, cur, TILEB, landed);
                    }
                    TS(4, i < 4 ? 94 : 95);
                } else {
                    if (elect()) mbar_expect(landed + (B_FULL - B_QFULL), i < 4 ? (2 + w) * SLAB : 16384);
                    i += __byte_perm(0x03020202u, 0x00010202u, 0x7770 + slot);
                    slot = __byte_perm(0x05060302u, 0x00040100u, 0x7770 + slot);
                }
            }
        } else {
            bar_sync(3, 288);
            __nanosleep(HALO_NS);
            uint4 v[7];
            do {
                bad = 0;
#pragma unroll
                for (int i = 0; i < 7; i++) { v[i] = ld_relaxed4(G->halo[c - (tb > 0)] + i * 512 + lane * 16); bad = or_diff(bad, v[i].x, ep); }
            } while (bad & 1);
#pragma unroll
            for (int i = 0; i < 7; i++) sts4(sbase + OFF_X + i * 512 + lane * 16, v[i]);
            __syncwarp();
            if (elect()) mbar_arrive(bars + B_HALO);
            TS(2, 21);
            bar_sync(2, 160);
            if (elect()) bulk_store(out + row0 * D_, sbase + OFF_Y, TILEB);
            __syncwarp();
            bar_sync(4, 288);
            if (elect()) {
                fence_async_shared();
                bulk_store(G->O[tb][hp], sbase + OFF_X, TILEB);
                bulk_flush();
                TS(2, 7);
                mbar_arrive_remote(mapa(bars + B_FREE, rank ^ 1));
                mbar_arrive(bars + B_FREE);
                hint(G->flag[16 + tb]);
                signal(G->flag[16 + (row0 >> 7)] + 1);
                TS(2, 22);
            }
            __syncwarp();
            uint32_t late = ~0u;
            const uint32_t* hints = G->flag[8 + nt2 * 2 + ks] + (lane & 7);
            mbar_wait(bars + (has_g1 ? B_X : B_FREE), 0);
            Ring r{has_g1 ? 2u : 6u, has_g1};
#pragma unroll 1
            for (int i = 0; i < 14; i++) {
                while ((late >> i) & 1) late = __ballot_sync(~0u, ld_relaxed(hints) != 2 * ep) & 127;
                if (i == 0) TS(4, 17);
                mbar_wait(bars + B_EMPTY + 8 * r.slot, r.ph);
                TS(8, 192 + i);
                if (elect()) {
                    mbar_expect(bars + B_QFULL + 8 * r.slot, TILEB);
                    bulk_load(sbase + r.slot * SLOT + 16384, src, TILEB, bars + B_QFULL + 8 * r.slot);
                }
                src += TILEB; r.next2();
            }
            if (elect()) {
                wait_flag(G->flag[16 + mt] + 1, 8 * ep, spins);
                mbar_arrive(bars + B_ROW);
                TS(2, 27);
                G->epoch[c][0] = ep;
            }
        }
    } else {
        const int wg = warp >> 2;
        Mma M{bars, mapa(bars, rank ^ (lane & 1)), (threadIdx.x & 127) < 2, wg, wg, w, Ring{0, 1}, 0};
        const int r = lane >> 2, t = lane & 3;
        uint32_t ep;
        const uint32_t kv = sbase + OFF_X + (w * 2 + wg) * KV + lane * 16;
        uint32_t q[8][2], k0[7], k1[14], v0[7];
        float f0, f1;
        {
            const int half = (lane >> 3) & 1, r16 = warp * 2 + (half ^ (lane >> 4)), nt = (lane >> 1) & 3;
            const uint32_t row = sbase + OFF_Y + r16 * (2 * D_), part = row + nt * 224 + half * 112 + (lane & 1) * 8;
            const uint32_t hb = sbase + OFF_X + nt * HSTG + r16 * 16 + (half ^ (row0 >> 10)) * (7 * 256) + (lane & 1) * 8;
            mbar_wait(bars + B_ROW, 0);
            TS0(1, 67);
            const float x0 = bf_lo(__float_as_uint(lds1f(row)));
            float d[28], m1 = 0.f, n1 = 0.f, m2 = 0.f, n2 = 0.f;
#pragma unroll
            for (int i = 0; i < 7; i++) {
                const uint2 v = lds2(part + i * 16);
#pragma unroll
                for (int k = 0; k < 2; k++) {
                    const float d0 = d[4 * i + 2 * k] = bf_lo(k ? v.y : v.x) - x0, d1 = d[4 * i + 2 * k + 1] = bf_hi(k ? v.y : v.x) - x0;
                    m1 += d0; n1 += d1; m2 = fmaf(d0, d0, m2); n2 = fmaf(d1, d1, n2);
                }
            }
            const float md = row_sum(m1 + n1) * (1.f / D_), var = fmaf(-md, md, row_sum(m2 + n2) * (1.f / D_)), nmean = -(x0 + md);
            const float rstd = rsq(var + LN_EPS);
            const float sc = rstd * rsq(fmaf(var * rstd, 4 * rstd, 4 * LN_EPS)), nb = -md * sc;
            sts2(sbase + OFF_ST + r16 * 8, __float_as_uint(rstd), pack2(nmean, nmean - bf_hi(pack2(nmean, nmean))));
#pragma unroll
            for (int i = 0; i < 7; i++) sts2(hb + i * 256, pack2(fmaf(d[4 * i], sc, nb), fmaf(d[4 * i + 1], sc, nb)), pack2(fmaf(d[4 * i + 2], sc, nb), fmaf(d[4 * i + 3], sc, nb)));
            TS0(1, 25);
            bar_arrive(6, 288);
            float acc[84];
#pragma unroll 1
            for (int kb = 0; kb < 7; kb++) {
                const bool held = kb == (wg ? 7 - HOLD : -1);
                if (held) { wg_wait<0>(); M.release_pair(4 - HOLD); TS0(1, 138); bar_sync(7, 256); }
                mbar_wait(bars + B_FULL + 8 * kb, 0);
                if (!TSQ || !kb) TS0(1, 68 + wg * 7 + kb);
                const uint32_t dA = (xslot(kb) + wg) * 512, dB = wslot(kb) * 512 + (hp & 1);
                wg_fence();
#pragma unroll
                for (int k = 0; k < 4; k++) {
                    wgmma_n168<0, 1, HI_SW, HI_SW>(acc, dA + desc_lo(k * 32, 16), dB + desc_lo((k & 1) * 2048 + (k >> 1) * 12288, 4096), k > 0 || kb > 0);
                    if (k == 0) { wg_commit(); wg_wait<1>(); if (kb > 0 && !held) M.release_pair(kb - 3); if (TSQ && kb) TS0(1, 68 + wg * 7 + kb); }
                }
                wg_commit();
            }
            if (wg == 0 && !LATEREL) bar_arrive(7, 256);
            if (wg == 0) TS0(1, 139);
            bar_sync(8 + wg, 224);
            if (wg == 0) TS0(1, 174);
            ep = __float_as_uint(lds1f(bars + 8 * NBAR));
            const uint32_t st = sbase + OFF_ST + (w * 32 + r * 2 + wg) * 8;
            const uint2 s0 = lds2(st), s1 = lds2(st + 128);
            const uint32_t a0 = t < 2 ? s0.y : 0, a1 = t < 2 ? s1.y : 0;
            wg_fence();
            wgmma_rs_n168<desc_hi(128, 0)>(acc, a0, a1, desc_lo(OFF_X, 0) + (hp & 1) * 8);
            wg_commit();
            if (wg == 0 && LATEREL) bar_arrive(7, 256);
            if (wg == 0) TS0(1, 175);
            wg_wait<1>();
            TS0(1, 190 + wg);
            M.release_pair(4);
            wg_wait<0>();
            pin(acc);
            TS0(1, 4 + 7 * wg);
            f0 = __uint_as_float(s0.x); f1 = __uint_as_float(s1.x);
#pragma unroll
            for (int g = 13; g >= 0; g--) {
                const float* a = acc + (g < 7 ? g + 8 : g < 12 ? g + 9 : g * 8 - 89) * 4;
                (g < 7 ? k0[g] : v0[g - 7]) = pack2(a[0] * f0, a[1] * f0);
                k1[g] = pack2(a[2] * f1, a[3] * f1);
            }
#pragma unroll
            for (int i = 0; i < 3; i++) stsm4(kv + 2 * KV + i * 512, k1[4 * i], k1[4 * i + 1], k1[4 * i + 2], k1[4 * i + 3]);
            stsm2(kv + 2 * KV + 1536, k1[12], k1[13]);
            if (w == 3) {
#pragma unroll
                for (int i = 0; i < 14; i++) stg1(G->halo[c] + wg * KV + lane * 4 + i * 128, tag(k1[i], t == 0, ep));
            }
            bar_arrive(3, 288);
#pragma unroll
            for (int g = 0; g < 7; g++) { q[g][0] = pack2(acc[4 * g], acc[4 * g + 1]); q[g][1] = pack2(acc[4 * g + 2], acc[4 * g + 3]); }
#pragma unroll
            for (int j = 0; j < 2; j++) { q[7][j] = t < 2 ? 0u : q[3][j]; q[3][j] = t < 2 ? q[3][j] : 0u; }
#pragma unroll
            for (int g = 0; g < 7; g++) v0[g] = transpose8(v0[g]);
        }
        TS0(1, 9 + 11 * wg);
        float a[56];
#pragma unroll
        for (int i = 0; i < 56; i++) asm volatile("" : "=f"(a[i]));
        if (__builtin_expect(!has_g1, 0)) {
            const int g = min(lane >> 1, 13), nt = rank * 2 + wg;
            const uint4* src = (const uint4*)(wo + (hp * 56 - (hp & 1) * 8 + w * 16 + (lane & 1)) * D_ + nt * 112) + g;
            uint4 v[8];
#pragma unroll
            for (int i = 0; i < 8; i++) v[i] = __ldg(src + i * (D_ / 4));
#pragma unroll
            for (int i = 0; i < 8; i++) ((uint4*)G->Wo[nt][hp])[w * (SLAB / 16) + g * 16 + (lane & 1) + 2 * i] = v[i];
            bar_arrive(5, 288);
        }
        M.run<true>(a, has_g1 ? PAUSE : 0, 1, 16, 0, 0, 32);
        const uint32_t bias0 = ld_u16(b1 + ft * 128 + warp * 16 + r), bias1 = ld_u16(b1 + ft * 128 + warp * 16 + r + 8);
        {
            uint32_t kp[8], vv[14];
            mbar_wait(bars + B_HALO, 0);
            ldsm4(kp, kv); ldsm4(kp + 4, kv + (lane < 24 ? 512 : 0));
            const uint32_t va = kv + 896 + (lane & 8) * (2 * KV / 8 - 16) - (lane & 16) * 8;
            ldsm4t(vv, va); ldsm4t(vv + 4, va + 256); ldsm4t(vv + 8, va + 512); ldsm2t(vv + 12, va + 768);
            const bool e0 = 2 * t > r, e1 = 2 * t >= r;
            const uint32_t mk = (e0 ? 0xffffu : 0u) | (e1 ? 0xffff0000u : 0u);
            wg_wait<0>();
            pin(a);
            if (has_g1) M.release(M.prev);
            TS0(2, 144 + wg);
            bar_arrive(10 + wg, 256);
            if (wg) bar_arrive(2, 160);
            block_end();
            TS0(2, 12 + 16 * wg);
            float sv[2][4];
#pragma unroll
            for (int h = 0; h < 2; h++) {
                const int ga = h * 4, gb = h * 4 + 1, gc = h * 4 + 2, gd = h * 4 + 3;
                float s[3][4] = {};
                mma16(s[0], q[ga][0], q[ga][1], q[gb][0], q[gb][1], kp[ga], kp[gb]);
                mma16(s[1], q[ga][0], q[ga][1], q[gb][0], q[gb][1], k0[ga], k0[gb]);
                mma16(s[2], q[ga][0], q[ga][1], q[gb][0], q[gb][1], k1[ga], k1[gb]);
                mma16(s[0], q[gc][0], q[gc][1], q[gd][0], q[gd][1], kp[gc], kp[gd]);
                mma16(s[1], q[gc][0], q[gc][1], q[gd][0], q[gd][1], k0[gc], k0[3]);
                mma16(s[2], q[gc][0], q[gc][1], q[gd][0], q[gd][1], k1[gc], k1[3]);
                if ((tb | w) == 0) s[0][0] = s[0][1] = -1e30f;
                sv[h][0] = e0 ? s[0][0] : s[1][0];
                sv[h][1] = e1 ? s[0][1] : s[1][1];
                sv[h][2] = e0 ? s[1][2] : s[2][2];
                sv[h][3] = e1 ? s[1][3] : s[2][3];
            }
            uint32_t pp[2][2];
#pragma unroll
            for (int i = 0; i < 4; i++) {
                float* v = &sv[i >> 1][(i & 1) * 2];
                const float f = ((i & 1) ? f1 : f0) * QK_SCALE, m = quad_max(fmaxf(v[0], v[1])) * f;
                const float p0 = ex2(fmaf(v[0], f, -m)), p1 = ex2(fmaf(v[1], f, -m));
                const float inv = rcp(quad_sum(p0 + p1));
                pp[i >> 1][i & 1] = pack2(p0 * inv, p1 * inv);
            }
            uint32_t o[8][2];
#pragma unroll
            for (int i = 0; i < 8; i++) {
                const int h = i >> 2, g = i - h;
                float d[4] = {};
                mma16(d, pp[h][0] & mk, 0u, 0u, pp[h][1] & ~mk, vv[2 * g], vv[2 * g + 1]);
                mma8(d, pp[h][0] & ~mk, pp[h][1] & mk, v0[g]);
                o[i][0] = pack2(d[0], d[1]); o[i][1] = pack2(d[2], d[3]);
            }
            if (t >= 2) { o[3][0] = o[4][0]; o[3][1] = o[4][1]; }
            const int word = wg * 4 + t - (w & 1) * 4 - (r >> 2);
#pragma unroll
            for (int i = 0; i < 8; i++) { o[i][0] = tag(o[i][0], word == 0, ep); o[i][1] = tag(o[i][1], word == 2, ep); }
            const uint32_t dst = sbase + OFF_X + (w >> 1) * HALF + ((w & 1) * 32 + (lane & 15) * 2 + wg) * 16 + (lane >> 4) * 1024;
            bar_sync(11 - wg, 256);
            stsm4(dst, o[0][0], o[0][1], o[1][0], o[1][1]);
            stsm4(dst + 2048, o[2][0], o[2][1], o[3][0], o[3][1]);
            stsm4(dst + 4096, o[5][0], o[5][1], o[6][0], o[6][1]);
            stsm2(dst + 6144, o[7][0], o[7][1]);
            bar_arrive(4, 288);
            TS0(2, 10 + 19 * wg);
        }
        if (has_g1) {
            M.run<true>(a, 16 - PAUSE, 1, 16, LAG1, 1, 32 + PAUSE);
            mbar_wait(bars + B_FREE, 0);
            const uint32_t xb = sbase + OFF_X + wg * 8192 + (threadIdx.x & 127) * 16, xbar = bars + B_X + 16 * wg;
            const uint32_t rx = mapa(xb, rank ^ 1), rbar = mapa(xbar, rank ^ 1);
            wg_wait<0>();
            pin(a);
            M.release(M.prev);
            TS0(4, 5 + wg);
#pragma unroll
            for (int i = 0; i < 3; i++)
                st_async4(rx + i * 2048, rbar + 8 * (i >> 1), pack2(a[28 + 8 * i], a[29 + 8 * i]), pack2(a[30 + 8 * i], a[31 + 8 * i]), pack2(a[32 + 8 * i], a[33 + 8 * i]), pack2(a[34 + 8 * i], a[35 + 8 * i]));
            const uint32_t tail = 6144 - (threadIdx.x & 127) * 8;
            st_async2(rx + tail, rbar + 8, pack2(a[52], a[53]), pack2(a[54], a[55]));
            uint8_t* dst = G->U[nt1][((ft >= 7) + wg) * 7 + ft] + rank * HALF + w * 256 + lane * 4;
            uint32_t u[14];
#pragma unroll
            for (int i = 0; i < 28; i++) a[i] = fmaf(bf_lo((i & 2) ? bias1 : bias0), 0.5f, a[i]);
#pragma unroll
            for (int i = 0; i < 14; i++) {
                if (i % 8 == 0) {
                    if (i) TS0(4, 134 + wg);
                    mbar_wait(xbar + i, 0);
                    TS0(4, (i ? 136 : 1) + wg);
#pragma unroll
                    for (int k = i / 4; k < i / 4 + 2; k++) {
                        if (k < 3) { const uint4 v = lds4(xb + k * 2048); u[4 * k] = v.x; u[4 * k + 1] = v.y; u[4 * k + 2] = v.z; u[4 * k + 3] = v.w; }
                        else { const uint2 v = lds2(xb + tail); u[12] = v.x; u[13] = v.y; }
                    }
                    if (i && lane < 2) mbar_arrive(bars + B_EMPTY + 48);
                }
                if (i == HINT && threadIdx.x == 0) hint(G->flag[8 + nt1 * 2] + ft + (ft >= 7) * 25);
                stg1(dst + (i >> 1) * 1024 + (i & 1) * 128, tag(pack2(gelu2(a[2 * i] + bf_lo(u[i])), gelu2(a[2 * i + 1] + bf_hi(u[i]))), (lane & 7) == w * 2 + (i & 1), ep));
            }
            TS0(4, 30 + wg);
        } else {
            mbar_wait(bars + B_FREE, 0);
            if (lane < 2) mbar_arrive(bars + B_EMPTY + 48);
        }
        M.half = wg ^ ks;
        const uint32_t orow = mt * 128 + M.half * 64 + w * 16;
        M.run_o(a);
        if (wg == 1) TS0(4, 13);
        M.run<false>(a, 14, 0, 14 - NSLOT, NSLOT + 1, 1, 52, b2 + orow + r);
        mbar_wait(bars + B_ROW, 1);
        const uint32_t stg = sbase + (4 + (w >> 1)) * SLOT + M.half * 8192 + (w & 1) * (PITCH * 16);
        const uint32_t sa = stg + (lane & 7) * PITCH + (lane >> 3) * 16;
        const bool one = elect();
        wg_wait<1>();
        if (wg == 0) bar_arrive(7, 256);
        wg_wait<0>();
        pin(a);
        TS0(8, 14 + wg);
#pragma unroll
        for (int h = 0; h < 2; h++) {
            const float* e = a + 2 * h;
#pragma unroll
            for (int i = 0; i < 3; i++)
                stsm4(sa + h * 8 * PITCH + i * 64, pack2(e[16 * i], e[16 * i + 1]), pack2(e[16 * i + 4], e[16 * i + 5]), pack2(e[16 * i + 8], e[16 * i + 9]), pack2(e[16 * i + 12], e[16 * i + 13]));
            stsm2(sa + h * 8 * PITCH + 192, pack2(e[48], e[49]), pack2(e[52], e[53]));
            fence_async_shared();
            __syncwarp();
            if (one) asm volatile("cp.reduce.async.bulk.tensor.3d.global.shared::cta.add.tile.bulk_group [%0, {%4, %2, %3}], [%1];" ::"l"(&P.tmOut), "r"(stg + h * 8 * PITCH), "r"(nt2), "r"(orow + 8 * h), "r"(0) : "memory");
        }
        if (one) {
            asm volatile("cp.async.bulk.commit_group;" ::: "memory");
            if (w == 0) mbar_arrive(bars + B_END);
            asm volatile("cp.async.bulk.wait_group.read 0;" ::: "memory");
        }
        TS0(15, wg ? 19 : 207);
        TSDUMP();
    }
}

typedef CUresult (*EncodeFn)(CUtensorMap*, CUtensorMapDataType, cuuint32_t, void*, const cuuint64_t*, const cuuint64_t*, const cuuint32_t*, const cuuint32_t*,
                             CUtensorMapInterleave, CUtensorMapSwizzle, CUtensorMapL2promotion, CUtensorMapFloatOOBfill);

void make_map(EncodeFn enc, CUtensorMap* tm, const void* base, bool swizzle, int d0, int d1, int d2, int s1, int s2, int b0, int b1, int b2) {
    const cuuint64_t dims[3] = {(cuuint64_t)d0, (cuuint64_t)d1, (cuuint64_t)d2}, strides[2] = {(cuuint64_t)s1 * 2, (cuuint64_t)s2 * 2};
    const cuuint32_t box[3] = {(cuuint32_t)b0, (cuuint32_t)b1, (cuuint32_t)b2}, es[3] = {1, 1, 1};
    enc(tm, CU_TENSOR_MAP_DATA_TYPE_BFLOAT16, d2 ? 3 : 2, (void*)base, dims, strides, box, es, CU_TENSOR_MAP_INTERLEAVE_NONE,
        swizzle ? CU_TENSOR_MAP_SWIZZLE_128B : CU_TENSOR_MAP_SWIZZLE_NONE, CU_TENSOR_MAP_L2_PROMOTION_L2_128B, CU_TENSOR_MAP_FLOAT_OOB_FILL_NONE);
}

}

extern "C" void kernel_launch(void* const* d_in, const int* in_sizes, int n_in, void* d_out, int out_size) {
    static EncodeFn enc = nullptr;
    static Scratch* scratch = nullptr;
    if (!enc) {
        void* fn = nullptr;
        cudaDriverEntryPointQueryResult qr;
        cudaGetDriverEntryPoint("cuTensorMapEncodeTiled", &fn, cudaEnableDefault, &qr);
        enc = (EncodeFn)fn;
        cudaGetSymbolAddress((void**)&scratch, g_s);
        cudaFuncSetAttribute(fused_kernel, cudaFuncAttributeMaxDynamicSharedMemorySize, SMEM_BYTES);
    }
    Params P;
    const __nv_bfloat16* x = (const __nv_bfloat16*)d_in[0];
    make_map(enc, &P.tmX, x, true, D_, S_ / 2, 2, 2 * D_, D_, 64, 64, 2);
    make_map(enc, &P.tmWqkv, d_in[1], true, D_, D_, 3, 3 * D_, D_, 64, 32, 3);
    make_map(enc, &P.tmW1, d_in[4], true, 64, S_, F_ / 64, F_, 64, 64, 64, 2);
    make_map(enc, &P.tmW2, d_in[6], true, 64, F_, S_ / 64, S_, 64, 64, 64, 2);
    make_map(enc, &P.tmOut, d_out, false, 112, 4, S_, 112, D_, PITCH / 2, 1, 8);
    fused_kernel<<<NCTA, NTHREADS, SMEM_BYTES, cudaStreamPerThread>>>(x, (const __nv_bfloat16*)d_in[5], (const __nv_bfloat16*)d_in[7], (const __nv_bfloat16*)d_in[2], (__nv_bfloat16*)d_out, scratch,
                                                                      (const __nv_bfloat16*)d_in[4], P);
}
```

```cpp
#include <cuda_runtime.h>
#include <cuda_bf16.h>
#include <cuda.h>
#include <stdint.h>

#define HALO_NS 300
#define HINT 5
#define HOLD 1
#define LATEREL 1
#define PF 400
#define PF0 2
#define PF1 8
#define LEADW 4
#define LEADN 7
#define TSQ 0
#define PF2 14
#define PFD 1500
#define PACE 580
#define PAUSE 8
#define LAG1 4

namespace {

constexpr int S_ = 2048, D_ = 448, F_ = 1792;
constexpr int NCTA = 128, NTHREADS = 384;
constexpr int NSLOT = 6, SLOT = 32768, WSLOT = 24576, TILEB = 14336, SLAB = 3584, HALF = 7168;
constexpr int KV = 1792, HSTG = SLAB + 32, PITCH = 240;
constexpr int OFF_X = NSLOT * SLOT;
constexpr int OFF_Y = OFF_X + 10 * KV;
constexpr int OFF_ST = OFF_Y + TILEB;
constexpr int OFF_BAR = OFF_ST + 1024;
constexpr int SMEM_BYTES = OFF_BAR + 1280;
constexpr uint32_t SMEM0 = 1024;
constexpr int B_QFULL = 0, B_FULL = 56, B_HALO = 128, B_X = 136, B_CS = 168, B_FREE = 192, B_END = 200, B_QEMPTY = 216, B_EMPTY = 232, B_ROW = 288, NBAR = 37;
constexpr float LN_EPS = 1e-5f, QK_SCALE = 0.1889822365046136f * 1.4426950408889634f;
constexpr int SPIN_LIMIT = 1 << 22;

struct Scratch {
    uint8_t H[4][32][TILEB];
    uint8_t U[4][28][TILEB];
    uint8_t O[16][8][TILEB];
    uint8_t Wo[4][8][TILEB];
    uint8_t halo[NCTA][2 * KV];
    uint2 stat[S_];
    uint2 colsum[8][8][96];
    uint32_t flag[32][32];
    uint32_t epoch[NCTA][32];
};
__device__ __align__(1024) Scratch g_s;

#define TS(g, i)
#define TS0(g, i)
#define TSDUMP()

struct Params {
    CUtensorMap tmX, tmWqkv, tmW1, tmW2, tmOut;
};

__device__ __forceinline__ bool elect() {
    uint32_t p;
    asm volatile("{\n.reg .pred p;\nelect.sync _|p, 0xffffffff;\nselp.u32 %0, 1, 0, p;\n}" : "=r"(p));
    return p;
}
__device__ __forceinline__ void mbar_init(uint32_t b, uint32_t c) { asm volatile("mbarrier.init.shared::cta.b64 [%0], %1;" ::"r"(b), "r"(c) : "memory"); }
__device__ __forceinline__ void mbar_expect(uint32_t b, uint32_t tx) { asm volatile("mbarrier.arrive.expect_tx.shared::cta.b64 _, [%0], %1;" ::"r"(b), "r"(tx) : "memory"); }
__device__ __forceinline__ void mbar_arrive(uint32_t b) { asm volatile("mbarrier.arrive.shared::cta.b64 _, [%0];" ::"r"(b) : "memory"); }
template <int N> __device__ __forceinline__ void mbar_arrive_n(uint32_t b) { asm volatile("mbarrier.arrive.shared::cta.b64 _, [%0], %1;" ::"r"(b), "n"(N) : "memory"); }
__device__ __forceinline__ void mbar_arrive4_remote(uint32_t b) { asm volatile("mbarrier.arrive.shared::cluster.b64 _, [%0], 4;" ::"r"(b) : "memory"); }
__device__ __forceinline__ void mbar_arrive_remote(uint32_t b) { asm volatile("mbarrier.arrive.shared::cluster.b64 _, [%0];" ::"r"(b) : "memory"); }
#define MBAR_WAIT_ASM(SEM) \
    asm volatile("{\n.reg .pred p;\nWAIT:\nmbarrier.try_wait.parity" SEM ".shared::cta.b64 p, [%0], %1;\n@!p bra WAIT;\n}" ::"r"(b), "r"(parity) : "memory")
__device__ __forceinline__ void mbar_wait(uint32_t b, uint32_t parity) { MBAR_WAIT_ASM(""); }
__device__ __forceinline__ void mbar_wait_bounded(uint32_t b, uint32_t parity, uint32_t& n) {
    asm volatile("{\n.reg .pred p;\nWAIT:\nadd.u32 %0, %0, 1;\nsetp.gt.u32 p, %0, %3;\n@p st.global.u32 [%4], %0;\n"
                 "mbarrier.try_wait.parity.shared::cta.b64 p, [%1], %2;\n@!p bra WAIT;\n}" : "+r"(n) : "r"(b), "r"(parity), "n"(SPIN_LIMIT), "l"(0ull) : "memory");
}
__device__ __forceinline__ uint32_t mapa(uint32_t a, uint32_t rank) { uint32_t r; asm("mapa.shared::cluster.u32 %0, %1, %2;" : "=r"(r) : "r"(a), "r"(rank)); return r; }
__device__ __forceinline__ void tma3d(uint32_t dst, const CUtensorMap* tm, uint32_t bar, int c0, int c1, int c2) {
    asm volatile("cp.async.bulk.tensor.3d.shared::cluster.global.mbarrier::complete_tx::bytes [%0], [%1, {%3, %4, %5}], [%2];" ::"r"(dst), "l"(tm), "r"(bar), "r"(c0), "r"(c1), "r"(c2) : "memory");
}
__device__ __forceinline__ void tma3d_pair(uint32_t dst, const CUtensorMap* tm, uint32_t bar, int c0, int c1, int c2) {
    asm volatile("cp.async.bulk.tensor.3d.shared::cluster.global.mbarrier::complete_tx::bytes.multicast::cluster [%0], [%1, {%3, %4, %5}], [%2], %6;" ::"r"(dst), "l"(tm), "r"(bar), "r"(c0), "r"(c1), "r"(c2), "h"((uint16_t)3) : "memory");
}
__device__ __forceinline__ void bulk_load(uint32_t dst, const void* src, uint32_t bytes, uint32_t bar) {
    asm volatile("cp.async.bulk.shared::cluster.global.mbarrier::complete_tx::bytes [%0], [%1], %2, [%3];" ::"r"(dst), "l"(src), "r"(bytes), "r"(bar) : "memory");
}
template <int BYTES> __device__ __forceinline__ void prefetch_l2(const void* p) { asm volatile("cp.async.bulk.prefetch.L2.global [%0], %1;" ::"l"(p), "n"(BYTES) : "memory"); }
__device__ __forceinline__ void bulk_store(void* dst, uint32_t src, uint32_t bytes) {
    asm volatile("cp.async.bulk.global.shared::cta.bulk_group [%0], [%1], %2;" ::"l"(dst), "r"(src), "r"(bytes) : "memory");
}
__device__ __forceinline__ uint32_t ld_u16(const void* p) { uint32_t v; asm volatile("ld.global.nc.u16 %0, [%1];" : "=r"(v) : "l"(p)); return v; }
__device__ __forceinline__ uint32_t ld_relaxed(const uint32_t* p) { uint32_t v; asm volatile("ld.relaxed.gpu.global.u32 %0, [%1];" : "=r"(v) : "l"(p) : "memory"); return v; }
__device__ __forceinline__ void bulk_flush() { asm volatile("cp.async.bulk.commit_group;\ncp.async.bulk.wait_group 0;" ::: "memory"); }
__device__ __forceinline__ void signal(uint32_t* flag) { asm volatile("fence.acq_rel.gpu;\nred.relaxed.gpu.global.add.u32 [%0], 1;" ::"l"(flag) : "memory"); }
__device__ __forceinline__ void hint(uint32_t* flag) { asm volatile("red.relaxed.gpu.global.add.u32 [%0], 1;" ::"l"(flag) : "memory"); }
__device__ __forceinline__ uint32_t tag(uint32_t v, uint32_t mask, uint32_t parity) { return (v & ~mask) | (parity & mask); }
__device__ __forceinline__ uint32_t or_diff(uint32_t acc, uint32_t v, uint32_t parity) { asm("lop3.b32 %0, %0, %1, %2, 0xf6;" : "+r"(acc) : "r"(v), "r"(parity)); return acc; }
__device__ __forceinline__ uint32_t or3(uint32_t a, uint32_t b, uint32_t c) { asm("lop3.b32 %0, %0, %1, %2, 0xfe;" : "+r"(a) : "r"(b), "r"(c)); return a; }
__device__ __forceinline__ uint4 ld_relaxed4(const void* p) {
    uint4 v;
    asm volatile("ld.relaxed.gpu.global.v4.u32 {%0, %1, %2, %3}, [%4];" : "=r"(v.x), "=r"(v.y), "=r"(v.z), "=r"(v.w) : "l"(p) : "memory");
    return v;
}
__device__ __forceinline__ uint2 ld_relaxed2(const void* p) { uint2 v; asm volatile("ld.relaxed.gpu.global.v2.u32 {%0, %1}, [%2];" : "=r"(v.x), "=r"(v.y) : "l"(p) : "memory"); return v; }
__device__ __forceinline__ void sts4(uint32_t a, uint4 v) { asm volatile("st.shared.v4.b32 [%0], {%1, %2, %3, %4};" ::"r"(a), "r"(v.x), "r"(v.y), "r"(v.z), "r"(v.w) : "memory"); }
__device__ __forceinline__ void sts1(uint32_t a, uint32_t v) { asm volatile("st.shared.b32 [%0], %1;" ::"r"(a), "r"(v) : "memory"); }
__device__ __forceinline__ void sts2(uint32_t a, uint32_t v0, uint32_t v1) { asm volatile("st.shared.v2.b32 [%0], {%1, %2};" ::"r"(a), "r"(v0), "r"(v1) : "memory"); }
__device__ __forceinline__ void stg1(void* p, uint32_t v) { asm volatile("st.global.b32 [%0], %1;" ::"l"(p), "r"(v) : "memory"); }
__device__ __forceinline__ void fence_async_shared() { asm volatile("fence.proxy.async.shared::cta;" ::: "memory"); }
#define BOUND "add.u32 %0, %0, 16;\nsetp.gt.u32 p, %0, %1;\n@p st.global.u32 [%2], %0;\n"
__device__ __forceinline__ void wait_flag(const uint32_t* p, uint32_t target, uint32_t& n) {
    asm volatile("{\n.reg .pred p;\n.reg .u32 v;\nPOLL:\n" BOUND "ld.acquire.gpu.global.u32 v, [%3];\nsetp.ne.u32 p, v, %4;\n@p bra POLL;\nfence.proxy.async.global;\n}"
                 : "+r"(n) : "n"(SPIN_LIMIT), "l"(0ull), "l"(p), "r"(target) : "memory");
}
__device__ __forceinline__ void wait_flag2(const uint32_t* h, uint32_t th, const uint32_t* p, uint32_t target, uint32_t& n) {
    asm volatile("{\n.reg .pred p;\n.reg .u32 u, v;\nPOLL:\n" BOUND "ld.relaxed.gpu.global.u32 u, [%3];\nld.acquire.gpu.global.u32 v, [%5];\nsetp.ne.u32 p, u, %4;\nsetp.ne.or.u32 p, v, %6, p;\n@p bra POLL;\nfence.proxy.async.global;\n}"
                 : "+r"(n) : "n"(SPIN_LIMIT), "l"(0ull), "l"(h), "r"(th), "l"(p), "r"(target) : "memory");
}
__device__ __forceinline__ void block_end() { asm volatile("{\n.reg .pred p;\n.reg .u32 t;\nAGAIN:\nmov.u32 t, %%clock;\nsetp.eq.u32 p, t, %0;\n@p bra AGAIN;\n}" ::"n"(0) : "memory"); }
__device__ __forceinline__ void bar_sync(int id, int n) { asm volatile("bar.sync %0, %1;" ::"r"(id), "r"(n) : "memory"); }
__device__ __forceinline__ void bar_arrive(int id, int n) { asm volatile("bar.arrive %0, %1;" ::"r"(id), "r"(n) : "memory"); }
__device__ __forceinline__ void wg_fence() { asm volatile("wgmma.fence.sync.aligned;" ::: "memory"); }
__device__ __forceinline__ void wg_commit() { asm volatile("wgmma.commit_group.sync.aligned;" ::: "memory"); }
template <int N> __device__ __forceinline__ void wg_wait() { asm volatile("wgmma.wait_group.sync.aligned %0;" ::"n"(N) : "memory"); }
template <int N> __device__ __forceinline__ void pin(float (&d)[N]) {
#pragma unroll
    for (int i = 0; i < N; i++) asm volatile("" : "+f"(d[i])::"memory");
}
__host__ __device__ constexpr uint32_t desc_hi(uint32_t sbo, uint32_t swz) { return (sbo >> 4) | (swz << 30); }
__host__ __device__ constexpr uint32_t desc_lo(uint32_t off, uint32_t lbo) { return ((SMEM0 + off) >> 4) | ((lbo >> 4) << 16); }
__device__ __forceinline__ uint32_t pack2(float lo, float hi) { uint32_t r; asm("cvt.rn.bf16x2.f32 %0, %1, %2;" : "=r"(r) : "f"(hi), "f"(lo)); return r; }
__device__ __forceinline__ float bf_lo(uint32_t v) { return __uint_as_float(v << 16); }
__device__ __forceinline__ float bf_hi(uint32_t v) { return __uint_as_float(v & 0xffff0000u); }
__device__ __forceinline__ void stsm4(uint32_t a, uint32_t r0, uint32_t r1, uint32_t r2, uint32_t r3) {
    asm volatile("stmatrix.sync.aligned.m8n8.x4.shared.b16 [%0], {%1, %2, %3, %4};" ::"r"(a), "r"(r0), "r"(r1), "r"(r2), "r"(r3) : "memory");
}
__device__ __forceinline__ void stsm2(uint32_t a, uint32_t r0, uint32_t r1) {
    asm volatile("stmatrix.sync.aligned.m8n8.x2.shared.b16 [%0], {%1, %2};" ::"r"(a), "r"(r0), "r"(r1) : "memory");
}
__device__ __forceinline__ uint4 lds4(uint32_t a) { uint4 v; asm volatile("ld.shared.v4.b32 {%0, %1, %2, %3}, [%4];" : "=r"(v.x), "=r"(v.y), "=r"(v.z), "=r"(v.w) : "r"(a) : "memory"); return v; }
__device__ __forceinline__ uint2 lds2(uint32_t a) { uint2 v; asm volatile("ld.shared.v2.b32 {%0, %1}, [%2];" : "=r"(v.x), "=r"(v.y) : "r"(a) : "memory"); return v; }
__device__ __forceinline__ float lds1f(uint32_t a) { float v; asm volatile("ld.shared.f32 %0, [%1];" : "=f"(v) : "r"(a) : "memory"); return v; }
__device__ __forceinline__ void ldsm4(uint32_t* r, uint32_t a) {
    asm volatile("ldmatrix.sync.aligned.m8n8.x4.shared.b16 {%0, %1, %2, %3}, [%4];" : "=r"(r[0]), "=r"(r[1]), "=r"(r[2]), "=r"(r[3]) : "r"(a) : "memory");
}
__device__ __forceinline__ void ldsm4t(uint32_t* r, uint32_t a) {
    asm volatile("ldmatrix.sync.aligned.m8n8.x4.trans.shared.b16 {%0, %1, %2, %3}, [%4];" : "=r"(r[0]), "=r"(r[1]), "=r"(r[2]), "=r"(r[3]) : "r"(a) : "memory");
}
__device__ __forceinline__ void ldsm2t(uint32_t* r, uint32_t a) {
    asm volatile("ldmatrix.sync.aligned.m8n8.x2.trans.shared.b16 {%0, %1}, [%2];" : "=r"(r[0]), "=r"(r[1]) : "r"(a) : "memory");
}
__device__ __forceinline__ uint32_t transpose8(uint32_t v) { uint32_t r; asm volatile("movmatrix.sync.aligned.m8n8.trans.b16 %0, %1;" : "=r"(r) : "r"(v)); return r; }
__device__ __forceinline__ void mma16(float (&c)[4], uint32_t a0, uint32_t a1, uint32_t a2, uint32_t a3, uint32_t b0, uint32_t b1) {
    asm volatile("mma.sync.aligned.m16n8k16.row.col.f32.bf16.bf16.f32 {%0, %1, %2, %3}, {%4, %5, %6, %7}, {%8, %9}, {%0, %1, %2, %3};"
                 : "+f"(c[0]), "+f"(c[1]), "+f"(c[2]), "+f"(c[3]) : "r"(a0), "r"(a1), "r"(a2), "r"(a3), "r"(b0), "r"(b1));
}
__device__ __forceinline__ void mma8(float (&c)[4], uint32_t a0, uint32_t a1, uint32_t b0) {
    asm volatile("mma.sync.aligned.m16n8k8.row.col.f32.bf16.bf16.f32 {%0, %1, %2, %3}, {%4, %5}, {%6}, {%0, %1, %2, %3};"
                 : "+f"(c[0]), "+f"(c[1]), "+f"(c[2]), "+f"(c[3]) : "r"(a0), "r"(a1), "r"(b0));
}
__device__ __forceinline__ void st_async4(uint32_t a, uint32_t bar, uint32_t v0, uint32_t v1, uint32_t v2, uint32_t v3) {
    asm volatile("st.async.weak.shared::cluster.mbarrier::complete_tx::bytes.v4.b32 [%0], {%2, %3, %4, %5}, [%1];" ::"r"(a), "r"(bar), "r"(v0), "r"(v1), "r"(v2), "r"(v3) : "memory");
}
__device__ __forceinline__ void st_async2(uint32_t a, uint32_t bar, uint32_t v0, uint32_t v1) {
    asm volatile("st.async.weak.shared::cluster.mbarrier::complete_tx::bytes.v2.b32 [%0], {%2, %3}, [%1];" ::"r"(a), "r"(bar), "r"(v0), "r"(v1) : "memory");
}
__device__ __forceinline__ float quad_max(float v) { v = fmaxf(v, __shfl_xor_sync(~0u, v, 1)); return fmaxf(v, __shfl_xor_sync(~0u, v, 2)); }
__device__ __forceinline__ float quad_sum(float v) { v += __shfl_xor_sync(~0u, v, 1); return v + __shfl_xor_sync(~0u, v, 2); }
__device__ __forceinline__ float ex2(float v) { float r; asm("ex2.approx.ftz.f32 %0, %1;" : "=f"(r) : "f"(v)); return r; }
__device__ __forceinline__ float rcp(float v) { float r; asm("rcp.approx.ftz.f32 %0, %1;" : "=f"(r) : "f"(v)); return r; }
__device__ __forceinline__ float rsq(float v) { float r; asm("rsqrt.approx.ftz.f32 %0, %1;" : "=f"(r) : "f"(v)); return r; }
__device__ __forceinline__ float gelu2(float v) {
    float z = v * fmaf(v * v, 8 * 0.044715f * 0.7978845608028654f, 2 * 0.7978845608028654f), t;
    asm("tanh.approx.f32 %0, %1;" : "=f"(t) : "f"(z));
    return fmaf(v, t, v);
}
__device__ __forceinline__ float row_sum(float v) {
    v = quad_sum(v); v += __shfl_xor_sync(~0u, v, 4);
    return v + __shfl_xor_sync(~0u, v, 24);
}

template <int TA, int TB, uint32_t HA, uint32_t HB>
__device__ __forceinline__ void wgmma_n112(float (&d)[56], uint32_t da, uint32_t db, int accumulate) {
    asm volatile("{\n.reg .pred p;\n.reg .b64 a, b;\nmov.b64 a, {%56, %61};\nmov.b64 b, {%57, %62};\nsetp.ne.b32 p, %58, 0;\n"
        "wgmma.mma_async.sync.aligned.m64n112k16.f32.bf16.bf16 {"
        "%0, %1, %2, %3, %4, %5, %6, %7, %8, %9, %10, %11, %12, %13, %14, %15, "
        "%16, %17, %18, %19, %20, %21, %22, %23, %24, %25, %26, %27, %28, %29, %30, %31, "
        "%32, %33, %34, %35, %36, %37, %38, %39, %40, %41, %42, %43, %44, %45, %46, %47, "
        "%48, %49, %50, %51, %52, %53, %54, %55"
        "}, a, b, p, 1, 1, %59, %60;\n}\n"
        : "+f"(d[0]), "+f"(d[1]), "+f"(d[2]), "+f"(d[3]), "+f"(d[4]), "+f"(d[5]), "+f"(d[6]), "+f"(d[7]),
          "+f"(d[8]), "+f"(d[9]), "+f"(d[10]), "+f"(d[11]), "+f"(d[12]), "+f"(d[13]), "+f"(d[14]), "+f"(d[15]),
          "+f"(d[16]), "+f"(d[17]), "+f"(d[18]), "+f"(d[19]), "+f"(d[20]), "+f"(d[21]), "+f"(d[22]), "+f"(d[23]),
          "+f"(d[24]), "+f"(d[25]), "+f"(d[26]), "+f"(d[27]), "+f"(d[28]), "+f"(d[29]), "+f"(d[30]), "+f"(d[31]),
          "+f"(d[32]), "+f"(d[33]), "+f"(d[34]), "+f"(d[35]), "+f"(d[36]), "+f"(d[37]), "+f"(d[38]), "+f"(d[39]),
          "+f"(d[40]), "+f"(d[41]), "+f"(d[42]), "+f"(d[43]), "+f"(d[44]), "+f"(d[45]), "+f"(d[46]), "+f"(d[47]),
          "+f"(d[48]), "+f"(d[49]), "+f"(d[50]), "+f"(d[51]), "+f"(d[52]), "+f"(d[53]), "+f"(d[54]), "+f"(d[55])
        : "r"(da), "r"(db), "r"(accumulate), "n"(TA), "n"(TB), "n"(HA), "n"(HB));
}

template <int TA, int TB, uint32_t HA, uint32_t HB>
__device__ __forceinline__ void wgmma_n168(float (&d)[84], uint32_t da, uint32_t db, int accumulate) {
    asm volatile("{\n.reg .pred p;\n.reg .b64 a, b;\nmov.b64 a, {%84, %89};\nmov.b64 b, {%85, %90};\nsetp.ne.b32 p, %86, 0;\n"
        "wgmma.mma_async.sync.aligned.m64n168k16.f32.bf16.bf16 {"
        "%0, %1, %2, %3, %4, %5, %6, %7, %8, %9, %10, %11, %12, %13, %14, %15, "
        "%16, %17, %18, %19, %20, %21, %22, %23, %24, %25, %26, %27, %28, %29, %30, %31, "
        "%32, %33, %34, %35, %36, %37, %38, %39, %40, %41, %42, %43, %44, %45, %46, %47, "
        "%48, %49, %50, %51, %52, %53, %54, %55, %56, %57, %58, %59, %60, %61, %62, %63, "
        "%64, %65, %66, %67, %68, %69, %70, %71, %72, %73, %74, %75, %76, %77, %78, %79, "
        "%80, %81, %82, %83"
        "}, a, b, p, 1, 1, %87, %88;\n}\n"
        : "+f"(d[0]), "+f"(d[1]), "+f"(d[2]), "+f"(d[3]), "+f"(d[4]), "+f"(d[5]), "+f"(d[6]), "+f"(d[7]),
          "+f"(d[8]), "+f"(d[9]), "+f"(d[10]), "+f"(d[11]), "+f"(d[12]), "+f"(d[13]), "+f"(d[14]), "+f"(d[15]),
          "+f"(d[16]), "+f"(d[17]), "+f"(d[18]), "+f"(d[19]), "+f"(d[20]), "+f"(d[21]), "+f"(d[22]), "+f"(d[23]),
          "+f"(d[24]), "+f"(d[25]), "+f"(d[26]), "+f"(d[27]), "+f"(d[28]), "+f"(d[29]), "+f"(d[30]), "+f"(d[31]),
          "+f"(d[32]), "+f"(d[33]), "+f"(d[34]), "+f"(d[35]), "+f"(d[36]), "+f"(d[37]), "+f"(d[38]), "+f"(d[39]),
          "+f"(d[40]), "+f"(d[41]), "+f"(d[42]), "+f"(d[43]), "+f"(d[44]), "+f"(d[45]), "+f"(d[46]), "+f"(d[47]),
          "+f"(d[48]), "+f"(d[49]), "+f"(d[50]), "+f"(d[51]), "+f"(d[52]), "+f"(d[53]), "+f"(d[54]), "+f"(d[55]),
          "+f"(d[56]), "+f"(d[57]), "+f"(d[58]), "+f"(d[59]), "+f"(d[60]), "+f"(d[61]), "+f"(d[62]), "+f"(d[63]),
          "+f"(d[64]), "+f"(d[65]), "+f"(d[66]), "+f"(d[67]), "+f"(d[68]), "+f"(d[69]), "+f"(d[70]), "+f"(d[71]),
          "+f"(d[72]), "+f"(d[73]), "+f"(d[74]), "+f"(d[75]), "+f"(d[76]), "+f"(d[77]), "+f"(d[78]), "+f"(d[79]),
          "+f"(d[80]), "+f"(d[81]), "+f"(d[82]), "+f"(d[83])
        : "r"(da), "r"(db), "r"(accumulate), "n"(TA), "n"(TB), "n"(HA), "n"(HB));
}

template <uint32_t HB>
__device__ __forceinline__ void wgmma_rs_n168(float (&d)[84], uint32_t a0, uint32_t a1, uint32_t db) {
    asm volatile("{\n.reg .b64 b;\nmov.b64 b, {%86, %88};\n"
        "wgmma.mma_async.sync.aligned.m64n168k16.f32.bf16.bf16 {"
        "%0, %1, %2, %3, %4, %5, %6, %7, %8, %9, %10, %11, %12, %13, %14, %15, "
        "%16, %17, %18, %19, %20, %21, %22, %23, %24, %25, %26, %27, %28, %29, %30, %31, "
        "%32, %33, %34, %35, %36, %37, %38, %39, %40, %41, %42, %43, %44, %45, %46, %47, "
        "%48, %49, %50, %51, %52, %53, %54, %55, %56, %57, %58, %59, %60, %61, %62, %63, "
        "%64, %65, %66, %67, %68, %69, %70, %71, %72, %73, %74, %75, %76, %77, %78, %79, "
        "%80, %81, %82, %83"
        "}, {%84, %85, %87, %87}, b, 1, 1, 1, 0;\n}\n"
        : "+f"(d[0]), "+f"(d[1]), "+f"(d[2]), "+f"(d[3]), "+f"(d[4]), "+f"(d[5]), "+f"(d[6]), "+f"(d[7]),
          "+f"(d[8]), "+f"(d[9]), "+f"(d[10]), "+f"(d[11]), "+f"(d[12]), "+f"(d[13]), "+f"(d[14]), "+f"(d[15]),
          "+f"(d[16]), "+f"(d[17]), "+f"(d[18]), "+f"(d[19]), "+f"(d[20]), "+f"(d[21]), "+f"(d[22]), "+f"(d[23]),
          "+f"(d[24]), "+f"(d[25]), "+f"(d[26]), "+f"(d[27]), "+f"(d[28]), "+f"(d[29]), "+f"(d[30]), "+f"(d[31]),
          "+f"(d[32]), "+f"(d[33]), "+f"(d[34]), "+f"(d[35]), "+f"(d[36]), "+f"(d[37]), "+f"(d[38]), "+f"(d[39]),
          "+f"(d[40]), "+f"(d[41]), "+f"(d[42]), "+f"(d[43]), "+f"(d[44]), "+f"(d[45]), "+f"(d[46]), "+f"(d[47]),
          "+f"(d[48]), "+f"(d[49]), "+f"(d[50]), "+f"(d[51]), "+f"(d[52]), "+f"(d[53]), "+f"(d[54]), "+f"(d[55]),
          "+f"(d[56]), "+f"(d[57]), "+f"(d[58]), "+f"(d[59]), "+f"(d[60]), "+f"(d[61]), "+f"(d[62]), "+f"(d[63]),
          "+f"(d[64]), "+f"(d[65]), "+f"(d[66]), "+f"(d[67]), "+f"(d[68]), "+f"(d[69]), "+f"(d[70]), "+f"(d[71]),
          "+f"(d[72]), "+f"(d[73]), "+f"(d[74]), "+f"(d[75]), "+f"(d[76]), "+f"(d[77]), "+f"(d[78]), "+f"(d[79]),
          "+f"(d[80]), "+f"(d[81]), "+f"(d[82]), "+f"(d[83])
        : "r"(a0), "r"(a1), "r"(db), "r"(0), "n"(HB));
}

struct Ring {
    uint32_t slot, ph;
    __device__ __forceinline__ void next() { if (++slot == NSLOT) { slot = 0; ph ^= 1; } }
    __device__ __forceinline__ void next2() { ph ^= slot == 5; slot = __byte_perm(0x06030201u, 0x00040005u, 0x7770 + slot); }
};
struct Slot {
    uint32_t dst, bar, ph;
    __device__ __forceinline__ void next(uint32_t bars) {
        dst += SLOT; bar += 8;
        if (bar == bars + 8 * NSLOT) { dst -= NSLOT * SLOT; bar = bars; ph ^= 1; }
    }
};
__device__ __forceinline__ uint32_t xslot(int i) { return __byte_perm(0x04130e0cu, 0x00130e0cu, 0x7770 + i); }
__device__ __forceinline__ uint32_t wslot(int i) { return __byte_perm(0x06001510u, 0x00151009u, 0x7770 + i); }

constexpr uint32_t HI_SW = desc_hi(1024, 1);

struct Mma {
    uint32_t bars, rel;
    bool lead;
    int wg, half, w;
    Ring r;
    uint32_t prev;
    __device__ __forceinline__ void release_pair(uint32_t s) { if (lead) mbar_arrive4_remote(rel + B_EMPTY + 8 * s); }
    __device__ __forceinline__ void release(uint32_t s) { if (lead) mbar_arrive_n<4>(bars + B_EMPTY + 8 * s); }
    template <bool G1>
    __device__ __forceinline__ void run(float (&a)[56], int n, int first, int last, int lag, int accumulate, int ts, const __nv_bfloat16* bias = nullptr) {
#pragma unroll 1
        for (int i = 0; i < n; i++) {
            if (lag && i == (wg ? n - lag : -1)) {
                if (!G1) {
                    const uint32_t c0 = ld_u16(bias), c1 = ld_u16(bias + 8);
                    wg_wait<0>(); release(prev); last = first;
                    pin(a);
#pragma unroll
                    for (int k = 0; k < 56; k++) a[k] += bf_lo((k & 2) ? c1 : c0);
                    pin(a);
                }
                bar_sync(7, 256);
            }
            const bool seen = !G1 && last == first;
            const uint32_t s = seen ? n - 1 - i : r.slot;
            if (!seen) mbar_wait(bars + B_FULL + 8 * s, r.ph);
            if (G1) r.next(); else r.next2();
            if (!TSQ || !i) TS0(G1 ? 2 : 8, ts + i + wg * 68);
            const uint32_t dB = s * (SLOT >> 4), dA = dB + half * 512;
            wg_fence();
#pragma unroll
            for (int k = 0; k < 4; k++) {
                wgmma_n112<1, 1, HI_SW, desc_hi(G1 ? 256 : 1024, 0)>(a, dA + desc_lo(k * 2048, 8192), dB + desc_lo(16384 + k * (G1 ? SLAB : 256), 128), k > 0 || accumulate || i > 0);
                if (k == 1) {
                    wg_commit(); wg_wait<1>();
                    if ((uint32_t)(i - first) < (uint32_t)(last - first)) release(prev);
                    if (G1 && lag && i == (wg ? -1 : n - 1)) bar_arrive(7, 256);
                    if (TSQ && i) TS0(G1 ? 2 : 8, ts + i + wg * 68);
                }
            }
            wg_commit();
            prev = s;
        }
    }
    __device__ __forceinline__ void run_o(float (&a)[56]) {
#pragma unroll 1
        for (int i = 0; i < 2; i++) {
            const uint32_t s = r.slot, dB = s * (SLOT >> 4), dA = dB + half * (HALF >> 4);
            mbar_wait(bars + B_FULL + 8 * s, r.ph);
            TS0(8, 48 + 2 * i + wg * 68);
            wg_fence();
#pragma unroll
            for (int k = 0; k < 7; k++) {
                if (k == 3) { mbar_wait(bars + B_FULL + 8 * s + 8, r.ph); wg_fence(); }
                wgmma_n112<0, 1, desc_hi(128, 0), desc_hi(256, 0)>(a, dA + desc_lo(k * 2048 + (k > 3) * (SLOT - HALF), k == 3 ? SLOT - 6144 : 1024),
                                                                   dB + desc_lo(16384 + k * SLAB + (k > 2) * (SLOT - 3 * SLAB), 128), k > 0 || i > 0);
                if (k & 1) wg_commit();
                if (k == 1) { wg_wait<1>(); if (i) release(prev); }
                if (k == 5) { wg_wait<1>(); release(s); }
            }
            wg_commit();
            prev = s + 1;
            r.slot++; r.next2();
        }
    }
};

__global__ void __cluster_dims__(2, 1, 1) __launch_bounds__(NTHREADS, 1)
fused_kernel(const __nv_bfloat16* __restrict__ x, const __nv_bfloat16* __restrict__ b1, const __nv_bfloat16* __restrict__ b2, const __nv_bfloat16* __restrict__ wo, __nv_bfloat16* out, Scratch* G,
             const __nv_bfloat16* __restrict__ w1,
             const __grid_constant__ Params P) {
    extern __shared__ __align__(1024) uint8_t smem[];
    const uint32_t sbase = (uint32_t)__cvta_generic_to_shared(smem);
    const uint32_t bars = sbase + OFF_BAR;
    const uint32_t rank = blockIdx.x & 1, pr = blockIdx.x >> 1;
    const uint32_t row0 = blockIdx.x * 16;
    if (threadIdx.x == 32) prefetch_l2<TILEB>(x + row0 * D_);
    if (threadIdx.x == 0) {
        TS(15, 0);
        mbar_init(bars + B_ROW, 1);
        asm volatile("fence.mbarrier_init.release.cluster;" ::: "memory");
        bulk_load(sbase + OFF_Y, x + row0 * D_, TILEB, bars + B_ROW);
        mbar_expect(bars + B_ROW, TILEB);
        TS(1, 97);
    }
    const int lane = threadIdx.x & 31;
    const int warp = __shfl_sync(~0u, threadIdx.x >> 5, 0), w = warp & 3;
    if (elect()) {
        const uint32_t first = bars + warp * 24, count = warp < 7 ? 1 : warp < 9 ? 18 - 2 * warp : 16;
#pragma unroll
        for (int i = 0; i < 3; i++) mbar_init(first + 8 * i, count);
        asm volatile("fence.mbarrier_init.release.cluster;" ::: "memory");
    }
    __syncwarp();
    asm volatile("barrier.cluster.arrive.relaxed.aligned;" ::: "memory");
    const uint32_t pv = pr < 4 ? pr * 8 + 36 : pr - 4 + (max((int)pr - 33, 0) * 37 >> 8);
    const uint32_t gp = (pv + 4) & 7, hp = pv >> 3;
    const uint32_t tb = gp * 2 + rank, c = hp * 16 + tb;
    const bool has_g1 = gp > 0;
    const uint32_t nt1 = hp & 3, ft = max((int)gp - 1, 0) * 2 + (hp >> 2);
    const uint32_t nt2 = (hp & 1) * 2 + rank, mt = (gp & 3) * 4 + (hp >> 1), ks = gp >> 2;
    asm volatile("barrier.cluster.wait.aligned;" ::: "memory");

    if (warp == 8) {
        uint32_t kw = (gp & 1) * 192, kx;
        if (elect()) {
            mbar_expect(bars + B_QFULL, WSLOT);
            tma3d(sbase + xslot(0) * 8192, &P.tmX, bars + B_FULL, 0, tb * 64, 0);
            tma3d_pair(sbase + wslot(0) * 8192 + rank * 12288, &P.tmWqkv, bars + B_QFULL, (hp * 56) & ~15, rank * 32, 0);
            TS(1, 23);
            asm volatile("prefetch.tensormap [%0];\nprefetch.tensormap [%1];\nprefetch.tensormap [%2];" ::"l"(&P.tmW1), "l"(&P.tmW2), "l"(&P.tmOut) : "memory");
            uint32_t due = (uint32_t)clock() + PACE, ep = ld_relaxed(G->epoch[c]);
            uint32_t spins = sbase == (rank << 24 | SMEM0) ? 0 : SPIN_LIMIT;
#pragma unroll 1
            for (int i = 1; i < 8; i++) {
                kx = kw; kw += 64;
                if (i >= 5) mbar_wait_bounded(bars + B_QEMPTY + 8 * (i - 5), 0, spins);
                else { while ((int)((uint32_t)clock() - due) < 0) {} due += PACE; }
                if (kw == D_) kw = 64;
                if (i < 4) kx = kw;
                const int ix = i - (i > 4);
                if (i < 7) mbar_expect(bars + B_QFULL + 8 * i, WSLOT);
                if (i != 4) tma3d(sbase + xslot(ix) * 8192, &P.tmX, bars + B_FULL + 8 * ix, kx, tb * 64, 0);
                if (i & (i >> 2)) mbar_wait_bounded(bars + B_CS - 20 + 4 * i, 0, spins);
                if (i < 7) tma3d_pair(sbase + wslot(i) * 8192 + rank * 12288, &P.tmWqkv, bars + B_QFULL + 8 * i, (hp * 56) & ~15, kw + rank * 32, 0);
            }
            ep++;
            Slot r{sbase, bars, 0};
            if (has_g1) {
                const uint8_t* src = G->H[nt1][rank * 16];
                const int row = rank * 1024;
                mbar_expect(bars + B_FULL, 16384 + TILEB);
                tma3d(sbase, &P.tmW1, bars + B_FULL, 0, row, ft * 2);
                wait_flag(G->flag[2 + rank * 2], 20 * ep, spins);
                TS(1, 16);
#pragma unroll 1
                for (int j = 64;; j += 64) {
                    bulk_load(r.dst + 16384, src, TILEB, r.bar + B_FULL);
                    src += TILEB;
                    r.next(bars);
                    if (j == 1024) break;
                    mbar_wait_bounded(r.bar + B_EMPTY, r.ph, spins);
                    if (j < 14 * 64) TS(2, 146 + j / 64);
                    mbar_expect(r.bar + B_FULL, 16384 + TILEB);
                    tma3d(r.dst, &P.tmW1, r.bar + B_FULL, 0, row + j, ft * 2);
                }
                mbar_arrive(bars + B_FULL + 48); mbar_arrive_n<16>(bars + B_EMPTY + 48);
#pragma unroll
                for (int i = 0; i < 4; i++) mbar_expect(bars + B_X + 8 * i, (i & 1) ? 3072 : 4096);
            } else {
                due = (uint32_t)clock();
                const __nv_bfloat16* at = w1 + (rank * 1024 + PF0 * 64 + hp * 8) * F_;
#pragma unroll 1
                for (int j = PF0; j < PF1 + 16 - PF2; j++) {
                    while ((int)((uint32_t)clock() - due) < 0) {}
                    prefetch_l2<16 * F_>(at);
                    due += j == PF1 - 1 ? PF + PFD : PF;
                    at += j == PF1 - 1 ? (PF2 - PF1 + 1) * 64 * F_ : 64 * F_;
                }
            }
            const uint8_t *so = G->O[mt][ks * 4], *sw = G->Wo[nt2][ks * 4];
            wait_flag2(G->flag[16 + mt], 8 * ep, G->flag[0], 16 * ep, spins);
            TS(4, 18);
#pragma unroll 1
            for (int j = 0; j < 4 * TILEB; j += TILEB) {
                mbar_wait_bounded(r.bar + B_EMPTY, r.ph, spins);
                mbar_expect(r.bar + B_QFULL, TILEB);
                bulk_load(r.dst, so + j, TILEB, r.bar + B_QFULL);
                bulk_load(r.dst + 16384, sw + j, (r.bar & 8) ? TILEB : 3 * SLAB, r.bar + B_FULL);
                r.next(bars);
            }
            Ring q{has_g1 ? 2u : 6u, has_g1}, p{q.slot, !has_g1};
#pragma unroll 1
            for (int j = 0; j < 14 * 128; j += 128) {
                mbar_wait_bounded(bars + B_EMPTY + 8 * q.slot, q.ph, spins);
                if (LEADW && j >= LEADW * 128 && j < LEADN * 128) { mbar_wait_bounded(bars + B_FULL + 8 * p.slot, p.ph, spins); p.next2(); }
                TS(8, 176 + j / 128);
                tma3d(sbase + q.slot * SLOT, &P.tmW2, bars + B_FULL + 8 * q.slot, 0, ks * 896 + j - (j < 896 ? 0 : 832), mt * 2);
                q.next2();
            }
            mbar_wait_bounded(bars + B_END, 0, spins);
        }
    } else if (warp > 8) {
        const uint32_t ep = ld_relaxed(G->epoch[c]) + 1;
        uint32_t spins = 0, bad;
        {
            uint2* cs = G->colsum[hp][0];
            const int i0 = threadIdx.x - 288, j0 = i0 - (hp & 1) * 4;
            const uint32_t at_cs = __shfl_sync(~0u, (hp * 768 + i0 + ((j0 & 92) == 28 ? (j0 & 32 ? 28 : 56) : 0)) * 8, lane);
            const uint32_t at_st = __shfl_sync(~0u, (tb * 64 + (i0 & 63)) * 16, lane), to_st = __shfl_sync(~0u, sbase + i0 * 16, lane);
            if (w == 2) {
                bar_sync(6, 288);
                TS(1, 8);
                stg1((uint32_t*)(G->stat + row0) + lane, tag(__float_as_uint(lds1f(sbase + OFF_ST + lane * 4)), ~lane & 1, ep));
                if (elect()) {
                    fence_async_shared();
#pragma unroll
                    for (int i = 0; i < 4; i++) bulk_store(G->H[i][0] + row0 * (SLAB / 16), sbase + OFF_X + i * HSTG, SLAB);
                    bulk_flush();
                    TS(1, 99);
                    signal(G->flag[2 + (row0 >> 10) * 2 + ((row0 & 1023) >= 320)]);
                }
                __syncwarp();
            } else {
                const uint32_t word = rank * 16 + (w & 2) * 4 + (lane & 7), done = mapa(bars + B_CS, rank ^ (lane & 1));
                const uint32_t from = (sbase + word * 4 + (gp >> 2) * 12288 + (gp & 2) * 1024) ^ ((lane >> 3) * 288);
                auto swz = [](uint32_t a) { return a ^ ((a >> 3) & 0x70); };
                const uint32_t lin = sbase + lane * 128 + (hp & 1) * 16, f0 = swz(lin + 80) + 8192, f1 = swz(lin + 96) + 8192, to = swz(lin + 112);
                float s[6] = {};
#pragma unroll 1
                for (int i = 0; i < 7; i++) {
                    const uint32_t o = wslot(i) * 8192, a0 = from + o, a1 = a0 ^ 144;
                    mbar_wait(bars + B_QFULL + 8 * i, 0);
                    if (i < 2 && w == 1) TS(1, 140 + i);
                    if ((i ^ (w >> 1)) & 1) {
                        const uint4 v0 = lds4(f0 + o), v1 = lds4(f1 + o), v2 = lds4(f0 + o + 12288), v3 = lds4(f1 + o + 12288);
                        sts4(to + o, v0); sts4(to + o + 4096, v1); sts4(to + o + 12288, v2); sts4(to + o + 16384, v3);
                        fence_async_shared();
                        __syncwarp();
                        if (elect()) mbar_expect(bars + B_FULL + 8 * i, 16384);
                    }
                    if (i > 3 || i < (gp & 1)) continue;
                    if (w == 1) TS(1, 66);
                    uint32_t v[12];
#pragma unroll
                    for (int k = 0; k < 12; k++) v[k] = __float_as_uint(lds1f(((k & 1) ? a1 : a0) + (k & 2) * 512 + (k >> 2) * 4096));
#pragma unroll
                    for (int k = 0; k < 12; k++) { s[(k >> 2) * 2] += bf_lo(v[k]); s[(k >> 2) * 2 + 1] += bf_hi(v[k]); }
                    __syncwarp();
                    if ((i & 1) && lane < 2) mbar_arrive_remote(done + (i & 2) * 4);
                    if (i < 3) continue;
#pragma unroll
                    for (int k = 0; k < 6; k++) { s[k] += __shfl_xor_sync(~0u, s[k], 8); s[k] += __shfl_xor_sync(~0u, s[k], 16); }
                    const float s0 = lane < 8 ? s[0] : lane < 16 ? s[2] : s[4], s1 = lane < 8 ? s[1] : lane < 16 ? s[3] : s[5];
                    if (lane < 24) cs[gp * 96 + (lane >> 3) * 32 + word] = make_uint2(tag(__float_as_uint(s0), 1, ep), __float_as_uint(s1));
                    if (w == 1) TS(1, 24);
                }
            }
            bar_sync(1, 96);
            if (w == 1) TS(1, 98);
            uint4 sv;
            float f[2];
            do {
                uint2 u[8];
#pragma unroll
                for (int i = 0; i < 8; i++) u[i] = ld_relaxed2((const uint8_t*)G->colsum + at_cs + i * 768);
                sv = ld_relaxed4((const uint8_t*)G->stat + at_st);
#pragma unroll
                for (int e = 0; e < 2; e++) {
                    float g[4];
#pragma unroll
                    for (int i = 0; i < 4; i++) g[i] = __uint_as_float(e ? u[2 * i].y : u[2 * i].x) + __uint_as_float(e ? u[2 * i + 1].y : u[2 * i + 1].x);
                    f[e] = (g[0] + g[1]) + (g[2] + g[3]);
                }
                bad = or_diff(or_diff(u[0].x ^ ep, u[1].x, ep), u[2].x, ep) | or_diff(or_diff(u[3].x ^ ep, u[4].x, ep), u[5].x, ep) | or_diff(or_diff(u[6].x ^ ep, u[7].x, ep), sv.x, ep);
                if (bad & 1) TS(1, 3);
            } while (bad & 1);
            if (w < 3) sts4(to_st + OFF_ST, sv);
#pragma unroll
            for (int e = 0; e < 2; e++) {
                const uint32_t hi = pack2(f[e], f[e]);
                sts4(to_st + i0 * 16 + OFF_X + e * 16, make_uint4(hi, pack2(f[e] - bf_hi(hi), f[e] - bf_hi(hi)), 0, 0));
            }
            sts1(bars + 8 * NBAR, ep);
            fence_async_shared();
            __syncwarp();
            bar_arrive(8, 224); bar_arrive(9, 224);
            TS(1, 90 + w);
        }
        block_end();
        const uint8_t* src = G->U[nt2][ks * 14];
        if (w < 3) {
            if (w == 1) {
                if (elect()) {
                    wait_flag(G->flag[3 + rank * 2], 44 * ep, spins);
                    mbar_arrive_n<16>(bars + B_EMPTY + 8 * 5);
                    TS(1, 96);
                }
                __syncwarp();
                if (!has_g1) { bar_sync(5, 288); if (elect()) signal(G->flag[0]); __syncwarp(); TS(2, 26); }
            }
            mbar_wait(bars + B_HALO, 0);
            uint32_t slot = (has_g1 ? 16 % NSLOT : 0) + w - 1, ph = ~0u;
#pragma unroll 1
            for (int i = w - 1; i < 18;) {
                const uint32_t d0 = sbase + slot * SLOT + (i < 4 ? 0 : 16384), landed = bars + B_QFULL + 8 * slot, tx = i < 4 ? (2 + w) * SLAB : 16384;
                mbar_wait(landed, (ph >> slot) & 1);
                ph ^= 1 << slot;
                if (i < 8) TS(4, 82 + i);
                if (i >= 4) TS(8, 156 + i);
                uint32_t v[14];
#pragma unroll
                for (int k = 0; k < 14; k++) v[k] = __float_as_uint(lds1f(d0 + k * 1024 + lane * 32 + (lane >> 2) * 4));
#pragma unroll
                for (int k = 0; k < 7; k++) asm("lop3.b32 %0, %0, %1, %2, 0x7e;" : "+r"(v[k]) : "r"(v[13 - k]), "r"(ep));
                const bool stale = __any_sync(~0u, (or3(or3(v[6], v[5], v[4]), or3(v[3], v[2], v[1]), v[0])) & 1);
                if (!stale && lane == 0) mbar_expect(landed + (B_FULL - B_QFULL), tx);
                if (stale) {
                    if (elect()) {
                        const uint8_t* cur = (i < 4 ? G->O[mt][ks * 4] : src - 4 * TILEB) + i * TILEB;
                        fence_async_shared();
                        mbar_expect(landed, TILEB);
                        bulk_load(d0, cur, TILEB, landed);
                    }
                    TS(4, i < 4 ? 94 : 95);
                } else {
                    i += __byte_perm(0x03020202u, 0x00010202u, 0x7770 + slot);
                    slot = __byte_perm(0x05060302u, 0x00040100u, 0x7770 + slot);
                }
            }
        } else {
            bar_sync(3, 288);
            __nanosleep(HALO_NS);
            uint4 v[7];
            do {
                bad = 0;
#pragma unroll
                for (int i = 0; i < 7; i++) { v[i] = ld_relaxed4(G->halo[c - (tb > 0)] + i * 512 + lane * 16); bad = or_diff(bad, v[i].x, ep); }
            } while (bad & 1);
#pragma unroll
            for (int i = 0; i < 7; i++) sts4(sbase + OFF_X + i * 512 + lane * 16, v[i]);
            __syncwarp();
            if (elect()) mbar_arrive(bars + B_HALO);
            TS(2, 21);
            bar_sync(2, 160);
            if (elect()) bulk_store(out + row0 * D_, sbase + OFF_Y, TILEB);
            __syncwarp();
            bar_sync(4, 288);
            if (elect()) {
                fence_async_shared();
                bulk_store(G->O[tb][hp], sbase + OFF_X, TILEB);
                bulk_flush();
                TS(2, 7);
                mbar_arrive_remote(mapa(bars + B_FREE, rank ^ 1));
                mbar_arrive(bars + B_FREE);
                hint(G->flag[16 + tb]);
                signal(G->flag[16 + (row0 >> 7)] + 1);
                TS(2, 22);
            }
            __syncwarp();
            uint32_t late = ~0u;
            const uint32_t* hints = G->flag[8 + nt2 * 2 + ks] + (lane & 7);
            mbar_wait(bars + (has_g1 ? B_X : B_FREE), 0);
            Ring r{has_g1 ? 2u : 6u, has_g1};
#pragma unroll 1
            for (int i = 0; i < 14; i++) {
                while ((late >> i) & 1) late = __ballot_sync(~0u, ld_relaxed(hints) != 2 * ep) & 127;
                if (i == 0) TS(4, 17);
                mbar_wait(bars + B_EMPTY + 8 * r.slot, r.ph);
                TS(8, 192 + i);
                if (elect()) {
                    mbar_expect(bars + B_QFULL + 8 * r.slot, TILEB);
                    bulk_load(sbase + r.slot * SLOT + 16384, src, TILEB, bars + B_QFULL + 8 * r.slot);
                }
                src += TILEB; r.next2();
            }
            if (elect()) {
                wait_flag(G->flag[16 + mt] + 1, 8 * ep, spins);
                mbar_arrive(bars + B_ROW);
                TS(2, 27);
                G->epoch[c][0] = ep;
            }
        }
    } else {
        const int wg = warp >> 2;
        Mma M{bars, mapa(bars, rank ^ (lane & 1)), (threadIdx.x & 127) < 2, wg, wg, w, Ring{0, 1}, 0};
        const int r = lane >> 2, t = lane & 3;
        uint32_t ep;
        const uint32_t kv = sbase + OFF_X + (w * 2 + wg) * KV + lane * 16;
        uint32_t q[8][2], k0[7], k1[14], v0[7];
        float f0, f1;
        {
            const int half = (lane >> 3) & 1, r16 = warp * 2 + (half ^ (lane >> 4)), nt = (lane >> 1) & 3;
            const uint32_t row = sbase + OFF_Y + r16 * (2 * D_), part = row + nt * 224 + half * 112 + (lane & 1) * 8;
            const uint32_t hb = sbase + OFF_X + nt * HSTG + r16 * 16 + (half ^ (row0 >> 10)) * (7 * 256) + (lane & 1) * 8;
            mbar_wait(bars + B_ROW, 0);
            TS0(1, 67);
            const float x0 = bf_lo(__float_as_uint(lds1f(row)));
            float d[28], m1 = 0.f, n1 = 0.f, m2 = 0.f, n2 = 0.f;
#pragma unroll
            for (int i = 0; i < 7; i++) {
                const uint2 v = lds2(part + i * 16);
#pragma unroll
                for (int k = 0; k < 2; k++) {
                    const float d0 = d[4 * i + 2 * k] = bf_lo(k ? v.y : v.x) - x0, d1 = d[4 * i + 2 * k + 1] = bf_hi(k ? v.y : v.x) - x0;
                    m1 += d0; n1 += d1; m2 = fmaf(d0, d0, m2); n2 = fmaf(d1, d1, n2);
                }
            }
            const float md = row_sum(m1 + n1) * (1.f / D_), var = fmaf(-md, md, row_sum(m2 + n2) * (1.f / D_)), nmean = -(x0 + md);
            const float rstd = rsq(var + LN_EPS);
            const float sc = rstd * rsq(fmaf(var * rstd, 4 * rstd, 4 * LN_EPS)), nb = -md * sc;
            sts2(sbase + OFF_ST + r16 * 8, __float_as_uint(rstd), pack2(nmean, nmean - bf_hi(pack2(nmean, nmean))));
#pragma unroll
            for (int i = 0; i < 7; i++) sts2(hb + i * 256, pack2(fmaf(d[4 * i], sc, nb), fmaf(d[4 * i + 1], sc, nb)), pack2(fmaf(d[4 * i + 2], sc, nb), fmaf(d[4 * i + 3], sc, nb)));
            TS0(1, 25);
            bar_arrive(6, 288);
            float acc[84];
#pragma unroll 1
            for (int kb = 0; kb < 7; kb++) {
                const bool held = kb == (wg ? 7 - HOLD : -1);
                if (held) { wg_wait<0>(); M.release_pair(4 - HOLD); TS0(1, 138); bar_sync(7, 256); }
                mbar_wait(bars + B_FULL + 8 * kb, 0);
                if (!TSQ || !kb) TS0(1, 68 + wg * 7 + kb);
                const uint32_t dA = (xslot(kb) + wg) * 512, dB = wslot(kb) * 512 + (hp & 1);
                wg_fence();
#pragma unroll
                for (int k = 0; k < 4; k++) {
                    wgmma_n168<0, 1, HI_SW, HI_SW>(acc, dA + desc_lo(k * 32, 16), dB + desc_lo((k & 1) * 2048 + (k >> 1) * 12288, 4096), k > 0 || kb > 0);
                    if (k == 0) { wg_commit(); wg_wait<1>(); if (kb > 0 && !held) M.release_pair(kb - 3); if (TSQ && kb) TS0(1, 68 + wg * 7 + kb); }
                }
                wg_commit();
            }
            if (wg == 0 && !LATEREL) bar_arrive(7, 256);
            if (wg == 0) TS0(1, 139);
            bar_sync(8 + wg, 224);
            if (wg == 0) TS0(1, 174);
            ep = __float_as_uint(lds1f(bars + 8 * NBAR));
            const uint32_t st = sbase + OFF_ST + (w * 32 + r * 2 + wg) * 8;
            const uint2 s0 = lds2(st), s1 = lds2(st + 128);
            const uint32_t a0 = t < 2 ? s0.y : 0, a1 = t < 2 ? s1.y : 0;
            wg_fence();
            wgmma_rs_n168<desc_hi(128, 0)>(acc, a0, a1, desc_lo(OFF_X, 0) + (hp & 1) * 8);
            wg_commit();
            if (wg == 0 && LATEREL) bar_arrive(7, 256);
            if (wg == 0) TS0(1, 175);
            wg_wait<1>();
            TS0(1, 190 + wg);
            M.release_pair(4);
            wg_wait<0>();
            pin(acc);
            TS0(1, 4 + 7 * wg);
            f0 = __uint_as_float(s0.x); f1 = __uint_as_float(s1.x);
#pragma unroll
            for (int g = 13; g >= 0; g--) {
                const float* a = acc + (g < 7 ? g + 8 : g < 12 ? g + 9 : g * 8 - 89) * 4;
                (g < 7 ? k0[g] : v0[g - 7]) = pack2(a[0] * f0, a[1] * f0);
                k1[g] = pack2(a[2] * f1, a[3] * f1);
            }
#pragma unroll
            for (int i = 0; i < 3; i++) stsm4(kv + 2 * KV + i * 512, k1[4 * i], k1[4 * i + 1], k1[4 * i + 2], k1[4 * i + 3]);
            stsm2(kv + 2 * KV + 1536, k1[12], k1[13]);
            if (w == 3) {
#pragma unroll
                for (int i = 0; i < 14; i++) stg1(G->halo[c] + wg * KV + lane * 4 + i * 128, tag(k1[i], t == 0, ep));
            }
            bar_arrive(3, 288);
#pragma unroll
            for (int g = 0; g < 7; g++) { q[g][0] = pack2(acc[4 * g], acc[4 * g + 1]); q[g][1] = pack2(acc[4 * g + 2], acc[4 * g + 3]); }
#pragma unroll
            for (int j = 0; j < 2; j++) { q[7][j] = t < 2 ? 0u : q[3][j]; q[3][j] = t < 2 ? q[3][j] : 0u; }
#pragma unroll
            for (int g = 0; g < 7; g++) v0[g] = transpose8(v0[g]);
        }
        TS0(1, 9 + 11 * wg);
        float a[56];
#pragma unroll
        for (int i = 0; i < 56; i++) asm volatile("" : "=f"(a[i]));
        if (__builtin_expect(!has_g1, 0)) {
            const int g = min(lane >> 1, 13), nt = rank * 2 + wg;
            const uint4* src = (const uint4*)(wo + (hp * 56 - (hp & 1) * 8 + w * 16 + (lane & 1)) * D_ + nt * 112) + g;
            uint4 v[8];
#pragma unroll
            for (int i = 0; i < 8; i++) v[i] = __ldg(src + i * (D_ / 4));
#pragma unroll
            for (int i = 0; i < 8; i++) ((uint4*)G->Wo[nt][hp])[w * (SLAB / 16) + g * 16 + (lane & 1) + 2 * i] = v[i];
            bar_arrive(5, 288);
        }
        M.run<true>(a, has_g1 ? PAUSE : 0, 1, 16, 0, 0, 32);
        const uint32_t bias0 = ld_u16(b1 + ft * 128 + warp * 16 + r), bias1 = ld_u16(b1 + ft * 128 + warp * 16 + r + 8);
        {
            uint32_t kp[8], vv[14];
            mbar_wait(bars + B_HALO, 0);
            ldsm4(kp, kv); ldsm4(kp + 4, kv + (lane < 24 ? 512 : 0));
            const uint32_t va = kv + 896 + (lane & 8) * (2 * KV / 8 - 16) - (lane & 16) * 8;
            ldsm4t(vv, va); ldsm4t(vv + 4, va + 256); ldsm4t(vv + 8, va + 512); ldsm2t(vv + 12, va + 768);
            const bool e0 = 2 * t > r, e1 = 2 * t >= r;
            const uint32_t mk = (e0 ? 0xffffu : 0u) | (e1 ? 0xffff0000u : 0u);
            wg_wait<0>();
            pin(a);
            if (has_g1) M.release(M.prev);
            TS0(2, 144 + wg);
            bar_arrive(10 + wg, 256);
            if (wg) bar_arrive(2, 160);
            block_end();
            TS0(2, 12 + 16 * wg);
            float sv[2][4];
#pragma unroll
            for (int h = 0; h < 2; h++) {
                const int ga = h * 4, gb = h * 4 + 1, gc = h * 4 + 2, gd = h * 4 + 3;
                float s[3][4] = {};
                mma16(s[0], q[ga][0], q[ga][1], q[gb][0], q[gb][1], kp[ga], kp[gb]);
                mma16(s[1], q[ga][0], q[ga][1], q[gb][0], q[gb][1], k0[ga], k0[gb]);
                mma16(s[2], q[ga][0], q[ga][1], q[gb][0], q[gb][1], k1[ga], k1[gb]);
                mma16(s[0], q[gc][0], q[gc][1], q[gd][0], q[gd][1], kp[gc], kp[gd]);
                mma16(s[1], q[gc][0], q[gc][1], q[gd][0], q[gd][1], k0[gc], k0[3]);
                mma16(s[2], q[gc][0], q[gc][1], q[gd][0], q[gd][1], k1[gc], k1[3]);
                if ((tb | w) == 0) s[0][0] = s[0][1] = -1e30f;
                sv[h][0] = e0 ? s[0][0] : s[1][0];
                sv[h][1] = e1 ? s[0][1] : s[1][1];
                sv[h][2] = e0 ? s[1][2] : s[2][2];
                sv[h][3] = e1 ? s[1][3] : s[2][3];
            }
            uint32_t pp[2][2];
#pragma unroll
            for (int i = 0; i < 4; i++) {
                float* v = &sv[i >> 1][(i & 1) * 2];
                const float f = ((i & 1) ? f1 : f0) * QK_SCALE, m = quad_max(fmaxf(v[0], v[1])) * f;
                const float p0 = ex2(fmaf(v[0], f, -m)), p1 = ex2(fmaf(v[1], f, -m));
                const float inv = rcp(quad_sum(p0 + p1));
                pp[i >> 1][i & 1] = pack2(p0 * inv, p1 * inv);
            }
            uint32_t o[8][2];
#pragma unroll
            for (int i = 0; i < 8; i++) {
                const int h = i >> 2, g = i - h;
                float d[4] = {};
                mma16(d, pp[h][0] & mk, 0u, 0u, pp[h][1] & ~mk, vv[2 * g], vv[2 * g + 1]);
                mma8(d, pp[h][0] & ~mk, pp[h][1] & mk, v0[g]);
                o[i][0] = pack2(d[0], d[1]); o[i][1] = pack2(d[2], d[3]);
            }
            if (t >= 2) { o[3][0] = o[4][0]; o[3][1] = o[4][1]; }
            const int word = wg * 4 + t - (w & 1) * 4 - (r >> 2);
#pragma unroll
            for (int i = 0; i < 8; i++) { o[i][0] = tag(o[i][0], word == 0, ep); o[i][1] = tag(o[i][1], word == 2, ep); }
            const uint32_t dst = sbase + OFF_X + (w >> 1) * HALF + ((w & 1) * 32 + (lane & 15) * 2 + wg) * 16 + (lane >> 4) * 1024;
            bar_sync(11 - wg, 256);
            stsm4(dst, o[0][0], o[0][1], o[1][0], o[1][1]);
            stsm4(dst + 2048, o[2][0], o[2][1], o[3][0], o[3][1]);
            stsm4(dst + 4096, o[5][0], o[5][1], o[6][0], o[6][1]);
            stsm2(dst + 6144, o[7][0], o[7][1]);
            bar_arrive(4, 288);
            TS0(2, 10 + 19 * wg);
        }
        if (has_g1) {
            M.run<true>(a, 16 - PAUSE, 1, 16, LAG1, 1, 32 + PAUSE);
            mbar_wait(bars + B_FREE, 0);
            const uint32_t xb = sbase + OFF_X + wg * 8192 + (threadIdx.x & 127) * 16, xbar = bars + B_X + 16 * wg;
            const uint32_t rx = mapa(xb, rank ^ 1), rbar = mapa(xbar, rank ^ 1);
            wg_wait<0>();
            pin(a);
            M.release(M.prev);
            TS0(4, 5 + wg);
#pragma unroll
            for (int i = 0; i < 3; i++)
                st_async4(rx + i * 2048, rbar + 8 * (i >> 1), pack2(a[28 + 8 * i], a[29 + 8 * i]), pack2(a[30 + 8 * i], a[31 + 8 * i]), pack2(a[32 + 8 * i], a[33 + 8 * i]), pack2(a[34 + 8 * i], a[35 + 8 * i]));
            const uint32_t tail = 6144 - (threadIdx.x & 127) * 8;
            st_async2(rx + tail, rbar + 8, pack2(a[52], a[53]), pack2(a[54], a[55]));
            uint8_t* dst = G->U[nt1][((ft >= 7) + wg) * 7 + ft] + rank * HALF + w * 256 + lane * 4;
            uint32_t u[14];
#pragma unroll
            for (int i = 0; i < 28; i++) a[i] = fmaf(bf_lo((i & 2) ? bias1 : bias0), 0.5f, a[i]);
#pragma unroll
            for (int i = 0; i < 14; i++) {
                if (i % 8 == 0) {
                    if (i) TS0(4, 134 + wg);
                    mbar_wait(xbar + i, 0);
                    TS0(4, (i ? 136 : 1) + wg);
#pragma unroll
                    for (int k = i / 4; k < i / 4 + 2; k++) {
                        if (k < 3) { const uint4 v = lds4(xb + k * 2048); u[4 * k] = v.x; u[4 * k + 1] = v.y; u[4 * k + 2] = v.z; u[4 * k + 3] = v.w; }
                        else { const uint2 v = lds2(xb + tail); u[12] = v.x; u[13] = v.y; }
                    }
                    if (i && lane < 2) mbar_arrive(bars + B_EMPTY + 48);
                }
                if (i == HINT && threadIdx.x == 0) hint(G->flag[8 + nt1 * 2] + ft + (ft >= 7) * 25);
                stg1(dst + (i >> 1) * 1024 + (i & 1) * 128, tag(pack2(gelu2(a[2 * i] + bf_lo(u[i])), gelu2(a[2 * i + 1] + bf_hi(u[i]))), (lane & 7) == w * 2 + (i & 1), ep));
            }
            TS0(4, 30 + wg);
        } else {
            mbar_wait(bars + B_FREE, 0);
            if (lane < 2) mbar_arrive(bars + B_EMPTY + 48);
        }
        M.half = wg ^ ks;
        const uint32_t orow = mt * 128 + M.half * 64 + w * 16;
        M.run_o(a);
        if (wg == 1) TS0(4, 13);
        M.run<false>(a, 14, 0, 14 - NSLOT, NSLOT + 1, 1, 52, b2 + orow + r);
        mbar_wait(bars + B_ROW, 1);
        const uint32_t stg = sbase + (4 + (w >> 1)) * SLOT + M.half * 8192 + (w & 1) * (PITCH * 16);
        const uint32_t sa = stg + (lane & 7) * PITCH + (lane >> 3) * 16;
        const bool one = elect();
        wg_wait<1>();
        if (wg == 0) bar_arrive(7, 256);
        wg_wait<0>();
        pin(a);
        TS0(8, 14 + wg);
#pragma unroll
        for (int h = 0; h < 2; h++) {
            const float* e = a + 2 * h;
#pragma unroll
            for (int i = 0; i < 3; i++)
                stsm4(sa + h * 8 * PITCH + i * 64, pack2(e[16 * i], e[16 * i + 1]), pack2(e[16 * i + 4], e[16 * i + 5]), pack2(e[16 * i + 8], e[16 * i + 9]), pack2(e[16 * i + 12], e[16 * i + 13]));
            stsm2(sa + h * 8 * PITCH + 192, pack2(e[48], e[49]), pack2(e[52], e[53]));
            fence_async_shared();
            __syncwarp();
            if (one) asm volatile("cp.reduce.async.bulk.tensor.3d.global.shared::cta.add.tile.bulk_group [%0, {%4, %2, %3}], [%1];" ::"l"(&P.tmOut), "r"(stg + h * 8 * PITCH), "r"(nt2), "r"(orow + 8 * h), "r"(0) : "memory");
        }
        if (one) {
            asm volatile("cp.async.bulk.commit_group;" ::: "memory");
            if (w == 0) mbar_arrive(bars + B_END);
            asm volatile("cp.async.bulk.wait_group.read 0;" ::: "memory");
        }
        TS0(15, wg ? 19 : 207);
        TSDUMP();
    }
}

typedef CUresult (*EncodeFn)(CUtensorMap*, CUtensorMapDataType, cuuint32_t, void*, const cuuint64_t*, const cuuint64_t*, const cuuint32_t*, const cuuint32_t*,
                             CUtensorMapInterleave, CUtensorMapSwizzle, CUtensorMapL2promotion, CUtensorMapFloatOOBfill);

void make_map(EncodeFn enc, CUtensorMap* tm, const void* base, bool swizzle, int d0, int d1, int d2, int s1, int s2, int b0, int b1, int b2) {
    const cuuint64_t dims[3] = {(cuuint64_t)d0, (cuuint64_t)d1, (cuuint64_t)d2}, strides[2] = {(cuuint64_t)s1 * 2, (cuuint64_t)s2 * 2};
    const cuuint32_t box[3] = {(cuuint32_t)b0, (cuuint32_t)b1, (cuuint32_t)b2}, es[3] = {1, 1, 1};
    enc(tm, CU_TENSOR_MAP_DATA_TYPE_BFLOAT16, d2 ? 3 : 2, (void*)base, dims, strides, box, es, CU_TENSOR_MAP_INTERLEAVE_NONE,
        swizzle ? CU_TENSOR_MAP_SWIZZLE_128B : CU_TENSOR_MAP_SWIZZLE_NONE, CU_TENSOR_MAP_L2_PROMOTION_L2_128B, CU_TENSOR_MAP_FLOAT_OOB_FILL_NONE);
}

}

extern "C" void kernel_launch(void* const* d_in, const int* in_sizes, int n_in, void* d_out, int out_size) {
    static EncodeFn enc = nullptr;
    static Scratch* scratch = nullptr;
    if (!enc) {
        void* fn = nullptr;
        cudaDriverEntryPointQueryResult qr;
        cudaGetDriverEntryPoint("cuTensorMapEncodeTiled", &fn, cudaEnableDefault, &qr);
        enc = (EncodeFn)fn;
        cudaGetSymbolAddress((void**)&scratch, g_s);
        cudaFuncSetAttribute(fused_kernel, cudaFuncAttributeMaxDynamicSharedMemorySize, SMEM_BYTES);
    }
    Params P;
    const __nv_bfloat16* x = (const __nv_bfloat16*)d_in[0];
    make_map(enc, &P.tmX, x, true, D_, S_ / 2, 2, 2 * D_, D_, 64, 64, 2);
    make_map(enc, &P.tmWqkv, d_in[1], true, D_, D_, 3, 3 * D_, D_, 64, 32, 3);
    make_map(enc, &P.tmW1, d_in[4], true, 64, S_, F_ / 64, F_, 64, 64, 64, 2);
    make_map(enc, &P.tmW2, d_in[6], true, 64, F_, S_ / 64, S_, 64, 64, 64, 2);
    make_map(enc, &P.tmOut, d_out, false, 112, 4, S_, 112, D_, PITCH / 2, 1, 8);
    fused_kernel<<<NCTA, NTHREADS, SMEM_BYTES, cudaStreamPerThread>>>(x, (const __nv_bfloat16*)d_in[5], (const __nv_bfloat16*)d_in[7], (const __nv_bfloat16*)d_in[2], (__nv_bfloat16*)d_out, scratch,
                                                                      (const __nv_bfloat16*)d_in[4], P);
}
```

```cpp
#include <cuda_runtime.h>
#include <cuda_bf16.h>
#include <cuda.h>
#include <stdint.h>

constexpr int PACE = 580;
constexpr int HOLD = 1;
constexpr int HALO_NS = 300;
constexpr int PF = 400;
constexpr int PF0 = 2;
constexpr int PF1 = 8;
constexpr int PF2 = 14;
constexpr int PFD = 1500;
constexpr int PAUSE = 8;
constexpr int LAG1 = 4;
constexpr int HINT = 5;
constexpr int LEADW = 4;

namespace {

constexpr int S_ = 2048, D_ = 448, F_ = 1792;
constexpr int NCTA = 128, NTHREADS = 384;
constexpr int NSLOT = 6, SLOT = 32768, WSLOT = 24576, TILEB = 14336, SLAB = 3584, HALF = 7168;
constexpr int KV = 1792, HSTG = SLAB + 32, PITCH = 240;
constexpr int OFF_X = NSLOT * SLOT;
constexpr int OFF_Y = OFF_X + 10 * KV;
constexpr int OFF_ST = OFF_Y + TILEB;
constexpr int OFF_BAR = OFF_ST + 1024;
constexpr int SMEM_BYTES = OFF_BAR + 1280;
constexpr uint32_t SMEM0 = 1024;
constexpr int B_QFULL = 0, B_FULL = 56, B_HALO = 128, B_X = 136, B_CS = 168, B_FREE = 192, B_END = 200, B_QEMPTY = 216, B_EMPTY = 232, B_ROW = 288, NBAR = 37;
constexpr float LN_EPS = 1e-5f, QK_SCALE = 0.1889822365046136f * 1.4426950408889634f;
constexpr int SPIN_LIMIT = 1 << 22;

struct Scratch {
    uint8_t H[4][32][TILEB];
    uint8_t U[4][28][TILEB];
    uint8_t O[16][8][TILEB];
    uint8_t Wo[4][8][TILEB];
    uint8_t halo[NCTA][2 * KV];
    uint2 stat[S_];
    uint2 colsum[8][8][96];
    uint32_t flag[32][32];
    uint32_t epoch[NCTA][32];
};
__device__ __align__(1024) Scratch g_s;

struct Params {
    CUtensorMap tmX, tmWqkv, tmW1, tmW2, tmOut;
};

__device__ __forceinline__ bool elect() {
    uint32_t p;
    asm volatile("{\n.reg .pred p;\nelect.sync _|p, 0xffffffff;\nselp.u32 %0, 1, 0, p;\n}" : "=r"(p));
    return p;
}
__device__ __forceinline__ void mbar_init(uint32_t b, uint32_t c) { asm volatile("mbarrier.init.shared::cta.b64 [%0], %1;" ::"r"(b), "r"(c) : "memory"); }
__device__ __forceinline__ void mbar_expect(uint32_t b, uint32_t tx) { asm volatile("mbarrier.arrive.expect_tx.shared::cta.b64 _, [%0], %1;" ::"r"(b), "r"(tx) : "memory"); }
__device__ __forceinline__ void mbar_arrive(uint32_t b) { asm volatile("mbarrier.arrive.shared::cta.b64 _, [%0];" ::"r"(b) : "memory"); }
template <int N> __device__ __forceinline__ void mbar_arrive_n(uint32_t b) { asm volatile("mbarrier.arrive.shared::cta.b64 _, [%0], %1;" ::"r"(b), "n"(N) : "memory"); }
__device__ __forceinline__ void mbar_arrive4_remote(uint32_t b) { asm volatile("mbarrier.arrive.shared::cluster.b64 _, [%0], 4;" ::"r"(b) : "memory"); }
__device__ __forceinline__ void mbar_arrive_remote(uint32_t b) { asm volatile("mbarrier.arrive.shared::cluster.b64 _, [%0];" ::"r"(b) : "memory"); }
#define MBAR_WAIT_ASM(SEM) \
    asm volatile("{\n.reg .pred p;\nWAIT:\nmbarrier.try_wait.parity" SEM ".shared::cta.b64 p, [%0], %1;\n@!p bra WAIT;\n}" ::"r"(b), "r"(parity) : "memory")
__device__ __forceinline__ void mbar_wait(uint32_t b, uint32_t parity) { MBAR_WAIT_ASM(""); }
__device__ __forceinline__ void mbar_wait_bounded(uint32_t b, uint32_t parity, uint32_t& n) {
    asm volatile("{\n.reg .pred p;\nWAIT:\nadd.u32 %0, %0, 1;\nsetp.gt.u32 p, %0, %3;\n@p st.global.u32 [%4], %0;\n"
                 "mbarrier.try_wait.parity.shared::cta.b64 p, [%1], %2;\n@!p bra WAIT;\n}" : "+r"(n) : "r"(b), "r"(parity), "n"(SPIN_LIMIT), "l"(0ull) : "memory");
}
__device__ __forceinline__ uint32_t mapa(uint32_t a, uint32_t rank) { uint32_t r; asm("mapa.shared::cluster.u32 %0, %1, %2;" : "=r"(r) : "r"(a), "r"(rank)); return r; }
__device__ __forceinline__ void tma3d(uint32_t dst, const CUtensorMap* tm, uint32_t bar, int c0, int c1, int c2) {
    asm volatile("cp.async.bulk.tensor.3d.shared::cluster.global.mbarrier::complete_tx::bytes [%0], [%1, {%3, %4, %5}], [%2];" ::"r"(dst), "l"(tm), "r"(bar), "r"(c0), "r"(c1), "r"(c2) : "memory");
}
__device__ __forceinline__ void tma3d_pair(uint32_t dst, const CUtensorMap* tm, uint32_t bar, int c0, int c1, int c2) {
    asm volatile("cp.async.bulk.tensor.3d.shared::cluster.global.mbarrier::complete_tx::bytes.multicast::cluster [%0], [%1, {%3, %4, %5}], [%2], %6;" ::"r"(dst), "l"(tm), "r"(bar), "r"(c0), "r"(c1), "r"(c2), "h"((uint16_t)3) : "memory");
}
__device__ __forceinline__ void bulk_load(uint32_t dst, const void* src, uint32_t bytes, uint32_t bar) {
    asm volatile("cp.async.bulk.shared::cluster.global.mbarrier::complete_tx::bytes [%0], [%1], %2, [%3];" ::"r"(dst), "l"(src), "r"(bytes), "r"(bar) : "memory");
}
template <int BYTES> __device__ __forceinline__ void prefetch_l2(const void* p) { asm volatile("cp.async.bulk.prefetch.L2.global [%0], %1;" ::"l"(p), "n"(BYTES) : "memory"); }
__device__ __forceinline__ void bulk_store(void* dst, uint32_t src, uint32_t bytes) {
    asm volatile("cp.async.bulk.global.shared::cta.bulk_group [%0], [%1], %2;" ::"l"(dst), "r"(src), "r"(bytes) : "memory");
}
__device__ __forceinline__ uint32_t ld_u16(const void* p) { uint32_t v; asm volatile("ld.global.nc.u16 %0, [%1];" : "=r"(v) : "l"(p)); return v; }
__device__ __forceinline__ uint32_t ld_relaxed(const uint32_t* p) { uint32_t v; asm volatile("ld.relaxed.gpu.global.u32 %0, [%1];" : "=r"(v) : "l"(p) : "memory"); return v; }
__device__ __forceinline__ void bulk_flush() { asm volatile("cp.async.bulk.commit_group;\ncp.async.bulk.wait_group 0;" ::: "memory"); }
__device__ __forceinline__ void signal(uint32_t* flag) { asm volatile("fence.acq_rel.gpu;\nred.relaxed.gpu.global.add.u32 [%0], 1;" ::"l"(flag) : "memory"); }
__device__ __forceinline__ void hint(uint32_t* flag) { asm volatile("red.relaxed.gpu.global.add.u32 [%0], 1;" ::"l"(flag) : "memory"); }
__device__ __forceinline__ uint32_t tag(uint32_t v, uint32_t mask, uint32_t parity) { return (v & ~mask) | (parity & mask); }
__device__ __forceinline__ uint32_t or_diff(uint32_t acc, uint32_t v, uint32_t parity) { asm("lop3.b32 %0, %0, %1, %2, 0xf6;" : "+r"(acc) : "r"(v), "r"(parity)); return acc; }
__device__ __forceinline__ uint32_t or3(uint32_t a, uint32_t b, uint32_t c) { asm("lop3.b32 %0, %0, %1, %2, 0xfe;" : "+r"(a) : "r"(b), "r"(c)); return a; }
__device__ __forceinline__ uint4 ld_relaxed4(const void* p) {
    uint4 v;
    asm volatile("ld.relaxed.gpu.global.v4.u32 {%0, %1, %2, %3}, [%4];" : "=r"(v.x), "=r"(v.y), "=r"(v.z), "=r"(v.w) : "l"(p) : "memory");
    return v;
}
__device__ __forceinline__ uint2 ld_relaxed2(const void* p) { uint2 v; asm volatile("ld.relaxed.gpu.global.v2.u32 {%0, %1}, [%2];" : "=r"(v.x), "=r"(v.y) : "l"(p) : "memory"); return v; }
__device__ __forceinline__ void sts4(uint32_t a, uint4 v) { asm volatile("st.shared.v4.b32 [%0], {%1, %2, %3, %4};" ::"r"(a), "r"(v.x), "r"(v.y), "r"(v.z), "r"(v.w) : "memory"); }
__device__ __forceinline__ void sts1(uint32_t a, uint32_t v) { asm volatile("st.shared.b32 [%0], %1;" ::"r"(a), "r"(v) : "memory"); }
__device__ __forceinline__ void sts2(uint32_t a, uint32_t v0, uint32_t v1) { asm volatile("st.shared.v2.b32 [%0], {%1, %2};" ::"r"(a), "r"(v0), "r"(v1) : "memory"); }
__device__ __forceinline__ void stg1(void* p, uint32_t v) { asm volatile("st.global.b32 [%0], %1;" ::"l"(p), "r"(v) : "memory"); }
__device__ __forceinline__ void fence_async_shared() { asm volatile("fence.proxy.async.shared::cta;" ::: "memory"); }
#define BOUND "add.u32 %0, %0, 16;\nsetp.gt.u32 p, %0, %1;\n@p st.global.u32 [%2], %0;\n"
__device__ __forceinline__ void wait_flag(const uint32_t* p, uint32_t target, uint32_t& n) {
    asm volatile("{\n.reg .pred p;\n.reg .u32 v;\nPOLL:\n" BOUND "ld.acquire.gpu.global.u32 v, [%3];\nsetp.ne.u32 p, v, %4;\n@p bra POLL;\nfence.proxy.async.global;\n}"
                 : "+r"(n) : "n"(SPIN_LIMIT), "l"(0ull), "l"(p), "r"(target) : "memory");
}
__device__ __forceinline__ void wait_flag2(const uint32_t* h, uint32_t th, const uint32_t* p, uint32_t target, uint32_t& n) {
    asm volatile("{\n.reg .pred p;\n.reg .u32 u, v;\nPOLL:\n" BOUND "ld.relaxed.gpu.global.u32 u, [%3];\nld.acquire.gpu.global.u32 v, [%5];\nsetp.ne.u32 p, u, %4;\nsetp.ne.or.u32 p, v, %6, p;\n@p bra POLL;\nfence.proxy.async.global;\n}"
                 : "+r"(n) : "n"(SPIN_LIMIT), "l"(0ull), "l"(h), "r"(th), "l"(p), "r"(target) : "memory");
}
__device__ __forceinline__ void block_end() { asm volatile("{\n.reg .pred p;\n.reg .u32 t;\nAGAIN:\nmov.u32 t, %%clock;\nsetp.eq.u32 p, t, %0;\n@p bra AGAIN;\n}" ::"n"(0) : "memory"); }
__device__ __forceinline__ void bar_sync(int id, int n) { asm volatile("bar.sync %0, %1;" ::"r"(id), "r"(n) : "memory"); }
__device__ __forceinline__ void bar_arrive(int id, int n) { asm volatile("bar.arrive %0, %1;" ::"r"(id), "r"(n) : "memory"); }
__device__ __forceinline__ void wg_fence() { asm volatile("wgmma.fence.sync.aligned;" ::: "memory"); }
__device__ __forceinline__ void wg_commit() { asm volatile("wgmma.commit_group.sync.aligned;" ::: "memory"); }
template <int N> __device__ __forceinline__ void wg_wait() { asm volatile("wgmma.wait_group.sync.aligned %0;" ::"n"(N) : "memory"); }
template <int N> __device__ __forceinline__ void pin(float (&d)[N]) {
#pragma unroll
    for (int i = 0; i < N; i++) asm volatile("" : "+f"(d[i])::"memory");
}
__host__ __device__ constexpr uint32_t desc_hi(uint32_t sbo, uint32_t swz) { return (sbo >> 4) | (swz << 30); }
__host__ __device__ constexpr uint32_t desc_lo(uint32_t off, uint32_t lbo) { return ((SMEM0 + off) >> 4) | ((lbo >> 4) << 16); }
__device__ __forceinline__ uint32_t pack2(float lo, float hi) { uint32_t r; asm("cvt.rn.bf16x2.f32 %0, %1, %2;" : "=r"(r) : "f"(hi), "f"(lo)); return r; }
__device__ __forceinline__ float bf_lo(uint32_t v) { return __uint_as_float(v << 16); }
__device__ __forceinline__ float bf_hi(uint32_t v) { return __uint_as_float(v & 0xffff0000u); }
__device__ __forceinline__ void stsm4(uint32_t a, uint32_t r0, uint32_t r1, uint32_t r2, uint32_t r3) {
    asm volatile("stmatrix.sync.aligned.m8n8.x4.shared.b16 [%0], {%1, %2, %3, %4};" ::"r"(a), "r"(r0), "r"(r1), "r"(r2), "r"(r3) : "memory");
}
__device__ __forceinline__ void stsm2(uint32_t a, uint32_t r0, uint32_t r1) {
    asm volatile("stmatrix.sync.aligned.m8n8.x2.shared.b16 [%0], {%1, %2};" ::"r"(a), "r"(r0), "r"(r1) : "memory");
}
__device__ __forceinline__ uint4 lds4(uint32_t a) { uint4 v; asm volatile("ld.shared.v4.b32 {%0, %1, %2, %3}, [%4];" : "=r"(v.x), "=r"(v.y), "=r"(v.z), "=r"(v.w) : "r"(a) : "memory"); return v; }
__device__ __forceinline__ uint2 lds2(uint32_t a) { uint2 v; asm volatile("ld.shared.v2.b32 {%0, %1}, [%2];" : "=r"(v.x), "=r"(v.y) : "r"(a) : "memory"); return v; }
__device__ __forceinline__ float lds1f(uint32_t a) { float v; asm volatile("ld.shared.f32 %0, [%1];" : "=f"(v) : "r"(a) : "memory"); return v; }
__device__ __forceinline__ void ldsm4(uint32_t* r, uint32_t a) {
    asm volatile("ldmatrix.sync.aligned.m8n8.x4.shared.b16 {%0, %1, %2, %3}, [%4];" : "=r"(r[0]), "=r"(r[1]), "=r"(r[2]), "=r"(r[3]) : "r"(a) : "memory");
}
__device__ __forceinline__ void ldsm4t(uint32_t* r, uint32_t a) {
    asm volatile("ldmatrix.sync.aligned.m8n8.x4.trans.shared.b16 {%0, %1, %2, %3}, [%4];" : "=r"(r[0]), "=r"(r[1]), "=r"(r[2]), "=r"(r[3]) : "r"(a) : "memory");
}
__device__ __forceinline__ void ldsm2t(uint32_t* r, uint32_t a) {
    asm volatile("ldmatrix.sync.aligned.m8n8.x2.trans.shared.b16 {%0, %1}, [%2];" : "=r"(r[0]), "=r"(r[1]) : "r"(a) : "memory");
}
__device__ __forceinline__ uint32_t transpose8(uint32_t v) { uint32_t r; asm volatile("movmatrix.sync.aligned.m8n8.trans.b16 %0, %1;" : "=r"(r) : "r"(v)); return r; }
__device__ __forceinline__ void mma16(float (&c)[4], uint32_t a0, uint32_t a1, uint32_t a2, uint32_t a3, uint32_t b0, uint32_t b1) {
    asm volatile("mma.sync.aligned.m16n8k16.row.col.f32.bf16.bf16.f32 {%0, %1, %2, %3}, {%4, %5, %6, %7}, {%8, %9}, {%0, %1, %2, %3};"
                 : "+f"(c[0]), "+f"(c[1]), "+f"(c[2]), "+f"(c[3]) : "r"(a0), "r"(a1), "r"(a2), "r"(a3), "r"(b0), "r"(b1));
}
__device__ __forceinline__ void mma8(float (&c)[4], uint32_t a0, uint32_t a1, uint32_t b0) {
    asm volatile("mma.sync.aligned.m16n8k8.row.col.f32.bf16.bf16.f32 {%0, %1, %2, %3}, {%4, %5}, {%6}, {%0, %1, %2, %3};"
                 : "+f"(c[0]), "+f"(c[1]), "+f"(c[2]), "+f"(c[3]) : "r"(a0), "r"(a1), "r"(b0));
}
__device__ __forceinline__ void st_async4(uint32_t a, uint32_t bar, uint32_t v0, uint32_t v1, uint32_t v2, uint32_t v3) {
    asm volatile("st.async.weak.shared::cluster.mbarrier::complete_tx::bytes.v4.b32 [%0], {%2, %3, %4, %5}, [%1];" ::"r"(a), "r"(bar), "r"(v0), "r"(v1), "r"(v2), "r"(v3) : "memory");
}
__device__ __forceinline__ void st_async2(uint32_t a, uint32_t bar, uint32_t v0, uint32_t v1) {
    asm volatile("st.async.weak.shared::cluster.mbarrier::complete_tx::bytes.v2.b32 [%0], {%2, %3}, [%1];" ::"r"(a), "r"(bar), "r"(v0), "r"(v1) : "memory");
}
__device__ __forceinline__ float quad_max(float v) { v = fmaxf(v, __shfl_xor_sync(~0u, v, 1)); return fmaxf(v, __shfl_xor_sync(~0u, v, 2)); }
__device__ __forceinline__ float quad_sum(float v) { v += __shfl_xor_sync(~0u, v, 1); return v + __shfl_xor_sync(~0u, v, 2); }
__device__ __forceinline__ float ex2(float v) { float r; asm("ex2.approx.ftz.f32 %0, %1;" : "=f"(r) : "f"(v)); return r; }
__device__ __forceinline__ float rcp(float v) { float r; asm("rcp.approx.ftz.f32 %0, %1;" : "=f"(r) : "f"(v)); return r; }
__device__ __forceinline__ float rsq(float v) { float r; asm("rsqrt.approx.ftz.f32 %0, %1;" : "=f"(r) : "f"(v)); return r; }
__device__ __forceinline__ float gelu2(float v) {
    float z = v * fmaf(v * v, 8 * 0.044715f * 0.7978845608028654f, 2 * 0.7978845608028654f), t;
    asm("tanh.approx.f32 %0, %1;" : "=f"(t) : "f"(z));
    return fmaf(v, t, v);
}
__device__ __forceinline__ float row_sum(float v) {
    v = quad_sum(v); v += __shfl_xor_sync(~0u, v, 4);
    return v + __shfl_xor_sync(~0u, v, 24);
}

template <int TA, int TB, uint32_t HA, uint32_t HB>
__device__ __forceinline__ void wgmma_n112(float (&d)[56], uint32_t da, uint32_t db, int accumulate) {
    asm volatile("{\n.reg .pred p;\n.reg .b64 a, b;\nmov.b64 a, {%56, %61};\nmov.b64 b, {%57, %62};\nsetp.ne.b32 p, %58, 0;\n"
        "wgmma.mma_async.sync.aligned.m64n112k16.f32.bf16.bf16 {"
        "%0, %1, %2, %3, %4, %5, %6, %7, %8, %9, %10, %11, %12, %13, %14, %15, "
        "%16, %17, %18, %19, %20, %21, %22, %23, %24, %25, %26, %27, %28, %29, %30, %31, "
        "%32, %33, %34, %35, %36, %37, %38, %39, %40, %41, %42, %43, %44, %45, %46, %47, "
        "%48, %49, %50, %51, %52, %53, %54, %55"
        "}, a, b, p, 1, 1, %59, %60;\n}\n"
        : "+f"(d[0]), "+f"(d[1]), "+f"(d[2]), "+f"(d[3]), "+f"(d[4]), "+f"(d[5]), "+f"(d[6]), "+f"(d[7]),
          "+f"(d[8]), "+f"(d[9]), "+f"(d[10]), "+f"(d[11]), "+f"(d[12]), "+f"(d[13]), "+f"(d[14]), "+f"(d[15]),
          "+f"(d[16]), "+f"(d[17]), "+f"(d[18]), "+f"(d[19]), "+f"(d[20]), "+f"(d[21]), "+f"(d[22]), "+f"(d[23]),
          "+f"(d[24]), "+f"(d[25]), "+f"(d[26]), "+f"(d[27]), "+f"(d[28]), "+f"(d[29]), "+f"(d[30]), "+f"(d[31]),
          "+f"(d[32]), "+f"(d[33]), "+f"(d[34]), "+f"(d[35]), "+f"(d[36]), "+f"(d[37]), "+f"(d[38]), "+f"(d[39]),
          "+f"(d[40]), "+f"(d[41]), "+f"(d[42]), "+f"(d[43]), "+f"(d[44]), "+f"(d[45]), "+f"(d[46]), "+f"(d[47]),
          "+f"(d[48]), "+f"(d[49]), "+f"(d[50]), "+f"(d[51]), "+f"(d[52]), "+f"(d[53]), "+f"(d[54]), "+f"(d[55])
        : "r"(da), "r"(db), "r"(accumulate), "n"(TA), "n"(TB), "n"(HA), "n"(HB));
}

template <int TA, int TB, uint32_t HA, uint32_t HB>
__device__ __forceinline__ void wgmma_n168(float (&d)[84], uint32_t da, uint32_t db, int accumulate) {
    asm volatile("{\n.reg .pred p;\n.reg .b64 a, b;\nmov.b64 a, {%84, %89};\nmov.b64 b, {%85, %90};\nsetp.ne.b32 p, %86, 0;\n"
        "wgmma.mma_async.sync.aligned.m64n168k16.f32.bf16.bf16 {"
        "%0, %1, %2, %3, %4, %5, %6, %7, %8, %9, %10, %11, %12, %13, %14, %15, "
        "%16, %17, %18, %19, %20, %21, %22, %23, %24, %25, %26, %27, %28, %29, %30, %31, "
        "%32, %33, %34, %35, %36, %37, %38, %39, %40, %41, %42, %43, %44, %45, %46, %47, "
        "%48, %49, %50, %51, %52, %53, %54, %55, %56, %57, %58, %59, %60, %61, %62, %63, "
        "%64, %65, %66, %67, %68, %69, %70, %71, %72, %73, %74, %75, %76, %77, %78, %79, "
        "%80, %81, %82, %83"
        "}, a, b, p, 1, 1, %87, %88;\n}\n"
        : "+f"(d[0]), "+f"(d[1]), "+f"(d[2]), "+f"(d[3]), "+f"(d[4]), "+f"(d[5]), "+f"(d[6]), "+f"(d[7]),
          "+f"(d[8]), "+f"(d[9]), "+f"(d[10]), "+f"(d[11]), "+f"(d[12]), "+f"(d[13]), "+f"(d[14]), "+f"(d[15]),
          "+f"(d[16]), "+f"(d[17]), "+f"(d[18]), "+f"(d[19]), "+f"(d[20]), "+f"(d[21]), "+f"(d[22]), "+f"(d[23]),
          "+f"(d[24]), "+f"(d[25]), "+f"(d[26]), "+f"(d[27]), "+f"(d[28]), "+f"(d[29]), "+f"(d[30]), "+f"(d[31]),
          "+f"(d[32]), "+f"(d[33]), "+f"(d[34]), "+f"(d[35]), "+f"(d[36]), "+f"(d[37]), "+f"(d[38]), "+f"(d[39]),
          "+f"(d[40]), "+f"(d[41]), "+f"(d[42]), "+f"(d[43]), "+f"(d[44]), "+f"(d[45]), "+f"(d[46]), "+f"(d[47]),
          "+f"(d[48]), "+f"(d[49]), "+f"(d[50]), "+f"(d[51]), "+f"(d[52]), "+f"(d[53]), "+f"(d[54]), "+f"(d[55]),
          "+f"(d[56]), "+f"(d[57]), "+f"(d[58]), "+f"(d[59]), "+f"(d[60]), "+f"(d[61]), "+f"(d[62]), "+f"(d[63]),
          "+f"(d[64]), "+f"(d[65]), "+f"(d[66]), "+f"(d[67]), "+f"(d[68]), "+f"(d[69]), "+f"(d[70]), "+f"(d[71]),
          "+f"(d[72]), "+f"(d[73]), "+f"(d[74]), "+f"(d[75]), "+f"(d[76]), "+f"(d[77]), "+f"(d[78]), "+f"(d[79]),
          "+f"(d[80]), "+f"(d[81]), "+f"(d[82]), "+f"(d[83])
        : "r"(da), "r"(db), "r"(accumulate), "n"(TA), "n"(TB), "n"(HA), "n"(HB));
}

template <uint32_t HB>
__device__ __forceinline__ void wgmma_rs_n168(float (&d)[84], uint32_t a0, uint32_t a1, uint32_t db) {
    asm volatile("{\n.reg .b64 b;\nmov.b64 b, {%86, %88};\n"
        "wgmma.mma_async.sync.aligned.m64n168k16.f32.bf16.bf16 {"
        "%0, %1, %2, %3, %4, %5, %6, %7, %8, %9, %10, %11, %12, %13, %14, %15, "
        "%16, %17, %18, %19, %20, %21, %22, %23, %24, %25, %26, %27, %28, %29, %30, %31, "
        "%32, %33, %34, %35, %36, %37, %38, %39, %40, %41, %42, %43, %44, %45, %46, %47, "
        "%48, %49, %50, %51, %52, %53, %54, %55, %56, %57, %58, %59, %60, %61, %62, %63, "
        "%64, %65, %66, %67, %68, %69, %70, %71, %72, %73, %74, %75, %76, %77, %78, %79, "
        "%80, %81, %82, %83"
        "}, {%84, %85, %87, %87}, b, 1, 1, 1, 0;\n}\n"
        : "+f"(d[0]), "+f"(d[1]), "+f"(d[2]), "+f"(d[3]), "+f"(d[4]), "+f"(d[5]), "+f"(d[6]), "+f"(d[7]),
          "+f"(d[8]), "+f"(d[9]), "+f"(d[10]), "+f"(d[11]), "+f"(d[12]), "+f"(d[13]), "+f"(d[14]), "+f"(d[15]),
          "+f"(d[16]), "+f"(d[17]), "+f"(d[18]), "+f"(d[19]), "+f"(d[20]), "+f"(d[21]), "+f"(d[22]), "+f"(d[23]),
          "+f"(d[24]), "+f"(d[25]), "+f"(d[26]), "+f"(d[27]), "+f"(d[28]), "+f"(d[29]), "+f"(d[30]), "+f"(d[31]),
          "+f"(d[32]), "+f"(d[33]), "+f"(d[34]), "+f"(d[35]), "+f"(d[36]), "+f"(d[37]), "+f"(d[38]), "+f"(d[39]),
          "+f"(d[40]), "+f"(d[41]), "+f"(d[42]), "+f"(d[43]), "+f"(d[44]), "+f"(d[45]), "+f"(d[46]), "+f"(d[47]),
          "+f"(d[48]), "+f"(d[49]), "+f"(d[50]), "+f"(d[51]), "+f"(d[52]), "+f"(d[53]), "+f"(d[54]), "+f"(d[55]),
          "+f"(d[56]), "+f"(d[57]), "+f"(d[58]), "+f"(d[59]), "+f"(d[60]), "+f"(d[61]), "+f"(d[62]), "+f"(d[63]),
          "+f"(d[64]), "+f"(d[65]), "+f"(d[66]), "+f"(d[67]), "+f"(d[68]), "+f"(d[69]), "+f"(d[70]), "+f"(d[71]),
          "+f"(d[72]), "+f"(d[73]), "+f"(d[74]), "+f"(d[75]), "+f"(d[76]), "+f"(d[77]), "+f"(d[78]), "+f"(d[79]),
          "+f"(d[80]), "+f"(d[81]), "+f"(d[82]), "+f"(d[83])
        : "r"(a0), "r"(a1), "r"(db), "r"(0), "n"(HB));
}


struct Ring {
    uint32_t slot, ph;
    __device__ __forceinline__ void next() { if (++slot == NSLOT) { slot = 0; ph ^= 1; } }
    __device__ __forceinline__ void next2() { ph ^= slot == 5; slot = __byte_perm(0x06030201u, 0x00040005u, 0x7770 + slot); }
};
struct Slot {
    uint32_t dst, bar, ph;
    __device__ __forceinline__ void next(uint32_t bars) {
        dst += SLOT; bar += 8;
        if (bar == bars + 8 * NSLOT) { dst -= NSLOT * SLOT; bar = bars; ph ^= 1; }
    }
};
__device__ __forceinline__ uint32_t xslot(int i) { return __byte_perm(0x04130e0cu, 0x00130e0cu, 0x7770 + i); }
__device__ __forceinline__ uint32_t wslot(int i) { return __byte_perm(0x06001510u, 0x00151009u, 0x7770 + i); }

constexpr uint32_t HI_SW = desc_hi(1024, 1);

struct Mma {
    uint32_t bars, rel;
    bool lead;
    int wg, half, w;
    Ring r;
    uint32_t prev;
    __device__ __forceinline__ void release_pair(uint32_t s) { if (lead) mbar_arrive4_remote(rel + B_EMPTY + 8 * s); }
    __device__ __forceinline__ void release(uint32_t s) { if (lead) mbar_arrive_n<4>(bars + B_EMPTY + 8 * s); }
    template <bool G1>
    __device__ __forceinline__ void run(float (&a)[56], int n, int first, int last, int lag, int accumulate, const __nv_bfloat16* bias = nullptr) {
#pragma unroll 1
        for (int i = 0; i < n; i++) {
            if (lag && i == (wg ? n - lag : -1)) {
                if (!G1) {
                    const uint32_t c0 = ld_u16(bias), c1 = ld_u16(bias + 8);
                    wg_wait<0>(); release(prev); last = first;
                    pin(a);
#pragma unroll
                    for (int k = 0; k < 56; k++) a[k] += bf_lo((k & 2) ? c1 : c0);
                    pin(a);
                }
                bar_sync(7, 256);
            }
            const bool seen = !G1 && last == first;
            const uint32_t s = seen ? n - 1 - i : r.slot;
            if (!seen) mbar_wait(bars + B_FULL + 8 * s, r.ph);
            if (G1) r.next(); else r.next2();
            const uint32_t dB = s * (SLOT >> 4), dA = dB + half * 512;
            wg_fence();
#pragma unroll
            for (int k = 0; k < 4; k++) {
                wgmma_n112<1, 1, HI_SW, desc_hi(G1 ? 256 : 1024, 0)>(a, dA + desc_lo(k * 2048, 8192), dB + desc_lo(16384 + k * (G1 ? SLAB : 256), 128), k > 0 || accumulate || i > 0);
                if (k == 1) {
                    wg_commit(); wg_wait<1>();
                    if ((uint32_t)(i - first) < (uint32_t)(last - first)) release(prev);
                    if (G1 && lag && i == (wg ? -1 : n - 1)) bar_arrive(7, 256);
                }
            }
            wg_commit();
            prev = s;
        }
    }
    __device__ __forceinline__ void run_o(float (&a)[56]) {
#pragma unroll 1
        for (int i = 0; i < 2; i++) {
            const uint32_t s = r.slot, dB = s * (SLOT >> 4), dA = dB + half * (HALF >> 4);
            mbar_wait(bars + B_FULL + 8 * s, r.ph);
            wg_fence();
#pragma unroll
            for (int k = 0; k < 7; k++) {
                if (k == 3) { mbar_wait(bars + B_FULL + 8 * s + 8, r.ph); wg_fence(); }
                wgmma_n112<0, 1, desc_hi(128, 0), desc_hi(256, 0)>(a, dA + desc_lo(k * 2048 + (k > 3) * (SLOT - HALF), k == 3 ? SLOT - 6144 : 1024),
                                                                   dB + desc_lo(16384 + k * SLAB + (k > 2) * (SLOT - 3 * SLAB), 128), k > 0 || i > 0);
                if (k & 1) wg_commit();
                if (k == 1) { wg_wait<1>(); if (i) release(prev); }
                if (k == 5) { wg_wait<1>(); release(s); }
            }
            wg_commit();
            prev = s + 1;
            r.slot++; r.next2();
        }
    }
};

__global__ void __cluster_dims__(2, 1, 1) __launch_bounds__(NTHREADS, 1)
fused_kernel(const __nv_bfloat16* __restrict__ x, const __nv_bfloat16* __restrict__ b1, const __nv_bfloat16* __restrict__ b2, const __nv_bfloat16* __restrict__ wo, __nv_bfloat16* out, Scratch* G,
             const __nv_bfloat16* __restrict__ w1,
             const __grid_constant__ Params P) {
    extern __shared__ __align__(1024) uint8_t smem[];
    const uint32_t sbase = (uint32_t)__cvta_generic_to_shared(smem);
    const uint32_t bars = sbase + OFF_BAR;
    const uint32_t rank = blockIdx.x & 1, pr = blockIdx.x >> 1;
    const uint32_t row0 = blockIdx.x * 16;
    if (threadIdx.x == 32) prefetch_l2<TILEB>(x + row0 * D_);
    if (threadIdx.x == 0) {
        mbar_init(bars + B_ROW, 1);
        asm volatile("fence.mbarrier_init.release.cluster;" ::: "memory");
        bulk_load(sbase + OFF_Y, x + row0 * D_, TILEB, bars + B_ROW);
        mbar_expect(bars + B_ROW, TILEB);
    }
    const int lane = threadIdx.x & 31;
    const int warp = __shfl_sync(~0u, threadIdx.x >> 5, 0), w = warp & 3;
    if (elect()) {
        const uint32_t first = bars + warp * 24, count = warp < 7 ? 1 : warp < 9 ? 18 - 2 * warp : 16;
#pragma unroll
        for (int i = 0; i < 3; i++) mbar_init(first + 8 * i, count);
        asm volatile("fence.mbarrier_init.release.cluster;" ::: "memory");
    }
    __syncwarp();
    asm volatile("barrier.cluster.arrive.relaxed.aligned;" ::: "memory");
    const uint32_t pv = pr < 4 ? pr * 8 + 36 : pr - 4 + (max((int)pr - 33, 0) * 37 >> 8);
    const uint32_t gp = (pv + 4) & 7, hp = pv >> 3;
    const uint32_t tb = gp * 2 + rank, c = hp * 16 + tb;
    const bool has_g1 = gp > 0;
    const uint32_t nt1 = hp & 3, ft = max((int)gp - 1, 0) * 2 + (hp >> 2);
    const uint32_t nt2 = (hp & 1) * 2 + rank, mt = (gp & 3) * 4 + (hp >> 1), ks = gp >> 2;
    asm volatile("barrier.cluster.wait.aligned;" ::: "memory");

    if (warp == 8) {
        uint32_t kw = (gp & 1) * 192, kx;
        if (elect()) {
            mbar_expect(bars + B_QFULL, WSLOT);
            tma3d(sbase + xslot(0) * 8192, &P.tmX, bars + B_FULL, 0, tb * 64, 0);
            tma3d_pair(sbase + wslot(0) * 8192 + rank * 12288, &P.tmWqkv, bars + B_QFULL, (hp * 56) & ~15, rank * 32, 0);
            asm volatile("prefetch.tensormap [%0];\nprefetch.tensormap [%1];\nprefetch.tensormap [%2];" ::"l"(&P.tmW1), "l"(&P.tmW2), "l"(&P.tmOut) : "memory");
            uint32_t due = (uint32_t)clock() + PACE, ep = ld_relaxed(G->epoch[c]);
            uint32_t spins = sbase == (rank << 24 | SMEM0) ? 0 : SPIN_LIMIT;
#pragma unroll 1
            for (int i = 1; i < 8; i++) {
                kx = kw; kw += 64;
                if (i >= 5) mbar_wait_bounded(bars + B_QEMPTY + 8 * (i - 5), 0, spins);
                else { while ((int)((uint32_t)clock() - due) < 0) {} due += PACE; }
                if (kw == D_) kw = 64;
                if (i < 4) kx = kw;
                const int ix = i - (i > 4);
                if (i < 7) mbar_expect(bars + B_QFULL + 8 * i, WSLOT);
                if (i != 4) tma3d(sbase + xslot(ix) * 8192, &P.tmX, bars + B_FULL + 8 * ix, kx, tb * 64, 0);
                if (i & (i >> 2)) mbar_wait_bounded(bars + B_CS - 20 + 4 * i, 0, spins);
                if (i < 7) tma3d_pair(sbase + wslot(i) * 8192 + rank * 12288, &P.tmWqkv, bars + B_QFULL + 8 * i, (hp * 56) & ~15, kw + rank * 32, 0);
            }
            ep++;
            Slot r{sbase, bars, 0};
            if (has_g1) {
                const uint8_t* src = G->H[nt1][rank * 16];
                const int row = rank * 1024;
                mbar_expect(bars + B_FULL, 16384 + TILEB);
                tma3d(sbase, &P.tmW1, bars + B_FULL, 0, row, ft * 2);
                wait_flag(G->flag[2 + rank * 2], 20 * ep, spins);
#pragma unroll 1
                for (int j = 64;; j += 64) {
                    bulk_load(r.dst + 16384, src, TILEB, r.bar + B_FULL);
                    src += TILEB;
                    r.next(bars);
                    if (j == 1024) break;
                    mbar_wait_bounded(r.bar + B_EMPTY, r.ph, spins);
                    mbar_expect(r.bar + B_FULL, 16384 + TILEB);
                    tma3d(r.dst, &P.tmW1, r.bar + B_FULL, 0, row + j, ft * 2);
                }
                mbar_arrive(bars + B_FULL + 48); mbar_arrive_n<16>(bars + B_EMPTY + 48);
#pragma unroll
                for (int i = 0; i < 4; i++) mbar_expect(bars + B_X + 8 * i, (i & 1) ? 3072 : 4096);
            } else {
                due = (uint32_t)clock();
                const __nv_bfloat16* at = w1 + (rank * 1024 + PF0 * 64 + hp * 8) * F_;
#pragma unroll 1
                for (int j = PF0; j < PF1 + 16 - PF2; j++) {
                    while ((int)((uint32_t)clock() - due) < 0) {}
                    prefetch_l2<16 * F_>(at);
                    due += j == PF1 - 1 ? PF + PFD : PF;
                    at += j == PF1 - 1 ? (PF2 - PF1 + 1) * 64 * F_ : 64 * F_;
                }
            }
            const uint8_t *so = G->O[mt][ks * 4], *sw = G->Wo[nt2][ks * 4];
            wait_flag2(G->flag[16 + mt], 8 * ep, G->flag[0], 16 * ep, spins);
#pragma unroll 1
            for (int j = 0; j < 4 * TILEB; j += TILEB) {
                mbar_wait_bounded(r.bar + B_EMPTY, r.ph, spins);
                mbar_expect(r.bar + B_QFULL, TILEB);
                bulk_load(r.dst, so + j, TILEB, r.bar + B_QFULL);
                bulk_load(r.dst + 16384, sw + j, (r.bar & 8) ? TILEB : 3 * SLAB, r.bar + B_FULL);
                r.next(bars);
            }
            Ring q{has_g1 ? 2u : 6u, has_g1}, p{q.slot, !has_g1};
#pragma unroll 1
            for (int j = 0; j < 14 * 128; j += 128) {
                mbar_wait_bounded(bars + B_EMPTY + 8 * q.slot, q.ph, spins);
                if (j >= LEADW * 128 && j < 7 * 128) { mbar_wait_bounded(bars + B_FULL + 8 * p.slot, p.ph, spins); p.next2(); }
                tma3d(sbase + q.slot * SLOT, &P.tmW2, bars + B_FULL + 8 * q.slot, 0, ks * 896 + j - (j < 896 ? 0 : 832), mt * 2);
                q.next2();
            }
            mbar_wait_bounded(bars + B_END, 0, spins);
        }
    } else if (warp > 8) {
        const uint32_t ep = ld_relaxed(G->epoch[c]) + 1;
        uint32_t spins = 0, bad;
        {
            uint2* cs = G->colsum[hp][0];
            const int i0 = threadIdx.x - 288, j0 = i0 - (hp & 1) * 4;
            const uint32_t at_cs = __shfl_sync(~0u, (hp * 768 + i0 + ((j0 & 92) == 28 ? (j0 & 32 ? 28 : 56) : 0)) * 8, lane);
            const uint32_t at_st = __shfl_sync(~0u, (tb * 64 + (i0 & 63)) * 16, lane), to_st = __shfl_sync(~0u, sbase + i0 * 16, lane);
            if (w == 2) {
                bar_sync(6, 288);
                stg1((uint32_t*)(G->stat + row0) + lane, tag(__float_as_uint(lds1f(sbase + OFF_ST + lane * 4)), ~lane & 1, ep));
                if (elect()) {
                    fence_async_shared();
#pragma unroll
                    for (int i = 0; i < 4; i++) bulk_store(G->H[i][0] + row0 * (SLAB / 16), sbase + OFF_X + i * HSTG, SLAB);
                    bulk_flush();
                    signal(G->flag[2 + (row0 >> 10) * 2 + ((row0 & 1023) >= 320)]);
                }
                __syncwarp();
            } else {
                const uint32_t word = rank * 16 + (w & 2) * 4 + (lane & 7), done = mapa(bars + B_CS, rank ^ (lane & 1));
                const uint32_t from = (sbase + word * 4 + (gp >> 2) * 12288 + (gp & 2) * 1024) ^ ((lane >> 3) * 288);
                auto swz = [](uint32_t a) { return a ^ ((a >> 3) & 0x70); };
                const uint32_t lin = sbase + lane * 128 + (hp & 1) * 16, f0 = swz(lin + 80) + 8192, f1 = swz(lin + 96) + 8192, to = swz(lin + 112);
                float s[6] = {};
#pragma unroll 1
                for (int i = 0; i < 7; i++) {
                    const uint32_t o = wslot(i) * 8192, a0 = from + o, a1 = a0 ^ 144;
                    mbar_wait(bars + B_QFULL + 8 * i, 0);
                    if ((i ^ (w >> 1)) & 1) {
                        const uint4 v0 = lds4(f0 + o), v1 = lds4(f1 + o), v2 = lds4(f0 + o + 12288), v3 = lds4(f1 + o + 12288);
                        sts4(to + o, v0); sts4(to + o + 4096, v1); sts4(to + o + 12288, v2); sts4(to + o + 16384, v3);
                        fence_async_shared();
                        __syncwarp();
                        if (elect()) mbar_expect(bars + B_FULL + 8 * i, 16384);
                    }
                    if (i > 3 || i < (gp & 1)) continue;
                    uint32_t v[12];
#pragma unroll
                    for (int k = 0; k < 12; k++) v[k] = __float_as_uint(lds1f(((k & 1) ? a1 : a0) + (k & 2) * 512 + (k >> 2) * 4096));
#pragma unroll
                    for (int k = 0; k < 12; k++) { s[(k >> 2) * 2] += bf_lo(v[k]); s[(k >> 2) * 2 + 1] += bf_hi(v[k]); }
                    __syncwarp();
                    if ((i & 1) && lane < 2) mbar_arrive_remote(done + (i & 2) * 4);
                    if (i < 3) continue;
#pragma unroll
                    for (int k = 0; k < 6; k++) { s[k] += __shfl_xor_sync(~0u, s[k], 8); s[k] += __shfl_xor_sync(~0u, s[k], 16); }
                    const float s0 = lane < 8 ? s[0] : lane < 16 ? s[2] : s[4], s1 = lane < 8 ? s[1] : lane < 16 ? s[3] : s[5];
                    if (lane < 24) cs[gp * 96 + (lane >> 3) * 32 + word] = make_uint2(tag(__float_as_uint(s0), 1, ep), __float_as_uint(s1));
                }
            }
            bar_sync(1, 96);
            uint4 sv;
            float f[2];
            do {
                uint2 u[8];
#pragma unroll
                for (int i = 0; i < 8; i++) u[i] = ld_relaxed2((const uint8_t*)G->colsum + at_cs + i * 768);
                sv = ld_relaxed4((const uint8_t*)G->stat + at_st);
#pragma unroll
                for (int e = 0; e < 2; e++) {
                    float g[4];
#pragma unroll
                    for (int i = 0; i < 4; i++) g[i] = __uint_as_float(e ? u[2 * i].y : u[2 * i].x) + __uint_as_float(e ? u[2 * i + 1].y : u[2 * i + 1].x);
                    f[e] = (g[0] + g[1]) + (g[2] + g[3]);
                }
                bad = or_diff(or_diff(u[0].x ^ ep, u[1].x, ep), u[2].x, ep) | or_diff(or_diff(u[3].x ^ ep, u[4].x, ep), u[5].x, ep) | or_diff(or_diff(u[6].x ^ ep, u[7].x, ep), sv.x, ep);
            } while (bad & 1);
            if (w < 3) sts4(to_st + OFF_ST, sv);
#pragma unroll
            for (int e = 0; e < 2; e++) {
                const uint32_t hi = pack2(f[e], f[e]);
                sts4(to_st + i0 * 16 + OFF_X + e * 16, make_uint4(hi, pack2(f[e] - bf_hi(hi), f[e] - bf_hi(hi)), 0, 0));
            }
            sts1(bars + 8 * NBAR, ep);
            fence_async_shared();
            __syncwarp();
            bar_arrive(8, 224); bar_arrive(9, 224);
        }
        block_end();
        const uint8_t* src = G->U[nt2][ks * 14];
        if (w < 3) {
            if (w == 1) {
                if (elect()) {
                    wait_flag(G->flag[3 + rank * 2], 44 * ep, spins);
                    mbar_arrive_n<16>(bars + B_EMPTY + 8 * 5);
                }
                __syncwarp();
                if (!has_g1) { bar_sync(5, 288); if (elect()) signal(G->flag[0]); __syncwarp(); }
            }
            mbar_wait(bars + B_HALO, 0);
            uint32_t slot = (has_g1 ? 16 % NSLOT : 0) + w - 1, ph = ~0u;
#pragma unroll 1
            for (int i = w - 1; i < 18;) {
                const uint32_t d0 = sbase + slot * SLOT + (i < 4 ? 0 : 16384), landed = bars + B_QFULL + 8 * slot, tx = i < 4 ? (2 + w) * SLAB : 16384;
                mbar_wait(landed, (ph >> slot) & 1);
                ph ^= 1 << slot;
                uint32_t v[14];
#pragma unroll
                for (int k = 0; k < 14; k++) v[k] = __float_as_uint(lds1f(d0 + k * 1024 + lane * 32 + (lane >> 2) * 4));
#pragma unroll
                for (int k = 0; k < 7; k++) asm("lop3.b32 %0, %0, %1, %2, 0x7e;" : "+r"(v[k]) : "r"(v[13 - k]), "r"(ep));
                const bool stale = __any_sync(~0u, (or3(or3(v[6], v[5], v[4]), or3(v[3], v[2], v[1]), v[0])) & 1);
                if (!stale && lane == 0) mbar_expect(landed + (B_FULL - B_QFULL), tx);
                if (stale) {
                    if (elect()) {
                        const uint8_t* cur = (i < 4 ? G->O[mt][ks * 4] : src - 4 * TILEB) + i * TILEB;
                        fence_async_shared();
                        mbar_expect(landed, TILEB);
                        bulk_load(d0, cur, TILEB, landed);
                    }
                } else {
                    i += __byte_perm(0x03020202u, 0x00010202u, 0x7770 + slot);
                    slot = __byte_perm(0x05060302u, 0x00040100u, 0x7770 + slot);
                }
            }
        } else {
            bar_sync(3, 288);
            __nanosleep(HALO_NS);
            uint4 v[7];
            do {
                bad = 0;
#pragma unroll
                for (int i = 0; i < 7; i++) { v[i] = ld_relaxed4(G->halo[c - (tb > 0)] + i * 512 + lane * 16); bad = or_diff(bad, v[i].x, ep); }
            } while (bad & 1);
#pragma unroll
            for (int i = 0; i < 7; i++) sts4(sbase + OFF_X + i * 512 + lane * 16, v[i]);
            __syncwarp();
            if (elect()) mbar_arrive(bars + B_HALO);
            bar_sync(2, 160);
            if (elect()) bulk_store(out + row0 * D_, sbase + OFF_Y, TILEB);
            __syncwarp();
            bar_sync(4, 288);
            if (elect()) {
                fence_async_shared();
                bulk_store(G->O[tb][hp], sbase + OFF_X, TILEB);
                bulk_flush();
                mbar_arrive_remote(mapa(bars + B_FREE, rank ^ 1));
                mbar_arrive(bars + B_FREE);
                hint(G->flag[16 + tb]);
                signal(G->flag[16 + (row0 >> 7)] + 1);
            }
            __syncwarp();
            uint32_t late = ~0u;
            const uint32_t* hints = G->flag[8 + nt2 * 2 + ks] + (lane & 7);
            mbar_wait(bars + (has_g1 ? B_X : B_FREE), 0);
            Ring r{has_g1 ? 2u : 6u, has_g1};
#pragma unroll 1
            for (int i = 0; i < 14; i++) {
                while ((late >> i) & 1) late = __ballot_sync(~0u, ld_relaxed(hints) != 2 * ep) & 127;
                mbar_wait(bars + B_EMPTY + 8 * r.slot, r.ph);
                if (elect()) {
                    mbar_expect(bars + B_QFULL + 8 * r.slot, TILEB);
                    bulk_load(sbase + r.slot * SLOT + 16384, src, TILEB, bars + B_QFULL + 8 * r.slot);
                }
                src += TILEB; r.next2();
            }
            if (elect()) {
                wait_flag(G->flag[16 + mt] + 1, 8 * ep, spins);
                mbar_arrive(bars + B_ROW);
                G->epoch[c][0] = ep;
            }
        }
    } else {
        const int wg = warp >> 2;
        Mma M{bars, mapa(bars, rank ^ (lane & 1)), (threadIdx.x & 127) < 2, wg, wg, w, Ring{0, 1}, 0};
        const int r = lane >> 2, t = lane & 3;
        uint32_t ep;
        const uint32_t kv = sbase + OFF_X + (w * 2 + wg) * KV + lane * 16;
        uint32_t q[8][2], k0[7], k1[14], v0[7];
        float f0, f1;
        {
            const int half = (lane >> 3) & 1, r16 = warp * 2 + (half ^ (lane >> 4)), nt = (lane >> 1) & 3;
            const uint32_t row = sbase + OFF_Y + r16 * (2 * D_), part = row + nt * 224 + half * 112 + (lane & 1) * 8;
            const uint32_t hb = sbase + OFF_X + nt * HSTG + r16 * 16 + (half ^ (row0 >> 10)) * (7 * 256) + (lane & 1) * 8;
            mbar_wait(bars + B_ROW, 0);
            const float x0 = bf_lo(__float_as_uint(lds1f(row)));
            float d[28], m1 = 0.f, n1 = 0.f, m2 = 0.f, n2 = 0.f;
#pragma unroll
            for (int i = 0; i < 7; i++) {
                const uint2 v = lds2(part + i * 16);
#pragma unroll
                for (int k = 0; k < 2; k++) {
                    const float d0 = d[4 * i + 2 * k] = bf_lo(k ? v.y : v.x) - x0, d1 = d[4 * i + 2 * k + 1] = bf_hi(k ? v.y : v.x) - x0;
                    m1 += d0; n1 += d1; m2 = fmaf(d0, d0, m2); n2 = fmaf(d1, d1, n2);
                }
            }
            const float md = row_sum(m1 + n1) * (1.f / D_), var = fmaf(-md, md, row_sum(m2 + n2) * (1.f / D_)), nmean = -(x0 + md);
            const float rstd = rsq(var + LN_EPS);
            const float sc = rstd * rsq(fmaf(var * rstd, 4 * rstd, 4 * LN_EPS)), nb = -md * sc;
            sts2(sbase + OFF_ST + r16 * 8, __float_as_uint(rstd), pack2(nmean, nmean - bf_hi(pack2(nmean, nmean))));
#pragma unroll
            for (int i = 0; i < 7; i++) sts2(hb + i * 256, pack2(fmaf(d[4 * i], sc, nb), fmaf(d[4 * i + 1], sc, nb)), pack2(fmaf(d[4 * i + 2], sc, nb), fmaf(d[4 * i + 3], sc, nb)));
            bar_arrive(6, 288);
            float acc[84];
#pragma unroll 1
            for (int kb = 0; kb < 7; kb++) {
                const bool held = kb == (wg ? 7 - HOLD : -1);
                if (held) { wg_wait<0>(); M.release_pair(4 - HOLD); bar_sync(7, 256); }
                mbar_wait(bars + B_FULL + 8 * kb, 0);
                const uint32_t dA = (xslot(kb) + wg) * 512, dB = wslot(kb) * 512 + (hp & 1);
                wg_fence();
#pragma unroll
                for (int k = 0; k < 4; k++) {
                    wgmma_n168<0, 1, HI_SW, HI_SW>(acc, dA + desc_lo(k * 32, 16), dB + desc_lo((k & 1) * 2048 + (k >> 1) * 12288, 4096), k > 0 || kb > 0);
                    if (k == 0) { wg_commit(); wg_wait<1>(); if (kb > 0 && !held) M.release_pair(kb - 3); }
                }
                wg_commit();
            }
            bar_sync(8 + wg, 224);
            ep = __float_as_uint(lds1f(bars + 8 * NBAR));
            const uint32_t st = sbase + OFF_ST + (w * 32 + r * 2 + wg) * 8;
            const uint2 s0 = lds2(st), s1 = lds2(st + 128);
            const uint32_t a0 = t < 2 ? s0.y : 0, a1 = t < 2 ? s1.y : 0;
            wg_fence();
            wgmma_rs_n168<desc_hi(128, 0)>(acc, a0, a1, desc_lo(OFF_X, 0) + (hp & 1) * 8);
            wg_commit();
            if (wg == 0) bar_arrive(7, 256);
            wg_wait<1>();
            M.release_pair(4);
            wg_wait<0>();
            pin(acc);
            f0 = __uint_as_float(s0.x); f1 = __uint_as_float(s1.x);
#pragma unroll
            for (int g = 13; g >= 0; g--) {
                const float* a = acc + (g < 7 ? g + 8 : g < 12 ? g + 9 : g * 8 - 89) * 4;
                (g < 7 ? k0[g] : v0[g - 7]) = pack2(a[0] * f0, a[1] * f0);
                k1[g] = pack2(a[2] * f1, a[3] * f1);
            }
#pragma unroll
            for (int i = 0; i < 3; i++) stsm4(kv + 2 * KV + i * 512, k1[4 * i], k1[4 * i + 1], k1[4 * i + 2], k1[4 * i + 3]);
            stsm2(kv + 2 * KV + 1536, k1[12], k1[13]);
            if (w == 3) {
#pragma unroll
                for (int i = 0; i < 14; i++) stg1(G->halo[c] + wg * KV + lane * 4 + i * 128, tag(k1[i], t == 0, ep));
            }
            bar_arrive(3, 288);
#pragma unroll
            for (int g = 0; g < 7; g++) { q[g][0] = pack2(acc[4 * g], acc[4 * g + 1]); q[g][1] = pack2(acc[4 * g + 2], acc[4 * g + 3]); }
#pragma unroll
            for (int j = 0; j < 2; j++) { q[7][j] = t < 2 ? 0u : q[3][j]; q[3][j] = t < 2 ? q[3][j] : 0u; }
#pragma unroll
            for (int g = 0; g < 7; g++) v0[g] = transpose8(v0[g]);
        }
        float a[56];
#pragma unroll
        for (int i = 0; i < 56; i++) asm volatile("" : "=f"(a[i]));
        if (__builtin_expect(!has_g1, 0)) {
            const int g = min(lane >> 1, 13), nt = rank * 2 + wg;
            const uint4* src = (const uint4*)(wo + (hp * 56 - (hp & 1) * 8 + w * 16 + (lane & 1)) * D_ + nt * 112) + g;
            uint4 v[8];
#pragma unroll
            for (int i = 0; i < 8; i++) v[i] = __ldg(src + i * (D_ / 4));
#pragma unroll
            for (int i = 0; i < 8; i++) ((uint4*)G->Wo[nt][hp])[w * (SLAB / 16) + g * 16 + (lane & 1) + 2 * i] = v[i];
            bar_arrive(5, 288);
        }
        M.run<true>(a, has_g1 ? PAUSE : 0, 1, 16, 0, 0);
        const uint32_t bias0 = ld_u16(b1 + ft * 128 + warp * 16 + r), bias1 = ld_u16(b1 + ft * 128 + warp * 16 + r + 8);
        {
            uint32_t kp[8], vv[14];
            mbar_wait(bars + B_HALO, 0);
            ldsm4(kp, kv); ldsm4(kp + 4, kv + (lane < 24 ? 512 : 0));
            const uint32_t va = kv + 896 + (lane & 8) * (2 * KV / 8 - 16) - (lane & 16) * 8;
            ldsm4t(vv, va); ldsm4t(vv + 4, va + 256); ldsm4t(vv + 8, va + 512); ldsm2t(vv + 12, va + 768);
            const bool e0 = 2 * t > r, e1 = 2 * t >= r;
            const uint32_t mk = (e0 ? 0xffffu : 0u) | (e1 ? 0xffff0000u : 0u);
            wg_wait<0>();
            pin(a);
            if (has_g1) M.release(M.prev);
            bar_arrive(10 + wg, 256);
            if (wg) bar_arrive(2, 160);
            block_end();
            float sv[2][4];
#pragma unroll
            for (int h = 0; h < 2; h++) {
                const int ga = h * 4, gb = h * 4 + 1, gc = h * 4 + 2, gd = h * 4 + 3;
                float s[3][4] = {};
                mma16(s[0], q[ga][0], q[ga][1], q[gb][0], q[gb][1], kp[ga], kp[gb]);
                mma16(s[1], q[ga][0], q[ga][1], q[gb][0], q[gb][1], k0[ga], k0[gb]);
                mma16(s[2], q[ga][0], q[ga][1], q[gb][0], q[gb][1], k1[ga], k1[gb]);
                mma16(s[0], q[gc][0], q[gc][1], q[gd][0], q[gd][1], kp[gc], kp[gd]);
                mma16(s[1], q[gc][0], q[gc][1], q[gd][0], q[gd][1], k0[gc], k0[3]);
                mma16(s[2], q[gc][0], q[gc][1], q[gd][0], q[gd][1], k1[gc], k1[3]);
                if ((tb | w) == 0) s[0][0] = s[0][1] = -1e30f;
                sv[h][0] = e0 ? s[0][0] : s[1][0];
                sv[h][1] = e1 ? s[0][1] : s[1][1];
                sv[h][2] = e0 ? s[1][2] : s[2][2];
                sv[h][3] = e1 ? s[1][3] : s[2][3];
            }
            uint32_t pp[2][2];
#pragma unroll
            for (int i = 0; i < 4; i++) {
                float* v = &sv[i >> 1][(i & 1) * 2];
                const float f = ((i & 1) ? f1 : f0) * QK_SCALE, m = quad_max(fmaxf(v[0], v[1])) * f;
                const float p0 = ex2(fmaf(v[0], f, -m)), p1 = ex2(fmaf(v[1], f, -m));
                const float inv = rcp(quad_sum(p0 + p1));
                pp[i >> 1][i & 1] = pack2(p0 * inv, p1 * inv);
            }
            uint32_t o[8][2];
#pragma unroll
            for (int i = 0; i < 8; i++) {
                const int h = i >> 2, g = i - h;
                float d[4] = {};
                mma16(d, pp[h][0] & mk, 0u, 0u, pp[h][1] & ~mk, vv[2 * g], vv[2 * g + 1]);
                mma8(d, pp[h][0] & ~mk, pp[h][1] & mk, v0[g]);
                o[i][0] = pack2(d[0], d[1]); o[i][1] = pack2(d[2], d[3]);
            }
            if (t >= 2) { o[3][0] = o[4][0]; o[3][1] = o[4][1]; }
            const int word = wg * 4 + t - (w & 1) * 4 - (r >> 2);
#pragma unroll
            for (int i = 0; i < 8; i++) { o[i][0] = tag(o[i][0], word == 0, ep); o[i][1] = tag(o[i][1], word == 2, ep); }
            const uint32_t dst = sbase + OFF_X + (w >> 1) * HALF + ((w & 1) * 32 + (lane & 15) * 2 + wg) * 16 + (lane >> 4) * 1024;
            bar_sync(11 - wg, 256);
            stsm4(dst, o[0][0], o[0][1], o[1][0], o[1][1]);
            stsm4(dst + 2048, o[2][0], o[2][1], o[3][0], o[3][1]);
            stsm4(dst + 4096, o[5][0], o[5][1], o[6][0], o[6][1]);
            stsm2(dst + 6144, o[7][0], o[7][1]);
            bar_arrive(4, 288);
        }
        if (has_g1) {
            M.run<true>(a, 16 - PAUSE, 1, 16, LAG1, 1);
            mbar_wait(bars + B_FREE, 0);
            const uint32_t xb = sbase + OFF_X + wg * 8192 + (threadIdx.x & 127) * 16, xbar = bars + B_X + 16 * wg;
            const uint32_t rx = mapa(xb, rank ^ 1), rbar = mapa(xbar, rank ^ 1);
            wg_wait<0>();
            pin(a);
            M.release(M.prev);
#pragma unroll
            for (int i = 0; i < 3; i++)
                st_async4(rx + i * 2048, rbar + 8 * (i >> 1), pack2(a[28 + 8 * i], a[29 + 8 * i]), pack2(a[30 + 8 * i], a[31 + 8 * i]), pack2(a[32 + 8 * i], a[33 + 8 * i]), pack2(a[34 + 8 * i], a[35 + 8 * i]));
            const uint32_t tail = 6144 - (threadIdx.x & 127) * 8;
            st_async2(rx + tail, rbar + 8, pack2(a[52], a[53]), pack2(a[54], a[55]));
            uint8_t* dst = G->U[nt1][((ft >= 7) + wg) * 7 + ft] + rank * HALF + w * 256 + lane * 4;
            uint32_t u[14];
#pragma unroll
            for (int i = 0; i < 28; i++) a[i] = fmaf(bf_lo((i & 2) ? bias1 : bias0), 0.5f, a[i]);
#pragma unroll
            for (int i = 0; i < 14; i++) {
                if (i % 8 == 0) {
                    mbar_wait(xbar + i, 0);
#pragma unroll
                    for (int k = i / 4; k < i / 4 + 2; k++) {
                        if (k < 3) { const uint4 v = lds4(xb + k * 2048); u[4 * k] = v.x; u[4 * k + 1] = v.y; u[4 * k + 2] = v.z; u[4 * k + 3] = v.w; }
                        else { const uint2 v = lds2(xb + tail); u[12] = v.x; u[13] = v.y; }
                    }
                    if (i && lane < 2) mbar_arrive(bars + B_EMPTY + 48);
                }
                if (i == HINT && threadIdx.x == 0) hint(G->flag[8 + nt1 * 2] + ft + (ft >= 7) * 25);
                stg1(dst + (i >> 1) * 1024 + (i & 1) * 128, tag(pack2(gelu2(a[2 * i] + bf_lo(u[i])), gelu2(a[2 * i + 1] + bf_hi(u[i]))), (lane & 7) == w * 2 + (i & 1), ep));
            }
        } else {
            mbar_wait(bars + B_FREE, 0);
            if (lane < 2) mbar_arrive(bars + B_EMPTY + 48);
        }
        M.half = wg ^ ks;
        const uint32_t orow = mt * 128 + M.half * 64 + w * 16;
        M.run_o(a);
        M.run<false>(a, 14, 0, 14 - NSLOT, NSLOT + 1, 1, b2 + orow + r);
        mbar_wait(bars + B_ROW, 1);
        const uint32_t stg = sbase + (4 + (w >> 1)) * SLOT + M.half * 8192 + (w & 1) * (PITCH * 16);
        const uint32_t sa = stg + (lane & 7) * PITCH + (lane >> 3) * 16;
        const bool one = elect();
        wg_wait<1>();
        if (wg == 0) bar_arrive(7, 256);
        wg_wait<0>();
        pin(a);
#pragma unroll
        for (int h = 0; h < 2; h++) {
            const float* e = a + 2 * h;
#pragma unroll
            for (int i = 0; i < 3; i++)
                stsm4(sa + h * 8 * PITCH + i * 64, pack2(e[16 * i], e[16 * i + 1]), pack2(e[16 * i + 4], e[16 * i + 5]), pack2(e[16 * i + 8], e[16 * i + 9]), pack2(e[16 * i + 12], e[16 * i + 13]));
            stsm2(sa + h * 8 * PITCH + 192, pack2(e[48], e[49]), pack2(e[52], e[53]));
            fence_async_shared();
            __syncwarp();
            if (one) asm volatile("cp.reduce.async.bulk.tensor.3d.global.shared::cta.add.tile.bulk_group [%0, {%4, %2, %3}], [%1];" ::"l"(&P.tmOut), "r"(stg + h * 8 * PITCH), "r"(nt2), "r"(orow + 8 * h), "r"(0) : "memory");
        }
        if (one) {
            asm volatile("cp.async.bulk.commit_group;" ::: "memory");
            if (w == 0) mbar_arrive(bars + B_END);
            asm volatile("cp.async.bulk.wait_group.read 0;" ::: "memory");
        }
    }
}

typedef CUresult (*EncodeFn)(CUtensorMap*, CUtensorMapDataType, cuuint32_t, void*, const cuuint64_t*, const cuuint64_t*, const cuuint32_t*, const cuuint32_t*,
                             CUtensorMapInterleave, CUtensorMapSwizzle, CUtensorMapL2promotion, CUtensorMapFloatOOBfill);

void make_map(EncodeFn enc, CUtensorMap* tm, const void* base, bool swizzle, int d0, int d1, int d2, int s1, int s2, int b0, int b1, int b2) {
    const cuuint64_t dims[3] = {(cuuint64_t)d0, (cuuint64_t)d1, (cuuint64_t)d2}, strides[2] = {(cuuint64_t)s1 * 2, (cuuint64_t)s2 * 2};
    const cuuint32_t box[3] = {(cuuint32_t)b0, (cuuint32_t)b1, (cuuint32_t)b2}, es[3] = {1, 1, 1};
    enc(tm, CU_TENSOR_MAP_DATA_TYPE_BFLOAT16, d2 ? 3 : 2, (void*)base, dims, strides, box, es, CU_TENSOR_MAP_INTERLEAVE_NONE,
        swizzle ? CU_TENSOR_MAP_SWIZZLE_128B : CU_TENSOR_MAP_SWIZZLE_NONE, CU_TENSOR_MAP_L2_PROMOTION_L2_128B, CU_TENSOR_MAP_FLOAT_OOB_FILL_NONE);
}

}

extern "C" void kernel_launch(void* const* d_in, const int* in_sizes, int n_in, void* d_out, int out_size) {
    static EncodeFn enc = nullptr;
    static Scratch* scratch = nullptr;
    if (!enc) {
        void* fn = nullptr;
        cudaDriverEntryPointQueryResult qr;
        cudaGetDriverEntryPoint("cuTensorMapEncodeTiled", &fn, cudaEnableDefault, &qr);
        enc = (EncodeFn)fn;
        cudaGetSymbolAddress((void**)&scratch, g_s);
        cudaFuncSetAttribute(fused_kernel, cudaFuncAttributeMaxDynamicSharedMemorySize, SMEM_BYTES);
    }
    Params P;
    const __nv_bfloat16* x = (const __nv_bfloat16*)d_in[0];
    make_map(enc, &P.tmX, x, true, D_, S_ / 2, 2, 2 * D_, D_, 64, 64, 2);
    make_map(enc, &P.tmWqkv, d_in[1], true, D_, D_, 3, 3 * D_, D_, 64, 32, 3);
    make_map(enc, &P.tmW1, d_in[4], true, 64, S_, F_ / 64, F_, 64, 64, 64, 2);
    make_map(enc, &P.tmW2, d_in[6], true, 64, F_, S_ / 64, S_, 64, 64, 64, 2);
    make_map(enc, &P.tmOut, d_out, false, 112, 4, S_, 112, D_, PITCH / 2, 1, 8);
    fused_kernel<<<NCTA, NTHREADS, SMEM_BYTES, cudaStreamPerThread>>>(x, (const __nv_bfloat16*)d_in[5], (const __nv_bfloat16*)d_in[7], (const __nv_bfloat16*)d_in[2], (__nv_bfloat16*)d_out, scratch,
                                                                      (const __nv_bfloat16*)d_in[4], P);
}
```

```cpp
#include <cuda_runtime.h>
#include <cuda_bf16.h>
#include <cuda.h>
#include <stdint.h>

constexpr int PACE = 580;
constexpr int HOLD = 1;
constexpr int HALO_NS = 300;
constexpr int PF = 400;
constexpr int PF0 = 2;
constexpr int PF1 = 8;
constexpr int PF2 = 13;
constexpr int PFD = 1200;
constexpr int PAUSE = 7;
constexpr int LAG1 = 4;
constexpr int HINT = 6;
constexpr int LEADW = 4;

namespace {

constexpr int S_ = 2048, D_ = 448, F_ = 1792;
constexpr int NCTA = 128, NTHREADS = 384;
constexpr int NSLOT = 6, SLOT = 32768, WSLOT = 24576, TILEB = 14336, SLAB = 3584, HALF = 7168;
constexpr int KV = 1792, HSTG = SLAB + 32, PITCH = 240;
constexpr int OFF_X = NSLOT * SLOT;
constexpr int OFF_Y = OFF_X + 10 * KV;
constexpr int OFF_ST = OFF_Y + TILEB;
constexpr int OFF_BAR = OFF_ST + 1024;
constexpr int SMEM_BYTES = OFF_BAR + 1280;
constexpr uint32_t SMEM0 = 1024;
constexpr int B_QFULL = 0, B_FULL = 56, B_HALO = 128, B_X = 136, B_CS = 168, B_FREE = 192, B_END = 200, B_QEMPTY = 216, B_EMPTY = 232, B_ROW = 288, NBAR = 37;
constexpr float LN_EPS = 1e-5f, QK_SCALE = 0.1889822365046136f * 1.4426950408889634f;
constexpr int SPIN_LIMIT = 1 << 22;

struct Scratch {
    uint8_t H[4][32][TILEB];
    uint8_t U[4][28][TILEB];
    uint8_t O[16][8][TILEB];
    uint8_t Wo[4][8][TILEB];
    uint8_t halo[NCTA][2 * KV];
    uint2 stat[S_];
    uint2 colsum[8][8][96];
    uint32_t flag[32][32];
    uint32_t epoch[NCTA][32];
};
__device__ __align__(1024) Scratch g_s;

struct Params {
    CUtensorMap tmX, tmWqkv, tmW1, tmW2, tmOut;
};

__device__ __forceinline__ bool elect() {
    uint32_t p;
    asm volatile("{\n.reg .pred p;\nelect.sync _|p, 0xffffffff;\nselp.u32 %0, 1, 0, p;\n}" : "=r"(p));
    return p;
}
__device__ __forceinline__ void mbar_init(uint32_t b, uint32_t c) { asm volatile("mbarrier.init.shared::cta.b64 [%0], %1;" ::"r"(b), "r"(c) : "memory"); }
__device__ __forceinline__ void mbar_expect(uint32_t b, uint32_t tx) { asm volatile("mbarrier.arrive.expect_tx.shared::cta.b64 _, [%0], %1;" ::"r"(b), "r"(tx) : "memory"); }
__device__ __forceinline__ void mbar_arrive(uint32_t b) { asm volatile("mbarrier.arrive.shared::cta.b64 _, [%0];" ::"r"(b) : "memory"); }
template <int N> __device__ __forceinline__ void mbar_arrive_n(uint32_t b) { asm volatile("mbarrier.arrive.shared::cta.b64 _, [%0], %1;" ::"r"(b), "n"(N) : "memory"); }
__device__ __forceinline__ void mbar_arrive4_remote(uint32_t b) { asm volatile("mbarrier.arrive.shared::cluster.b64 _, [%0], 4;" ::"r"(b) : "memory"); }
__device__ __forceinline__ void mbar_arrive_remote(uint32_t b) { asm volatile("mbarrier.arrive.shared::cluster.b64 _, [%0];" ::"r"(b) : "memory"); }
#define MBAR_WAIT_ASM(SEM) \
    asm volatile("{\n.reg .pred p;\nWAIT:\nmbarrier.try_wait.parity" SEM ".shared::cta.b64 p, [%0], %1;\n@!p bra WAIT;\n}" ::"r"(b), "r"(parity) : "memory")
__device__ __forceinline__ void mbar_wait(uint32_t b, uint32_t parity) { MBAR_WAIT_ASM(""); }
__device__ __forceinline__ void mbar_wait_bounded(uint32_t b, uint32_t parity, uint32_t& n) {
    asm volatile("{\n.reg .pred p;\nWAIT:\nadd.u32 %0, %0, 1;\nsetp.gt.u32 p, %0, %3;\n@p st.global.u32 [%4], %0;\n"
                 "mbarrier.try_wait.parity.shared::cta.b64 p, [%1], %2;\n@!p bra WAIT;\n}" : "+r"(n) : "r"(b), "r"(parity), "n"(SPIN_LIMIT), "l"(0ull) : "memory");
}
__device__ __forceinline__ uint32_t mapa(uint32_t a, uint32_t rank) { uint32_t r; asm("mapa.shared::cluster.u32 %0, %1, %2;" : "=r"(r) : "r"(a), "r"(rank)); return r; }
__device__ __forceinline__ void tma3d(uint32_t dst, const CUtensorMap* tm, uint32_t bar, int c0, int c1, int c2) {
    asm volatile("cp.async.bulk.tensor.3d.shared::cluster.global.mbarrier::complete_tx::bytes [%0], [%1, {%3, %4, %5}], [%2];" ::"r"(dst), "l"(tm), "r"(bar), "r"(c0), "r"(c1), "r"(c2) : "memory");
}
__device__ __forceinline__ void tma3d_pair(uint32_t dst, const CUtensorMap* tm, uint32_t bar, int c0, int c1, int c2) {
    asm volatile("cp.async.bulk.tensor.3d.shared::cluster.global.mbarrier::complete_tx::bytes.multicast::cluster [%0], [%1, {%3, %4, %5}], [%2], %6;" ::"r"(dst), "l"(tm), "r"(bar), "r"(c0), "r"(c1), "r"(c2), "h"((uint16_t)3) : "memory");
}
__device__ __forceinline__ void bulk_load(uint32_t dst, const void* src, uint32_t bytes, uint32_t bar) {
    asm volatile("cp.async.bulk.shared::cluster.global.mbarrier::complete_tx::bytes [%0], [%1], %2, [%3];" ::"r"(dst), "l"(src), "r"(bytes), "r"(bar) : "memory");
}
template <int BYTES> __device__ __forceinline__ void prefetch_l2(const void* p) { asm volatile("cp.async.bulk.prefetch.L2.global [%0], %1;" ::"l"(p), "n"(BYTES) : "memory"); }
__device__ __forceinline__ void bulk_store(void* dst, uint32_t src, uint32_t bytes) {
    asm volatile("cp.async.bulk.global.shared::cta.bulk_group [%0], [%1], %2;" ::"l"(dst), "r"(src), "r"(bytes) : "memory");
}
__device__ __forceinline__ uint32_t ld_u16(const void* p) { uint32_t v; asm volatile("ld.global.nc.u16 %0, [%1];" : "=r"(v) : "l"(p)); return v; }
__device__ __forceinline__ uint32_t ld_relaxed(const uint32_t* p) { uint32_t v; asm volatile("ld.relaxed.gpu.global.u32 %0, [%1];" : "=r"(v) : "l"(p) : "memory"); return v; }
__device__ __forceinline__ void bulk_flush() { asm volatile("cp.async.bulk.commit_group;\ncp.async.bulk.wait_group 0;" ::: "memory"); }
__device__ __forceinline__ void signal(uint32_t* flag) { asm volatile("fence.acq_rel.gpu;\nred.relaxed.gpu.global.add.u32 [%0], 1;" ::"l"(flag) : "memory"); }
__device__ __forceinline__ void hint(uint32_t* flag) { asm volatile("red.relaxed.gpu.global.add.u32 [%0], 1;" ::"l"(flag) : "memory"); }
__device__ __forceinline__ uint32_t tag(uint32_t v, uint32_t mask, uint32_t parity) { return (v & ~mask) | (parity & mask); }
__device__ __forceinline__ uint32_t or_diff(uint32_t acc, uint32_t v, uint32_t parity) { asm("lop3.b32 %0, %0, %1, %2, 0xf6;" : "+r"(acc) : "r"(v), "r"(parity)); return acc; }
__device__ __forceinline__ uint32_t or3(uint32_t a, uint32_t b, uint32_t c) { asm("lop3.b32 %0, %0, %1, %2, 0xfe;" : "+r"(a) : "r"(b), "r"(c)); return a; }
__device__ __forceinline__ uint4 ld_relaxed4(const void* p) {
    uint4 v;
    asm volatile("ld.relaxed.gpu.global.v4.u32 {%0, %1, %2, %3}, [%4];" : "=r"(v.x), "=r"(v.y), "=r"(v.z), "=r"(v.w) : "l"(p) : "memory");
    return v;
}
__device__ __forceinline__ uint2 ld_relaxed2(const void* p) { uint2 v; asm volatile("ld.relaxed.gpu.global.v2.u32 {%0, %1}, [%2];" : "=r"(v.x), "=r"(v.y) : "l"(p) : "memory"); return v; }
__device__ __forceinline__ void sts4(uint32_t a, uint4 v) { asm volatile("st.shared.v4.b32 [%0], {%1, %2, %3, %4};" ::"r"(a), "r"(v.x), "r"(v.y), "r"(v.z), "r"(v.w) : "memory"); }
__device__ __forceinline__ void sts1(uint32_t a, uint32_t v) { asm volatile("st.shared.b32 [%0], %1;" ::"r"(a), "r"(v) : "memory"); }
__device__ __forceinline__ void sts2(uint32_t a, uint32_t v0, uint32_t v1) { asm volatile("st.shared.v2.b32 [%0], {%1, %2};" ::"r"(a), "r"(v0), "r"(v1) : "memory"); }
__device__ __forceinline__ void stg1(void* p, uint32_t v) { asm volatile("st.global.b32 [%0], %1;" ::"l"(p), "r"(v) : "memory"); }
__device__ __forceinline__ void fence_async_shared() { asm volatile("fence.proxy.async.shared::cta;" ::: "memory"); }
#define BOUND "add.u32 %0, %0, 16;\nsetp.gt.u32 p, %0, %1;\n@p st.global.u32 [%2], %0;\n"
__device__ __forceinline__ void wait_flag(const uint32_t* p, uint32_t target, uint32_t& n) {
    asm volatile("{\n.reg .pred p;\n.reg .u32 v;\nPOLL:\n" BOUND "ld.acquire.gpu.global.u32 v, [%3];\nsetp.ne.u32 p, v, %4;\n@p bra POLL;\nfence.proxy.async.global;\n}"
                 : "+r"(n) : "n"(SPIN_LIMIT), "l"(0ull), "l"(p), "r"(target) : "memory");
}
__device__ __forceinline__ void wait_flag2(const uint32_t* h, uint32_t th, const uint32_t* p, uint32_t target, uint32_t& n) {
    asm volatile("{\n.reg .pred p;\n.reg .u32 u, v;\nPOLL:\n" BOUND "ld.relaxed.gpu.global.u32 u, [%3];\nld.acquire.gpu.global.u32 v, [%5];\nsetp.ne.u32 p, u, %4;\nsetp.ne.or.u32 p, v, %6, p;\n@p bra POLL;\nfence.proxy.async.global;\n}"
                 : "+r"(n) : "n"(SPIN_LIMIT), "l"(0ull), "l"(h), "r"(th), "l"(p), "r"(target) : "memory");
}
__device__ __forceinline__ void block_end() { asm volatile("{\n.reg .pred p;\n.reg .u32 t;\nAGAIN:\nmov.u32 t, %%clock;\nsetp.eq.u32 p, t, %0;\n@p bra AGAIN;\n}" ::"n"(0) : "memory"); }
__device__ __forceinline__ void bar_sync(int id, int n) { asm volatile("bar.sync %0, %1;" ::"r"(id), "r"(n) : "memory"); }
__device__ __forceinline__ void bar_arrive(int id, int n) { asm volatile("bar.arrive %0, %1;" ::"r"(id), "r"(n) : "memory"); }
__device__ __forceinline__ void wg_fence() { asm volatile("wgmma.fence.sync.aligned;" ::: "memory"); }
__device__ __forceinline__ void wg_commit() { asm volatile("wgmma.commit_group.sync.aligned;" ::: "memory"); }
template <int N> __device__ __forceinline__ void wg_wait() { asm volatile("wgmma.wait_group.sync.aligned %0;" ::"n"(N) : "memory"); }
template <int N> __device__ __forceinline__ void pin(float (&d)[N]) {
#pragma unroll
    for (int i = 0; i < N; i++) asm volatile("" : "+f"(d[i])::"memory");
}
__host__ __device__ constexpr uint32_t desc_hi(uint32_t sbo, uint32_t swz) { return (sbo >> 4) | (swz << 30); }
__host__ __device__ constexpr uint32_t desc_lo(uint32_t off, uint32_t lbo) { return ((SMEM0 + off) >> 4) | ((lbo >> 4) << 16); }
__device__ __forceinline__ uint32_t pack2(float lo, float hi) { uint32_t r; asm("cvt.rn.bf16x2.f32 %0, %1, %2;" : "=r"(r) : "f"(hi), "f"(lo)); return r; }
__device__ __forceinline__ float bf_lo(uint32_t v) { return __uint_as_float(v << 16); }
__device__ __forceinline__ float bf_hi(uint32_t v) { return __uint_as_float(v & 0xffff0000u); }
__device__ __forceinline__ void stsm4(uint32_t a, uint32_t r0, uint32_t r1, uint32_t r2, uint32_t r3) {
    asm volatile("stmatrix.sync.aligned.m8n8.x4.shared.b16 [%0], {%1, %2, %3, %4};" ::"r"(a), "r"(r0), "r"(r1), "r"(r2), "r"(r3) : "memory");
}
__device__ __forceinline__ void stsm2(uint32_t a, uint32_t r0, uint32_t r1) {
    asm volatile("stmatrix.sync.aligned.m8n8.x2.shared.b16 [%0], {%1, %2};" ::"r"(a), "r"(r0), "r"(r1) : "memory");
}
__device__ __forceinline__ uint4 lds4(uint32_t a) { uint4 v; asm volatile("ld.shared.v4.b32 {%0, %1, %2, %3}, [%4];" : "=r"(v.x), "=r"(v.y), "=r"(v.z), "=r"(v.w) : "r"(a) : "memory"); return v; }
__device__ __forceinline__ uint2 lds2(uint32_t a) { uint2 v; asm volatile("ld.shared.v2.b32 {%0, %1}, [%2];" : "=r"(v.x), "=r"(v.y) : "r"(a) : "memory"); return v; }
__device__ __forceinline__ float lds1f(uint32_t a) { float v; asm volatile("ld.shared.f32 %0, [%1];" : "=f"(v) : "r"(a) : "memory"); return v; }
__device__ __forceinline__ void ldsm4(uint32_t* r, uint32_t a) {
    asm volatile("ldmatrix.sync.aligned.m8n8.x4.shared.b16 {%0, %1, %2, %3}, [%4];" : "=r"(r[0]), "=r"(r[1]), "=r"(r[2]), "=r"(r[3]) : "r"(a) : "memory");
}
__device__ __forceinline__ void ldsm4t(uint32_t* r, uint32_t a) {
    asm volatile("ldmatrix.sync.aligned.m8n8.x4.trans.shared.b16 {%0, %1, %2, %3}, [%4];" : "=r"(r[0]), "=r"(r[1]), "=r"(r[2]), "=r"(r[3]) : "r"(a) : "memory");
}
__device__ __forceinline__ void ldsm2t(uint32_t* r, uint32_t a) {
    asm volatile("ldmatrix.sync.aligned.m8n8.x2.trans.shared.b16 {%0, %1}, [%2];" : "=r"(r[0]), "=r"(r[1]) : "r"(a) : "memory");
}
__device__ __forceinline__ uint32_t transpose8(uint32_t v) { uint32_t r; asm volatile("movmatrix.sync.aligned.m8n8.trans.b16 %0, %1;" : "=r"(r) : "r"(v)); return r; }
__device__ __forceinline__ void mma16(float (&c)[4], uint32_t a0, uint32_t a1, uint32_t a2, uint32_t a3, uint32_t b0, uint32_t b1) {
    asm volatile("mma.sync.aligned.m16n8k16.row.col.f32.bf16.bf16.f32 {%0, %1, %2, %3}, {%4, %5, %6, %7}, {%8, %9}, {%0, %1, %2, %3};"
                 : "+f"(c[0]), "+f"(c[1]), "+f"(c[2]), "+f"(c[3]) : "r"(a0), "r"(a1), "r"(a2), "r"(a3), "r"(b0), "r"(b1));
}
__device__ __forceinline__ void mma8(float (&c)[4], uint32_t a0, uint32_t a1, uint32_t b0) {
    asm volatile("mma.sync.aligned.m16n8k8.row.col.f32.bf16.bf16.f32 {%0, %1, %2, %3}, {%4, %5}, {%6}, {%0, %1, %2, %3};"
                 : "+f"(c[0]), "+f"(c[1]), "+f"(c[2]), "+f"(c[3]) : "r"(a0), "r"(a1), "r"(b0));
}
__device__ __forceinline__ void st_async4(uint32_t a, uint32_t bar, uint32_t v0, uint32_t v1, uint32_t v2, uint32_t v3) {
    asm volatile("st.async.weak.shared::cluster.mbarrier::complete_tx::bytes.v4.b32 [%0], {%2, %3, %4, %5}, [%1];" ::"r"(a), "r"(bar), "r"(v0), "r"(v1), "r"(v2), "r"(v3) : "memory");
}
__device__ __forceinline__ void st_async2(uint32_t a, uint32_t bar, uint32_t v0, uint32_t v1) {
    asm volatile("st.async.weak.shared::cluster.mbarrier::complete_tx::bytes.v2.b32 [%0], {%2, %3}, [%1];" ::"r"(a), "r"(bar), "r"(v0), "r"(v1) : "memory");
}
__device__ __forceinline__ float quad_max(float v) { v = fmaxf(v, __shfl_xor_sync(~0u, v, 1)); return fmaxf(v, __shfl_xor_sync(~0u, v, 2)); }
__device__ __forceinline__ float quad_sum(float v) { v += __shfl_xor_sync(~0u, v, 1); return v + __shfl_xor_sync(~0u, v, 2); }
__device__ __forceinline__ float ex2(float v) { float r; asm("ex2.approx.ftz.f32 %0, %1;" : "=f"(r) : "f"(v)); return r; }
__device__ __forceinline__ float rcp(float v) { float r; asm("rcp.approx.ftz.f32 %0, %1;" : "=f"(r) : "f"(v)); return r; }
__device__ __forceinline__ float rsq(float v) { float r; asm("rsqrt.approx.ftz.f32 %0, %1;" : "=f"(r) : "f"(v)); return r; }
__device__ __forceinline__ float gelu2(float v) {
    float z = v * fmaf(v * v, 8 * 0.044715f * 0.7978845608028654f, 2 * 0.7978845608028654f), t;
    asm("tanh.approx.f32 %0, %1;" : "=f"(t) : "f"(z));
    return fmaf(v, t, v);
}
__device__ __forceinline__ float row_sum(float v) {
    v = quad_sum(v); v += __shfl_xor_sync(~0u, v, 4);
    return v + __shfl_xor_sync(~0u, v, 24);
}

template <int TA, int TB, uint32_t HA, uint32_t HB>
__device__ __forceinline__ void wgmma_n112(float (&d)[56], uint32_t da, uint32_t db, int accumulate) {
    asm volatile("{\n.reg .pred p;\n.reg .b64 a, b;\nmov.b64 a, {%56, %61};\nmov.b64 b, {%57, %62};\nsetp.ne.b32 p, %58, 0;\n"
        "wgmma.mma_async.sync.aligned.m64n112k16.f32.bf16.bf16 {"
        "%0, %1, %2, %3, %4, %5, %6, %7, %8, %9, %10, %11, %12, %13, %14, %15, "
        "%16, %17, %18, %19, %20, %21, %22, %23, %24, %25, %26, %27, %28, %29, %30, %31, "
        "%32, %33, %34, %35, %36, %37, %38, %39, %40, %41, %42, %43, %44, %45, %46, %47, "
        "%48, %49, %50, %51, %52, %53, %54, %55"
        "}, a, b, p, 1, 1, %59, %60;\n}\n"
        : "+f"(d[0]), "+f"(d[1]), "+f"(d[2]), "+f"(d[3]), "+f"(d[4]), "+f"(d[5]), "+f"(d[6]), "+f"(d[7]),
          "+f"(d[8]), "+f"(d[9]), "+f"(d[10]), "+f"(d[11]), "+f"(d[12]), "+f"(d[13]), "+f"(d[14]), "+f"(d[15]),
          "+f"(d[16]), "+f"(d[17]), "+f"(d[18]), "+f"(d[19]), "+f"(d[20]), "+f"(d[21]), "+f"(d[22]), "+f"(d[23]),
          "+f"(d[24]), "+f"(d[25]), "+f"(d[26]), "+f"(d[27]), "+f"(d[28]), "+f"(d[29]), "+f"(d[30]), "+f"(d[31]),
          "+f"(d[32]), "+f"(d[33]), "+f"(d[34]), "+f"(d[35]), "+f"(d[36]), "+f"(d[37]), "+f"(d[38]), "+f"(d[39]),
          "+f"(d[40]), "+f"(d[41]), "+f"(d[42]), "+f"(d[43]), "+f"(d[44]), "+f"(d[45]), "+f"(d[46]), "+f"(d[47]),
          "+f"(d[48]), "+f"(d[49]), "+f"(d[50]), "+f"(d[51]), "+f"(d[52]), "+f"(d[53]), "+f"(d[54]), "+f"(d[55])
        : "r"(da), "r"(db), "r"(accumulate), "n"(TA), "n"(TB), "n"(HA), "n"(HB));
}

template <int TA, int TB, uint32_t HA, uint32_t HB>
__device__ __forceinline__ void wgmma_n168(float (&d)[84], uint32_t da, uint32_t db, int accumulate) {
    asm volatile("{\n.reg .pred p;\n.reg .b64 a, b;\nmov.b64 a, {%84, %89};\nmov.b64 b, {%85, %90};\nsetp.ne.b32 p, %86, 0;\n"
        "wgmma.mma_async.sync.aligned.m64n168k16.f32.bf16.bf16 {"
        "%0, %1, %2, %3, %4, %5, %6, %7, %8, %9, %10, %11, %12, %13, %14, %15, "
        "%16, %17, %18, %19, %20, %21, %22, %23, %24, %25, %26, %27, %28, %29, %30, %31, "
        "%32, %33, %34, %35, %36, %37, %38, %39, %40, %41, %42, %43, %44, %45, %46, %47, "
        "%48, %49, %50, %51, %52, %53, %54, %55, %56, %57, %58, %59, %60, %61, %62, %63, "
        "%64, %65, %66, %67, %68, %69, %70, %71, %72, %73, %74, %75, %76, %77, %78, %79, "
        "%80, %81, %82, %83"
        "}, a, b, p, 1, 1, %87, %88;\n}\n"
        : "+f"(d[0]), "+f"(d[1]), "+f"(d[2]), "+f"(d[3]), "+f"(d[4]), "+f"(d[5]), "+f"(d[6]), "+f"(d[7]),
          "+f"(d[8]), "+f"(d[9]), "+f"(d[10]), "+f"(d[11]), "+f"(d[12]), "+f"(d[13]), "+f"(d[14]), "+f"(d[15]),
          "+f"(d[16]), "+f"(d[17]), "+f"(d[18]), "+f"(d[19]), "+f"(d[20]), "+f"(d[21]), "+f"(d[22]), "+f"(d[23]),
          "+f"(d[24]), "+f"(d[25]), "+f"(d[26]), "+f"(d[27]), "+f"(d[28]), "+f"(d[29]), "+f"(d[30]), "+f"(d[31]),
          "+f"(d[32]), "+f"(d[33]), "+f"(d[34]), "+f"(d[35]), "+f"(d[36]), "+f"(d[37]), "+f"(d[38]), "+f"(d[39]),
          "+f"(d[40]), "+f"(d[41]), "+f"(d[42]), "+f"(d[43]), "+f"(d[44]), "+f"(d[45]), "+f"(d[46]), "+f"(d[47]),
          "+f"(d[48]), "+f"(d[49]), "+f"(d[50]), "+f"(d[51]), "+f"(d[52]), "+f"(d[53]), "+f"(d[54]), "+f"(d[55]),
          "+f"(d[56]), "+f"(d[57]), "+f"(d[58]), "+f"(d[59]), "+f"(d[60]), "+f"(d[61]), "+f"(d[62]), "+f"(d[63]),
          "+f"(d[64]), "+f"(d[65]), "+f"(d[66]), "+f"(d[67]), "+f"(d[68]), "+f"(d[69]), "+f"(d[70]), "+f"(d[71]),
          "+f"(d[72]), "+f"(d[73]), "+f"(d[74]), "+f"(d[75]), "+f"(d[76]), "+f"(d[77]), "+f"(d[78]), "+f"(d[79]),
          "+f"(d[80]), "+f"(d[81]), "+f"(d[82]), "+f"(d[83])
        : "r"(da), "r"(db), "r"(accumulate), "n"(TA), "n"(TB), "n"(HA), "n"(HB));
}

template <uint32_t HB>
__device__ __forceinline__ void wgmma_rs_n168(float (&d)[84], uint32_t a0, uint32_t a1, uint32_t db) {
    asm volatile("{\n.reg .b64 b;\nmov.b64 b, {%86, %88};\n"
        "wgmma.mma_async.sync.aligned.m64n168k16.f32.bf16.bf16 {"
        "%0, %1, %2, %3, %4, %5, %6, %7, %8, %9, %10, %11, %12, %13, %14, %15, "
        "%16, %17, %18, %19, %20, %21, %22, %23, %24, %25, %26, %27, %28, %29, %30, %31, "
        "%32, %33, %34, %35, %36, %37, %38, %39, %40, %41, %42, %43, %44, %45, %46, %47, "
        "%48, %49, %50, %51, %52, %53, %54, %55, %56, %57, %58, %59, %60, %61, %62, %63, "
        "%64, %65, %66, %67, %68, %69, %70, %71, %72, %73, %74, %75, %76, %77, %78, %79, "
        "%80, %81, %82, %83"
        "}, {%84, %85, %87, %87}, b, 1, 1, 1, 0;\n}\n"
        : "+f"(d[0]), "+f"(d[1]), "+f"(d[2]), "+f"(d[3]), "+f"(d[4]), "+f"(d[5]), "+f"(d[6]), "+f"(d[7]),
          "+f"(d[8]), "+f"(d[9]), "+f"(d[10]), "+f"(d[11]), "+f"(d[12]), "+f"(d[13]), "+f"(d[14]), "+f"(d[15]),
          "+f"(d[16]), "+f"(d[17]), "+f"(d[18]), "+f"(d[19]), "+f"(d[20]), "+f"(d[21]), "+f"(d[22]), "+f"(d[23]),
          "+f"(d[24]), "+f"(d[25]), "+f"(d[26]), "+f"(d[27]), "+f"(d[28]), "+f"(d[29]), "+f"(d[30]), "+f"(d[31]),
          "+f"(d[32]), "+f"(d[33]), "+f"(d[34]), "+f"(d[35]), "+f"(d[36]), "+f"(d[37]), "+f"(d[38]), "+f"(d[39]),
          "+f"(d[40]), "+f"(d[41]), "+f"(d[42]), "+f"(d[43]), "+f"(d[44]), "+f"(d[45]), "+f"(d[46]), "+f"(d[47]),
          "+f"(d[48]), "+f"(d[49]), "+f"(d[50]), "+f"(d[51]), "+f"(d[52]), "+f"(d[53]), "+f"(d[54]), "+f"(d[55]),
          "+f"(d[56]), "+f"(d[57]), "+f"(d[58]), "+f"(d[59]), "+f"(d[60]), "+f"(d[61]), "+f"(d[62]), "+f"(d[63]),
          "+f"(d[64]), "+f"(d[65]), "+f"(d[66]), "+f"(d[67]), "+f"(d[68]), "+f"(d[69]), "+f"(d[70]), "+f"(d[71]),
          "+f"(d[72]), "+f"(d[73]), "+f"(d[74]), "+f"(d[75]), "+f"(d[76]), "+f"(d[77]), "+f"(d[78]), "+f"(d[79]),
          "+f"(d[80]), "+f"(d[81]), "+f"(d[82]), "+f"(d[83])
        : "r"(a0), "r"(a1), "r"(db), "r"(0), "n"(HB));
}


struct Ring {
    uint32_t slot, ph;
    __device__ __forceinline__ void next() { if (++slot == NSLOT) { slot = 0; ph ^= 1; } }
    __device__ __forceinline__ void next2() { ph ^= slot == 5; slot = __byte_perm(0x06030201u, 0x00040005u, 0x7770 + slot); }
};
struct Slot {
    uint32_t dst, bar, ph;
    __device__ __forceinline__ void next(uint32_t bars) {
        dst += SLOT; bar += 8;
        if (bar == bars + 8 * NSLOT) { dst -= NSLOT * SLOT; bar = bars; ph ^= 1; }
    }
};
__device__ __forceinline__ uint32_t xslot(int i) { return __byte_perm(0x04130e0cu, 0x00130e0cu, 0x7770 + i); }
__device__ __forceinline__ uint32_t wslot(int i) { return __byte_perm(0x06001510u, 0x00151009u, 0x7770 + i); }

constexpr uint32_t HI_SW = desc_hi(1024, 1);

struct Mma {
    uint32_t bars, rel;
    bool lead;
    int wg, half, w;
    Ring r;
    uint32_t prev;
    __device__ __forceinline__ void release_pair(uint32_t s) { if (lead) mbar_arrive4_remote(rel + B_EMPTY + 8 * s); }
    __device__ __forceinline__ void release(uint32_t s) { if (lead) mbar_arrive_n<4>(bars + B_EMPTY + 8 * s); }
    template <bool G1>
    __device__ __forceinline__ void run(float (&a)[56], int n, int first, int last, int lag, int accumulate, const __nv_bfloat16* bias = nullptr) {
#pragma unroll 1
        for (int i = 0; i < n; i++) {
            if (lag && i == (wg ? n - lag : -1)) {
                if (!G1) {
                    const uint32_t c0 = ld_u16(bias), c1 = ld_u16(bias + 8);
                    wg_wait<0>(); release(prev); last = first;
                    pin(a);
#pragma unroll
                    for (int k = 0; k < 56; k++) a[k] += bf_lo((k & 2) ? c1 : c0);
                    pin(a);
                }
                bar_sync(7, 256);
            }
            const bool seen = !G1 && last == first;
            const uint32_t s = seen ? n - 1 - i : r.slot;
            if (!seen) mbar_wait(bars + B_FULL + 8 * s, r.ph);
            if (G1) r.next(); else r.next2();
            const uint32_t dB = s * (SLOT >> 4), dA = dB + half * 512;
            wg_fence();
#pragma unroll
            for (int k = 0; k < 4; k++) {
                wgmma_n112<1, 1, HI_SW, desc_hi(G1 ? 256 : 1024, 0)>(a, dA + desc_lo(k * 2048, 8192), dB + desc_lo(16384 + k * (G1 ? SLAB : 256), 128), k > 0 || accumulate || i > 0);
                if (k == 1) {
                    wg_commit(); wg_wait<1>();
                    if ((uint32_t)(i - first) < (uint32_t)(last - first)) release(prev);
                    if (G1 && lag && i == (wg ? -1 : n - 1)) bar_arrive(7, 256);
                }
            }
            wg_commit();
            prev = s;
        }
    }
    __device__ __forceinline__ void run_o(float (&a)[56]) {
#pragma unroll 1
        for (int i = 0; i < 2; i++) {
            const uint32_t s = r.slot, dB = s * (SLOT >> 4), dA = dB + half * (HALF >> 4);
            mbar_wait(bars + B_FULL + 8 * s, r.ph);
            wg_fence();
#pragma unroll
            for (int k = 0; k < 7; k++) {
                if (k == 3) { mbar_wait(bars + B_FULL + 8 * s + 8, r.ph); wg_fence(); }
                wgmma_n112<0, 1, desc_hi(128, 0), desc_hi(256, 0)>(a, dA + desc_lo(k * 2048 + (k > 3) * (SLOT - HALF), k == 3 ? SLOT - 6144 : 1024),
                                                                   dB + desc_lo(16384 + k * SLAB + (k > 2) * (SLOT - 3 * SLAB), 128), k > 0 || i > 0);
                if (k & 1) wg_commit();
                if (k == 1) { wg_wait<1>(); if (i) release(prev); }
                if (k == 5) { wg_wait<1>(); release(s); }
            }
            wg_commit();
            prev = s + 1;
            r.slot++; r.next2();
        }
    }
};

__global__ void __cluster_dims__(2, 1, 1) __launch_bounds__(NTHREADS, 1)
fused_kernel(const __nv_bfloat16* __restrict__ x, const __nv_bfloat16* __restrict__ b1, const __nv_bfloat16* __restrict__ b2, const __nv_bfloat16* __restrict__ wo, __nv_bfloat16* out, Scratch* G,
             const __nv_bfloat16* __restrict__ w1,
             const __grid_constant__ Params P) {
    extern __shared__ __align__(1024) uint8_t smem[];
    const uint32_t sbase = (uint32_t)__cvta_generic_to_shared(smem);
    const uint32_t bars = sbase + OFF_BAR;
    const uint32_t rank = blockIdx.x & 1, pr = blockIdx.x >> 1;
    const uint32_t row0 = blockIdx.x * 16;
    if (threadIdx.x == 32) prefetch_l2<TILEB>(x + row0 * D_);
    if (threadIdx.x == 0) {
        mbar_init(bars + B_ROW, 1);
        asm volatile("fence.mbarrier_init.release.cluster;" ::: "memory");
        bulk_load(sbase + OFF_Y, x + row0 * D_, TILEB, bars + B_ROW);
        mbar_expect(bars + B_ROW, TILEB);
    }
    const int lane = threadIdx.x & 31;
    const int warp = __shfl_sync(~0u, threadIdx.x >> 5, 0), w = warp & 3;
    if (elect()) {
        const uint32_t first = bars + warp * 24, count = warp < 7 ? 1 : warp < 9 ? 18 - 2 * warp : 16;
#pragma unroll
        for (int i = 0; i < 3; i++) mbar_init(first + 8 * i, count);
        asm volatile("fence.mbarrier_init.release.cluster;" ::: "memory");
    }
    __syncwarp();
    asm volatile("barrier.cluster.arrive.relaxed.aligned;" ::: "memory");
    const uint32_t pv = pr < 4 ? pr * 8 + 36 : pr - 4 + (max((int)pr - 33, 0) * 37 >> 8);
    const uint32_t gp = (pv + 4) & 7, hp = pv >> 3;
    const uint32_t tb = gp * 2 + rank, c = hp * 16 + tb;
    const bool has_g1 = gp > 0;
    const uint32_t nt1 = hp & 3, ft = max((int)gp - 1, 0) * 2 + (hp >> 2);
    const uint32_t nt2 = (hp & 1) * 2 + rank, mt = (gp & 3) * 4 + (hp >> 1), ks = gp >> 2;
    asm volatile("barrier.cluster.wait.aligned;" ::: "memory");

    if (warp == 8) {
        uint32_t kw = (gp & 1) * 192, kx;
        if (elect()) {
            mbar_expect(bars + B_QFULL, WSLOT);
            tma3d(sbase + xslot(0) * 8192, &P.tmX, bars + B_FULL, 0, tb * 64, 0);
            tma3d_pair(sbase + wslot(0) * 8192 + rank * 12288, &P.tmWqkv, bars + B_QFULL, (hp * 56) & ~15, rank * 32, 0);
            asm volatile("prefetch.tensormap [%0];\nprefetch.tensormap [%1];\nprefetch.tensormap [%2];" ::"l"(&P.tmW1), "l"(&P.tmW2), "l"(&P.tmOut) : "memory");
            uint32_t due = (uint32_t)clock() + PACE, ep = ld_relaxed(G->epoch[c]);
            uint32_t spins = sbase == (rank << 24 | SMEM0) ? 0 : SPIN_LIMIT;
#pragma unroll 1
            for (int i = 1; i < 8; i++) {
                kx = kw; kw += 64;
                if (i >= 5) mbar_wait_bounded(bars + B_QEMPTY + 8 * (i - 5), 0, spins);
                else { while ((int)((uint32_t)clock() - due) < 0) {} due += PACE; }
                if (kw == D_) kw = 64;
                if (i < 4) kx = kw;
                const int ix = i - (i > 4);
                if (i < 7) mbar_expect(bars + B_QFULL + 8 * i, WSLOT);
                if (i != 4) tma3d(sbase + xslot(ix) * 8192, &P.tmX, bars + B_FULL + 8 * ix, kx, tb * 64, 0);
                if (i & (i >> 2)) mbar_wait_bounded(bars + B_CS - 20 + 4 * i, 0, spins);
                if (i < 7) tma3d_pair(sbase + wslot(i) * 8192 + rank * 12288, &P.tmWqkv, bars + B_QFULL + 8 * i, (hp * 56) & ~15, kw + rank * 32, 0);
            }
            ep++;
            Slot r{sbase, bars, 0};
            if (has_g1) {
                const uint8_t* src = G->H[nt1][rank * 16];
                const int row = rank * 1024;
                mbar_expect(bars + B_FULL, 16384 + TILEB);
                tma3d(sbase, &P.tmW1, bars + B_FULL, 0, row, ft * 2);
                wait_flag(G->flag[2 + rank * 2], 20 * ep, spins);
#pragma unroll 1
                for (int j = 64;; j += 64) {
                    bulk_load(r.dst + 16384, src, TILEB, r.bar + B_FULL);
                    src += TILEB;
                    r.next(bars);
                    if (j == 1024) break;
                    mbar_wait_bounded(r.bar + B_EMPTY, r.ph, spins);
                    mbar_expect(r.bar + B_FULL, 16384 + TILEB);
                    tma3d(r.dst, &P.tmW1, r.bar + B_FULL, 0, row + j, ft * 2);
                }
                mbar_arrive(bars + B_FULL + 48); mbar_arrive_n<16>(bars + B_EMPTY + 48);
#pragma unroll
                for (int i = 0; i < 4; i++) mbar_expect(bars + B_X + 8 * i, (i & 1) ? 3072 : 4096);
            } else {
                due = (uint32_t)clock();
                const __nv_bfloat16* at = w1 + (rank * 1024 + PF0 * 64 + hp * 8) * F_;
#pragma unroll 1
                for (int j = PF0; j < PF1 + 16 - PF2; j++) {
                    while ((int)((uint32_t)clock() - due) < 0) {}
                    prefetch_l2<16 * F_>(at);
                    due += j == PF1 - 1 ? PF + PFD : PF;
                    at += j == PF1 - 1 ? (PF2 - PF1 + 1) * 64 * F_ : 64 * F_;
                }
            }
            const uint8_t *so = G->O[mt][ks * 4], *sw = G->Wo[nt2][ks * 4];
            wait_flag2(G->flag[16 + mt], 8 * ep, G->flag[0], 16 * ep, spins);
#pragma unroll 1
            for (int j = 0; j < 4 * TILEB; j += TILEB) {
                mbar_wait_bounded(r.bar + B_EMPTY, r.ph, spins);
                mbar_expect(r.bar + B_QFULL, TILEB);
                bulk_load(r.dst, so + j, TILEB, r.bar + B_QFULL);
                bulk_load(r.dst + 16384, sw + j, (r.bar & 8) ? TILEB : 3 * SLAB, r.bar + B_FULL);
                r.next(bars);
            }
            Ring q{has_g1 ? 2u : 6u, has_g1}, p{q.slot, !has_g1};
#pragma unroll 1
            for (int j = 0; j < 14 * 128; j += 128) {
                mbar_wait_bounded(bars + B_EMPTY + 8 * q.slot, q.ph, spins);
                if (j >= LEADW * 128 && j < 7 * 128) { mbar_wait_bounded(bars + B_FULL + 8 * p.slot, p.ph, spins); p.next2(); }
                tma3d(sbase + q.slot * SLOT, &P.tmW2, bars + B_FULL + 8 * q.slot, 0, ks * 896 + j - (j < 896 ? 0 : 832), mt * 2);
                q.next2();
            }
            mbar_wait_bounded(bars + B_END, 0, spins);
        }
    } else if (warp > 8) {
        const uint32_t ep = ld_relaxed(G->epoch[c]) + 1;
        uint32_t spins = 0, bad;
        {
            uint2* cs = G->colsum[hp][0];
            const int i0 = threadIdx.x - 288, j0 = i0 - (hp & 1) * 4;
            const uint32_t at_cs = __shfl_sync(~0u, (hp * 768 + i0 + ((j0 & 92) == 28 ? (j0 & 32 ? 28 : 56) : 0)) * 8, lane);
            const uint32_t at_st = __shfl_sync(~0u, (tb * 64 + (i0 & 63)) * 16, lane), to_st = __shfl_sync(~0u, sbase + i0 * 16, lane);
            if (w == 2) {
                bar_sync(6, 288);
                stg1((uint32_t*)(G->stat + row0) + lane, tag(__float_as_uint(lds1f(sbase + OFF_ST + lane * 4)), ~lane & 1, ep));
                if (elect()) {
                    fence_async_shared();
#pragma unroll
                    for (int i = 0; i < 4; i++) bulk_store(G->H[i][0] + row0 * (SLAB / 16), sbase + OFF_X + i * HSTG, SLAB);
                    bulk_flush();
                    signal(G->flag[2 + (row0 >> 10) * 2 + ((row0 & 1023) >= 320)]);
                }
                __syncwarp();
            } else {
                const uint32_t word = rank * 16 + (w & 2) * 4 + (lane & 7), done = mapa(bars + B_CS, rank ^ (lane & 1));
                const uint32_t from = (sbase + word * 4 + (gp >> 2) * 12288 + (gp & 2) * 1024) ^ ((lane >> 3) * 288);
                auto swz = [](uint32_t a) { return a ^ ((a >> 3) & 0x70); };
                const uint32_t lin = sbase + lane * 128 + (hp & 1) * 16, f0 = swz(lin + 80) + 8192, f1 = swz(lin + 96) + 8192, to = swz(lin + 112);
                float s[6] = {};
#pragma unroll 1
                for (int i = 0; i < 7; i++) {
                    const uint32_t o = wslot(i) * 8192, a0 = from + o, a1 = a0 ^ 144;
                    mbar_wait(bars + B_QFULL + 8 * i, 0);
                    if ((i ^ (w >> 1)) & 1) {
                        const uint4 v0 = lds4(f0 + o), v1 = lds4(f1 + o), v2 = lds4(f0 + o + 12288), v3 = lds4(f1 + o + 12288);
                        sts4(to + o, v0); sts4(to + o + 4096, v1); sts4(to + o + 12288, v2); sts4(to + o + 16384, v3);
                        fence_async_shared();
                        __syncwarp();
                        if (elect()) mbar_expect(bars + B_FULL + 8 * i, 16384);
                    }
                    if (i > 3 || i < (gp & 1)) continue;
                    uint32_t v[12];
#pragma unroll
                    for (int k = 0; k < 12; k++) v[k] = __float_as_uint(lds1f(((k & 1) ? a1 : a0) + (k & 2) * 512 + (k >> 2) * 4096));
#pragma unroll
                    for (int k = 0; k < 12; k++) { s[(k >> 2) * 2] += bf_lo(v[k]); s[(k >> 2) * 2 + 1] += bf_hi(v[k]); }
                    __syncwarp();
                    if ((i & 1) && lane < 2) mbar_arrive_remote(done + (i & 2) * 4);
                    if (i < 3) continue;
#pragma unroll
                    for (int k = 0; k < 6; k++) { s[k] += __shfl_xor_sync(~0u, s[k], 8); s[k] += __shfl_xor_sync(~0u, s[k], 16); }
                    const float s0 = lane < 8 ? s[0] : lane < 16 ? s[2] : s[4], s1 = lane < 8 ? s[1] : lane < 16 ? s[3] : s[5];
                    if (lane < 24) cs[gp * 96 + (lane >> 3) * 32 + word] = make_uint2(tag(__float_as_uint(s0), 1, ep), __float_as_uint(s1));
                }
            }
            bar_sync(1, 96);
            uint4 sv;
            float f[2];
            do {
                uint2 u[8];
#pragma unroll
                for (int i = 0; i < 8; i++) u[i] = ld_relaxed2((const uint8_t*)G->colsum + at_cs + i * 768);
                sv = ld_relaxed4((const uint8_t*)G->stat + at_st);
#pragma unroll
                for (int e = 0; e < 2; e++) {
                    float g[4];
#pragma unroll
                    for (int i = 0; i < 4; i++) g[i] = __uint_as_float(e ? u[2 * i].y : u[2 * i].x) + __uint_as_float(e ? u[2 * i + 1].y : u[2 * i + 1].x);
                    f[e] = (g[0] + g[1]) + (g[2] + g[3]);
                }
                bad = or_diff(or_diff(u[0].x ^ ep, u[1].x, ep), u[2].x, ep) | or_diff(or_diff(u[3].x ^ ep, u[4].x, ep), u[5].x, ep) | or_diff(or_diff(u[6].x ^ ep, u[7].x, ep), sv.x, ep);
            } while (bad & 1);
            if (w < 3) sts4(to_st + OFF_ST, sv);
#pragma unroll
            for (int e = 0; e < 2; e++) {
                const uint32_t hi = pack2(f[e], f[e]);
                sts4(to_st + i0 * 16 + OFF_X + e * 16, make_uint4(hi, pack2(f[e] - bf_hi(hi), f[e] - bf_hi(hi)), 0, 0));
            }
            sts1(bars + 8 * NBAR, ep);
            fence_async_shared();
            __syncwarp();
            bar_arrive(8, 224); bar_arrive(9, 224);
        }
        block_end();
        const uint8_t* src = G->U[nt2][ks * 14];
        if (w < 3) {
            if (w == 1) {
                if (elect()) {
                    wait_flag(G->flag[3 + rank * 2], 44 * ep, spins);
                    mbar_arrive_n<16>(bars + B_EMPTY + 8 * 5);
                }
                __syncwarp();
                if (!has_g1) { bar_sync(5, 288); if (elect()) signal(G->flag[0]); __syncwarp(); }
            }
            mbar_wait(bars + B_HALO, 0);
            uint32_t slot = (has_g1 ? 16 % NSLOT : 0) + w - 1, ph = ~0u;
#pragma unroll 1
            for (int i = w - 1; i < 18;) {
                const uint32_t d0 = sbase + slot * SLOT + (i < 4 ? 0 : 16384), landed = bars + B_QFULL + 8 * slot, tx = i < 4 ? (2 + w) * SLAB : 16384;
                mbar_wait(landed, (ph >> slot) & 1);
                ph ^= 1 << slot;
                uint32_t v[14];
#pragma unroll
                for (int k = 0; k < 14; k++) v[k] = __float_as_uint(lds1f(d0 + k * 1024 + lane * 32 + (lane >> 2) * 4));
#pragma unroll
                for (int k = 0; k < 7; k++) asm("lop3.b32 %0, %0, %1, %2, 0x7e;" : "+r"(v[k]) : "r"(v[13 - k]), "r"(ep));
                const bool stale = __any_sync(~0u, (or3(or3(v[6], v[5], v[4]), or3(v[3], v[2], v[1]), v[0])) & 1);
                if (!stale && lane == 0) mbar_expect(landed + (B_FULL - B_QFULL), tx);
                if (stale) {
                    if (elect()) {
                        const uint8_t* cur = (i < 4 ? G->O[mt][ks * 4] : src - 4 * TILEB) + i * TILEB;
                        fence_async_shared();
                        mbar_expect(landed, TILEB);
                        bulk_load(d0, cur, TILEB, landed);
                    }
                } else {
                    i += __byte_perm(0x03020202u, 0x00010202u, 0x7770 + slot);
                    slot = __byte_perm(0x05060302u, 0x00040100u, 0x7770 + slot);
                }
            }
        } else {
            bar_sync(3, 288);
            __nanosleep(HALO_NS);
            uint4 v[7];
            do {
                bad = 0;
#pragma unroll
                for (int i = 0; i < 7; i++) { v[i] = ld_relaxed4(G->halo[c - (tb > 0)] + i * 512 + lane * 16); bad = or_diff(bad, v[i].x, ep); }
            } while (bad & 1);
#pragma unroll
            for (int i = 0; i < 7; i++) sts4(sbase + OFF_X + i * 512 + lane * 16, v[i]);
            __syncwarp();
            if (elect()) mbar_arrive(bars + B_HALO);
            bar_sync(2, 160);
            if (elect()) bulk_store(out + row0 * D_, sbase + OFF_Y, TILEB);
            __syncwarp();
            bar_sync(4, 288);
            if (elect()) {
                fence_async_shared();
                bulk_store(G->O[tb][hp], sbase + OFF_X, TILEB);
                bulk_flush();
                mbar_arrive_remote(mapa(bars + B_FREE, rank ^ 1));
                mbar_arrive(bars + B_FREE);
                hint(G->flag[16 + tb]);
                signal(G->flag[16 + (row0 >> 7)] + 1);
            }
            __syncwarp();
            uint32_t late = ~0u;
            const uint32_t* hints = G->flag[8 + nt2 * 2 + ks] + (lane & 7);
            mbar_wait(bars + (has_g1 ? B_X : B_FREE), 0);
            Ring r{has_g1 ? 2u : 6u, has_g1};
#pragma unroll 1
            for (int i = 0; i < 14; i++) {
                while ((late >> i) & 1) late = __ballot_sync(~0u, ld_relaxed(hints) != 2 * ep) & 127;
                mbar_wait(bars + B_EMPTY + 8 * r.slot, r.ph);
                if (elect()) {
                    mbar_expect(bars + B_QFULL + 8 * r.slot, TILEB);
                    bulk_load(sbase + r.slot * SLOT + 16384, src, TILEB, bars + B_QFULL + 8 * r.slot);
                }
                src += TILEB; r.next2();
            }
            if (elect()) {
                wait_flag(G->flag[16 + mt] + 1, 8 * ep, spins);
                mbar_arrive(bars + B_ROW);
                G->epoch[c][0] = ep;
            }
        }
    } else {
        const int wg = warp >> 2;
        Mma M{bars, mapa(bars, rank ^ (lane & 1)), (threadIdx.x & 127) < 2, wg, wg, w, Ring{0, 1}, 0};
        const int r = lane >> 2, t = lane & 3;
        uint32_t ep;
        const uint32_t kv = sbase + OFF_X + (w * 2 + wg) * KV + lane * 16;
        uint32_t q[8][2], k0[7], k1[14], v0[7];
        float f0, f1;
        {
            const int half = (lane >> 3) & 1, r16 = warp * 2 + (half ^ (lane >> 4)), nt = (lane >> 1) & 3;
            const uint32_t row = sbase + OFF_Y + r16 * (2 * D_), part = row + nt * 224 + half * 112 + (lane & 1) * 8;
            const uint32_t hb = sbase + OFF_X + nt * HSTG + r16 * 16 + (half ^ (row0 >> 10)) * (7 * 256) + (lane & 1) * 8;
            mbar_wait(bars + B_ROW, 0);
            const float x0 = bf_lo(__float_as_uint(lds1f(row)));
            float d[28], m1 = 0.f, n1 = 0.f, m2 = 0.f, n2 = 0.f;
#pragma unroll
            for (int i = 0; i < 7; i++) {
                const uint2 v = lds2(part + i * 16);
#pragma unroll
                for (int k = 0; k < 2; k++) {
                    const float d0 = d[4 * i + 2 * k] = bf_lo(k ? v.y : v.x) - x0, d1 = d[4 * i + 2 * k + 1] = bf_hi(k ? v.y : v.x) - x0;
                    m1 += d0; n1 += d1; m2 = fmaf(d0, d0, m2); n2 = fmaf(d1, d1, n2);
                }
            }
            const float md = row_sum(m1 + n1) * (1.f / D_), var = fmaf(-md, md, row_sum(m2 + n2) * (1.f / D_)), nmean = -(x0 + md);
            const float rstd = rsq(var + LN_EPS);
            const float sc = rstd * rsq(fmaf(var * rstd, 4 * rstd, 4 * LN_EPS)), nb = -md * sc;
            sts2(sbase + OFF_ST + r16 * 8, __float_as_uint(rstd), pack2(nmean, nmean - bf_hi(pack2(nmean, nmean))));
#pragma unroll
            for (int i = 0; i < 7; i++) sts2(hb + i * 256, pack2(fmaf(d[4 * i], sc, nb), fmaf(d[4 * i + 1], sc, nb)), pack2(fmaf(d[4 * i + 2], sc, nb), fmaf(d[4 * i + 3], sc, nb)));
            bar_arrive(6, 288);
            float acc[84];
#pragma unroll 1
            for (int kb = 0; kb < 7; kb++) {
                const bool held = kb == (wg ? 7 - HOLD : -1);
                if (held) { wg_wait<0>(); M.release_pair(4 - HOLD); bar_sync(7, 256); }
                mbar_wait(bars + B_FULL + 8 * kb, 0);
                const uint32_t dA = (xslot(kb) + wg) * 512, dB = wslot(kb) * 512 + (hp & 1);
                wg_fence();
#pragma unroll
                for (int k = 0; k < 4; k++) {
                    wgmma_n168<0, 1, HI_SW, HI_SW>(acc, dA + desc_lo(k * 32, 16), dB + desc_lo((k & 1) * 2048 + (k >> 1) * 12288, 4096), k > 0 || kb > 0);
                    if (k == 0) { wg_commit(); wg_wait<1>(); if (kb > 0 && !held) M.release_pair(kb - 3); }
                }
                wg_commit();
            }
            bar_sync(8 + wg, 224);
            ep = __float_as_uint(lds1f(bars + 8 * NBAR));
            const uint32_t st = sbase + OFF_ST + (w * 32 + r * 2 + wg) * 8;
            const uint2 s0 = lds2(st), s1 = lds2(st + 128);
            const uint32_t a0 = t < 2 ? s0.y : 0, a1 = t < 2 ? s1.y : 0;
            wg_fence();
            wgmma_rs_n168<desc_hi(128, 0)>(acc, a0, a1, desc_lo(OFF_X, 0) + (hp & 1) * 8);
            wg_commit();
            if (wg == 0) bar_arrive(7, 256);
            wg_wait<1>();
            M.release_pair(4);
            wg_wait<0>();
            pin(acc);
            f0 = __uint_as_float(s0.x); f1 = __uint_as_float(s1.x);
#pragma unroll
            for (int g = 13; g >= 0; g--) {
                const float* a = acc + (g < 7 ? g + 8 : g < 12 ? g + 9 : g * 8 - 89) * 4;
                (g < 7 ? k0[g] : v0[g - 7]) = pack2(a[0] * f0, a[1] * f0);
                k1[g] = pack2(a[2] * f1, a[3] * f1);
            }
#pragma unroll
            for (int i = 0; i < 3; i++) stsm4(kv + 2 * KV + i * 512, k1[4 * i], k1[4 * i + 1], k1[4 * i + 2], k1[4 * i + 3]);
            stsm2(kv + 2 * KV + 1536, k1[12], k1[13]);
            if (w == 3) {
#pragma unroll
                for (int i = 0; i < 14; i++) stg1(G->halo[c] + wg * KV + lane * 4 + i * 128, tag(k1[i], t == 0, ep));
            }
            bar_arrive(3, 288);
#pragma unroll
            for (int g = 0; g < 7; g++) { q[g][0] = pack2(acc[4 * g], acc[4 * g + 1]); q[g][1] = pack2(acc[4 * g + 2], acc[4 * g + 3]); }
#pragma unroll
            for (int j = 0; j < 2; j++) { q[7][j] = t < 2 ? 0u : q[3][j]; q[3][j] = t < 2 ? q[3][j] : 0u; }
#pragma unroll
            for (int g = 0; g < 7; g++) v0[g] = transpose8(v0[g]);
        }
        float a[56];
#pragma unroll
        for (int i = 0; i < 56; i++) asm volatile("" : "=f"(a[i]));
        if (__builtin_expect(!has_g1, 0)) {
            const int g = min(lane >> 1, 13), nt = rank * 2 + wg;
            const uint4* src = (const uint4*)(wo + (hp * 56 - (hp & 1) * 8 + w * 16 + (lane & 1)) * D_ + nt * 112) + g;
            uint4 v[8];
#pragma unroll
            for (int i = 0; i < 8; i++) v[i] = __ldg(src + i * (D_ / 4));
#pragma unroll
            for (int i = 0; i < 8; i++) ((uint4*)G->Wo[nt][hp])[w * (SLAB / 16) + g * 16 + (lane & 1) + 2 * i] = v[i];
            bar_arrive(5, 288);
        }
        M.run<true>(a, has_g1 ? PAUSE : 0, 1, 16, 0, 0);
        const uint32_t bias0 = ld_u16(b1 + ft * 128 + warp * 16 + r), bias1 = ld_u16(b1 + ft * 128 + warp * 16 + r + 8);
        {
            uint32_t kp[8], vv[14];
            mbar_wait(bars + B_HALO, 0);
            ldsm4(kp, kv); ldsm4(kp + 4, kv + (lane < 24 ? 512 : 0));
            const uint32_t va = kv + 896 + (lane & 8) * (2 * KV / 8 - 16) - (lane & 16) * 8;
            ldsm4t(vv, va); ldsm4t(vv + 4, va + 256); ldsm4t(vv + 8, va + 512); ldsm2t(vv + 12, va + 768);
            const bool e0 = 2 * t > r, e1 = 2 * t >= r;
            const uint32_t mk = (e0 ? 0xffffu : 0u) | (e1 ? 0xffff0000u : 0u);
            wg_wait<0>();
            pin(a);
            if (has_g1) M.release(M.prev);
            bar_arrive(10 + wg, 256);
            if (wg) bar_arrive(2, 160);
            block_end();
            float sv[2][4];
#pragma unroll
            for (int h = 0; h < 2; h++) {
                const int ga = h * 4, gb = h * 4 + 1, gc = h * 4 + 2, gd = h * 4 + 3;
                float s[3][4] = {};
                mma16(s[0], q[ga][0], q[ga][1], q[gb][0], q[gb][1], kp[ga], kp[gb]);
                mma16(s[1], q[ga][0], q[ga][1], q[gb][0], q[gb][1], k0[ga], k0[gb]);
                mma16(s[2], q[ga][0], q[ga][1], q[gb][0], q[gb][1], k1[ga], k1[gb]);
                mma16(s[0], q[gc][0], q[gc][1], q[gd][0], q[gd][1], kp[gc], kp[gd]);
                mma16(s[1], q[gc][0], q[gc][1], q[gd][0], q[gd][1], k0[gc], k0[3]);
                mma16(s[2], q[gc][0], q[gc][1], q[gd][0], q[gd][1], k1[gc], k1[3]);
                if ((tb | w) == 0) s[0][0] = s[0][1] = -1e30f;
                sv[h][0] = e0 ? s[0][0] : s[1][0];
                sv[h][1] = e1 ? s[0][1] : s[1][1];
                sv[h][2] = e0 ? s[1][2] : s[2][2];
                sv[h][3] = e1 ? s[1][3] : s[2][3];
            }
            uint32_t pp[2][2];
#pragma unroll
            for (int i = 0; i < 4; i++) {
                float* v = &sv[i >> 1][(i & 1) * 2];
                const float f = ((i & 1) ? f1 : f0) * QK_SCALE, m = quad_max(fmaxf(v[0], v[1])) * f;
                const float p0 = ex2(fmaf(v[0], f, -m)), p1 = ex2(fmaf(v[1], f, -m));
                const float inv = rcp(quad_sum(p0 + p1));
                pp[i >> 1][i & 1] = pack2(p0 * inv, p1 * inv);
            }
            uint32_t o[8][2];
#pragma unroll
            for (int i = 0; i < 8; i++) {
                const int h = i >> 2, g = i - h;
                float d[4] = {};
                mma16(d, pp[h][0] & mk, 0u, 0u, pp[h][1] & ~mk, vv[2 * g], vv[2 * g + 1]);
                mma8(d, pp[h][0] & ~mk, pp[h][1] & mk, v0[g]);
                o[i][0] = pack2(d[0], d[1]); o[i][1] = pack2(d[2], d[3]);
            }
            if (t >= 2) { o[3][0] = o[4][0]; o[3][1] = o[4][1]; }
            const int word = wg * 4 + t - (w & 1) * 4 - (r >> 2);
#pragma unroll
            for (int i = 0; i < 8; i++) { o[i][0] = tag(o[i][0], word == 0, ep); o[i][1] = tag(o[i][1], word == 2, ep); }
            const uint32_t dst = sbase + OFF_X + (w >> 1) * HALF + ((w & 1) * 32 + (lane & 15) * 2 + wg) * 16 + (lane >> 4) * 1024;
            bar_sync(11 - wg, 256);
            stsm4(dst, o[0][0], o[0][1], o[1][0], o[1][1]);
            stsm4(dst + 2048, o[2][0], o[2][1], o[3][0], o[3][1]);
            stsm4(dst + 4096, o[5][0], o[5][1], o[6][0], o[6][1]);
            stsm2(dst + 6144, o[7][0], o[7][1]);
            bar_arrive(4, 288);
        }
        if (has_g1) {
            M.run<true>(a, 16 - PAUSE, 1, 16, LAG1, 1);
            mbar_wait(bars + B_FREE, 0);
            const uint32_t xb = sbase + OFF_X + wg * 8192 + (threadIdx.x & 127) * 16, xbar = bars + B_X + 16 * wg;
            const uint32_t rx = mapa(xb, rank ^ 1), rbar = mapa(xbar, rank ^ 1);
            wg_wait<0>();
            pin(a);
            M.release(M.prev);
#pragma unroll
            for (int i = 0; i < 3; i++)
                st_async4(rx + i * 2048, rbar + 8 * (i >> 1), pack2(a[28 + 8 * i], a[29 + 8 * i]), pack2(a[30 + 8 * i], a[31 + 8 * i]), pack2(a[32 + 8 * i], a[33 + 8 * i]), pack2(a[34 + 8 * i], a[35 + 8 * i]));
            const uint32_t tail = 6144 - (threadIdx.x & 127) * 8;
            st_async2(rx + tail, rbar + 8, pack2(a[52], a[53]), pack2(a[54], a[55]));
            uint8_t* dst = G->U[nt1][((ft >= 7) + wg) * 7 + ft] + rank * HALF + w * 256 + lane * 4;
            uint32_t u[14];
#pragma unroll
            for (int i = 0; i < 28; i++) a[i] = fmaf(bf_lo((i & 2) ? bias1 : bias0), 0.5f, a[i]);
#pragma unroll
            for (int i = 0; i < 14; i++) {
                if (i % 8 == 0) {
                    mbar_wait(xbar + i, 0);
#pragma unroll
                    for (int k = i / 4; k < i / 4 + 2; k++) {
                        if (k < 3) { const uint4 v = lds4(xb + k * 2048); u[4 * k] = v.x; u[4 * k + 1] = v.y; u[4 * k + 2] = v.z; u[4 * k + 3] = v.w; }
                        else { const uint2 v = lds2(xb + tail); u[12] = v.x; u[13] = v.y; }
                    }
                    if (i && lane < 2) mbar_arrive(bars + B_EMPTY + 48);
                }
                if (i == HINT && threadIdx.x == 0) hint(G->flag[8 + nt1 * 2] + ft + (ft >= 7) * 25);
                stg1(dst + (i >> 1) * 1024 + (i & 1) * 128, tag(pack2(gelu2(a[2 * i] + bf_lo(u[i])), gelu2(a[2 * i + 1] + bf_hi(u[i]))), (lane & 7) == w * 2 + (i & 1), ep));
            }
        } else {
            mbar_wait(bars + B_FREE, 0);
            if (lane < 2) mbar_arrive(bars + B_EMPTY + 48);
        }
        M.half = wg ^ ks;
        const uint32_t orow = mt * 128 + M.half * 64 + w * 16;
        M.run_o(a);
        M.run<false>(a, 14, 0, 14 - NSLOT, NSLOT + 1, 1, b2 + orow + r);
        mbar_wait(bars + B_ROW, 1);
        const uint32_t stg = sbase + (4 + (w >> 1)) * SLOT + M.half * 8192 + (w & 1) * (PITCH * 16);
        const uint32_t sa = stg + (lane & 7) * PITCH + (lane >> 3) * 16;
        const bool one = elect();
        wg_wait<1>();
        if (wg == 0) bar_arrive(7, 256);
        wg_wait<0>();
        pin(a);
#pragma unroll
        for (int h = 0; h < 2; h++) {
            const float* e = a + 2 * h;
#pragma unroll
            for (int i = 0; i < 3; i++)
                stsm4(sa + h * 8 * PITCH + i * 64, pack2(e[16 * i], e[16 * i + 1]), pack2(e[16 * i + 4], e[16 * i + 5]), pack2(e[16 * i + 8], e[16 * i + 9]), pack2(e[16 * i + 12], e[16 * i + 13]));
            stsm2(sa + h * 8 * PITCH + 192, pack2(e[48], e[49]), pack2(e[52], e[53]));
            fence_async_shared();
            __syncwarp();
            if (one) asm volatile("cp.reduce.async.bulk.tensor.3d.global.shared::cta.add.tile.bulk_group [%0, {%4, %2, %3}], [%1];" ::"l"(&P.tmOut), "r"(stg + h * 8 * PITCH), "r"(nt2), "r"(orow + 8 * h), "r"(0) : "memory");
        }
        if (one) {
            asm volatile("cp.async.bulk.commit_group;" ::: "memory");
            if (w == 0) mbar_arrive(bars + B_END);
            asm volatile("cp.async.bulk.wait_group.read 0;" ::: "memory");
        }
    }
}

typedef CUresult (*EncodeFn)(CUtensorMap*, CUtensorMapDataType, cuuint32_t, void*, const cuuint64_t*, const cuuint64_t*, const cuuint32_t*, const cuuint32_t*,
                             CUtensorMapInterleave, CUtensorMapSwizzle, CUtensorMapL2promotion, CUtensorMapFloatOOBfill);

void make_map(EncodeFn enc, CUtensorMap* tm, const void* base, bool swizzle, int d0, int d1, int d2, int s1, int s2, int b0, int b1, int b2) {
    const cuuint64_t dims[3] = {(cuuint64_t)d0, (cuuint64_t)d1, (cuuint64_t)d2}, strides[2] = {(cuuint64_t)s1 * 2, (cuuint64_t)s2 * 2};
    const cuuint32_t box[3] = {(cuuint32_t)b0, (cuuint32_t)b1, (cuuint32_t)b2}, es[3] = {1, 1, 1};
    enc(tm, CU_TENSOR_MAP_DATA_TYPE_BFLOAT16, d2 ? 3 : 2, (void*)base, dims, strides, box, es, CU_TENSOR_MAP_INTERLEAVE_NONE,
        swizzle ? CU_TENSOR_MAP_SWIZZLE_128B : CU_TENSOR_MAP_SWIZZLE_NONE, CU_TENSOR_MAP_L2_PROMOTION_L2_128B, CU_TENSOR_MAP_FLOAT_OOB_FILL_NONE);
}

}

extern "C" void kernel_launch(void* const* d_in, const int* in_sizes, int n_in, void* d_out, int out_size) {
    static EncodeFn enc = nullptr;
    static Scratch* scratch = nullptr;
    if (!enc) {
        void* fn = nullptr;
        cudaDriverEntryPointQueryResult qr;
        cudaGetDriverEntryPoint("cuTensorMapEncodeTiled", &fn, cudaEnableDefault, &qr);
        enc = (EncodeFn)fn;
        cudaGetSymbolAddress((void**)&scratch, g_s);
        cudaFuncSetAttribute(fused_kernel, cudaFuncAttributeMaxDynamicSharedMemorySize, SMEM_BYTES);
    }
    Params P;
    const __nv_bfloat16* x = (const __nv_bfloat16*)d_in[0];
    make_map(enc, &P.tmX, x, true, D_, S_ / 2, 2, 2 * D_, D_, 64, 64, 2);
    make_map(enc, &P.tmWqkv, d_in[1], true, D_, D_, 3, 3 * D_, D_, 64, 32, 3);
    make_map(enc, &P.tmW1, d_in[4], true, 64, S_, F_ / 64, F_, 64, 64, 64, 2);
    make_map(enc, &P.tmW2, d_in[6], true, 64, F_, S_ / 64, S_, 64, 64, 64, 2);
    make_map(enc, &P.tmOut, d_out, false, 112, 4, S_, 112, D_, PITCH / 2, 1, 8);
    fused_kernel<<<NCTA, NTHREADS, SMEM_BYTES, cudaStreamPerThread>>>(x, (const __nv_bfloat16*)d_in[5], (const __nv_bfloat16*)d_in[7], (const __nv_bfloat16*)d_in[2], (__nv_bfloat16*)d_out, scratch,
                                                                      (const __nv_bfloat16*)d_in[4], P);
}
```
